```python
import torch

def _softmax(x, axis=-1):
    return torch.softmax(x, dim=axis)

def _gelu(x):
    return torch.nn.functional.gelu(x, approximate='tanh')

def _silu(x):
    return torch.nn.functional.silu(x)

def _sigmoid(x):
    return torch.sigmoid(x)

def _layernorm(x, axis=-1, eps=1e-05):
    m = x.mean(dim=axis, keepdim=True)
    v = x.var(dim=axis, keepdim=True, unbiased=False)
    return (x - m) / torch.sqrt(v + eps)

def _scatter_add(tgt, idx, src, axis=0):
    return tgt.clone().index_add_(axis, idx, src)

def _segment_sum(src, seg, n):
    out = torch.zeros((n,) + src.shape[1:], dtype=src.dtype)
    return out.index_add_(0, seg, src)

def _pad(x, pw):
    flat = tuple((v for pair in reversed(pw) for v in pair))
    return torch.nn.functional.pad(x, flat)
kernel_name = 'recurrent_scan__memory_aug_recurrent_mem_tr__mixer_channel_mlp__prompt'

def setup_inputs():

    _w = lambda a: (lambda t: t.to(torch.bfloat16) if t.is_floating_point() else t)(torch.as_tensor(a))

    def _A_setup():
        B, S, Dm = (1, 2048, 512)
        H, Dh = (32, 128)
        M, seg = (8, 32)
        seg = min(seg, S)
        S = S // seg * seg
        return {'x': _w((lambda *s: torch.randn(*s, dtype=torch.bfloat16) * 0.05)(B, S, Dm)), 'mem0': _w((lambda *s: torch.randn(*s, dtype=torch.bfloat16) * 0.8)(B, M, Dm)), 'Wq': _w((lambda *s: torch.randn(*s, dtype=torch.bfloat16) * 0.8)(Dm, H, Dh) * Dm ** (-0.5)), 'Wk': _w((lambda *s: torch.randn(*s, dtype=torch.bfloat16) * 0.8)(Dm, H, Dh) * Dm ** (-0.5)), 'Wv': _w((lambda *s: torch.randn(*s, dtype=torch.bfloat16) * 0.8)(Dm, H, Dh) * Dm ** (-0.5)), 'Wo': _w((lambda *s: torch.randn(*s, dtype=torch.bfloat16) * 0.8)(H, Dh, Dm) * (H * Dh) ** (-0.5)), 'seg_len': seg}
    _A_in = _A_setup()

    def _B_setup():
        B, S, D, F = (1, 2048, 512, 1792)
        return {'x': _w((lambda *s: torch.randn(*s, dtype=torch.bfloat16) * 0.05)(B, S, D)), 'w1': _w((lambda *s: torch.randn(*s, dtype=torch.bfloat16) * 0.8)(D, F) * D ** (-0.5)), 'b1': _w((lambda *s: torch.randn(*s, dtype=torch.bfloat16) * 0.4)(F)), 'w2': _w((lambda *s: torch.randn(*s, dtype=torch.bfloat16) * 0.2)(F, D) * F ** (-0.5)), 'b2': _w((lambda *s: torch.randn(*s, dtype=torch.bfloat16) * 0.2)(D))}
    _B_in = _B_setup()
    return {'A_x': _A_in['x'], 'A_mem0': _A_in['mem0'], 'A_Wq': _A_in['Wq'], 'A_Wk': _A_in['Wk'], 'A_Wv': _A_in['Wv'], 'A_Wo': _A_in['Wo'], 'A_seg_len': _A_in['seg_len'], 'B_x': _B_in['x'], 'B_w1': _B_in['w1'], 'B_b1': _B_in['b1'], 'B_w2': _B_in['w2'], 'B_b2': _B_in['b2']}

def reference(A_x, A_mem0, A_Wq, A_Wk, A_Wv, A_Wo, A_seg_len, B_x, B_w1, B_b1, B_w2, B_b2):

    def _A_ref(x, mem0, Wq, Wk, Wv, Wo, seg_len):
        B, S, Dm = x.shape
        H, Dh = (Wq.shape[1], Wq.shape[2])
        M = mem0.shape[1]
        scale = Dh ** (-0.5)
        n_seg = S // seg_len
        L = M + seg_len
        idx = torch.arange(L)
        mask = (idx[:, None] < M) | (idx[:, None] >= idx[None, :])
        mem = mem0
        outs = []
        for s in range(n_seg):
            xs = x[:, s * seg_len:(s + 1) * seg_len, :].clone()
            h = torch.concatenate([mem, xs], axis=1)
            q = torch.einsum('btd,dhe->bhte', h, Wq)
            k = torch.einsum('btd,dhe->bhte', h, Wk)
            v = torch.einsum('btd,dhe->bhte', h, Wv)
            scores = torch.einsum('bhqe,bhke->bhqk', q, k) * scale
            scores = torch.where(mask[None, None], scores, -1000000000.0)
            p = _softmax(scores, axis=-1)
            o = torch.einsum('bhqk,bhke->bhqe', p, v)
            o = torch.einsum('bhte,hed->btd', o, Wo)
            mem = o[:, :M, :].clone()
            outs.append(o[:, M:, :])
        return torch.concatenate(outs, axis=1)

    def _B_ref(x, w1, b1, w2, b2):
        y = _layernorm(x, axis=-1)
        h = _gelu(torch.einsum('bsd,df->bsf', y, w1) + b1)
        return torch.einsum('bsf,fd->bsd', h, w2) + b2
    x = A_x
    xn = _layernorm(x, axis=-1)
    s = _A_ref(xn, A_mem0, A_Wq, A_Wk, A_Wv, A_Wo, A_seg_len)
    g = _silu(_B_ref(xn, B_w1, B_b1, B_w2, B_b2))
    return x + s * g
```

```cpp
#include <cuda_runtime.h>
#include <cuda_bf16.h>
#include <cuda.h>
#include <stdint.h>

typedef __nv_bfloat16 bf16;

#define S_TOK 2048
#define DM 512
#define NH 32
#define DH 128
#define HD 4096
#define NMEM 8
#define SEG 32
#define NSEG 64
#define FF 1792
#define NBLK 16
#define NREC 64
#define NCTA 132
#define NBULK (NCTA - NREC)

__device__ __align__(1024) bf16 g_xn[S_TOK * DM];
__device__ __align__(1024) bf16 g_y[S_TOK * DM];
__device__ __align__(1024) bf16 g_qkv[(size_t)S_TOK * 3 * HD];
__device__ __align__(1024) bf16 g_h1[S_TOK * FF];
__device__ __align__(1024) bf16 g_g[S_TOK * DM];
__device__ __align__(1024) bf16 g_o[(size_t)S_TOK * HD];
__device__ __align__(1024) bf16 g_km[NSEG * NH * NMEM * DH];
__device__ __align__(1024) bf16 g_vmt[NSEG * NH * DH * NMEM];
__device__ __align__(1024) float g_opart[(size_t)4 * S_TOK * DM];
__device__ __align__(1024) unsigned g_part[2 * NREC * NH * 64];
__device__ __align__(1024) unsigned g_pub[NSEG * 2048];
struct Flags {
  unsigned qkv[NBLK * 48];
  unsigned h1[NBLK];
  unsigned g[NBLK];
  unsigned o[NBLK * 4];
  unsigned p[NBLK * 2];
  unsigned ctr;
  unsigned rec[NREC];
  unsigned abort_;
};
__device__ __align__(1024) Flags g_flags;

__device__ __forceinline__ unsigned smem_u32(const void* p) { return (unsigned)__cvta_generic_to_shared(p); }
__device__ __forceinline__ float bf16r(float x) { return __bfloat162float(__float2bfloat16_rn(x)); }
__device__ __forceinline__ unsigned pack_bf16(float lo, float hi) {
  __nv_bfloat162 v = __floats2bfloat162_rn(lo, hi);
  return *reinterpret_cast<unsigned*>(&v);
}
__device__ __forceinline__ float bf_lo(unsigned u) { return __uint_as_float(u << 16); }
__device__ __forceinline__ float bf_hi(unsigned u) { return __uint_as_float(u & 0xffff0000u); }

#define SPIN_LIMIT (1u << 20)
__device__ __forceinline__ unsigned ld_acquire(const unsigned* p) {
  unsigned v; asm volatile("ld.acquire.gpu.global.u32 %0, [%1];" : "=r"(v) : "l"(p) : "memory"); return v;
}
__device__ __forceinline__ unsigned ld_relaxed(const unsigned* p) {
  unsigned v; asm volatile("ld.relaxed.gpu.global.u32 %0, [%1];" : "=r"(v) : "l"(p) : "memory"); return v;
}
__device__ __forceinline__ void red_release_add(unsigned* p, unsigned v) {
  asm volatile("red.release.gpu.global.add.u32 [%0], %1;" ::"l"(p), "r"(v) : "memory");
}
__device__ __forceinline__ void st_release(unsigned* p, unsigned v) {
  asm volatile("st.release.gpu.global.u32 [%0], %1;" ::"l"(p), "r"(v) : "memory");
}
__device__ __forceinline__ void wait_flag_ge(const unsigned* p, unsigned target) {
  unsigned it = 0;
  while (ld_acquire(p) < target) {
    __nanosleep(64);
    if (++it > SPIN_LIMIT) asm volatile("trap;");
  }
}
__device__ __forceinline__ uint4 ldv4_relaxed(const void* p) {
  uint4 a; asm volatile("ld.relaxed.gpu.global.v4.u32 {%0,%1,%2,%3}, [%4];" : "=r"(a.x), "=r"(a.y), "=r"(a.z), "=r"(a.w) : "l"(p) : "memory"); return a;
}
__device__ __forceinline__ void mbar_init(unsigned mb, unsigned cnt) { asm volatile("mbarrier.init.shared::cta.b64 [%0], %1;" ::"r"(mb), "r"(cnt) : "memory"); }
__device__ __forceinline__ void mbar_expect_tx(unsigned mb, unsigned bytes) { asm volatile("mbarrier.arrive.expect_tx.shared::cta.b64 _, [%0], %1;" ::"r"(mb), "r"(bytes) : "memory"); }
__device__ __forceinline__ void mbar_arrive(unsigned mb) { asm volatile("mbarrier.arrive.shared::cta.b64 _, [%0];" ::"r"(mb) : "memory"); }
__device__ __forceinline__ void mbar_wait(unsigned mb, unsigned parity) {
  unsigned ok, it = 0;
  while (true) {
    asm volatile("{.reg .pred p; mbarrier.try_wait.parity.shared::cta.b64 p, [%1], %2; selp.u32 %0,1,0,p;}" : "=r"(ok) : "r"(mb), "r"(parity) : "memory");
    if (ok) break;
    if (++it > SPIN_LIMIT) asm volatile("trap;");
  }
}
__device__ __forceinline__ void mbar_wait_cluster(unsigned mb, unsigned parity) {
  unsigned ok, it = 0;
  while (true) {
    asm volatile("{.reg .pred p; mbarrier.try_wait.parity.acquire.cluster.shared::cta.b64 p, [%1], %2; selp.u32 %0,1,0,p;}" : "=r"(ok) : "r"(mb), "r"(parity) : "memory");
    if (ok) break;
    if (++it > SPIN_LIMIT) asm volatile("trap;");
  }
}
__device__ __forceinline__ void bar_sync(int id, int n) { asm volatile("bar.sync %0, %1;" ::"r"(id), "r"(n) : "memory"); }
__device__ __forceinline__ void bar_arrive(int id, int n) { asm volatile("bar.arrive %0, %1;" ::"r"(id), "r"(n) : "memory"); }
__device__ __forceinline__ void tma_load_2d(unsigned dst, const CUtensorMap* map, int c0, int c1, unsigned mb) {
  asm volatile("cp.async.bulk.tensor.2d.shared::cluster.global.mbarrier::complete_tx::bytes [%0], [%1, {%3, %4}], [%2];"
               ::"r"(dst), "l"((uint64_t)map), "r"(mb), "r"(c0), "r"(c1) : "memory");
}
__device__ __forceinline__ void tma_store_2d(const CUtensorMap* map, unsigned src, int c0, int c1) {
  asm volatile("cp.async.bulk.tensor.2d.global.shared::cta.bulk_group [%0, {%2, %3}], [%1];"
               ::"l"((uint64_t)map), "r"(src), "r"(c0), "r"(c1) : "memory");
}
__device__ __forceinline__ void fence_proxy_async() { asm volatile("fence.proxy.async;" ::: "memory"); }
__device__ __forceinline__ void fence_proxy_async_smem() { asm volatile("fence.proxy.async.shared::cta;" ::: "memory"); }
__device__ __forceinline__ void ldsm_x4(unsigned* r, unsigned addr) {
  asm volatile("ldmatrix.sync.aligned.m8n8.x4.shared.b16 {%0,%1,%2,%3}, [%4];" : "=r"(r[0]), "=r"(r[1]), "=r"(r[2]), "=r"(r[3]) : "r"(addr) : "memory");
}
__device__ __forceinline__ void ldsm_x4_t(unsigned* r, unsigned addr) {
  asm volatile("ldmatrix.sync.aligned.m8n8.x4.trans.shared.b16 {%0,%1,%2,%3}, [%4];" : "=r"(r[0]), "=r"(r[1]), "=r"(r[2]), "=r"(r[3]) : "r"(addr) : "memory");
}
__device__ __forceinline__ void stsm_x2_t(unsigned addr, unsigned r0, unsigned r1) {
  asm volatile("stmatrix.sync.aligned.m8n8.x2.trans.shared.b16 [%0], {%1,%2};" ::"r"(addr), "r"(r0), "r"(r1) : "memory");
}
__device__ __forceinline__ void stsm_x4(unsigned addr, unsigned r0, unsigned r1, unsigned r2, unsigned r3) {
  asm volatile("stmatrix.sync.aligned.m8n8.x4.shared.b16 [%0], {%1,%2,%3,%4};" ::"r"(addr), "r"(r0), "r"(r1), "r"(r2), "r"(r3) : "memory");
}
__device__ __forceinline__ void mma16816(float* d, const unsigned* a, unsigned b0, unsigned b1) {
  asm volatile("mma.sync.aligned.m16n8k16.row.col.f32.bf16.bf16.f32 {%0,%1,%2,%3}, {%4,%5,%6,%7}, {%8,%9}, {%0,%1,%2,%3};"
               : "+f"(d[0]), "+f"(d[1]), "+f"(d[2]), "+f"(d[3]) : "r"(a[0]), "r"(a[1]), "r"(a[2]), "r"(a[3]), "r"(b0), "r"(b1));
}
__device__ __forceinline__ void mma1688(float* d, unsigned a0, unsigned a1, unsigned b0) {
  asm volatile("mma.sync.aligned.m16n8k8.row.col.f32.bf16.bf16.f32 {%0,%1,%2,%3}, {%4,%5}, {%6}, {%0,%1,%2,%3};"
               : "+f"(d[0]), "+f"(d[1]), "+f"(d[2]), "+f"(d[3]) : "r"(a0), "r"(a1), "r"(b0));
}
__device__ __forceinline__ uint64_t mkdesc(unsigned addr, unsigned lbo, unsigned sbo) {
  return (uint64_t)((addr >> 4) & 0x3fff) | ((uint64_t)(lbo >> 4) << 16) | ((uint64_t)(sbo >> 4) << 32) | (1ull << 62);
}
#define R8(b) "+f"(d[b]), "+f"(d[b + 1]), "+f"(d[b + 2]), "+f"(d[b + 3]), "+f"(d[b + 4]), "+f"(d[b + 5]), "+f"(d[b + 6]), "+f"(d[b + 7])
#define R32(b) R8(b), R8(b + 8), R8(b + 16), R8(b + 24)
__device__ __forceinline__ void wgmma_n256(float* d, uint64_t ad, uint64_t bd, int acc) {
  asm volatile(
      "{.reg .pred p; setp.ne.b32 p, %130, 0;\n"
      "wgmma.mma_async.sync.aligned.m64n256k16.f32.bf16.bf16 "
      "{%0,%1,%2,%3,%4,%5,%6,%7,%8,%9,%10,%11,%12,%13,%14,%15,%16,%17,%18,%19,%20,%21,%22,%23,%24,%25,%26,%27,%28,%29,%30,%31,"
      "%32,%33,%34,%35,%36,%37,%38,%39,%40,%41,%42,%43,%44,%45,%46,%47,%48,%49,%50,%51,%52,%53,%54,%55,%56,%57,%58,%59,%60,%61,%62,%63,"
      "%64,%65,%66,%67,%68,%69,%70,%71,%72,%73,%74,%75,%76,%77,%78,%79,%80,%81,%82,%83,%84,%85,%86,%87,%88,%89,%90,%91,%92,%93,%94,%95,"
      "%96,%97,%98,%99,%100,%101,%102,%103,%104,%105,%106,%107,%108,%109,%110,%111,%112,%113,%114,%115,%116,%117,%118,%119,%120,%121,%122,%123,%124,%125,%126,%127},"
      "%128, %129, p, 1, 1, 0, 1;}\n"
      : R32(0), R32(32), R32(64), R32(96)
      : "l"(ad), "l"(bd), "r"(acc));
}

__device__ __forceinline__ void ln16(const float* x, float* o) {
  float s = 0;
#pragma unroll
  for (int i = 0; i < 16; i++) s += x[i];
#pragma unroll
  for (int of = 16; of > 0; of >>= 1) s += __shfl_xor_sync(~0u, s, of);
  float mean = s * (1.0f / DM);
  float v = 0;
#pragma unroll
  for (int i = 0; i < 16; i++) { float dd = x[i] - mean; v += dd * dd; }
#pragma unroll
  for (int of = 16; of > 0; of >>= 1) v += __shfl_xor_sync(~0u, v, of);
  float mb = bf16r(mean);
  float vb = bf16r(v * (1.0f / DM));
  float den = bf16r(sqrtf(bf16r(vb + 1e-5f)));
#pragma unroll
  for (int i = 0; i < 16; i++) o[i] = bf16r(__fdiv_rn(bf16r(x[i] - mb), den));
}
__global__ void __launch_bounds__(256) k_pre(const bf16* __restrict__ x) {
  int t = threadIdx.x, lane = t & 31, w = t >> 5;
  int row = blockIdx.x * 8 + w;
  const uint4* src = reinterpret_cast<const uint4*>(x + (size_t)row * DM);
  uint4 a = src[lane], b = src[lane + 32];
  unsigned u[8] = {a.x, a.y, a.z, a.w, b.x, b.y, b.z, b.w};
  float f[16], o[16], o2[16];
#pragma unroll
  for (int i = 0; i < 8; i++) { f[2 * i] = bf_lo(u[i]); f[2 * i + 1] = bf_hi(u[i]); }
  ln16(f, o);
  ln16(o, o2);
  uint4* d1 = reinterpret_cast<uint4*>(g_xn + (size_t)row * DM);
  uint4* d2 = reinterpret_cast<uint4*>(g_y + (size_t)row * DM);
  d1[lane] = make_uint4(pack_bf16(o[0], o[1]), pack_bf16(o[2], o[3]), pack_bf16(o[4], o[5]), pack_bf16(o[6], o[7]));
  d1[lane + 32] = make_uint4(pack_bf16(o[8], o[9]), pack_bf16(o[10], o[11]), pack_bf16(o[12], o[13]), pack_bf16(o[14], o[15]));
  d2[lane] = make_uint4(pack_bf16(o2[0], o2[1]), pack_bf16(o2[2], o2[3]), pack_bf16(o2[4], o2[5]), pack_bf16(o2[6], o2[7]));
  d2[lane + 32] = make_uint4(pack_bf16(o2[8], o2[9]), pack_bf16(o2[10], o2[11]), pack_bf16(o2[12], o2[13]), pack_bf16(o2[14], o2[15]));
  int gt = blockIdx.x * 256 + t;
  uint4 z = make_uint4(0, 0, 0, 0);
  reinterpret_cast<uint4*>(g_part)[gt] = z;
  if (gt < NSEG * 2048 / 4) reinterpret_cast<uint4*>(g_pub)[gt] = z;
  if (gt < (int)(sizeof(Flags) / 4)) reinterpret_cast<unsigned*>(&g_flags)[gt] = 0;
}

struct Maps { CUtensorMap xn, y, h1, o, qkv_st, qkv_ld, g, wq, wk, wv, wo, w1, w2; };

#define NSTAGE 3
#define STAGE_BYTES 49152
#define B_STG (NSTAGE * STAGE_BYTES)
#define R_WO 0
#define R_T1 65536
#define R_T2 131072
#define R_RING 65536
#define RING_N 8
#define RING_BYTES 12288
#define R_MEM 196608
#define R_QS (R_MEM + 8448)
#define R_KS (R_QS + 1152)
#define R_OS (R_KS + 1152)
#define R_SOWN (R_OS + 2176)
#define R_SPEER (R_SOWN + 1280)
#define R_VM (R_SPEER + 1280)
#define R_VRED (R_VM + 2048)
#define R_RED (R_VRED + 2048)
#define SM_BAR (R_RED + 2048)
#define SMEM_TOTAL (SM_BAR + 256 + 1024)
#define MB_FULL 0
#define MB_EMPTY 8
#define MB_STGF 16
#define MB_STGE 17
#define MB_W0 18
#define MB_W1 19
#define MB_WO 20
#define MB_S 21
#define MB_V 22
#define MB_KVR 23
#define MB_KVF 24
#define SM_MISC (SM_BAR + 208)

#define N_KV 512
#define I_Q 512
#define I_M1 768
#define I_M2 880
#define I_POST 912
#define N_ITEMS 1296
enum { T_QKV = 0, T_M1 = 1, T_M2 = 2, T_ATT = 3, T_OUT = 4 };
struct Item { int type, b, c, ks; };
__device__ __forceinline__ Item decode_item(int i) {
  Item it; it.ks = 0;
  if (i < N_KV) { it.type = T_QKV; it.b = i >> 5; it.c = 16 + (i & 31); }
  else if (i < I_M1) { it.type = T_QKV; it.b = (i - I_Q) >> 4; it.c = (i - I_Q) & 15; }
  else if (i < I_M2) { it.type = T_M1; it.b = (i - I_M1) / 7; it.c = (i - I_M1) % 7; }
  else if (i < I_POST) { it.type = T_M2; it.b = (i - I_M2) >> 1; it.c = (i - I_M2) & 1; }
  else {
    int x = i - I_POST;
    if (x < 16) { it.type = T_ATT; it.b = 0; it.c = x; }
    else {
      x -= 16; int p = 1 + x / 24, r = x % 24;
      if (p < 16 && r < 16) { it.type = T_ATT; it.b = p; it.c = r; }
      else { if (p < 16) r -= 16; it.type = T_OUT; it.b = p - 1; it.c = r & 1; it.ks = r >> 1; }
    }
  }
  return it;
}
__device__ __forceinline__ int item_nkb(int type) { return type == T_M2 ? 28 : (type == T_OUT ? 16 : (type == T_ATT ? 4 : 8)); }


__device__ __forceinline__ void st_async_b64(unsigned raddr, unsigned lo, unsigned hi, unsigned rmb) {
  asm volatile("st.async.weak.shared::cluster.mbarrier::complete_tx::bytes.v2.b32 [%0], {%1,%2}, [%3];" ::"r"(raddr), "r"(lo), "r"(hi), "r"(rmb) : "memory");
}
__device__ __forceinline__ unsigned mapa(unsigned a, unsigned rank) {
  unsigned r; asm volatile("mapa.shared::cluster.u32 %0, %1, %2;" : "=r"(r) : "r"(a), "r"(rank)); return r;
}
__device__ __forceinline__ void sts64(unsigned a, unsigned x, unsigned y) { asm volatile("st.shared.v2.b32 [%0], {%1,%2};" ::"r"(a), "r"(x), "r"(y) : "memory"); }
__device__ __forceinline__ void sts128(unsigned a, uint4 v) { asm volatile("st.shared.v4.b32 [%0], {%1,%2,%3,%4};" ::"r"(a), "r"(v.x), "r"(v.y), "r"(v.z), "r"(v.w) : "memory"); }
__device__ __forceinline__ uint2 lds64(unsigned a) { uint2 v; asm volatile("ld.shared.v2.b32 {%0,%1}, [%2];" : "=r"(v.x), "=r"(v.y) : "r"(a) : "memory"); return v; }
__device__ __forceinline__ uint4 lds128(unsigned a) { uint4 v; asm volatile("ld.shared.v4.b32 {%0,%1,%2,%3}, [%4];" : "=r"(v.x), "=r"(v.y), "=r"(v.z), "=r"(v.w) : "r"(a) : "memory"); return v; }
__device__ __forceinline__ float lds32f(unsigned a) { float v; asm volatile("ld.shared.f32 %0, [%1];" : "=f"(v) : "r"(a) : "memory"); return v; }
__device__ __forceinline__ void spin_check(unsigned& it) { if (++it > SPIN_LIMIT) asm volatile("trap;"); }
#define SCALE_QK 0.08838834764831845f

__device__ __forceinline__ void rec_worker(const Maps& maps, unsigned sb, const bf16* __restrict__ mem0) {
  const int c = blockIdx.x, h = c >> 1, j = c & 1;
  const int t = threadIdx.x, lane = t & 31, w = t >> 5, g = lane >> 2, tq = lane & 3;
  const int m = lane >> 3, r8 = lane & 7, kh = w >> 2, et = w & 3;
  const unsigned bar = sb + SM_BAR;
  unsigned wqk[32][4], wv[16][4];
  mbar_wait(bar + 8 * MB_W0, 0);
  {
    unsigned base = sb + (kh ? R_T1 : R_WO);
#pragma unroll
    for (int i = 0; i < 32; i++) {
      int ks = (i + 16 * kh) & 31;
      int row = (ks & 3) * 16 + (m >> 1) * 8 + r8;
      ldsm_x4_t(wqk[i], base + (ks >> 2) * 8192 + row * 128 + (((et * 2 + (m & 1)) ^ r8) << 4));
    }
  }
  bar_sync(1, 256);
  if (t == 0) {
    fence_proxy_async_smem();
    mbar_expect_tx(bar + 8 * MB_WO, 65536);
    for (int kb = 0; kb < 2; kb++)
      for (int cb = 0; cb < 4; cb++) tma_load_2d(sb + R_WO + (kb * 4 + cb) * 8192, &maps.wo, j * 256 + cb * 64, h * 128 + kb * 64, bar + 8 * MB_WO);
  }
  mbar_wait(bar + 8 * MB_W1, 0);
#pragma unroll
  for (int i = 0; i < 16; i++) {
    int ks = i + 16 * kh;
    int row = (ks & 3) * 16 + (m >> 1) * 8 + r8;
    ldsm_x4_t(wv[i], sb + R_T2 + (ks >> 2) * 8192 + row * 128 + (((et * 2 + (m & 1)) ^ r8) << 4));
  }
  bar_sync(2, 288);
  const unsigned peer = j ^ 1;
  const unsigned rS = mapa(sb + R_SPEER, peer), rV = mapa(sb + R_VM, peer), rmbS = mapa(bar + 8 * MB_S, peer), rmbV = mapa(bar + 8 * MB_V, peer);
  const unsigned pA = sb + R_MEM + r8 * 1040 + m * 16 + kh * 512, pB = sb + R_MEM + r8 * 1040 + m * 16 + (1 - kh) * 512;
  mbar_wait(bar + 8 * MB_WO, 0);

#pragma unroll 1
  for (int s = 0; s < NSEG; s++) {
    const unsigned par = s & 1;
    const unsigned slot = s & (RING_N - 1), rpar = (s / RING_N) & 1;
    const unsigned ring = sb + R_RING + slot * RING_BYTES;
    if (t == 0 && s < NSEG - 1) { mbar_expect_tx(bar + 8 * MB_S, 1280); mbar_expect_tx(bar + 8 * MB_V, 1024); }
    if (s > 0) mbar_wait(bar + 8 * MB_KVF, par ^ 1);
    if (s == 0) {
#pragma unroll
      for (int u = 0; u < 2; u++) {
        int i = t + 256 * u;
        uint4 v = __ldg(reinterpret_cast<const uint4*>(mem0) + i);
        sts128(sb + R_MEM + (i >> 6) * 1040 + (i & 63) * 16, v);
      }
    } else {
      const uint4* src = reinterpret_cast<const uint4*>(g_pub) + s * 512 + t;
      uint4 a, b; bool oka = false, okb = false; unsigned it = 0;
      while (true) {
        if (!oka) { a = ldv4_relaxed(src); oka = a.x && a.y && a.z && a.w; }
        if (!okb) { b = ldv4_relaxed(src + 256); okb = b.x && b.y && b.z && b.w; }
        if (oka && okb) break;
        spin_check(it);
      }
      sts128(sb + R_MEM + (t & 7) * 1040 + (t >> 3) * 16, a);
      sts128(sb + R_MEM + (t & 7) * 1040 + (t >> 3) * 16 + 512, b);
    }
    bar_sync(1, 256);
    float a0[4] = {0, 0, 0, 0}, a1[4] = {0, 0, 0, 0}, v0[4] = {0, 0, 0, 0}, v1[4] = {0, 0, 0, 0};
#pragma unroll
    for (int i = 0; i < 8; i++) {
      unsigned b[4]; ldsm_x4(b, pA + i * 64);
      mma16816(a0, wqk[2 * i], b[0], b[1]); mma16816(v0, wv[2 * i], b[0], b[1]);
      mma16816(a1, wqk[2 * i + 1], b[2], b[3]); mma16816(v1, wv[2 * i + 1], b[2], b[3]);
    }
#pragma unroll
    for (int i = 0; i < 8; i++) {
      unsigned b[4]; ldsm_x4(b, pB + i * 64);
      mma16816(a0, wqk[16 + 2 * i], b[0], b[1]);
      mma16816(a1, wqk[16 + 2 * i + 1], b[2], b[3]);
    }
    stsm_x2_t(sb + (kh ? R_KS : R_QS) + r8 * 144 + (et * 16 + (m & 1) * 8) * 2, pack_bf16(a0[0] + a1[0], a0[1] + a1[1]), pack_bf16(a0[2] + a1[2], a0[3] + a1[3]));
#pragma unroll
    for (int i = 0; i < 4; i++) v0[i] += v1[i];
    if (kh == 0) asm volatile("st.shared.v4.f32 [%0], {%1,%2,%3,%4};" ::"r"(sb + R_VRED + et * 512 + lane * 16), "f"(v0[0]), "f"(v0[1]), "f"(v0[2]), "f"(v0[3]) : "memory");
    mbar_wait(bar + 8 * (MB_FULL + slot), rpar);
    bar_sync(1, 256);
    if (w <= 4 && s < NSEG - 1) {
      unsigned qa[8], kb[8];
      ldsm_x4(qa, sb + R_QS + r8 * 144 + m * 16); ldsm_x4(qa + 4, sb + R_QS + r8 * 144 + m * 16 + 64);
      if (w == 4) { ldsm_x4(kb, sb + R_KS + r8 * 144 + m * 16); ldsm_x4(kb + 4, sb + R_KS + r8 * 144 + m * 16 + 64); }
      else { unsigned ka = ring + (w * 8 + r8) * 128; ldsm_x4(kb, ka + ((m ^ r8) << 4)); ldsm_x4(kb + 4, ka + (((m + 4) ^ r8) << 4)); }
      float s0[4] = {0, 0, 0, 0}, s1[4] = {0, 0, 0, 0};
      unsigned af[4];
      af[1] = af[3] = 0;
      af[0] = qa[0]; af[2] = qa[1]; mma16816(s0, af, kb[0], kb[1]);
      af[0] = qa[2]; af[2] = qa[3]; mma16816(s1, af, kb[2], kb[3]);
      af[0] = qa[4]; af[2] = qa[5]; mma16816(s0, af, kb[4], kb[5]);
      af[0] = qa[6]; af[2] = qa[7]; mma16816(s1, af, kb[6], kb[7]);
      unsigned x = __float_as_uint(s0[0] + s1[0]), y = __float_as_uint(s0[1] + s1[1]);
      st_async_b64(rS + w * 256 + lane * 8, x, y, rmbS);
      sts64(sb + R_SOWN + w * 256 + lane * 8, x, y);
    }
    if (kh == 1) {
      uint4 o = lds128(sb + R_VRED + et * 512 + lane * 16);
      unsigned x = pack_bf16(v0[0] + __uint_as_float(o.x), v0[1] + __uint_as_float(o.y)), y = pack_bf16(v0[2] + __uint_as_float(o.z), v0[3] + __uint_as_float(o.w));
      if (s < NSEG - 1) st_async_b64(rV + (j * 4 + et) * 256 + lane * 8, x, y, rmbV);
      sts64(sb + R_VM + (j * 4 + et) * 256 + lane * 8, x, y);
    }
    unsigned vx[2][4];
    {
      unsigned vb = ring + 4096 + kh * 4096;
#pragma unroll
      for (int kk = 0; kk < 2; kk++) { int row = kk * 16 + (m >> 1) * 8 + r8; ldsm_x4_t(vx[kk], vb + row * 128 + (((et * 2 + (m & 1)) ^ r8) << 4)); }
    }
    bar_sync(1, 256);
    if (lane == 0) { mbar_arrive(bar + 8 * (MB_EMPTY + slot)); if (w == 0) mbar_arrive(bar + 8 * MB_KVR); }
    if (s == NSEG - 1) break;
    mbar_wait_cluster(bar + 8 * MB_S, par);
    float sc[10];
#pragma unroll
    for (int i = 0; i < 5; i++) {
      uint2 o = lds64(sb + R_SOWN + i * 256 + lane * 8), p = lds64(sb + R_SPEER + i * 256 + lane * 8);
      float x0 = __uint_as_float(o.x) + __uint_as_float(p.x);
      float x1 = __uint_as_float(o.y) + __uint_as_float(p.y);
      sc[2 * i] = bf16r(bf16r(x0) * SCALE_QK); sc[2 * i + 1] = bf16r(bf16r(x1) * SCALE_QK);
    }
    float mx = sc[0];
#pragma unroll
    for (int i = 1; i < 10; i++) mx = fmaxf(mx, sc[i]);
    mx = fmaxf(mx, __shfl_xor_sync(~0u, mx, 1)); mx = fmaxf(mx, __shfl_xor_sync(~0u, mx, 2));
    float sum = 0;
#pragma unroll
    for (int i = 0; i < 10; i++) { sc[i] = __expf(sc[i] - mx); sum += sc[i]; }
    sum += __shfl_xor_sync(~0u, sum, 1); sum += __shfl_xor_sync(~0u, sum, 2);
    float inv = __fdividef(1.0f, sum);
    unsigned p[5];
#pragma unroll
    for (int i = 0; i < 5; i++) p[i] = pack_bf16(sc[2 * i] * inv, sc[2 * i + 1] * inv);
    float o0[4] = {0, 0, 0, 0}, o1[4] = {0, 0, 0, 0};
    mma16816(o0, vx[0], p[0], p[1]); mma16816(o1, vx[1], p[2], p[3]);
    mbar_wait_cluster(bar + 8 * MB_V, par);
    { uint2 vm = lds64(sb + R_VM + w * 256 + lane * 8); mma1688(o0, vm.x, vm.y, p[4]); }
    stsm_x2_t(sb + R_OS + r8 * 272 + (w * 16 + (m & 1) * 8) * 2, pack_bf16(o0[0] + o1[0], o0[1] + o1[1]), pack_bf16(o0[2] + o1[2], o0[3] + o1[3]));
    bar_sync(1, 256);
    {
      float d0[4] = {0, 0, 0, 0}, d1[4] = {0, 0, 0, 0};
#pragma unroll
      for (int k2 = 0; k2 < 4; k2++) {
        unsigned b[4]; ldsm_x4(b, sb + R_OS + r8 * 272 + m * 16 + k2 * 64);
#pragma unroll
        for (int u = 0; u < 2; u++) {
          int ks = 2 * k2 + u;
          int row = (ks & 3) * 16 + (m >> 1) * 8 + r8;
          unsigned wa = sb + R_WO + ((ks >> 2) * 4 + (w >> 1)) * 8192 + row * 128;
          unsigned f0[4], f1[4];
          ldsm_x4_t(f0, wa + ((((w & 1) * 4 + (m & 1)) ^ r8) << 4));
          ldsm_x4_t(f1, wa + ((((w & 1) * 4 + 2 + (m & 1)) ^ r8) << 4));
          mma16816(d0, f0, b[2 * u], b[2 * u + 1]); mma16816(d1, f1, b[2 * u], b[2 * u + 1]);
        }
      }
      const unsigned tag = ((s >> 1) & 1) ^ 1;
      unsigned* dst = g_part + ((size_t)(par * NREC + 32 * j + 4 * w) * NH + h) * 64 + g * 8 + 2 * tq;
#define PST(ptr, x, y) asm volatile("st.relaxed.gpu.global.v2.u32 [%0], {%1,%2};" ::"l"(ptr), "r"((__float_as_uint(x) & ~1u) | tag), "r"((__float_as_uint(y) & ~1u) | tag) : "memory")
      PST(dst, d0[0], d0[1]); PST(dst + NH * 64, d0[2], d0[3]); PST(dst + 2 * NH * 64, d1[0], d1[1]); PST(dst + 3 * NH * 64, d1[2], d1[3]);
      const uint4* src = reinterpret_cast<const uint4*>(g_part + ((size_t)(par * NREC + c) * NH + 4 * w) * 64) + lane;
      uint4 a, b; bool oka = false, okb = false; unsigned it = 0;
      while (true) {
        if (!oka) { a = ldv4_relaxed(src); oka = ((a.x & a.y & a.z & a.w & 1u) == tag) && (((a.x | a.y | a.z | a.w) & 1u) == tag); }
        if (!okb) { b = ldv4_relaxed(src + 32); okb = ((b.x & b.y & b.z & b.w & 1u) == tag) && (((b.x | b.y | b.z | b.w) & 1u) == tag); }
        if (oka && okb) break;
        spin_check(it);
      }
      float r0 = __uint_as_float(a.x) + __uint_as_float(b.x), r1 = __uint_as_float(a.y) + __uint_as_float(b.y);
      float r2 = __uint_as_float(a.z) + __uint_as_float(b.z), r3 = __uint_as_float(a.w) + __uint_as_float(b.w);
      r0 += __shfl_xor_sync(~0u, r0, 16); r1 += __shfl_xor_sync(~0u, r1, 16); r2 += __shfl_xor_sync(~0u, r2, 16); r3 += __shfl_xor_sync(~0u, r3, 16);
      if (lane < 16) asm volatile("st.shared.v4.f32 [%0], {%1,%2,%3,%4};" ::"r"(sb + R_RED + w * 256 + lane * 16), "f"(r0), "f"(r1), "f"(r2), "f"(r3) : "memory");
      if (w != 0) { bar_arrive(3, 256); }
      else {
        bar_sync(3, 256);
        float x0 = 0, x1 = 0;
#pragma unroll
        for (int i = 0; i < 8; i++) { x0 += lds32f(sb + R_RED + i * 256 + (2 * tq) * 32 + g * 4); x1 += lds32f(sb + R_RED + i * 256 + (2 * tq + 1) * 32 + g * 4); }
        unsigned u = pack_bf16(x0, x1);
        if (u == 0) u = 0x80000000u;
        asm volatile("st.relaxed.gpu.global.u32 [%0], %1;" ::"l"(g_pub + (s + 1) * 2048 + c * 32 + lane), "r"(u) : "memory");
      }
    }
  }
}

__device__ __forceinline__ void rec_ring(const Maps& maps, unsigned sb) {
  const int c = blockIdx.x, h = c >> 1, j = c & 1;
  const unsigned bar = sb + SM_BAR;
  const int lane = threadIdx.x & 31;
  if (lane == 0) {
    mbar_expect_tx(bar + 8 * MB_W0, 131072);
    for (int kb = 0; kb < 8; kb++) tma_load_2d(sb + R_WO + kb * 8192, &maps.wq, h * 128 + j * 64, kb * 64, bar + 8 * MB_W0);
    for (int kb = 0; kb < 8; kb++) tma_load_2d(sb + R_T1 + kb * 8192, &maps.wk, h * 128 + j * 64, kb * 64, bar + 8 * MB_W0);
    mbar_expect_tx(bar + 8 * MB_W1, 65536);
    for (int kb = 0; kb < 8; kb++) tma_load_2d(sb + R_T2 + kb * 8192, &maps.wv, h * 128 + j * 64, kb * 64, bar + 8 * MB_W1);
  }
  __syncwarp();
  bar_sync(2, 288);
  if (lane == 0) {
    fence_proxy_async_smem();
    for (int s = 0; s < NSEG; s++) {
      unsigned slot = s & (RING_N - 1);
      if ((s & 3) == 0) {
        wait_flag_ge(&g_flags.qkv[(s >> 2) * 48 + 16 + (h >> 1)], 1);
        wait_flag_ge(&g_flags.qkv[(s >> 2) * 48 + 32 + (h >> 1)], 1);
        fence_proxy_async();
      }
      if (s >= RING_N) mbar_wait(bar + 8 * (MB_EMPTY + slot), ((s / RING_N) - 1) & 1);
      unsigned dst = sb + R_RING + slot * RING_BYTES, mb = bar + 8 * (MB_FULL + slot);
      mbar_expect_tx(mb, RING_BYTES);
      tma_load_2d(dst, &maps.qkv_ld, HD + h * 128 + j * 64, s * SEG, mb);
      tma_load_2d(dst + 4096, &maps.qkv_ld, 2 * HD + h * 128, s * SEG, mb);
      tma_load_2d(dst + 8192, &maps.qkv_ld, 2 * HD + h * 128 + 64, s * SEG, mb);
    }
  }
}
__device__ __forceinline__ void rec_copy(unsigned sb) {
  const int c = blockIdx.x, h = c >> 1, j = c & 1;
  const unsigned bar = sb + SM_BAR;
  const int lane = threadIdx.x & 31;
  for (int s = 0; s < NSEG; s++) {
    mbar_wait(bar + 8 * MB_KVR, s & 1);
    uint4 k0 = lds128(sb + R_KS + (lane >> 3) * 144 + (lane & 7) * 16), k1 = lds128(sb + R_KS + (4 + (lane >> 3)) * 144 + (lane & 7) * 16);
    uint2 v[4];
#pragma unroll
    for (int i = 0; i < 4; i++) v[i] = lds64(sb + R_VM + (j * 4 + i) * 256 + lane * 8);
    __syncwarp();
    if (lane == 0) mbar_arrive(bar + 8 * MB_KVF);
    bf16* kd = g_km + ((size_t)(s * NH + h) * NMEM) * DH + j * 64;
    *reinterpret_cast<uint4*>(kd + (lane >> 3) * DH + (lane & 7) * 8) = k0;
    *reinterpret_cast<uint4*>(kd + (4 + (lane >> 3)) * DH + (lane & 7) * 8) = k1;
    unsigned* vd = reinterpret_cast<unsigned*>(g_vmt) + ((size_t)(s * NH + h) * DH + j * 64) * 4;
#pragma unroll
    for (int i = 0; i < 4; i++) { vd[(i * 16) * 4 + lane] = v[i].x; vd[(i * 16 + 8) * 4 + lane] = v[i].y; }
    __threadfence();
    __syncwarp();
    if (lane == 0) st_release(&g_flags.rec[c], s + 1);
  }
}

__device__ __forceinline__ void bulk_producer(const Maps& maps, unsigned sb, int* misc) {
  const unsigned bar = sb + SM_BAR;
  unsigned st = 0, ph = 0, seq = 0;
  while (true) {
    int idx = (int)atomicAdd(&g_flags.ctr, 1u);
    if (idx >= N_ITEMS) {
      mbar_wait(bar + 8 * (MB_EMPTY + st), ph ^ 1);
      misc[seq & 3] = -1;
      mbar_arrive(bar + 8 * (MB_FULL + st));
      break;
    }
    Item it = decode_item(idx);
    const CUtensorMap *ma, *mb_; int ka = 0, kbr = 0, nb0 = it.c * 256;
    if (it.type == T_QKV) { ma = &maps.xn; mb_ = it.c < 16 ? &maps.wq : (it.c < 32 ? &maps.wk : &maps.wv); nb0 = (it.c & 15) * 256; }
    else if (it.type == T_M1) { ma = &maps.y; mb_ = &maps.w1; }
    else if (it.type == T_M2) { ma = &maps.h1; mb_ = &maps.w2; wait_flag_ge(&g_flags.h1[it.b], 7); }
    else if (it.type == T_OUT) { ma = &maps.o; mb_ = &maps.wo; ka = kbr = it.ks * 1024; wait_flag_ge(&g_flags.o[it.b * 4 + it.ks], 4); wait_flag_ge(&g_flags.g[it.b], 2); }
    else {
      ma = mb_ = &maps.qkv_ld;
      wait_flag_ge(&g_flags.qkv[it.b * 48 + it.c], 1); wait_flag_ge(&g_flags.qkv[it.b * 48 + 16 + it.c], 1); wait_flag_ge(&g_flags.qkv[it.b * 48 + 32 + it.c], 1);
      for (int i = 0; i < 4; i++) wait_flag_ge(&g_flags.rec[it.c * 4 + i], it.b * 4 + 4);
    }
    fence_proxy_async();
    const int nkb = item_nkb(it.type);
    for (int kb = 0; kb < nkb; kb++) {
      mbar_wait(bar + 8 * (MB_EMPTY + st), ph ^ 1);
      if (kb == 0) { misc[seq & 3] = idx; seq++; }
      unsigned dst = sb + st * STAGE_BYTES, mb = bar + 8 * (MB_FULL + st);
      mbar_expect_tx(mb, STAGE_BYTES);
      if (it.type == T_ATT) {
        int head = it.c * 2 + (kb >> 1), row = it.b * 128 + (kb & 1) * 64;
        for (int i = 0; i < 12; i++) tma_load_2d(dst + i * 4096, ma, (i >> 2) * HD + head * 128 + (i & 1) * 64, row + ((i >> 1) & 1) * 32, mb);
      } else {
        tma_load_2d(dst, ma, ka + kb * 64, it.b * 128, mb);
        for (int i = 0; i < 4; i++) tma_load_2d(dst + 16384 + i * 8192, mb_, nb0 + i * 64, kbr + kb * 64, mb);
      }
      if (++st == NSTAGE) { st = 0; ph ^= 1; }
    }
  }
}
__device__ __forceinline__ void bulk_store(const Maps& maps, unsigned sb, volatile int* misc) {
  const unsigned bar = sb + SM_BAR;
  unsigned ph = 0;
  while (true) {
    mbar_wait(bar + 8 * MB_STGF, ph); ph ^= 1;
    int idx = misc[4];
    if (idx < 0) break;
    Item it = decode_item(idx);
    const CUtensorMap* mp = it.type == T_QKV ? &maps.qkv_st : (it.type == T_M1 ? &maps.h1 : (it.type == T_M2 ? &maps.g : &maps.o));
    unsigned* flag = it.type == T_QKV ? &g_flags.qkv[it.b * 48 + it.c] : (it.type == T_M1 ? &g_flags.h1[it.b] : (it.type == T_M2 ? &g_flags.g[it.b] : &g_flags.o[it.b * 4 + (it.c >> 2)]));
    for (int i = 0; i < 4; i++) tma_store_2d(mp, sb + B_STG + i * 16384, it.c * 256 + i * 64, it.b * 128);
    asm volatile("cp.async.bulk.commit_group;" ::: "memory");
    asm volatile("cp.async.bulk.wait_group.read 0;" ::: "memory");
    mbar_arrive(bar + 8 * MB_STGE);
    asm volatile("cp.async.bulk.wait_group 0;" ::: "memory");
    fence_proxy_async();
    __threadfence();
    red_release_add(flag, 1);
  }
}
__device__ __forceinline__ float gelu_t(float x) {
  float u = 0.7978845608028654f * (x + 0.044715f * x * x * x);
  return __fdividef(x, 1.0f + __expf(-2.0f * u));
}
__device__ __forceinline__ float silu_f(float x) { return __fdividef(x, 1.0f + __expf(-x)); }

__device__ __forceinline__ void bulk_att_stage(unsigned sa, unsigned stg, int b, int hp, int kb, int w, int lane) {
  const int g = lane >> 2, tq = lane & 3, m = lane >> 3, r8 = lane & 7;
  const int seg = w >> 2, mt = (w >> 1) & 1, eh = w & 1;
  const int head = hp * 2 + (kb >> 1), sg = b * 4 + (kb & 1) * 2 + seg;
  const unsigned* kmp = reinterpret_cast<const unsigned*>(g_km + ((size_t)(sg * NH + head) * NMEM + g) * DH) + tq;
  const unsigned* vmp = reinterpret_cast<const unsigned*>(g_vmt) + ((size_t)(sg * NH + head) * DH + eh * 64) * 4 + lane;
  unsigned km[16], vm[8];
#pragma unroll
  for (int i = 0; i < 16; i++) km[i] = __ldcg(kmp + i * 4);
#pragma unroll
  for (int i = 0; i < 8; i++) vm[i] = __ldcg(vmp + i * 32);
  float s[5][4];
#pragma unroll
  for (int i = 0; i < 5; i++) { s[i][0] = s[i][1] = s[i][2] = s[i][3] = 0; }
  const unsigned qb = sa + (0 * 2 + seg) * 8192, kbs = sa + (1 * 2 + seg) * 8192, vb = sa + (2 * 2 + seg) * 8192 + eh * 4096;
  unsigned qa[8][4];
#pragma unroll
  for (int ks = 0; ks < 8; ks++) {
    int row = mt * 16 + (m & 1) * 8 + r8;
    ldsm_x4(qa[ks], qb + (ks >> 2) * 4096 + row * 128 + ((((ks & 3) * 2 + (m >> 1)) ^ r8) << 4));
    unsigned kf[4];
    int krow = (m >> 1) * 8 + r8;
    unsigned ka = kbs + (ks >> 2) * 4096 + krow * 128 + ((((ks & 3) * 2 + (m & 1)) ^ r8) << 4);
    ldsm_x4(kf, ka);
    mma16816(s[0], qa[ks], kf[0], kf[1]); mma16816(s[1], qa[ks], kf[2], kf[3]);
    if (mt) { ldsm_x4(kf, ka + 2048); mma16816(s[2], qa[ks], kf[0], kf[1]); mma16816(s[3], qa[ks], kf[2], kf[3]); }
  }
#pragma unroll
  for (int ks = 0; ks < 8; ks++) mma16816(s[4], qa[ks], km[2 * ks], km[2 * ks + 1]);
  float mx0 = -INFINITY, mx1 = -INFINITY;
  const int t0 = mt * 16 + g, t1 = t0 + 8;
#pragma unroll
  for (int i = 0; i < 5; i++) {
#pragma unroll
    for (int e = 0; e < 4; e++) {
      float v = bf16r(bf16r(s[i][e]) * SCALE_QK);
      if (i < 4) { int kj = i * 8 + 2 * tq + (e & 1); if (kj > (e < 2 ? t0 : t1)) v = -INFINITY; }
      s[i][e] = v;
      if (e < 2) mx0 = fmaxf(mx0, v); else mx1 = fmaxf(mx1, v);
    }
  }
  mx0 = fmaxf(mx0, __shfl_xor_sync(~0u, mx0, 1)); mx0 = fmaxf(mx0, __shfl_xor_sync(~0u, mx0, 2));
  mx1 = fmaxf(mx1, __shfl_xor_sync(~0u, mx1, 1)); mx1 = fmaxf(mx1, __shfl_xor_sync(~0u, mx1, 2));
  float sm0 = 0, sm1 = 0;
#pragma unroll
  for (int i = 0; i < 5; i++) {
    s[i][0] = __expf(s[i][0] - mx0); s[i][1] = __expf(s[i][1] - mx0); s[i][2] = __expf(s[i][2] - mx1); s[i][3] = __expf(s[i][3] - mx1);
    sm0 += s[i][0] + s[i][1]; sm1 += s[i][2] + s[i][3];
  }
  sm0 += __shfl_xor_sync(~0u, sm0, 1); sm0 += __shfl_xor_sync(~0u, sm0, 2);
  sm1 += __shfl_xor_sync(~0u, sm1, 1); sm1 += __shfl_xor_sync(~0u, sm1, 2);
  const float i0 = __fdividef(1.0f, sm0), i1 = __fdividef(1.0f, sm1);
  unsigned pa[2][4], pm0, pm1;
#pragma unroll
  for (int kk = 0; kk < 2; kk++) {
    pa[kk][0] = pack_bf16(s[2 * kk][0] * i0, s[2 * kk][1] * i0); pa[kk][1] = pack_bf16(s[2 * kk][2] * i1, s[2 * kk][3] * i1);
    pa[kk][2] = pack_bf16(s[2 * kk + 1][0] * i0, s[2 * kk + 1][1] * i0); pa[kk][3] = pack_bf16(s[2 * kk + 1][2] * i1, s[2 * kk + 1][3] * i1);
  }
  pm0 = pack_bf16(s[4][0] * i0, s[4][1] * i0); pm1 = pack_bf16(s[4][2] * i1, s[4][3] * i1);
  const int orow = (kb & 1) * 64 + seg * 32 + mt * 16 + (m & 1) * 8 + r8;
  const unsigned ob = stg + ((kb >> 1) * 2 + eh) * 16384 + orow * 128;
#pragma unroll
  for (int cp = 0; cp < 4; cp++) {
    float o0[4] = {0, 0, 0, 0}, o1[4] = {0, 0, 0, 0};
    mma1688(o0, pm0, pm1, vm[2 * cp]); mma1688(o1, pm0, pm1, vm[2 * cp + 1]);
    unsigned vf[4];
    int row = (m & 1) * 8 + r8;
    unsigned va = vb + row * 128 + (((cp * 2 + (m >> 1)) ^ r8) << 4);
    ldsm_x4_t(vf, va);
    mma16816(o0, pa[0], vf[0], vf[1]); mma16816(o1, pa[0], vf[2], vf[3]);
    if (mt) { ldsm_x4_t(vf, va + 2048); mma16816(o0, pa[1], vf[0], vf[1]); mma16816(o1, pa[1], vf[2], vf[3]); }
    stsm_x4(ob + (((cp * 2 + (m >> 1)) ^ r8) << 4), pack_bf16(o0[0], o0[1]), pack_bf16(o0[2], o0[3]), pack_bf16(o1[0], o1[1]), pack_bf16(o1[2], o1[3]));
  }
}

__device__ __forceinline__ void bulk_worker(unsigned sb, volatile int* misc, const bf16* __restrict__ x, const bf16* __restrict__ b1, const bf16* __restrict__ b2, bf16* __restrict__ out) {
  const int t = threadIdx.x, lane = t & 31, w = t >> 5, wg = w >> 2, g = lane >> 2, tq = lane & 3, m = lane >> 3, r8 = lane & 7;
  const unsigned bar = sb + SM_BAR;
  unsigned st = 0, ph = 0, seq = 0, sph = 0;
  float d[128];
  while (true) {
    mbar_wait(bar + 8 * (MB_FULL + st), ph);
    const int idx = misc[seq & 3]; seq++;
    if (idx < 0 || idx >= N_ITEMS) break;
    const Item it = decode_item(idx);
    const int nkb = item_nkb(it.type);
    if (it.type == T_ATT) {
      mbar_wait(bar + 8 * MB_STGE, sph ^ 1);
      for (int kb = 0; kb < 4; kb++) {
        if (kb) mbar_wait(bar + 8 * (MB_FULL + st), ph);
        bulk_att_stage(sb + st * STAGE_BYTES, sb + B_STG, it.b, it.c, kb, w, lane);
        __syncwarp();
        if (lane == 0) mbar_arrive(bar + 8 * (MB_EMPTY + st));
        if (++st == NSTAGE) { st = 0; ph ^= 1; }
      }
      if (t == 0) misc[4] = idx;
      fence_proxy_async_smem();
      mbar_arrive(bar + 8 * MB_STGF); sph ^= 1;
      continue;
    }
    unsigned pst = 0;
    for (int kb = 0; kb < nkb; kb++) {
      if (kb) mbar_wait(bar + 8 * (MB_FULL + st), ph);
      unsigned sa = sb + st * STAGE_BYTES;
      uint64_t ad = mkdesc(sa + wg * 8192, 16, 1024), bd = mkdesc(sa + 16384, 8192, 1024);
      asm volatile("wgmma.fence.sync.aligned;" ::: "memory");
#pragma unroll
      for (int k = 0; k < 4; k++) wgmma_n256(d, ad + k * 2, bd + k * 128, (kb | k) != 0);
      asm volatile("wgmma.commit_group.sync.aligned;" ::: "memory");
      if (kb) {
        asm volatile("wgmma.wait_group.sync.aligned 1;" ::: "memory");
        if (lane == 0) mbar_arrive(bar + 8 * (MB_EMPTY + pst));
      }
      pst = st;
      if (++st == NSTAGE) { st = 0; ph ^= 1; }
    }
    asm volatile("wgmma.wait_group.sync.aligned 0;" ::: "memory");
    if (lane == 0) mbar_arrive(bar + 8 * (MB_EMPTY + pst));
    if (it.type == T_OUT) {
      const int row = it.b * 128 + w * 16 + g, col = it.c * 256 + 2 * tq;
      float* pp = g_opart + ((size_t)it.ks * S_TOK + row) * DM + col;
#pragma unroll
      for (int i = 0; i < 32; i++) {
        __stcg(reinterpret_cast<float2*>(pp + i * 8), make_float2(d[4 * i], d[4 * i + 1]));
        __stcg(reinterpret_cast<float2*>(pp + 8 * DM + i * 8), make_float2(d[4 * i + 2], d[4 * i + 3]));
      }
      __threadfence();
      bar_sync(1, 256);
      if (t == 0) misc[5] = (int)atomicAdd(&g_flags.p[it.b * 2 + it.c], 1u);
      bar_sync(1, 256);
      if (misc[5] == 3) {
        __threadfence();
        const float* p0 = g_opart + (size_t)row * DM + col;
#pragma unroll 4
        for (int i = 0; i < 64; i++) {
          size_t off = (size_t)(i & 1) * 8 * DM + (i >> 1) * 8;
          float2 a = __ldcg(reinterpret_cast<const float2*>(p0 + off)), b = __ldcg(reinterpret_cast<const float2*>(p0 + off + (size_t)S_TOK * DM));
          float2 c = __ldcg(reinterpret_cast<const float2*>(p0 + off + (size_t)2 * S_TOK * DM)), e = __ldcg(reinterpret_cast<const float2*>(p0 + off + (size_t)3 * S_TOK * DM));
          size_t o = (size_t)row * DM + col + off;
          unsigned gv = __ldcg(reinterpret_cast<const unsigned*>(g_g + o)), xv = __ldg(reinterpret_cast<const unsigned*>(x + o));
          float s0 = bf16r((a.x + b.x) + (c.x + e.x)), s1 = bf16r((a.y + b.y) + (c.y + e.y));
          *reinterpret_cast<unsigned*>(out + o) = pack_bf16(bf_lo(xv) + bf16r(s0 * bf_lo(gv)), bf_hi(xv) + bf16r(s1 * bf_hi(gv)));
        }
      }
      bar_sync(1, 256);
      continue;
    }
    if (it.type != T_QKV) {
      const unsigned* bp = reinterpret_cast<const unsigned*>((it.type == T_M1 ? b1 : b2) + it.c * 256) + tq;
#pragma unroll
      for (int i = 0; i < 32; i++) {
        unsigned bv = __ldg(bp + i * 4);
        float lo = bf_lo(bv), hi = bf_hi(bv);
        float x0 = bf16r(bf16r(d[4 * i]) + lo), x1 = bf16r(bf16r(d[4 * i + 1]) + hi), x2 = bf16r(bf16r(d[4 * i + 2]) + lo), x3 = bf16r(bf16r(d[4 * i + 3]) + hi);
        if (it.type == T_M1) { d[4 * i] = gelu_t(x0); d[4 * i + 1] = gelu_t(x1); d[4 * i + 2] = gelu_t(x2); d[4 * i + 3] = gelu_t(x3); }
        else { d[4 * i] = silu_f(x0); d[4 * i + 1] = silu_f(x1); d[4 * i + 2] = silu_f(x2); d[4 * i + 3] = silu_f(x3); }
      }
    }
    mbar_wait(bar + 8 * MB_STGE, sph ^ 1);
    {
      const unsigned ob = sb + B_STG + (w * 16 + (m & 1) * 8 + r8) * 128;
#pragma unroll
      for (int i = 0; i < 16; i++)
        stsm_x4(ob + (i >> 2) * 16384 + ((((i & 3) * 2 + (m >> 1)) ^ r8) << 4), pack_bf16(d[8 * i], d[8 * i + 1]), pack_bf16(d[8 * i + 2], d[8 * i + 3]),
                pack_bf16(d[8 * i + 4], d[8 * i + 5]), pack_bf16(d[8 * i + 6], d[8 * i + 7]));
    }
    if (t == 0) misc[4] = idx;
    fence_proxy_async_smem();
    mbar_arrive(bar + 8 * MB_STGF); sph ^= 1;
  }
  mbar_wait(bar + 8 * MB_STGE, sph ^ 1);
  if (t == 0) misc[4] = -1;
  mbar_arrive(bar + 8 * MB_STGF);
}

__global__ void __cluster_dims__(2, 1, 1) __launch_bounds__(384, 1)
k_main(const __grid_constant__ Maps maps, const bf16* __restrict__ x, const bf16* __restrict__ mem0, const bf16* __restrict__ b1, const bf16* __restrict__ b2, bf16* __restrict__ out) {
  extern __shared__ unsigned char smem_raw[];
  const unsigned sraw = smem_u32(smem_raw);
  const unsigned sb = (sraw + 1023u) & ~1023u;
  int* misc = reinterpret_cast<int*>(smem_raw + (sb - sraw) + SM_MISC);
  const int w = threadIdx.x >> 5;
  const bool rec = blockIdx.x < NREC;
  if (threadIdx.x == 0) {
    const unsigned bar = sb + SM_BAR;
    for (int i = 0; i < 8; i++) { mbar_init(bar + 8 * (MB_FULL + i), 1); mbar_init(bar + 8 * (MB_EMPTY + i), 8); }
    mbar_init(bar + 8 * MB_STGF, 256); mbar_init(bar + 8 * MB_STGE, 1);
    for (int i = MB_W0; i <= MB_KVF; i++) mbar_init(bar + 8 * i, 1);
    asm volatile("fence.mbarrier_init.release.cluster;" ::: "memory");
  }
  __syncthreads();
  asm volatile("barrier.cluster.arrive.release.aligned;\nbarrier.cluster.wait.acquire.aligned;" ::: "memory");
  if (w >= 8) {
    asm volatile("setmaxnreg.dec.sync.aligned.u32 40;");
    if (rec) { if (w == 8) rec_ring(maps, sb); else if (w == 9) rec_copy(sb); }
    else if ((threadIdx.x & 31) == 0) { if (w == 8) bulk_producer(maps, sb, misc); else if (w == 9) bulk_store(maps, sb, misc); }
  } else {
    asm volatile("setmaxnreg.inc.sync.aligned.u32 232;");
    if (rec) rec_worker(maps, sb, mem0);
    else bulk_worker(sb, misc, x, b1, b2, out);
  }
}

typedef CUresult (*EncFn)(CUtensorMap*, CUtensorMapDataType, cuuint32_t, void*, const cuuint64_t*, const cuuint64_t*, const cuuint32_t*, const cuuint32_t*,
                          CUtensorMapInterleave, CUtensorMapSwizzle, CUtensorMapL2promotion, CUtensorMapFloatOOBfill);
static void mk_map(EncFn enc, CUtensorMap* m, const void* ptr, uint64_t rows, uint64_t cols, uint32_t box_rows) {
  cuuint64_t dims[2] = {cols, rows}; cuuint64_t strides[1] = {cols * 2};
  cuuint32_t box[2] = {64, box_rows}, es[2] = {1, 1};
  enc(m, CU_TENSOR_MAP_DATA_TYPE_BFLOAT16, 2, const_cast<void*>(ptr), dims, strides, box, es, CU_TENSOR_MAP_INTERLEAVE_NONE, CU_TENSOR_MAP_SWIZZLE_128B,
      CU_TENSOR_MAP_L2_PROMOTION_L2_256B, CU_TENSOR_MAP_FLOAT_OOB_FILL_NONE);
}
extern "C" void kernel_launch(void* const* d_in, const int* in_sizes, int n_in, void* d_out, int out_size) {
  static EncFn enc = nullptr;
  static void *p_xn, *p_y, *p_h1, *p_o, *p_qkv, *p_g;
  if (!enc) {
    void* fn = nullptr; cudaDriverEntryPointQueryResult qr;
    cudaGetDriverEntryPoint("cuTensorMapEncodeTiled", &fn, cudaEnableDefault, &qr);
    enc = (EncFn)fn;
    cudaGetSymbolAddress(&p_xn, g_xn); cudaGetSymbolAddress(&p_y, g_y); cudaGetSymbolAddress(&p_h1, g_h1);
    cudaGetSymbolAddress(&p_o, g_o); cudaGetSymbolAddress(&p_qkv, g_qkv); cudaGetSymbolAddress(&p_g, g_g);
    cudaFuncSetAttribute(k_main, cudaFuncAttributeMaxDynamicSharedMemorySize, SMEM_TOTAL);
  }
  Maps maps;
  mk_map(enc, &maps.xn, p_xn, S_TOK, DM, 128); mk_map(enc, &maps.y, p_y, S_TOK, DM, 128); mk_map(enc, &maps.h1, p_h1, S_TOK, FF, 128);
  mk_map(enc, &maps.o, p_o, S_TOK, HD, 128); mk_map(enc, &maps.qkv_st, p_qkv, S_TOK, 3 * HD, 128); mk_map(enc, &maps.qkv_ld, p_qkv, S_TOK, 3 * HD, 32);
  mk_map(enc, &maps.g, p_g, S_TOK, DM, 128);
  mk_map(enc, &maps.wq, d_in[2], DM, HD, 64); mk_map(enc, &maps.wk, d_in[3], DM, HD, 64); mk_map(enc, &maps.wv, d_in[4], DM, HD, 64);
  mk_map(enc, &maps.wo, d_in[5], HD, DM, 64); mk_map(enc, &maps.w1, d_in[8], DM, FF, 64); mk_map(enc, &maps.w2, d_in[10], FF, DM, 64);
  cudaStream_t st = cudaStreamPerThread;
  k_pre<<<256, 256, 0, st>>>((const bf16*)d_in[0]);
  k_main<<<NCTA, 384, SMEM_TOTAL, st>>>(maps, (const bf16*)d_in[0], (const bf16*)d_in[1], (const bf16*)d_in[9], (const bf16*)d_in[11], (bf16*)d_out);
}
```

```cpp
#include <cuda_runtime.h>
#include <cuda_bf16.h>
#include <cuda.h>
#include <stdint.h>

typedef __nv_bfloat16 bf16;

#define S_TOK 2048
#define DM 512
#define NH 32
#define DH 128
#define HD 4096
#define NMEM 8
#define SEG 32
#define NSEG 64
#define FF 1792
#define NBLK 16
#define NREC 64
#define NCTA 132
#define NBULK (NCTA - NREC)

__device__ __align__(1024) bf16 g_xn[S_TOK * DM];
__device__ __align__(1024) bf16 g_y[S_TOK * DM];
__device__ __align__(1024) bf16 g_qkv[(size_t)S_TOK * 3 * HD];
__device__ __align__(1024) bf16 g_h1[S_TOK * FF];
__device__ __align__(1024) bf16 g_g[S_TOK * DM];
__device__ __align__(1024) bf16 g_o[(size_t)S_TOK * HD];
__device__ __align__(1024) bf16 g_km[NSEG * NH * NMEM * DH];
__device__ __align__(1024) bf16 g_vmt[NSEG * NH * DH * NMEM];
__device__ __align__(1024) float g_opart[(size_t)4 * S_TOK * DM];
__device__ __align__(1024) unsigned g_part[2 * NREC * NH * 64];
__device__ __align__(1024) unsigned g_pub[NSEG * 2048];
struct Flags {
  unsigned qkv[NBLK * 48];
  unsigned h1[NBLK];
  unsigned g[NBLK];
  unsigned o[NBLK * 4];
  unsigned p[NBLK * 2];
  unsigned ctr;
  unsigned rec[NREC];
  unsigned abort_;
};
__device__ __align__(1024) Flags g_flags;

#define RSTAMP(k)
#define ISTAMP(i, k)
__device__ __forceinline__ unsigned smem_u32(const void* p) { return (unsigned)__cvta_generic_to_shared(p); }
__device__ __forceinline__ float bf16r(float x) { unsigned u; asm("cvt.rn.bf16x2.f32 %0, %1, %2;" : "=r"(u) : "f"(x), "f"(0.0f)); return __uint_as_float(u); }
__device__ __forceinline__ unsigned pack_bf16(float lo, float hi) {
  __nv_bfloat162 v = __floats2bfloat162_rn(lo, hi);
  return *reinterpret_cast<unsigned*>(&v);
}
__device__ __forceinline__ float bf_lo(unsigned u) { return __uint_as_float(u << 16); }
__device__ __forceinline__ float bf_hi(unsigned u) { return __uint_as_float(u & 0xffff0000u); }

#define SPIN_LIMIT (1u << 20)
#define TRAP_IF(x) if ((x) > SPIN_LIMIT) { asm volatile("st.global.u32 [%0], %1;" ::"l"(0ull), "r"(0u) : "memory"); break; }
__device__ __forceinline__ unsigned ld_acquire(const unsigned* p) {
  unsigned v; asm volatile("ld.acquire.gpu.global.u32 %0, [%1];" : "=r"(v) : "l"(p) : "memory"); return v;
}
__device__ __forceinline__ unsigned ld_relaxed(const unsigned* p) {
  unsigned v; asm volatile("ld.relaxed.gpu.global.u32 %0, [%1];" : "=r"(v) : "l"(p) : "memory"); return v;
}
__device__ __forceinline__ void red_release_add(unsigned* p, unsigned v) {
  asm volatile("red.release.gpu.global.add.u32 [%0], %1;" ::"l"(p), "r"(v) : "memory");
}
__device__ __forceinline__ void st_release(unsigned* p, unsigned v) {
  asm volatile("st.release.gpu.global.u32 [%0], %1;" ::"l"(p), "r"(v) : "memory");
}
__device__ __forceinline__ void wait_flag_ge(const unsigned* p, unsigned target) {
  unsigned it = 0;
  while (ld_acquire(p) < target) {
    __nanosleep(64);
    TRAP_IF(++it);
  }
}
__device__ __forceinline__ uint4 ldv4_relaxed(const void* p) {
  uint4 a; asm volatile("ld.relaxed.gpu.global.v4.u32 {%0,%1,%2,%3}, [%4];" : "=r"(a.x), "=r"(a.y), "=r"(a.z), "=r"(a.w) : "l"(p) : "memory"); return a;
}
__device__ __forceinline__ void mbar_init(unsigned mb, unsigned cnt) { asm volatile("mbarrier.init.shared::cta.b64 [%0], %1;" ::"r"(mb), "r"(cnt) : "memory"); }
__device__ __forceinline__ void mbar_expect_tx(unsigned mb, unsigned bytes) { asm volatile("mbarrier.arrive.expect_tx.shared::cta.b64 _, [%0], %1;" ::"r"(mb), "r"(bytes) : "memory"); }
__device__ __forceinline__ void mbar_arrive(unsigned mb) { asm volatile("mbarrier.arrive.shared::cta.b64 _, [%0];" ::"r"(mb) : "memory"); }
__device__ __forceinline__ void mbar_wait(unsigned mb, unsigned parity) {
  unsigned ok, it = 0;
  while (true) {
    asm volatile("{.reg .pred p; mbarrier.try_wait.parity.shared::cta.b64 p, [%1], %2; selp.u32 %0,1,0,p;}" : "=r"(ok) : "r"(mb), "r"(parity) : "memory");
    if (ok) break;
    TRAP_IF(++it);
  }
}
__device__ __forceinline__ void mbar_wait_cluster(unsigned mb, unsigned parity) {
  unsigned ok, it = 0;
  while (true) {
    asm volatile("{.reg .pred p; mbarrier.try_wait.parity.acquire.cluster.shared::cta.b64 p, [%1], %2; selp.u32 %0,1,0,p;}" : "=r"(ok) : "r"(mb), "r"(parity) : "memory");
    if (ok) break;
    TRAP_IF(++it);
  }
}
__device__ __forceinline__ void bar_sync(int id, int n) { asm volatile("bar.sync %0, %1;" ::"r"(id), "r"(n) : "memory"); }
__device__ __forceinline__ void bar_arrive(int id, int n) { asm volatile("bar.arrive %0, %1;" ::"r"(id), "r"(n) : "memory"); }
__device__ __forceinline__ void tma_load_2d(unsigned dst, const CUtensorMap* map, int c0, int c1, unsigned mb) {
  asm volatile("cp.async.bulk.tensor.2d.shared::cluster.global.mbarrier::complete_tx::bytes [%0], [%1, {%3, %4}], [%2];"
               ::"r"(dst), "l"((uint64_t)map), "r"(mb), "r"(c0), "r"(c1) : "memory");
}
__device__ __forceinline__ void tma_store_2d(const CUtensorMap* map, unsigned src, int c0, int c1) {
  asm volatile("cp.async.bulk.tensor.2d.global.shared::cta.bulk_group [%0, {%2, %3}], [%1];"
               ::"l"((uint64_t)map), "r"(src), "r"(c0), "r"(c1) : "memory");
}
__device__ __forceinline__ void fence_proxy_async() { asm volatile("fence.proxy.async;" ::: "memory"); }
__device__ __forceinline__ void fence_proxy_async_smem() { asm volatile("fence.proxy.async.shared::cta;" ::: "memory"); }
__device__ __forceinline__ void ldsm_x4(unsigned* r, unsigned addr) {
  asm volatile("ldmatrix.sync.aligned.m8n8.x4.shared.b16 {%0,%1,%2,%3}, [%4];" : "=r"(r[0]), "=r"(r[1]), "=r"(r[2]), "=r"(r[3]) : "r"(addr) : "memory");
}
__device__ __forceinline__ void ldsm_x4_t(unsigned* r, unsigned addr) {
  asm volatile("ldmatrix.sync.aligned.m8n8.x4.trans.shared.b16 {%0,%1,%2,%3}, [%4];" : "=r"(r[0]), "=r"(r[1]), "=r"(r[2]), "=r"(r[3]) : "r"(addr) : "memory");
}
__device__ __forceinline__ void stsm_x2_t(unsigned addr, unsigned r0, unsigned r1) {
  asm volatile("stmatrix.sync.aligned.m8n8.x2.trans.shared.b16 [%0], {%1,%2};" ::"r"(addr), "r"(r0), "r"(r1) : "memory");
}
__device__ __forceinline__ void stsm_x4(unsigned addr, unsigned r0, unsigned r1, unsigned r2, unsigned r3) {
  asm volatile("stmatrix.sync.aligned.m8n8.x4.shared.b16 [%0], {%1,%2,%3,%4};" ::"r"(addr), "r"(r0), "r"(r1), "r"(r2), "r"(r3) : "memory");
}
__device__ __forceinline__ void mma16816(float* d, const unsigned* a, unsigned b0, unsigned b1) {
  asm volatile("mma.sync.aligned.m16n8k16.row.col.f32.bf16.bf16.f32 {%0,%1,%2,%3}, {%4,%5,%6,%7}, {%8,%9}, {%0,%1,%2,%3};"
               : "+f"(d[0]), "+f"(d[1]), "+f"(d[2]), "+f"(d[3]) : "r"(a[0]), "r"(a[1]), "r"(a[2]), "r"(a[3]), "r"(b0), "r"(b1));
}
__device__ __forceinline__ void mma1688(float* d, unsigned a0, unsigned a1, unsigned b0) {
  asm volatile("mma.sync.aligned.m16n8k8.row.col.f32.bf16.bf16.f32 {%0,%1,%2,%3}, {%4,%5}, {%6}, {%0,%1,%2,%3};"
               : "+f"(d[0]), "+f"(d[1]), "+f"(d[2]), "+f"(d[3]) : "r"(a0), "r"(a1), "r"(b0));
}
__device__ __forceinline__ uint64_t mkdesc(unsigned addr, unsigned lbo, unsigned sbo) {
  return (uint64_t)((addr >> 4) & 0x3fff) | ((uint64_t)(lbo >> 4) << 16) | ((uint64_t)(sbo >> 4) << 32) | (1ull << 62);
}
#define R8(b) "+f"(d[b]), "+f"(d[b + 1]), "+f"(d[b + 2]), "+f"(d[b + 3]), "+f"(d[b + 4]), "+f"(d[b + 5]), "+f"(d[b + 6]), "+f"(d[b + 7])
#define R32(b) R8(b), R8(b + 8), R8(b + 16), R8(b + 24)
__device__ __forceinline__ void wgmma_n256(float* d, uint64_t ad, uint64_t bd, int acc) {
  asm volatile(
      "{.reg .pred p; setp.ne.b32 p, %130, 0;\n"
      "wgmma.mma_async.sync.aligned.m64n256k16.f32.bf16.bf16 "
      "{%0,%1,%2,%3,%4,%5,%6,%7,%8,%9,%10,%11,%12,%13,%14,%15,%16,%17,%18,%19,%20,%21,%22,%23,%24,%25,%26,%27,%28,%29,%30,%31,"
      "%32,%33,%34,%35,%36,%37,%38,%39,%40,%41,%42,%43,%44,%45,%46,%47,%48,%49,%50,%51,%52,%53,%54,%55,%56,%57,%58,%59,%60,%61,%62,%63,"
      "%64,%65,%66,%67,%68,%69,%70,%71,%72,%73,%74,%75,%76,%77,%78,%79,%80,%81,%82,%83,%84,%85,%86,%87,%88,%89,%90,%91,%92,%93,%94,%95,"
      "%96,%97,%98,%99,%100,%101,%102,%103,%104,%105,%106,%107,%108,%109,%110,%111,%112,%113,%114,%115,%116,%117,%118,%119,%120,%121,%122,%123,%124,%125,%126,%127},"
      "%128, %129, p, 1, 1, 0, 1;}\n"
      : R32(0), R32(32), R32(64), R32(96)
      : "l"(ad), "l"(bd), "r"(acc));
}

__device__ __forceinline__ void ln16(const float* x, float* o) {
  float s = 0;
#pragma unroll
  for (int i = 0; i < 16; i++) s += x[i];
#pragma unroll
  for (int of = 16; of > 0; of >>= 1) s += __shfl_xor_sync(~0u, s, of);
  float mean = s * (1.0f / DM);
  float v = 0;
#pragma unroll
  for (int i = 0; i < 16; i++) { float dd = x[i] - mean; v += dd * dd; }
#pragma unroll
  for (int of = 16; of > 0; of >>= 1) v += __shfl_xor_sync(~0u, v, of);
  float mb = bf16r(mean);
  float vb = bf16r(v * (1.0f / DM));
  float den = bf16r(sqrtf(bf16r(vb + 1e-5f)));
#pragma unroll
  for (int i = 0; i < 16; i++) o[i] = bf16r(__fdiv_rn(bf16r(x[i] - mb), den));
}
__global__ void __launch_bounds__(256) k_pre(const bf16* __restrict__ x) {
  int t = threadIdx.x, lane = t & 31, w = t >> 5;
  int row = blockIdx.x * 8 + w;
  const uint4* src = reinterpret_cast<const uint4*>(x + (size_t)row * DM);
  uint4 a = src[lane], b = src[lane + 32];
  unsigned u[8] = {a.x, a.y, a.z, a.w, b.x, b.y, b.z, b.w};
  float f[16], o[16], o2[16];
#pragma unroll
  for (int i = 0; i < 8; i++) { f[2 * i] = bf_lo(u[i]); f[2 * i + 1] = bf_hi(u[i]); }
  ln16(f, o);
  ln16(o, o2);
  uint4* d1 = reinterpret_cast<uint4*>(g_xn + (size_t)row * DM);
  uint4* d2 = reinterpret_cast<uint4*>(g_y + (size_t)row * DM);
  d1[lane] = make_uint4(pack_bf16(o[0], o[1]), pack_bf16(o[2], o[3]), pack_bf16(o[4], o[5]), pack_bf16(o[6], o[7]));
  d1[lane + 32] = make_uint4(pack_bf16(o[8], o[9]), pack_bf16(o[10], o[11]), pack_bf16(o[12], o[13]), pack_bf16(o[14], o[15]));
  d2[lane] = make_uint4(pack_bf16(o2[0], o2[1]), pack_bf16(o2[2], o2[3]), pack_bf16(o2[4], o2[5]), pack_bf16(o2[6], o2[7]));
  d2[lane + 32] = make_uint4(pack_bf16(o2[8], o2[9]), pack_bf16(o2[10], o2[11]), pack_bf16(o2[12], o2[13]), pack_bf16(o2[14], o2[15]));
  int gt = blockIdx.x * 256 + t;
  uint4 z = make_uint4(0, 0, 0, 0);
  reinterpret_cast<uint4*>(g_part)[gt] = z;
  if (gt < NSEG * 2048 / 4) reinterpret_cast<uint4*>(g_pub)[gt] = z;
  if (gt < (int)(sizeof(Flags) / 4)) reinterpret_cast<unsigned*>(&g_flags)[gt] = 0;
}

struct Maps { CUtensorMap xn, y, h1, o, qkv_st, qkv_ld, g, wq, wk, wv, wo, w1, w2; };

#define NSTAGE 3
#define STAGE_BYTES 49152
#define B_STG (NSTAGE * STAGE_BYTES)
#define R_WO 0
#define R_T1 65536
#define R_T2 131072
#define R_RING 65536
#define RING_N 4
#define RING_BYTES 12288
#define R_MEM 196608
#define R_QS (R_MEM + 8448)
#define R_KS (R_QS + 1152)
#define R_OS (R_KS + 1152)
#define R_SOWN (R_OS + 2176)
#define R_SPEER (R_SOWN + 1280)
#define R_VM (R_SPEER + 1280)
#define R_VRED (R_VM + 2048)
#define R_RED (R_VRED + 6144)
#define SM_BAR (R_RED + 2048)
#define SMEM_TOTAL (SM_BAR + 256 + 1024)
#define MB_FULL 0
#define MB_EMPTY 8
#define MB_STGF 16
#define MB_STGE 17
#define MB_W0 18
#define MB_W1 19
#define MB_WO 20
#define MB_S 21
#define MB_V 22
#define MB_KVR 23
#define MB_KVF 24
#define SM_MISC (SM_BAR + 208)

#define N_KV 512
#define I_Q 512
#define I_M1 768
#define I_M2 880
#define I_POST 912
#define N_ITEMS 1296
enum { T_QKV = 0, T_M1 = 1, T_M2 = 2, T_ATT = 3, T_OUT = 4 };
struct Item { int type, b, c, ks; };
__device__ __forceinline__ Item decode_item(int i) {
  Item it; it.ks = 0;
  if (i < N_KV) { it.type = T_QKV; it.b = i >> 5; it.c = 16 + (i & 31); }
  else if (i < I_M1) { it.type = T_QKV; it.b = (i - I_Q) >> 4; it.c = (i - I_Q) & 15; }
  else if (i < I_M2) { it.type = T_M1; it.b = (i - I_M1) / 7; it.c = (i - I_M1) % 7; }
  else if (i < I_POST) { it.type = T_M2; it.b = (i - I_M2) >> 1; it.c = (i - I_M2) & 1; }
  else {
    int x = i - I_POST;
    if (x < 16) { it.type = T_ATT; it.b = 0; it.c = x; }
    else {
      x -= 16; int p = 1 + x / 24, r = x % 24;
      if (p < 16 && r < 16) { it.type = T_ATT; it.b = p; it.c = r; }
      else { if (p < 16) r -= 16; it.type = T_OUT; it.b = p - 1; it.c = r & 1; it.ks = r >> 1; }
    }
  }
  return it;
}
__device__ __forceinline__ int item_nkb(int type) { return type == T_M2 ? 28 : (type == T_OUT ? 16 : (type == T_ATT ? 4 : 8)); }

__device__ __forceinline__ void st_async_b64(unsigned raddr, unsigned lo, unsigned hi, unsigned rmb) {
  asm volatile("st.async.weak.shared::cluster.mbarrier::complete_tx::bytes.v2.b32 [%0], {%1,%2}, [%3];" ::"r"(raddr), "r"(lo), "r"(hi), "r"(rmb) : "memory");
}
__device__ __forceinline__ unsigned mapa(unsigned a, unsigned rank) {
  unsigned r; asm volatile("mapa.shared::cluster.u32 %0, %1, %2;" : "=r"(r) : "r"(a), "r"(rank)); return r;
}
__device__ __forceinline__ void sts64(unsigned a, unsigned x, unsigned y) { asm volatile("st.shared.v2.b32 [%0], {%1,%2};" ::"r"(a), "r"(x), "r"(y) : "memory"); }
__device__ __forceinline__ void sts128(unsigned a, uint4 v) { asm volatile("st.shared.v4.b32 [%0], {%1,%2,%3,%4};" ::"r"(a), "r"(v.x), "r"(v.y), "r"(v.z), "r"(v.w) : "memory"); }
__device__ __forceinline__ uint2 lds64(unsigned a) { uint2 v; asm volatile("ld.shared.v2.b32 {%0,%1}, [%2];" : "=r"(v.x), "=r"(v.y) : "r"(a) : "memory"); return v; }
__device__ __forceinline__ uint4 lds128(unsigned a) { uint4 v; asm volatile("ld.shared.v4.b32 {%0,%1,%2,%3}, [%4];" : "=r"(v.x), "=r"(v.y), "=r"(v.z), "=r"(v.w) : "r"(a) : "memory"); return v; }
__device__ __forceinline__ float lds32f(unsigned a) { float v; asm volatile("ld.shared.f32 %0, [%1];" : "=f"(v) : "r"(a) : "memory"); return v; }
#define spin_check(it) TRAP_IF(++it)
#define SCALE_QK 0.08838834764831845f

__device__ __forceinline__ void rec_worker(const Maps& maps, unsigned sb, const bf16* __restrict__ mem0) {
  const int c = blockIdx.x, h = c >> 1, j = c & 1;
  const int t = threadIdx.x, lane = t & 31, w = t >> 5, g = lane >> 2, tq = lane & 3;
  const int m = lane >> 3, r8 = lane & 7, kh = w >> 2, et = w & 3;
  const unsigned bar = sb + SM_BAR;
  unsigned wq[16][4], wk[16][4], wv[8][4];
  const unsigned woff = (kh * 4) * 8192 + ((m >> 1) * 8 + r8) * 128 + (((et * 2 + (m & 1)) ^ r8) << 4);
  mbar_wait(bar + 8 * MB_W0, 0);
#pragma unroll
  for (int i = 0; i < 16; i++) {
    ldsm_x4_t(wq[i], sb + R_WO + woff + (i >> 2) * 8192 + (i & 3) * 2048);
    ldsm_x4_t(wk[i], sb + R_T1 + woff + (i >> 2) * 8192 + (i & 3) * 2048);
  }
  bar_sync(2, 288);
  if (t == 0) {
    fence_proxy_async_smem();
    mbar_expect_tx(bar + 8 * MB_WO, 65536);
    for (int kb = 0; kb < 2; kb++)
      for (int cb = 0; cb < 4; cb++) tma_load_2d(sb + R_WO + (kb * 4 + cb) * 8192, &maps.wo, j * 256 + cb * 64, h * 128 + kb * 64, bar + 8 * MB_WO);
  }
  mbar_wait(bar + 8 * MB_W1, 0);
  const unsigned pV = sb + R_T2 + woff;
#pragma unroll
  for (int i = 0; i < 8; i++) ldsm_x4_t(wv[i], pV + (i >> 1) * 8192 + (i & 1) * 4096);
  const unsigned peer = j ^ 1;
  const unsigned rS = mapa(sb + R_SPEER, peer), rV = mapa(sb + R_VM, peer), rmbS = mapa(bar + 8 * MB_S, peer), rmbV = mapa(bar + 8 * MB_V, peer);
  const unsigned pA = sb + R_MEM + r8 * 1040 + m * 16 + kh * 512;
  const unsigned pW = sb + R_WO + (w >> 1) * 8192 + ((m >> 1) * 8 + r8) * 128;
  const unsigned pW0 = pW + ((((w & 1) * 4 + (m & 1)) ^ r8) << 4), pW1 = pW + ((((w & 1) * 4 + 2 + (m & 1)) ^ r8) << 4);
  mbar_wait(bar + 8 * MB_WO, 0);

#pragma unroll 1
  for (int s = 0; s < NSEG; s++) {
    const unsigned par = s & 1;
    const unsigned slot = s & (RING_N - 1), rpar = (s / RING_N) & 1;
    const unsigned ring = sb + R_RING + slot * RING_BYTES;
    if (t == 0 && s < NSEG - 1) { mbar_expect_tx(bar + 8 * MB_S, 1280); mbar_expect_tx(bar + 8 * MB_V, 1024); }
    if (s > 0) mbar_wait(bar + 8 * MB_KVF, par ^ 1);
    RSTAMP(0); RSTAMP(1);
    if (s == 0) {
#pragma unroll
      for (int u = 0; u < 2; u++) {
        int i = t + 256 * u;
        uint4 v = __ldg(reinterpret_cast<const uint4*>(mem0) + i);
        sts128(sb + R_MEM + (i >> 6) * 1040 + (i & 63) * 16, v);
      }
    } else {
      const uint4* src = reinterpret_cast<const uint4*>(g_pub) + s * 512 + t;
      uint4 a, b; bool oka = false, okb = false; unsigned it = 0;
      while (true) {
        if (!oka) { a = ldv4_relaxed(src); oka = a.x && a.y && a.z && a.w; }
        if (!okb) { b = ldv4_relaxed(src + 256); okb = b.x && b.y && b.z && b.w; }
        if (oka && okb) break;
        spin_check(it);
      }
      sts128(sb + R_MEM + (t & 7) * 1040 + (t >> 3) * 16, a);
      sts128(sb + R_MEM + (t & 7) * 1040 + (t >> 3) * 16 + 512, b);
    }
    bar_sync(1, 256);
    RSTAMP(2);
    float aq[4] = {0, 0, 0, 0}, ak[4] = {0, 0, 0, 0}, av[4] = {0, 0, 0, 0};
#pragma unroll
    for (int i = 0; i < 8; i++) {
      unsigned b[4], f[4];
      ldsm_x4(b, pA + i * 64);
      ldsm_x4_t(f, pV + (i >> 1) * 8192 + (i & 1) * 4096 + 2048);
      mma16816(aq, wq[2 * i], b[0], b[1]); mma16816(ak, wk[2 * i], b[0], b[1]); mma16816(av, wv[i], b[0], b[1]);
      mma16816(aq, wq[2 * i + 1], b[2], b[3]); mma16816(ak, wk[2 * i + 1], b[2], b[3]); mma16816(av, f, b[2], b[3]);
    }
    {
      const unsigned xb = sb + R_VRED + et * 512 + lane * 16;
#define STSF4(a, v) asm volatile("st.shared.v4.f32 [%0], {%1,%2,%3,%4};" ::"r"(a), "f"(v[0]), "f"(v[1]), "f"(v[2]), "f"(v[3]) : "memory")
      if (kh) { STSF4(xb, aq); } else { STSF4(xb + 2048, ak); STSF4(xb + 4096, av); }
      bar_sync(4 + et, 64);
      uint4 o = lds128(xb + kh * 2048);
      float z0 = kh ? ak[0] : aq[0], z1 = kh ? ak[1] : aq[1], z2 = kh ? ak[2] : aq[2], z3 = kh ? ak[3] : aq[3];
      stsm_x2_t(sb + (kh ? R_KS : R_QS) + r8 * 144 + (et * 16 + (m & 1) * 8) * 2, pack_bf16(z0 + __uint_as_float(o.x), z1 + __uint_as_float(o.y)),
                pack_bf16(z2 + __uint_as_float(o.z), z3 + __uint_as_float(o.w)));
      if (kh) {
        o = lds128(xb + 4096);
        unsigned x = pack_bf16(av[0] + __uint_as_float(o.x), av[1] + __uint_as_float(o.y)), y = pack_bf16(av[2] + __uint_as_float(o.z), av[3] + __uint_as_float(o.w));
        if (s < NSEG - 1) st_async_b64(rV + (j * 4 + et) * 256 + lane * 8, x, y, rmbV);
        sts64(sb + R_VM + (j * 4 + et) * 256 + lane * 8, x, y);
      }
    }
    mbar_wait(bar + 8 * (MB_FULL + slot), rpar);
    bar_sync(1, 256);
    RSTAMP(3);
    if (w <= 4 && s < NSEG - 1) {
      unsigned qa[8], kb[8];
      ldsm_x4(qa, sb + R_QS + r8 * 144 + m * 16); ldsm_x4(qa + 4, sb + R_QS + r8 * 144 + m * 16 + 64);
      if (w == 4) { ldsm_x4(kb, sb + R_KS + r8 * 144 + m * 16); ldsm_x4(kb + 4, sb + R_KS + r8 * 144 + m * 16 + 64); }
      else { unsigned ka = ring + (w * 8 + r8) * 128; ldsm_x4(kb, ka + ((m ^ r8) << 4)); ldsm_x4(kb + 4, ka + (((m + 4) ^ r8) << 4)); }
      float s0[4] = {0, 0, 0, 0}, s1[4] = {0, 0, 0, 0};
      unsigned af[4];
      af[1] = af[3] = 0;
      af[0] = qa[0]; af[2] = qa[1]; mma16816(s0, af, kb[0], kb[1]);
      af[0] = qa[2]; af[2] = qa[3]; mma16816(s1, af, kb[2], kb[3]);
      af[0] = qa[4]; af[2] = qa[5]; mma16816(s0, af, kb[4], kb[5]);
      af[0] = qa[6]; af[2] = qa[7]; mma16816(s1, af, kb[6], kb[7]);
      unsigned x = __float_as_uint(s0[0] + s1[0]), y = __float_as_uint(s0[1] + s1[1]);
      st_async_b64(rS + w * 256 + lane * 8, x, y, rmbS);
      sts64(sb + R_SOWN + w * 256 + lane * 8, x, y);
    }
    unsigned vx[2][4];
    {
      unsigned vb = ring + 4096 + kh * 4096;
#pragma unroll
      for (int kk = 0; kk < 2; kk++) { int row = kk * 16 + (m >> 1) * 8 + r8; ldsm_x4_t(vx[kk], vb + row * 128 + (((et * 2 + (m & 1)) ^ r8) << 4)); }
    }
    bar_sync(1, 256);
    if (lane == 0) { mbar_arrive(bar + 8 * (MB_EMPTY + slot)); if (w == 0) mbar_arrive(bar + 8 * MB_KVR); }
    if (s == NSEG - 1) break;
    unsigned wo[8][4];
#pragma unroll
    for (int ks = 0; ks < 4; ks++) { ldsm_x4_t(wo[2 * ks], pW0 + ks * 2048); ldsm_x4_t(wo[2 * ks + 1], pW1 + ks * 2048); }
    mbar_wait(bar + 8 * MB_S, par);
    RSTAMP(4);
    float sc[10];
#pragma unroll
    for (int i = 0; i < 5; i++) {
      uint2 o = lds64(sb + R_SOWN + i * 256 + lane * 8), p = lds64(sb + R_SPEER + i * 256 + lane * 8);
      float x0 = __uint_as_float(o.x) + __uint_as_float(p.x);
      float x1 = __uint_as_float(o.y) + __uint_as_float(p.y);
      sc[2 * i] = bf16r(bf16r(x0) * SCALE_QK); sc[2 * i + 1] = bf16r(bf16r(x1) * SCALE_QK);
    }
    float mx = sc[0];
#pragma unroll
    for (int i = 1; i < 10; i++) mx = fmaxf(mx, sc[i]);
    mx = fmaxf(mx, __shfl_xor_sync(~0u, mx, 1)); mx = fmaxf(mx, __shfl_xor_sync(~0u, mx, 2));
    float sum = 0;
#pragma unroll
    for (int i = 0; i < 10; i++) { sc[i] = __expf(sc[i] - mx); sum += sc[i]; }
    sum += __shfl_xor_sync(~0u, sum, 1); sum += __shfl_xor_sync(~0u, sum, 2);
    float inv = __fdividef(1.0f, sum);
    unsigned p[5];
#pragma unroll
    for (int i = 0; i < 5; i++) p[i] = pack_bf16(sc[2 * i] * inv, sc[2 * i + 1] * inv);
    float o0[4] = {0, 0, 0, 0}, o1[4] = {0, 0, 0, 0};
    mma16816(o0, vx[0], p[0], p[1]); mma16816(o1, vx[1], p[2], p[3]);
    mbar_wait(bar + 8 * MB_V, par);
    { uint2 vm = lds64(sb + R_VM + w * 256 + lane * 8); mma1688(o0, vm.x, vm.y, p[4]); }
    stsm_x2_t(sb + R_OS + r8 * 272 + (w * 16 + (m & 1) * 8) * 2, pack_bf16(o0[0] + o1[0], o0[1] + o1[1]), pack_bf16(o0[2] + o1[2], o0[3] + o1[3]));
    bar_sync(1, 256);
    RSTAMP(5);
    {
      float d0[4] = {0, 0, 0, 0}, d1[4] = {0, 0, 0, 0}, e0[4] = {0, 0, 0, 0}, e1[4] = {0, 0, 0, 0};
      unsigned ob[4][4], f[4][4];
#pragma unroll
      for (int k2 = 0; k2 < 4; k2++) ldsm_x4(ob[k2], sb + R_OS + r8 * 272 + m * 16 + k2 * 64);
      ldsm_x4_t(f[0], pW0 + 32768); ldsm_x4_t(f[1], pW1 + 32768); ldsm_x4_t(f[2], pW0 + 32768 + 2048); ldsm_x4_t(f[3], pW1 + 32768 + 2048);
      mma16816(d0, wo[0], ob[0][0], ob[0][1]); mma16816(d1, wo[1], ob[0][0], ob[0][1]);
      mma16816(e0, wo[2], ob[0][2], ob[0][3]); mma16816(e1, wo[3], ob[0][2], ob[0][3]);
      ldsm_x4_t(wo[0], pW0 + 32768 + 4096); ldsm_x4_t(wo[1], pW1 + 32768 + 4096); ldsm_x4_t(wo[2], pW0 + 32768 + 6144); ldsm_x4_t(wo[3], pW1 + 32768 + 6144);
      mma16816(d0, wo[4], ob[1][0], ob[1][1]); mma16816(d1, wo[5], ob[1][0], ob[1][1]);
      mma16816(e0, wo[6], ob[1][2], ob[1][3]); mma16816(e1, wo[7], ob[1][2], ob[1][3]);
      mma16816(d0, f[0], ob[2][0], ob[2][1]); mma16816(d1, f[1], ob[2][0], ob[2][1]);
      mma16816(e0, f[2], ob[2][2], ob[2][3]); mma16816(e1, f[3], ob[2][2], ob[2][3]);
      mma16816(d0, wo[0], ob[3][0], ob[3][1]); mma16816(d1, wo[1], ob[3][0], ob[3][1]);
      mma16816(e0, wo[2], ob[3][2], ob[3][3]); mma16816(e1, wo[3], ob[3][2], ob[3][3]);
#pragma unroll
      for (int i = 0; i < 4; i++) { d0[i] += e0[i]; d1[i] += e1[i]; }
      const unsigned tag = ((s >> 1) & 1) ^ 1;
      unsigned* dst = g_part + ((size_t)(par * NREC + 32 * j + 4 * w) * NH + h) * 64 + g * 8 + 2 * tq;
#define PST(ptr, x, y) asm volatile("st.relaxed.gpu.global.v2.u32 [%0], {%1,%2};" ::"l"(ptr), "r"((__float_as_uint(x) & ~1u) | tag), "r"((__float_as_uint(y) & ~1u) | tag) : "memory")
      PST(dst, d0[0], d0[1]); PST(dst + NH * 64, d0[2], d0[3]); PST(dst + 2 * NH * 64, d1[0], d1[1]); PST(dst + 3 * NH * 64, d1[2], d1[3]);
      RSTAMP(6);
      const uint4* src = reinterpret_cast<const uint4*>(g_part + ((size_t)(par * NREC + c) * NH + 4 * w) * 64) + lane;
      uint4 a, b; bool oka = false, okb = false; unsigned it = 0;
      while (true) {
        if (!oka) { a = ldv4_relaxed(src); oka = ((a.x & a.y & a.z & a.w & 1u) == tag) && (((a.x | a.y | a.z | a.w) & 1u) == tag); }
        if (!okb) { b = ldv4_relaxed(src + 32); okb = ((b.x & b.y & b.z & b.w & 1u) == tag) && (((b.x | b.y | b.z | b.w) & 1u) == tag); }
        if (oka && okb) break;
        spin_check(it);
      }
      RSTAMP(7);
      float r0 = __uint_as_float(a.x) + __uint_as_float(b.x), r1 = __uint_as_float(a.y) + __uint_as_float(b.y);
      float r2 = __uint_as_float(a.z) + __uint_as_float(b.z), r3 = __uint_as_float(a.w) + __uint_as_float(b.w);
      r0 += __shfl_xor_sync(~0u, r0, 16); r1 += __shfl_xor_sync(~0u, r1, 16); r2 += __shfl_xor_sync(~0u, r2, 16); r3 += __shfl_xor_sync(~0u, r3, 16);
      if (lane < 16) asm volatile("st.shared.v4.f32 [%0], {%1,%2,%3,%4};" ::"r"(sb + R_RED + w * 256 + lane * 16), "f"(r0), "f"(r1), "f"(r2), "f"(r3) : "memory");
      if (w != 0) { bar_arrive(3, 256); }
      else {
        bar_sync(3, 256);
        float x0 = 0, x1 = 0;
#pragma unroll
        for (int i = 0; i < 8; i++) { x0 += lds32f(sb + R_RED + i * 256 + (2 * tq) * 32 + g * 4); x1 += lds32f(sb + R_RED + i * 256 + (2 * tq + 1) * 32 + g * 4); }
        unsigned u = pack_bf16(x0, x1);
        if (u == 0) u = 0x80000000u;
        asm volatile("st.relaxed.gpu.global.u32 [%0], %1;" ::"l"(g_pub + (s + 1) * 2048 + c * 32 + lane), "r"(u) : "memory");
      }
    }
  }
}

__device__ __forceinline__ void rec_ring(const Maps& maps, unsigned sb) {
  const int c = blockIdx.x, h = c >> 1, j = c & 1;
  const unsigned bar = sb + SM_BAR;
  const int lane = threadIdx.x & 31;
  if (lane == 0) {
    mbar_expect_tx(bar + 8 * MB_W0, 131072);
    for (int kb = 0; kb < 8; kb++) tma_load_2d(sb + R_WO + kb * 8192, &maps.wq, h * 128 + j * 64, kb * 64, bar + 8 * MB_W0);
    for (int kb = 0; kb < 8; kb++) tma_load_2d(sb + R_T1 + kb * 8192, &maps.wk, h * 128 + j * 64, kb * 64, bar + 8 * MB_W0);
    mbar_expect_tx(bar + 8 * MB_W1, 65536);
    for (int kb = 0; kb < 8; kb++) tma_load_2d(sb + R_T2 + kb * 8192, &maps.wv, h * 128 + j * 64, kb * 64, bar + 8 * MB_W1);
  }
  __syncwarp();
  bar_sync(2, 288);
  if (lane == 0) {
    fence_proxy_async_smem();
    for (int s = 0; s < NSEG; s++) {
      unsigned slot = s & (RING_N - 1);
      if ((s & 3) == 0) {
        wait_flag_ge(&g_flags.qkv[(s >> 2) * 48 + 16 + (h >> 1)], 1);
        wait_flag_ge(&g_flags.qkv[(s >> 2) * 48 + 32 + (h >> 1)], 1);
        fence_proxy_async();
      }
      if (s >= RING_N) mbar_wait(bar + 8 * (MB_EMPTY + slot), ((s / RING_N) - 1) & 1);
      unsigned dst = sb + R_RING + slot * RING_BYTES, mb = bar + 8 * (MB_FULL + slot);
      mbar_expect_tx(mb, RING_BYTES);
      tma_load_2d(dst, &maps.qkv_ld, HD + h * 128 + j * 64, s * SEG, mb);
      tma_load_2d(dst + 4096, &maps.qkv_ld, 2 * HD + h * 128, s * SEG, mb);
      tma_load_2d(dst + 8192, &maps.qkv_ld, 2 * HD + h * 128 + 64, s * SEG, mb);
    }
  }
}
__device__ __forceinline__ void rec_copy(unsigned sb) {
  const int c = blockIdx.x, h = c >> 1, j = c & 1;
  const unsigned bar = sb + SM_BAR;
  const int lane = threadIdx.x & 31;
  for (int s = 0; s < NSEG; s++) {
    mbar_wait(bar + 8 * MB_KVR, s & 1);
    uint4 k0 = lds128(sb + R_KS + (lane >> 3) * 144 + (lane & 7) * 16), k1 = lds128(sb + R_KS + (4 + (lane >> 3)) * 144 + (lane & 7) * 16);
    uint2 v[4];
#pragma unroll
    for (int i = 0; i < 4; i++) v[i] = lds64(sb + R_VM + (j * 4 + i) * 256 + lane * 8);
    __syncwarp();
    if (lane == 0) mbar_arrive(bar + 8 * MB_KVF);
    bf16* kd = g_km + ((size_t)(s * NH + h) * NMEM) * DH + j * 64;
    *reinterpret_cast<uint4*>(kd + (lane >> 3) * DH + (lane & 7) * 8) = k0;
    *reinterpret_cast<uint4*>(kd + (4 + (lane >> 3)) * DH + (lane & 7) * 8) = k1;
    unsigned* vd = reinterpret_cast<unsigned*>(g_vmt) + ((size_t)(s * NH + h) * DH + j * 64) * 4;
#pragma unroll
    for (int i = 0; i < 4; i++) { vd[(i * 16) * 4 + lane] = v[i].x; vd[(i * 16 + 8) * 4 + lane] = v[i].y; }
    __threadfence();
    __syncwarp();
    if (lane == 0) st_release(&g_flags.rec[c], s + 1);
  }
}

__device__ __forceinline__ void bulk_producer(const Maps& maps, unsigned sb, int* misc) {
  const unsigned bar = sb + SM_BAR;
  unsigned st = 0, ph = 0, seq = 0;
  while (true) {
    int idx = (int)atomicAdd(&g_flags.ctr, 1u);
    if (idx >= N_ITEMS) {
      mbar_wait(bar + 8 * (MB_EMPTY + st), ph ^ 1);
      misc[seq & 3] = -1;
      mbar_arrive(bar + 8 * (MB_FULL + st));
      break;
    }
    ISTAMP(idx, 0);
    Item it = decode_item(idx);
    const CUtensorMap *ma, *mb_; int ka = 0, kbr = 0, nb0 = it.c * 256;
    if (it.type == T_QKV) { ma = &maps.xn; mb_ = it.c < 16 ? &maps.wq : (it.c < 32 ? &maps.wk : &maps.wv); nb0 = (it.c & 15) * 256; }
    else if (it.type == T_M1) { ma = &maps.y; mb_ = &maps.w1; }
    else if (it.type == T_M2) { ma = &maps.h1; mb_ = &maps.w2; wait_flag_ge(&g_flags.h1[it.b], 7); }
    else if (it.type == T_OUT) { ma = &maps.o; mb_ = &maps.wo; ka = kbr = it.ks * 1024; wait_flag_ge(&g_flags.o[it.b * 4 + it.ks], 4); wait_flag_ge(&g_flags.g[it.b], 2); }
    else {
      ma = mb_ = &maps.qkv_ld;
      wait_flag_ge(&g_flags.qkv[it.b * 48 + it.c], 1); wait_flag_ge(&g_flags.qkv[it.b * 48 + 16 + it.c], 1); wait_flag_ge(&g_flags.qkv[it.b * 48 + 32 + it.c], 1);
      for (int i = 0; i < 4; i++) wait_flag_ge(&g_flags.rec[it.c * 4 + i], it.b * 4 + 4);
    }
    fence_proxy_async();
    ISTAMP(idx, 1);
    const int nkb = item_nkb(it.type);
    for (int kb = 0; kb < nkb; kb++) {
      mbar_wait(bar + 8 * (MB_EMPTY + st), ph ^ 1);
      if (kb == 0) { misc[seq & 3] = idx; seq++; }
      unsigned dst = sb + st * STAGE_BYTES, mb = bar + 8 * (MB_FULL + st);
      mbar_expect_tx(mb, STAGE_BYTES);
      if (it.type == T_ATT) {
        int head = it.c * 2 + (kb >> 1), row = it.b * 128 + (kb & 1) * 64;
        for (int i = 0; i < 12; i++) tma_load_2d(dst + i * 4096, ma, (i >> 2) * HD + head * 128 + (i & 1) * 64, row + ((i >> 1) & 1) * 32, mb);
      } else {
        tma_load_2d(dst, ma, ka + kb * 64, it.b * 128, mb);
        for (int i = 0; i < 4; i++) tma_load_2d(dst + 16384 + i * 8192, mb_, nb0 + i * 64, kbr + kb * 64, mb);
      }
      if (++st == NSTAGE) { st = 0; ph ^= 1; }
    }
  }
}
__device__ __forceinline__ void bulk_store(const Maps& maps, unsigned sb, volatile int* misc) {
  const unsigned bar = sb + SM_BAR;
  unsigned ph = 0;
  while (true) {
    mbar_wait(bar + 8 * MB_STGF, ph); ph ^= 1;
    int idx = misc[4];
    if (idx < 0) break;
    Item it = decode_item(idx);
    const CUtensorMap* mp = it.type == T_QKV ? &maps.qkv_st : (it.type == T_M1 ? &maps.h1 : (it.type == T_M2 ? &maps.g : &maps.o));
    unsigned* flag = it.type == T_QKV ? &g_flags.qkv[it.b * 48 + it.c] : (it.type == T_M1 ? &g_flags.h1[it.b] : (it.type == T_M2 ? &g_flags.g[it.b] : &g_flags.o[it.b * 4 + (it.c >> 2)]));
    for (int i = 0; i < 4; i++) tma_store_2d(mp, sb + B_STG + i * 16384, it.c * 256 + i * 64, it.b * 128);
    asm volatile("cp.async.bulk.commit_group;" ::: "memory");
    asm volatile("cp.async.bulk.wait_group.read 0;" ::: "memory");
    mbar_arrive(bar + 8 * MB_STGE);
    asm volatile("cp.async.bulk.wait_group 0;" ::: "memory");
    fence_proxy_async();
    __threadfence();
    red_release_add(flag, 1);
    ISTAMP(idx, 3);
  }
}
__device__ __forceinline__ float gelu_t(float x) {
  float u = 0.7978845608028654f * (x + 0.044715f * x * x * x);
  return __fdividef(x, 1.0f + __expf(-2.0f * u));
}
__device__ __forceinline__ float silu_f(float x) { return __fdividef(x, 1.0f + __expf(-x)); }

__device__ __forceinline__ void bulk_att_stage(unsigned sa, unsigned stg, int b, int hp, int kb, int w, int lane) {
  const int g = lane >> 2, tq = lane & 3, m = lane >> 3, r8 = lane & 7;
  const int seg = w >> 2, mt = (w >> 1) & 1, eh = w & 1;
  const int head = hp * 2 + (kb >> 1), sg = b * 4 + (kb & 1) * 2 + seg;
  const unsigned* kmp = reinterpret_cast<const unsigned*>(g_km + ((size_t)(sg * NH + head) * NMEM + g) * DH) + tq;
  const unsigned* vmp = reinterpret_cast<const unsigned*>(g_vmt) + ((size_t)(sg * NH + head) * DH + eh * 64) * 4 + lane;
  unsigned km[16], vm[8];
#pragma unroll
  for (int i = 0; i < 16; i++) km[i] = __ldcg(kmp + i * 4);
#pragma unroll
  for (int i = 0; i < 8; i++) vm[i] = __ldcg(vmp + i * 32);
  float s[5][4];
#pragma unroll
  for (int i = 0; i < 5; i++) { s[i][0] = s[i][1] = s[i][2] = s[i][3] = 0; }
  const unsigned qb = sa + (0 * 2 + seg) * 8192, kbs = sa + (1 * 2 + seg) * 8192, vb = sa + (2 * 2 + seg) * 8192 + eh * 4096;
  unsigned qa[8][4];
#pragma unroll
  for (int ks = 0; ks < 8; ks++) {
    int row = mt * 16 + (m & 1) * 8 + r8;
    ldsm_x4(qa[ks], qb + (ks >> 2) * 4096 + row * 128 + ((((ks & 3) * 2 + (m >> 1)) ^ r8) << 4));
    unsigned kf[4];
    int krow = (m >> 1) * 8 + r8;
    unsigned ka = kbs + (ks >> 2) * 4096 + krow * 128 + ((((ks & 3) * 2 + (m & 1)) ^ r8) << 4);
    ldsm_x4(kf, ka);
    mma16816(s[0], qa[ks], kf[0], kf[1]); mma16816(s[1], qa[ks], kf[2], kf[3]);
    if (mt) { ldsm_x4(kf, ka + 2048); mma16816(s[2], qa[ks], kf[0], kf[1]); mma16816(s[3], qa[ks], kf[2], kf[3]); }
  }
#pragma unroll
  for (int ks = 0; ks < 8; ks++) mma16816(s[4], qa[ks], km[2 * ks], km[2 * ks + 1]);
  float mx0 = -INFINITY, mx1 = -INFINITY;
  const int t0 = mt * 16 + g, t1 = t0 + 8;
#pragma unroll
  for (int i = 0; i < 5; i++) {
#pragma unroll
    for (int e = 0; e < 4; e++) {
      float v = bf16r(bf16r(s[i][e]) * SCALE_QK);
      if (i < 4) { int kj = i * 8 + 2 * tq + (e & 1); if (kj > (e < 2 ? t0 : t1)) v = -INFINITY; }
      s[i][e] = v;
      if (e < 2) mx0 = fmaxf(mx0, v); else mx1 = fmaxf(mx1, v);
    }
  }
  mx0 = fmaxf(mx0, __shfl_xor_sync(~0u, mx0, 1)); mx0 = fmaxf(mx0, __shfl_xor_sync(~0u, mx0, 2));
  mx1 = fmaxf(mx1, __shfl_xor_sync(~0u, mx1, 1)); mx1 = fmaxf(mx1, __shfl_xor_sync(~0u, mx1, 2));
  float sm0 = 0, sm1 = 0;
#pragma unroll
  for (int i = 0; i < 5; i++) {
    s[i][0] = __expf(s[i][0] - mx0); s[i][1] = __expf(s[i][1] - mx0); s[i][2] = __expf(s[i][2] - mx1); s[i][3] = __expf(s[i][3] - mx1);
    sm0 += s[i][0] + s[i][1]; sm1 += s[i][2] + s[i][3];
  }
  sm0 += __shfl_xor_sync(~0u, sm0, 1); sm0 += __shfl_xor_sync(~0u, sm0, 2);
  sm1 += __shfl_xor_sync(~0u, sm1, 1); sm1 += __shfl_xor_sync(~0u, sm1, 2);
  const float i0 = __fdividef(1.0f, sm0), i1 = __fdividef(1.0f, sm1);
  unsigned pa[2][4], pm0, pm1;
#pragma unroll
  for (int kk = 0; kk < 2; kk++) {
    pa[kk][0] = pack_bf16(s[2 * kk][0] * i0, s[2 * kk][1] * i0); pa[kk][1] = pack_bf16(s[2 * kk][2] * i1, s[2 * kk][3] * i1);
    pa[kk][2] = pack_bf16(s[2 * kk + 1][0] * i0, s[2 * kk + 1][1] * i0); pa[kk][3] = pack_bf16(s[2 * kk + 1][2] * i1, s[2 * kk + 1][3] * i1);
  }
  pm0 = pack_bf16(s[4][0] * i0, s[4][1] * i0); pm1 = pack_bf16(s[4][2] * i1, s[4][3] * i1);
  const int orow = (kb & 1) * 64 + seg * 32 + mt * 16 + (m & 1) * 8 + r8;
  const unsigned ob = stg + ((kb >> 1) * 2 + eh) * 16384 + orow * 128;
#pragma unroll
  for (int cp = 0; cp < 4; cp++) {
    float o0[4] = {0, 0, 0, 0}, o1[4] = {0, 0, 0, 0};
    mma1688(o0, pm0, pm1, vm[2 * cp]); mma1688(o1, pm0, pm1, vm[2 * cp + 1]);
    unsigned vf[4];
    int row = (m & 1) * 8 + r8;
    unsigned va = vb + row * 128 + (((cp * 2 + (m >> 1)) ^ r8) << 4);
    ldsm_x4_t(vf, va);
    mma16816(o0, pa[0], vf[0], vf[1]); mma16816(o1, pa[0], vf[2], vf[3]);
    if (mt) { ldsm_x4_t(vf, va + 2048); mma16816(o0, pa[1], vf[0], vf[1]); mma16816(o1, pa[1], vf[2], vf[3]); }
    stsm_x4(ob + (((cp * 2 + (m >> 1)) ^ r8) << 4), pack_bf16(o0[0], o0[1]), pack_bf16(o0[2], o0[3]), pack_bf16(o1[0], o1[1]), pack_bf16(o1[2], o1[3]));
  }
}

__device__ __forceinline__ void bulk_worker(unsigned sb, volatile int* misc, const bf16* __restrict__ x, const bf16* __restrict__ b1, const bf16* __restrict__ b2, bf16* __restrict__ out) {
  const int t = threadIdx.x, lane = t & 31, w = t >> 5, wg = w >> 2, g = lane >> 2, tq = lane & 3, m = lane >> 3, r8 = lane & 7;
  const unsigned bar = sb + SM_BAR;
  unsigned st = 0, ph = 0, seq = 0, sph = 0;
  float d[128];
  while (true) {
    mbar_wait(bar + 8 * (MB_FULL + st), ph);
    const int idx = misc[seq & 3]; seq++;
    if (idx < 0 || idx >= N_ITEMS) break;
    if (t == 0) ISTAMP(idx, 2);
    const Item it = decode_item(idx);
    const int nkb = item_nkb(it.type);
    if (it.type == T_ATT) {
      mbar_wait(bar + 8 * MB_STGE, sph ^ 1);
      for (int kb = 0; kb < 4; kb++) {
        if (kb) mbar_wait(bar + 8 * (MB_FULL + st), ph);
        bulk_att_stage(sb + st * STAGE_BYTES, sb + B_STG, it.b, it.c, kb, w, lane);
        __syncwarp();
        if (lane == 0) mbar_arrive(bar + 8 * (MB_EMPTY + st));
        if (++st == NSTAGE) { st = 0; ph ^= 1; }
      }
      if (t == 0) misc[4] = idx;
      fence_proxy_async_smem();
      mbar_arrive(bar + 8 * MB_STGF); sph ^= 1;
      continue;
    }
    unsigned pst = 0;
    for (int kb = 0; kb < nkb; kb++) {
      if (kb) mbar_wait(bar + 8 * (MB_FULL + st), ph);
      unsigned sa = sb + st * STAGE_BYTES;
      uint64_t ad = mkdesc(sa + wg * 8192, 16, 1024), bd = mkdesc(sa + 16384, 8192, 1024);
      asm volatile("wgmma.fence.sync.aligned;" ::: "memory");
#pragma unroll
      for (int k = 0; k < 4; k++) wgmma_n256(d, ad + k * 2, bd + k * 128, (kb | k) != 0);
      asm volatile("wgmma.commit_group.sync.aligned;" ::: "memory");
      if (kb) {
        asm volatile("wgmma.wait_group.sync.aligned 1;" ::: "memory");
        if (lane == 0) mbar_arrive(bar + 8 * (MB_EMPTY + pst));
      }
      pst = st;
      if (++st == NSTAGE) { st = 0; ph ^= 1; }
    }
    asm volatile("wgmma.wait_group.sync.aligned 0;" ::: "memory");
    if (lane == 0) mbar_arrive(bar + 8 * (MB_EMPTY + pst));
    if (it.type == T_OUT) {
      const int row = it.b * 128 + w * 16 + g, col = it.c * 256 + 2 * tq;
      float* pp = g_opart + ((size_t)it.ks * S_TOK + row) * DM + col;
#pragma unroll
      for (int i = 0; i < 32; i++) {
        __stcg(reinterpret_cast<float2*>(pp + i * 8), make_float2(d[4 * i], d[4 * i + 1]));
        __stcg(reinterpret_cast<float2*>(pp + 8 * DM + i * 8), make_float2(d[4 * i + 2], d[4 * i + 3]));
      }
      __threadfence();
      bar_sync(1, 256);
      if (t == 0) misc[5] = (int)atomicAdd(&g_flags.p[it.b * 2 + it.c], 1u);
      bar_sync(1, 256);
      if (misc[5] == 3) {
        __threadfence();
        const float* p0 = g_opart + (size_t)row * DM + col;
#pragma unroll 4
        for (int i = 0; i < 64; i++) {
          size_t off = (size_t)(i & 1) * 8 * DM + (i >> 1) * 8;
          float2 a = __ldcg(reinterpret_cast<const float2*>(p0 + off)), b = __ldcg(reinterpret_cast<const float2*>(p0 + off + (size_t)S_TOK * DM));
          float2 c = __ldcg(reinterpret_cast<const float2*>(p0 + off + (size_t)2 * S_TOK * DM)), e = __ldcg(reinterpret_cast<const float2*>(p0 + off + (size_t)3 * S_TOK * DM));
          size_t o = (size_t)row * DM + col + off;
          unsigned gv = __ldcg(reinterpret_cast<const unsigned*>(g_g + o)), xv = __ldg(reinterpret_cast<const unsigned*>(x + o));
          float s0 = bf16r((a.x + b.x) + (c.x + e.x)), s1 = bf16r((a.y + b.y) + (c.y + e.y));
          *reinterpret_cast<unsigned*>(out + o) = pack_bf16(bf_lo(xv) + bf16r(s0 * bf_lo(gv)), bf_hi(xv) + bf16r(s1 * bf_hi(gv)));
        }
      }
      bar_sync(1, 256);
      if (t == 0) ISTAMP(idx, 3);
      continue;
    }
    if (it.type != T_QKV) {
      const unsigned* bp = reinterpret_cast<const unsigned*>((it.type == T_M1 ? b1 : b2) + it.c * 256) + tq;
#pragma unroll
      for (int i = 0; i < 32; i++) {
        unsigned bv = __ldg(bp + i * 4);
        float lo = bf_lo(bv), hi = bf_hi(bv);
        float x0 = bf16r(bf16r(d[4 * i]) + lo), x1 = bf16r(bf16r(d[4 * i + 1]) + hi), x2 = bf16r(bf16r(d[4 * i + 2]) + lo), x3 = bf16r(bf16r(d[4 * i + 3]) + hi);
        if (it.type == T_M1) { d[4 * i] = gelu_t(x0); d[4 * i + 1] = gelu_t(x1); d[4 * i + 2] = gelu_t(x2); d[4 * i + 3] = gelu_t(x3); }
        else { d[4 * i] = silu_f(x0); d[4 * i + 1] = silu_f(x1); d[4 * i + 2] = silu_f(x2); d[4 * i + 3] = silu_f(x3); }
      }
    }
    mbar_wait(bar + 8 * MB_STGE, sph ^ 1);
    {
      const unsigned ob = sb + B_STG + (w * 16 + (m & 1) * 8 + r8) * 128;
#pragma unroll
      for (int i = 0; i < 16; i++)
        stsm_x4(ob + (i >> 2) * 16384 + ((((i & 3) * 2 + (m >> 1)) ^ r8) << 4), pack_bf16(d[8 * i], d[8 * i + 1]), pack_bf16(d[8 * i + 2], d[8 * i + 3]),
                pack_bf16(d[8 * i + 4], d[8 * i + 5]), pack_bf16(d[8 * i + 6], d[8 * i + 7]));
    }
    if (t == 0) misc[4] = idx;
    fence_proxy_async_smem();
    mbar_arrive(bar + 8 * MB_STGF); sph ^= 1;
  }
  mbar_wait(bar + 8 * MB_STGE, sph ^ 1);
  if (t == 0) misc[4] = -1;
  mbar_arrive(bar + 8 * MB_STGF);
}

__global__ void __cluster_dims__(2, 1, 1) __launch_bounds__(384, 1)
k_main(const __grid_constant__ Maps maps, const bf16* __restrict__ x, const bf16* __restrict__ mem0, const bf16* __restrict__ b1, const bf16* __restrict__ b2, bf16* __restrict__ out) {
  extern __shared__ unsigned char smem_raw[];
  const unsigned sraw = smem_u32(smem_raw);
  const unsigned sb = (sraw + 1023u) & ~1023u;
  int* misc = reinterpret_cast<int*>(smem_raw + (sb - sraw) + SM_MISC);
  const int w = threadIdx.x >> 5;
  const bool rec = blockIdx.x < NREC;
  if (threadIdx.x == 0) {
    const unsigned bar = sb + SM_BAR;
    for (int i = 0; i < 8; i++) { mbar_init(bar + 8 * (MB_FULL + i), 1); mbar_init(bar + 8 * (MB_EMPTY + i), 8); }
    mbar_init(bar + 8 * MB_STGF, 256); mbar_init(bar + 8 * MB_STGE, 1);
    for (int i = MB_W0; i <= MB_KVF; i++) mbar_init(bar + 8 * i, 1);
    asm volatile("fence.mbarrier_init.release.cluster;" ::: "memory");
  }
  __syncthreads();
  asm volatile("barrier.cluster.arrive.release.aligned;\nbarrier.cluster.wait.acquire.aligned;" ::: "memory");
  if (w >= 8) {
    asm volatile("setmaxnreg.dec.sync.aligned.u32 24;");
    if (rec) { if (w == 8) rec_ring(maps, sb); else if (w == 9) rec_copy(sb); }
    else if ((threadIdx.x & 31) == 0) { if (w == 8) bulk_producer(maps, sb, misc); else if (w == 9) bulk_store(maps, sb, misc); }
  } else {
    if (rec) { asm volatile("setmaxnreg.inc.sync.aligned.u32 240;"); rec_worker(maps, sb, mem0); }
    else { asm volatile("setmaxnreg.inc.sync.aligned.u32 240;"); bulk_worker(sb, misc, x, b1, b2, out); }
  }
}

typedef CUresult (*EncFn)(CUtensorMap*, CUtensorMapDataType, cuuint32_t, void*, const cuuint64_t*, const cuuint64_t*, const cuuint32_t*, const cuuint32_t*,
                          CUtensorMapInterleave, CUtensorMapSwizzle, CUtensorMapL2promotion, CUtensorMapFloatOOBfill);
static void mk_map(EncFn enc, CUtensorMap* m, const void* ptr, uint64_t rows, uint64_t cols, uint32_t box_rows) {
  cuuint64_t dims[2] = {cols, rows}; cuuint64_t strides[1] = {cols * 2};
  cuuint32_t box[2] = {64, box_rows}, es[2] = {1, 1};
  enc(m, CU_TENSOR_MAP_DATA_TYPE_BFLOAT16, 2, const_cast<void*>(ptr), dims, strides, box, es, CU_TENSOR_MAP_INTERLEAVE_NONE, CU_TENSOR_MAP_SWIZZLE_128B,
      CU_TENSOR_MAP_L2_PROMOTION_L2_256B, CU_TENSOR_MAP_FLOAT_OOB_FILL_NONE);
}
extern "C" void kernel_launch(void* const* d_in, const int* in_sizes, int n_in, void* d_out, int out_size) {
  static EncFn enc = nullptr;
  static void *p_xn, *p_y, *p_h1, *p_o, *p_qkv, *p_g;
  if (!enc) {
    void* fn = nullptr; cudaDriverEntryPointQueryResult qr;
    cudaGetDriverEntryPoint("cuTensorMapEncodeTiled", &fn, cudaEnableDefault, &qr);
    enc = (EncFn)fn;
    cudaGetSymbolAddress(&p_xn, g_xn); cudaGetSymbolAddress(&p_y, g_y); cudaGetSymbolAddress(&p_h1, g_h1);
    cudaGetSymbolAddress(&p_o, g_o); cudaGetSymbolAddress(&p_qkv, g_qkv); cudaGetSymbolAddress(&p_g, g_g);
    cudaFuncSetAttribute(k_main, cudaFuncAttributeMaxDynamicSharedMemorySize, SMEM_TOTAL);
  }
  Maps maps;
  mk_map(enc, &maps.xn, p_xn, S_TOK, DM, 128); mk_map(enc, &maps.y, p_y, S_TOK, DM, 128); mk_map(enc, &maps.h1, p_h1, S_TOK, FF, 128);
  mk_map(enc, &maps.o, p_o, S_TOK, HD, 128); mk_map(enc, &maps.qkv_st, p_qkv, S_TOK, 3 * HD, 128); mk_map(enc, &maps.qkv_ld, p_qkv, S_TOK, 3 * HD, 32);
  mk_map(enc, &maps.g, p_g, S_TOK, DM, 128);
  mk_map(enc, &maps.wq, d_in[2], DM, HD, 64); mk_map(enc, &maps.wk, d_in[3], DM, HD, 64); mk_map(enc, &maps.wv, d_in[4], DM, HD, 64);
  mk_map(enc, &maps.wo, d_in[5], HD, DM, 64); mk_map(enc, &maps.w1, d_in[8], DM, FF, 64); mk_map(enc, &maps.w2, d_in[10], FF, DM, 64);
  cudaStream_t st = cudaStreamPerThread;
  k_pre<<<256, 256, 0, st>>>((const bf16*)d_in[0]);
  k_main<<<NCTA, 384, SMEM_TOTAL, st>>>(maps, (const bf16*)d_in[0], (const bf16*)d_in[1], (const bf16*)d_in[9], (const bf16*)d_in[11], (bf16*)d_out);
}
```

```cpp
#include <cuda_runtime.h>
#include <cuda_bf16.h>
#include <cuda.h>
#include <stdint.h>

typedef __nv_bfloat16 bf16;

#define S_TOK 2048
#define DM 512
#define NH 32
#define DH 128
#define HD 4096
#define NMEM 8
#define SEG 32
#define NSEG 64
#define FF 1792
#define NBLK 16
#define NREC 64
#define NCTA 132
#define NBULK (NCTA - NREC)

__device__ __align__(1024) bf16 g_xn[S_TOK * DM];
__device__ __align__(1024) bf16 g_y[S_TOK * DM];
__device__ __align__(1024) bf16 g_qkv[(size_t)S_TOK * 3 * HD];
__device__ __align__(1024) bf16 g_h1[S_TOK * FF];
__device__ __align__(1024) bf16 g_g[S_TOK * DM];
__device__ __align__(1024) bf16 g_o[(size_t)S_TOK * HD];
__device__ __align__(1024) bf16 g_km[NSEG * NH * NMEM * DH];
__device__ __align__(1024) bf16 g_vmt[NSEG * NH * DH * NMEM];
__device__ __align__(1024) float g_opart[(size_t)4 * S_TOK * DM];
__device__ __align__(1024) unsigned g_part[2 * NREC * NH * 64];
__device__ __align__(1024) unsigned g_pub[NSEG * 2048];
struct Flags {
  unsigned qkv[NBLK * 48];
  unsigned h1[NBLK];
  unsigned g[NBLK];
  unsigned o[NBLK * 4];
  unsigned p[NBLK * 2];
  unsigned ctr;
  unsigned rec[NREC];
  unsigned abort_;
};
__device__ __align__(1024) Flags g_flags;

#define RSTAMP(k)
#define DBGMODE 0
#define ISTAMP(i, k)
__device__ __forceinline__ unsigned smem_u32(const void* p) { return (unsigned)__cvta_generic_to_shared(p); }
__device__ __forceinline__ float bf16r(float x) { unsigned u; asm("cvt.rn.bf16x2.f32 %0, %1, %2;" : "=r"(u) : "f"(x), "f"(0.0f)); return __uint_as_float(u); }
__device__ __forceinline__ unsigned pack_bf16(float lo, float hi) {
  __nv_bfloat162 v = __floats2bfloat162_rn(lo, hi);
  return *reinterpret_cast<unsigned*>(&v);
}
__device__ __forceinline__ float bf_lo(unsigned u) { return __uint_as_float(u << 16); }
__device__ __forceinline__ float bf_hi(unsigned u) { return __uint_as_float(u & 0xffff0000u); }

#define SPIN_LIMIT (1u << 20)
#define TRAP_IF(x) if ((x) > SPIN_LIMIT) { asm volatile("st.global.u32 [%0], %1;" ::"l"(0ull), "r"(0u) : "memory"); break; }
__device__ __forceinline__ unsigned ld_acquire(const unsigned* p) {
  unsigned v; asm volatile("ld.acquire.gpu.global.u32 %0, [%1];" : "=r"(v) : "l"(p) : "memory"); return v;
}
__device__ __forceinline__ unsigned ld_relaxed(const unsigned* p) {
  unsigned v; asm volatile("ld.relaxed.gpu.global.u32 %0, [%1];" : "=r"(v) : "l"(p) : "memory"); return v;
}
__device__ __forceinline__ void red_release_add(unsigned* p, unsigned v) {
  asm volatile("red.release.gpu.global.add.u32 [%0], %1;" ::"l"(p), "r"(v) : "memory");
}
__device__ __forceinline__ void st_release(unsigned* p, unsigned v) {
  asm volatile("st.release.gpu.global.u32 [%0], %1;" ::"l"(p), "r"(v) : "memory");
}
__device__ __forceinline__ void wait_flag_ge(const unsigned* p, unsigned target) {
  unsigned it = 0;
  while (ld_acquire(p) < target) {
    __nanosleep(64);
    TRAP_IF(++it);
  }
}
__device__ __forceinline__ uint4 ldv4_relaxed(const void* p) {
  uint4 a; asm volatile("ld.relaxed.gpu.global.v4.u32 {%0,%1,%2,%3}, [%4];" : "=r"(a.x), "=r"(a.y), "=r"(a.z), "=r"(a.w) : "l"(p) : "memory"); return a;
}
__device__ __forceinline__ void mbar_init(unsigned mb, unsigned cnt) { asm volatile("mbarrier.init.shared::cta.b64 [%0], %1;" ::"r"(mb), "r"(cnt) : "memory"); }
__device__ __forceinline__ void mbar_expect_tx(unsigned mb, unsigned bytes) { asm volatile("mbarrier.arrive.expect_tx.shared::cta.b64 _, [%0], %1;" ::"r"(mb), "r"(bytes) : "memory"); }
__device__ __forceinline__ void mbar_arrive(unsigned mb) { asm volatile("mbarrier.arrive.shared::cta.b64 _, [%0];" ::"r"(mb) : "memory"); }
__device__ __forceinline__ void mbar_wait(unsigned mb, unsigned parity) {
  unsigned ok, it = 0;
  while (true) {
    asm volatile("{.reg .pred p; mbarrier.try_wait.parity.shared::cta.b64 p, [%1], %2; selp.u32 %0,1,0,p;}" : "=r"(ok) : "r"(mb), "r"(parity) : "memory");
    if (ok) break;
    TRAP_IF(++it);
  }
}
__device__ __forceinline__ void mbar_wait_sleep(unsigned mb, unsigned parity) {
  unsigned ok, it = 0;
  while (true) {
    asm volatile("{.reg .pred p; mbarrier.test_wait.parity.shared::cta.b64 p, [%1], %2; selp.u32 %0,1,0,p;}" : "=r"(ok) : "r"(mb), "r"(parity) : "memory");
    if (ok) break;
    __nanosleep(200);
    TRAP_IF(++it);
  }
}
__device__ __forceinline__ float ex2f(float x) { float y; asm("ex2.approx.ftz.f32 %0, %1;" : "=f"(y) : "f"(x)); return y; }
__device__ __forceinline__ int opaque_tid() { int t = threadIdx.x; t = __shfl_sync(~0u, t, t & 31); return t; }
#define LOG2E 1.4426950408889634f
__device__ __forceinline__ void mbar_wait_cluster(unsigned mb, unsigned parity) {
  unsigned ok, it = 0;
  while (true) {
    asm volatile("{.reg .pred p; mbarrier.try_wait.parity.acquire.cluster.shared::cta.b64 p, [%1], %2; selp.u32 %0,1,0,p;}" : "=r"(ok) : "r"(mb), "r"(parity) : "memory");
    if (ok) break;
    TRAP_IF(++it);
  }
}
__device__ __forceinline__ void bar_sync(int id, int n) { asm volatile("bar.sync %0, %1;" ::"r"(id), "r"(n) : "memory"); }
__device__ __forceinline__ void bar_arrive(int id, int n) { asm volatile("bar.arrive %0, %1;" ::"r"(id), "r"(n) : "memory"); }
__device__ __forceinline__ void tma_load_2d(unsigned dst, const CUtensorMap* map, int c0, int c1, unsigned mb) {
  asm volatile("cp.async.bulk.tensor.2d.shared::cluster.global.mbarrier::complete_tx::bytes [%0], [%1, {%3, %4}], [%2];"
               ::"r"(dst), "l"((uint64_t)map), "r"(mb), "r"(c0), "r"(c1) : "memory");
}
__device__ __forceinline__ void tma_store_2d(const CUtensorMap* map, unsigned src, int c0, int c1) {
  asm volatile("cp.async.bulk.tensor.2d.global.shared::cta.bulk_group [%0, {%2, %3}], [%1];"
               ::"l"((uint64_t)map), "r"(src), "r"(c0), "r"(c1) : "memory");
}
__device__ __forceinline__ void fence_proxy_async() { asm volatile("fence.proxy.async;" ::: "memory"); }
__device__ __forceinline__ void fence_proxy_async_smem() { asm volatile("fence.proxy.async.shared::cta;" ::: "memory"); }
__device__ __forceinline__ void ldsm_x4(unsigned* r, unsigned addr) {
  asm volatile("ldmatrix.sync.aligned.m8n8.x4.shared.b16 {%0,%1,%2,%3}, [%4];" : "=r"(r[0]), "=r"(r[1]), "=r"(r[2]), "=r"(r[3]) : "r"(addr) : "memory");
}
__device__ __forceinline__ void ldsm_x4_t(unsigned* r, unsigned addr) {
  asm volatile("ldmatrix.sync.aligned.m8n8.x4.trans.shared.b16 {%0,%1,%2,%3}, [%4];" : "=r"(r[0]), "=r"(r[1]), "=r"(r[2]), "=r"(r[3]) : "r"(addr) : "memory");
}
__device__ __forceinline__ void stsm_x2_t(unsigned addr, unsigned r0, unsigned r1) {
  asm volatile("stmatrix.sync.aligned.m8n8.x2.trans.shared.b16 [%0], {%1,%2};" ::"r"(addr), "r"(r0), "r"(r1) : "memory");
}
__device__ __forceinline__ void stsm_x4(unsigned addr, unsigned r0, unsigned r1, unsigned r2, unsigned r3) {
  asm volatile("stmatrix.sync.aligned.m8n8.x4.shared.b16 [%0], {%1,%2,%3,%4};" ::"r"(addr), "r"(r0), "r"(r1), "r"(r2), "r"(r3) : "memory");
}
__device__ __forceinline__ void mma16816(float* d, const unsigned* a, unsigned b0, unsigned b1) {
  asm volatile("mma.sync.aligned.m16n8k16.row.col.f32.bf16.bf16.f32 {%0,%1,%2,%3}, {%4,%5,%6,%7}, {%8,%9}, {%0,%1,%2,%3};"
               : "+f"(d[0]), "+f"(d[1]), "+f"(d[2]), "+f"(d[3]) : "r"(a[0]), "r"(a[1]), "r"(a[2]), "r"(a[3]), "r"(b0), "r"(b1));
}
__device__ __forceinline__ void mma1688(float* d, unsigned a0, unsigned a1, unsigned b0) {
  asm volatile("mma.sync.aligned.m16n8k8.row.col.f32.bf16.bf16.f32 {%0,%1,%2,%3}, {%4,%5}, {%6}, {%0,%1,%2,%3};"
               : "+f"(d[0]), "+f"(d[1]), "+f"(d[2]), "+f"(d[3]) : "r"(a0), "r"(a1), "r"(b0));
}
__device__ __forceinline__ uint64_t mkdesc(unsigned addr, unsigned lbo, unsigned sbo) {
  return (uint64_t)((addr >> 4) & 0x3fff) | ((uint64_t)(lbo >> 4) << 16) | ((uint64_t)(sbo >> 4) << 32) | (1ull << 62);
}
#define R8(b) "+f"(d[b]), "+f"(d[b + 1]), "+f"(d[b + 2]), "+f"(d[b + 3]), "+f"(d[b + 4]), "+f"(d[b + 5]), "+f"(d[b + 6]), "+f"(d[b + 7])
#define R32(b) R8(b), R8(b + 8), R8(b + 16), R8(b + 24)
__device__ __forceinline__ void wgmma_n256(float* d, uint64_t ad, uint64_t bd, int acc) {
  asm volatile(
      "{.reg .pred p; setp.ne.b32 p, %130, 0;\n"
      "wgmma.mma_async.sync.aligned.m64n256k16.f32.bf16.bf16 "
      "{%0,%1,%2,%3,%4,%5,%6,%7,%8,%9,%10,%11,%12,%13,%14,%15,%16,%17,%18,%19,%20,%21,%22,%23,%24,%25,%26,%27,%28,%29,%30,%31,"
      "%32,%33,%34,%35,%36,%37,%38,%39,%40,%41,%42,%43,%44,%45,%46,%47,%48,%49,%50,%51,%52,%53,%54,%55,%56,%57,%58,%59,%60,%61,%62,%63,"
      "%64,%65,%66,%67,%68,%69,%70,%71,%72,%73,%74,%75,%76,%77,%78,%79,%80,%81,%82,%83,%84,%85,%86,%87,%88,%89,%90,%91,%92,%93,%94,%95,"
      "%96,%97,%98,%99,%100,%101,%102,%103,%104,%105,%106,%107,%108,%109,%110,%111,%112,%113,%114,%115,%116,%117,%118,%119,%120,%121,%122,%123,%124,%125,%126,%127},"
      "%128, %129, p, 1, 1, 0, 1;}\n"
      : R32(0), R32(32), R32(64), R32(96)
      : "l"(ad), "l"(bd), "r"(acc));
}

__device__ __forceinline__ void ln16(const float* x, float* o) {
  float s = 0;
#pragma unroll
  for (int i = 0; i < 16; i++) s += x[i];
#pragma unroll
  for (int of = 16; of > 0; of >>= 1) s += __shfl_xor_sync(~0u, s, of);
  float mean = s * (1.0f / DM);
  float v = 0;
#pragma unroll
  for (int i = 0; i < 16; i++) { float dd = x[i] - mean; v += dd * dd; }
#pragma unroll
  for (int of = 16; of > 0; of >>= 1) v += __shfl_xor_sync(~0u, v, of);
  float mb = bf16r(mean);
  float vb = bf16r(v * (1.0f / DM));
  float den = bf16r(sqrtf(bf16r(vb + 1e-5f)));
#pragma unroll
  for (int i = 0; i < 16; i++) o[i] = bf16r(__fdiv_rn(bf16r(x[i] - mb), den));
}
__global__ void __launch_bounds__(256) k_pre(const bf16* __restrict__ x) {
  int t = threadIdx.x, lane = t & 31, w = t >> 5;
  int row = blockIdx.x * 8 + w;
  const uint4* src = reinterpret_cast<const uint4*>(x + (size_t)row * DM);
  uint4 a = src[lane], b = src[lane + 32];
  unsigned u[8] = {a.x, a.y, a.z, a.w, b.x, b.y, b.z, b.w};
  float f[16], o[16], o2[16];
#pragma unroll
  for (int i = 0; i < 8; i++) { f[2 * i] = bf_lo(u[i]); f[2 * i + 1] = bf_hi(u[i]); }
  ln16(f, o);
  ln16(o, o2);
  uint4* d1 = reinterpret_cast<uint4*>(g_xn + (size_t)row * DM);
  uint4* d2 = reinterpret_cast<uint4*>(g_y + (size_t)row * DM);
  d1[lane] = make_uint4(pack_bf16(o[0], o[1]), pack_bf16(o[2], o[3]), pack_bf16(o[4], o[5]), pack_bf16(o[6], o[7]));
  d1[lane + 32] = make_uint4(pack_bf16(o[8], o[9]), pack_bf16(o[10], o[11]), pack_bf16(o[12], o[13]), pack_bf16(o[14], o[15]));
  d2[lane] = make_uint4(pack_bf16(o2[0], o2[1]), pack_bf16(o2[2], o2[3]), pack_bf16(o2[4], o2[5]), pack_bf16(o2[6], o2[7]));
  d2[lane + 32] = make_uint4(pack_bf16(o2[8], o2[9]), pack_bf16(o2[10], o2[11]), pack_bf16(o2[12], o2[13]), pack_bf16(o2[14], o2[15]));
  int gt = blockIdx.x * 256 + t;
  uint4 z = make_uint4(0, 0, 0, 0);
  reinterpret_cast<uint4*>(g_part)[gt] = z;
  if (gt < NSEG * 2048 / 4) reinterpret_cast<uint4*>(g_pub)[gt] = z;
  if (gt < (int)(sizeof(Flags) / 4)) reinterpret_cast<unsigned*>(&g_flags)[gt] = 0;
}

struct Maps { CUtensorMap xn, y, h1, o, qkv_st, qkv_ld, g, wq, wk, wv, wo, w1, w2; };

#define NSTAGE 3
#define STAGE_BYTES 49152
#define B_STG (NSTAGE * STAGE_BYTES)
#define R_WO 0
#define R_T1 65536
#define R_T2 131072
#define R_RING 65536
#define RING_N 4
#define RING_BYTES 12288
#define R_MEM 196608
#define R_QS (R_MEM + 8448)
#define R_KS (R_QS + 1152)
#define R_OS (R_KS + 1152)
#define R_SOWN (R_OS + 2176)
#define R_SPEER (R_SOWN + 1280)
#define R_VM (R_SPEER + 1280)
#define R_VRED (R_VM + 2048)
#define R_RED (R_VRED + 6144)
#define SM_BAR (R_RED + 2048)
#define SMEM_TOTAL (SM_BAR + 256 + 1024)
#define MB_FULL 0
#define MB_EMPTY 8
#define MB_STGF 16
#define MB_STGE 17
#define MB_W0 18
#define MB_W1 19
#define MB_WO 20
#define MB_S 21
#define MB_V 22
#define MB_KVR 23
#define MB_KVF 24
#define SM_MISC (SM_BAR + 208)

#define N_KV 512
#define I_Q 512
#define I_M1 768
#define I_M2 880
#define I_POST 912
#define N_ITEMS 1296
enum { T_QKV = 0, T_M1 = 1, T_M2 = 2, T_ATT = 3, T_OUT = 4 };
struct Item { int type, b, c, ks; };
__device__ __forceinline__ Item decode_item(int i) {
  Item it; it.ks = 0;
  if (i < N_KV) { it.type = T_QKV; it.b = i >> 5; it.c = 16 + (i & 31); }
  else if (i < I_M1) { it.type = T_QKV; it.b = (i - I_Q) >> 4; it.c = (i - I_Q) & 15; }
  else if (i < I_M2) { it.type = T_M1; it.b = (i - I_M1) / 7; it.c = (i - I_M1) % 7; }
  else if (i < I_POST) { it.type = T_M2; it.b = (i - I_M2) >> 1; it.c = (i - I_M2) & 1; }
  else {
    int x = i - I_POST;
    if (x < 16) { it.type = T_ATT; it.b = 0; it.c = x; }
    else {
      x -= 16; int p = 1 + x / 24, r = x % 24;
      if (p < 16 && r < 16) { it.type = T_ATT; it.b = p; it.c = r; }
      else { if (p < 16) r -= 16; it.type = T_OUT; it.b = p - 1; it.c = r & 1; it.ks = r >> 1; }
    }
  }
  return it;
}
__device__ __forceinline__ int item_nkb(int type) { return type == T_M2 ? 28 : (type == T_OUT ? 16 : (type == T_ATT ? 4 : 8)); }

__device__ __forceinline__ void st_async_b64(unsigned raddr, unsigned lo, unsigned hi, unsigned rmb) {
  asm volatile("st.async.weak.shared::cluster.mbarrier::complete_tx::bytes.v2.b32 [%0], {%1,%2}, [%3];" ::"r"(raddr), "r"(lo), "r"(hi), "r"(rmb) : "memory");
}
__device__ __forceinline__ unsigned mapa(unsigned a, unsigned rank) {
  unsigned r; asm volatile("mapa.shared::cluster.u32 %0, %1, %2;" : "=r"(r) : "r"(a), "r"(rank)); return r;
}
__device__ __forceinline__ void sts64(unsigned a, unsigned x, unsigned y) { asm volatile("st.shared.v2.b32 [%0], {%1,%2};" ::"r"(a), "r"(x), "r"(y) : "memory"); }
__device__ __forceinline__ void sts128(unsigned a, uint4 v) { asm volatile("st.shared.v4.b32 [%0], {%1,%2,%3,%4};" ::"r"(a), "r"(v.x), "r"(v.y), "r"(v.z), "r"(v.w) : "memory"); }
__device__ __forceinline__ uint2 lds64(unsigned a) { uint2 v; asm volatile("ld.shared.v2.b32 {%0,%1}, [%2];" : "=r"(v.x), "=r"(v.y) : "r"(a) : "memory"); return v; }
__device__ __forceinline__ uint4 lds128(unsigned a) { uint4 v; asm volatile("ld.shared.v4.b32 {%0,%1,%2,%3}, [%4];" : "=r"(v.x), "=r"(v.y), "=r"(v.z), "=r"(v.w) : "r"(a) : "memory"); return v; }
__device__ __forceinline__ float lds32f(unsigned a) { float v; asm volatile("ld.shared.f32 %0, [%1];" : "=f"(v) : "r"(a) : "memory"); return v; }
#define spin_check(it) TRAP_IF(++it)
#define SCALE_QK 0.08838834764831845f

__device__ __forceinline__ void rec_worker(const Maps& maps, unsigned sb, const bf16* __restrict__ mem0) {
  const int c = blockIdx.x, h = c >> 1, j = c & 1;
  const int t = opaque_tid(), lane = t & 31, w = t >> 5, g = lane >> 2, tq = lane & 3;
  const int m = lane >> 3, r8 = lane & 7, kh = w >> 2, et = w & 3;
  const unsigned bar = sb + SM_BAR;
  unsigned wq[16][4], wk[16][4], wo[8][4];
  const unsigned woff = (kh * 4) * 8192 + ((m >> 1) * 8 + r8) * 128 + (((et * 2 + (m & 1)) ^ r8) << 4);
  mbar_wait(bar + 8 * MB_W0, 0);
#pragma unroll
  for (int i = 0; i < 16; i++) {
    ldsm_x4_t(wq[i], sb + R_WO + woff + (i >> 2) * 8192 + (i & 3) * 2048);
    ldsm_x4_t(wk[i], sb + R_T1 + woff + (i >> 2) * 8192 + (i & 3) * 2048);
  }
  bar_sync(2, 288);
  if (t == 0) {
    fence_proxy_async_smem();
    mbar_expect_tx(bar + 8 * MB_WO, 65536);
    for (int kb = 0; kb < 2; kb++)
      for (int cb = 0; cb < 4; cb++) tma_load_2d(sb + R_WO + (kb * 4 + cb) * 8192, &maps.wo, j * 256 + cb * 64, h * 128 + kb * 64, bar + 8 * MB_WO);
  }
  mbar_wait(bar + 8 * MB_W1, 0);
  const unsigned pV = sb + R_T2 + woff;
  const unsigned peer = j ^ 1;
#define KEEP(x) x = __shfl_sync(~0u, x, lane)
  unsigned pA = sb + R_MEM + r8 * 1040 + m * 16 + kh * 512;
  unsigned pW0 = sb + R_WO + (w >> 1) * 8192 + ((m >> 1) * 8 + r8) * 128 + ((((w & 1) * 4 + (m & 1)) ^ r8) << 4);
  unsigned pW1 = pW0 ^ 32;
  unsigned pVk = pV;
  unsigned aMem = sb + R_MEM + (t & 7) * 1040 + (t >> 3) * 16;
  unsigned aX = sb + R_VRED + et * 512 + lane * 16;
  unsigned aQKst = sb + (kh ? R_KS : R_QS) + r8 * 144 + (et * 16 + (m & 1) * 8) * 2;
  unsigned aL8 = sb + lane * 8;
  unsigned aSl = mapa(sb + R_SOWN + w * 256 + lane * 8, j), aSr = mapa(sb + R_SPEER + w * 256 + lane * 8, peer);
  unsigned aVl = mapa(sb + R_VM + (j * 4 + et) * 256 + lane * 8, j), aVr = mapa(sb + R_VM + (j * 4 + et) * 256 + lane * 8, peer);
  const unsigned mbSl = mapa(bar + 8 * MB_S, j), mbSr = mapa(bar + 8 * MB_S, peer), mbVl = mbSl + 8, mbVr = mbSr + 8;
  unsigned aQ = sb + R_QS + r8 * 144 + m * 16;
  unsigned oKx = (et * 8 + r8) * 128 + ((m ^ r8) << 4);
  unsigned oVx = 4096 + kh * 4096 + ((m >> 1) * 8 + r8) * 128 + (((et * 2 + (m & 1)) ^ r8) << 4);
  unsigned aOst = sb + R_OS + r8 * 272 + (w * 16 + (m & 1) * 8) * 2;
  unsigned aOld = sb + R_OS + r8 * 272 + m * 16;
  unsigned aVm = sb + R_VM + w * 256 + lane * 8;
  unsigned aRst = sb + R_RED + w * 256 + lane * 16;
  unsigned aRld = sb + R_RED + tq * 64 + g * 4;
  unsigned oPd = ((32 * j + 4 * w) * NH + h) * 256 + g * 32 + tq * 8;
  unsigned oPs = (c * NH + 4 * w) * 256 + lane * 16;
  unsigned oPub = t * 16;
  KEEP(pA); KEEP(pW0); KEEP(pW1); KEEP(pVk); KEEP(aMem); KEEP(aX); KEEP(aQKst); KEEP(aL8); KEEP(aSl); KEEP(aSr); KEEP(aVl); KEEP(aVr); KEEP(aQ); KEEP(oKx); KEEP(oVx);
  KEEP(aOst); KEEP(aOld); KEEP(aVm); KEEP(aRst); KEEP(aRld); KEEP(oPd); KEEP(oPs); KEEP(oPub);
  mbar_wait(bar + 8 * MB_WO, 0);
#pragma unroll
  for (int ks = 0; ks < 4; ks++) { ldsm_x4_t(wo[2 * ks], pW0 + ks * 2048); ldsm_x4_t(wo[2 * ks + 1], pW1 + ks * 2048); }
#pragma unroll
  for (int u = 0; u < 2; u++) {
    int i = t + 256 * u;
    uint4 v = __ldg(reinterpret_cast<const uint4*>(mem0) + i);
    sts128(sb + R_MEM + (i >> 6) * 1040 + (i & 63) * 16, v);
  }
  if (t == 0) { mbar_expect_tx(bar + 8 * MB_S, 2560); mbar_expect_tx(bar + 8 * MB_V, 2048); }

#pragma unroll 1
  for (int s = 0;; s++) {
    const unsigned par = s & 1;
    const unsigned slot = s & (RING_N - 1), rpar = (s / RING_N) & 1;
    const unsigned ring = sb + R_RING + slot * RING_BYTES;
    RSTAMP(1);
    bar_sync(1, 256);
    RSTAMP(2);
    float aq[4] = {0, 0, 0, 0}, ak[4] = {0, 0, 0, 0}, av[4] = {0, 0, 0, 0};
#pragma unroll
    for (int i = 0; i < 8; i++) {
      unsigned b[4], f[4], f0[4];
      ldsm_x4(b, pA + i * 64);
      ldsm_x4_t(f0, pVk + (i >> 1) * 8192 + (i & 1) * 4096);
      ldsm_x4_t(f, pVk + (i >> 1) * 8192 + (i & 1) * 4096 + 2048);
      mma16816(aq, wq[2 * i], b[0], b[1]); mma16816(ak, wk[2 * i], b[0], b[1]); mma16816(av, f0, b[0], b[1]);
      mma16816(aq, wq[2 * i + 1], b[2], b[3]); mma16816(ak, wk[2 * i + 1], b[2], b[3]); mma16816(av, f, b[2], b[3]);
    }
    RSTAMP(3);
#define STSF4(a, v) asm volatile("st.shared.v4.f32 [%0], {%1,%2,%3,%4};" ::"r"(a), "f"(v[0]), "f"(v[1]), "f"(v[2]), "f"(v[3]) : "memory")
    unsigned kb[8], vx[2][4];
    if (kh) {
      STSF4(aX, aq);
      bar_sync(4 + et, 64);
      uint4 o = lds128(aX + 2048), o2 = lds128(aX + 4096);
      stsm_x2_t(aQKst, pack_bf16(ak[0] + __uint_as_float(o.x), ak[1] + __uint_as_float(o.y)), pack_bf16(ak[2] + __uint_as_float(o.z), ak[3] + __uint_as_float(o.w)));
      bar_arrive(1, 256);
      unsigned x = pack_bf16(av[0] + __uint_as_float(o2.x), av[1] + __uint_as_float(o2.y)), y = pack_bf16(av[2] + __uint_as_float(o2.z), av[3] + __uint_as_float(o2.w));
      st_async_b64(aVr, x, y, mbVr);
      st_async_b64(aVl, x, y, mbVl);
      mbar_wait(bar + 8 * (MB_FULL + slot), rpar);
      ldsm_x4_t(vx[0], ring + oVx); ldsm_x4_t(vx[1], ring + oVx + 2048);
    } else {
      STSF4(aX + 2048, ak); STSF4(aX + 4096, av);
      mbar_wait(bar + 8 * (MB_FULL + slot), rpar);
      ldsm_x4(kb, ring + oKx); ldsm_x4(kb + 4, ring + (oKx ^ 64));
      bar_sync(4 + et, 64);
      uint4 o = lds128(aX);
      stsm_x2_t(aQKst, pack_bf16(aq[0] + __uint_as_float(o.x), aq[1] + __uint_as_float(o.y)), pack_bf16(aq[2] + __uint_as_float(o.z), aq[3] + __uint_as_float(o.w)));
      RSTAMP(4);
      bar_sync(1, 256);
      RSTAMP(5);
      unsigned qa[8], km[8];
      ldsm_x4(qa, aQ); ldsm_x4(qa + 4, aQ + 64);
      if (w == 3) { ldsm_x4(km, aQ + 1152); ldsm_x4(km + 4, aQ + 1152 + 64); }
      float s0[4] = {0, 0, 0, 0}, s1[4] = {0, 0, 0, 0};
      unsigned af[4][4];
#pragma unroll
      for (int i = 0; i < 4; i++) { af[i][0] = qa[2 * i]; af[i][1] = 0; af[i][2] = qa[2 * i + 1]; af[i][3] = 0; }
      mma16816(s0, af[0], kb[0], kb[1]); mma16816(s1, af[1], kb[2], kb[3]);
      mma16816(s0, af[2], kb[4], kb[5]); mma16816(s1, af[3], kb[6], kb[7]);
      if (w == 3) {
        float m0[4] = {0, 0, 0, 0}, m1[4] = {0, 0, 0, 0};
        mma16816(m0, af[0], km[0], km[1]); mma16816(m1, af[1], km[2], km[3]);
        mma16816(m0, af[2], km[4], km[5]); mma16816(m1, af[3], km[6], km[7]);
        unsigned x = __float_as_uint(m0[0] + m1[0]), y = __float_as_uint(m0[1] + m1[1]);
        st_async_b64(aSr + 256, x, y, mbSr); st_async_b64(aSl + 256, x, y, mbSl);
      }
      unsigned x = __float_as_uint(s0[0] + s1[0]), y = __float_as_uint(s0[1] + s1[1]);
      st_async_b64(aSr, x, y, mbSr); st_async_b64(aSl, x, y, mbSl);
      RSTAMP(6);
      ldsm_x4_t(vx[0], ring + oVx); ldsm_x4_t(vx[1], ring + oVx + 2048);
    }
    unsigned f[4][4];
    ldsm_x4_t(f[0], pW0 + 32768); ldsm_x4_t(f[1], pW1 + 32768); ldsm_x4_t(f[2], pW0 + 32768 + 2048); ldsm_x4_t(f[3], pW1 + 32768 + 2048);
    RSTAMP(7);
    mbar_wait(bar + 8 * MB_S, par);
    RSTAMP(8);
    float sc[10];
#pragma unroll
    for (int i = 0; i < 5; i++) {
      uint2 o = lds64(aL8 + R_SOWN + i * 256), p = lds64(aL8 + R_SPEER + i * 256);
      sc[2 * i] = __uint_as_float(o.x) + __uint_as_float(p.x); sc[2 * i + 1] = __uint_as_float(o.y) + __uint_as_float(p.y);
    }
    float mx = fmaxf(fmaxf(fmaxf(sc[0], sc[1]), fmaxf(sc[2], sc[3])), fmaxf(fmaxf(fmaxf(sc[4], sc[5]), fmaxf(sc[6], sc[7])), fmaxf(sc[8], sc[9])));
    mx = fmaxf(mx, __shfl_xor_sync(~0u, mx, 1)); mx = fmaxf(mx, __shfl_xor_sync(~0u, mx, 2));
    const float nm = -mx * (SCALE_QK * LOG2E);
#pragma unroll
    for (int i = 0; i < 10; i++) sc[i] = ex2f(fmaf(sc[i], SCALE_QK * LOG2E, nm));
    float sum = (((sc[0] + sc[1]) + (sc[2] + sc[3])) + ((sc[4] + sc[5]) + (sc[6] + sc[7]))) + (sc[8] + sc[9]);
    sum += __shfl_xor_sync(~0u, sum, 1); sum += __shfl_xor_sync(~0u, sum, 2);
    float inv; asm("rcp.approx.ftz.f32 %0, %1;" : "=f"(inv) : "f"(sum));
    unsigned p[5];
#pragma unroll
    for (int i = 0; i < 5; i++) p[i] = pack_bf16(sc[2 * i] * inv, sc[2 * i + 1] * inv);
    RSTAMP(9);
    mbar_wait(bar + 8 * MB_V, par);
    uint2 vm = lds64(aVm);
    float o0[4] = {0, 0, 0, 0}, o1[4] = {0, 0, 0, 0}, o2[4] = {0, 0, 0, 0};
    mma16816(o0, vx[0], p[0], p[1]); mma16816(o1, vx[1], p[2], p[3]); mma1688(o2, vm.x, vm.y, p[4]);
    RSTAMP(10);
    if (s == NSEG - 1) { if (t == 0) mbar_arrive(bar + 8 * MB_KVR); break; }
    stsm_x2_t(aOst, pack_bf16(o0[0] + o1[0] + o2[0], o0[1] + o1[1] + o2[1]), pack_bf16(o0[2] + o1[2] + o2[2], o0[3] + o1[3] + o2[3]));
    bar_sync(1, 256);
    RSTAMP(11);
    float d0[4] = {0, 0, 0, 0}, d1[4] = {0, 0, 0, 0}, e0[4] = {0, 0, 0, 0}, e1[4] = {0, 0, 0, 0};
    unsigned ob[4][4], f2[4][4];
#pragma unroll
    for (int k2 = 0; k2 < 4; k2++) ldsm_x4(ob[k2], aOld + k2 * 64);
    ldsm_x4_t(f2[0], pW0 + 32768 + 4096); ldsm_x4_t(f2[1], pW1 + 32768 + 4096); ldsm_x4_t(f2[2], pW0 + 32768 + 6144); ldsm_x4_t(f2[3], pW1 + 32768 + 6144);
    mma16816(d0, wo[0], ob[0][0], ob[0][1]); mma16816(d1, wo[1], ob[0][0], ob[0][1]);
    mma16816(e0, wo[2], ob[0][2], ob[0][3]); mma16816(e1, wo[3], ob[0][2], ob[0][3]);
    mma16816(d0, wo[4], ob[1][0], ob[1][1]); mma16816(d1, wo[5], ob[1][0], ob[1][1]);
    mma16816(e0, wo[6], ob[1][2], ob[1][3]); mma16816(e1, wo[7], ob[1][2], ob[1][3]);
    mma16816(d0, f[0], ob[2][0], ob[2][1]); mma16816(d1, f[1], ob[2][0], ob[2][1]);
    mma16816(e0, f[2], ob[2][2], ob[2][3]); mma16816(e1, f[3], ob[2][2], ob[2][3]);
    mma16816(d0, f2[0], ob[3][0], ob[3][1]); mma16816(d1, f2[1], ob[3][0], ob[3][1]);
    mma16816(e0, f2[2], ob[3][2], ob[3][3]); mma16816(e1, f2[3], ob[3][2], ob[3][3]);
    const unsigned tag = ((s >> 1) & 1) ^ 1;
    const char* pbase = reinterpret_cast<const char*>(g_part) + par * (NREC * NH * 256);
    {
      const char* dst = pbase + oPd;
#define PST(ptr, x, y) asm volatile("st.relaxed.gpu.global.v2.u32 [%0], {%1,%2};" ::"l"(ptr), "r"((__float_as_uint(x) & ~1u) | tag), "r"((__float_as_uint(y) & ~1u) | tag) : "memory")
      PST(dst, d0[0] + e0[0], d0[1] + e0[1]); PST(dst + NH * 256, d0[2] + e0[2], d0[3] + e0[3]);
      PST(dst + 2 * NH * 256, d1[0] + e1[0], d1[1] + e1[1]); PST(dst + 3 * NH * 256, d1[2] + e1[2], d1[3] + e1[3]);
    }
    RSTAMP(12);
    if (t == 0) {
      mbar_arrive(bar + 8 * (MB_EMPTY + slot)); mbar_arrive(bar + 8 * MB_KVR);
      mbar_expect_tx(bar + 8 * MB_S, 2560); mbar_expect_tx(bar + 8 * MB_V, 2048);
    }
    {
      const char* src = pbase + oPs;
      uint4 a, b; unsigned it = 0;
      while (true) {
        a = ldv4_relaxed(src); b = ldv4_relaxed(src + 512);
        unsigned z = ((a.x ^ tag) | (a.y ^ tag)) | ((a.z ^ tag) | (a.w ^ tag)) | ((b.x ^ tag) | (b.y ^ tag)) | ((b.z ^ tag) | (b.w ^ tag));
        if (!(z & 1u)) break;
        spin_check(it);
      }
      RSTAMP(13);
      float r0 = __uint_as_float(a.x) + __uint_as_float(b.x), r1 = __uint_as_float(a.y) + __uint_as_float(b.y);
      float r2 = __uint_as_float(a.z) + __uint_as_float(b.z), r3 = __uint_as_float(a.w) + __uint_as_float(b.w);
      __syncwarp();
      r0 += __shfl_xor_sync(~0u, r0, 16); r1 += __shfl_xor_sync(~0u, r1, 16); r2 += __shfl_xor_sync(~0u, r2, 16); r3 += __shfl_xor_sync(~0u, r3, 16);
      if (lane < 16) asm volatile("st.shared.v4.f32 [%0], {%1,%2,%3,%4};" ::"r"(aRst), "f"(r0), "f"(r1), "f"(r2), "f"(r3) : "memory");
    }
    const char* pub = reinterpret_cast<const char*>(g_pub) + (s + 1) * 8192;
    if (w != 0) { bar_arrive(3, 256); }
    else {
      bar_sync(3, 256);
      RSTAMP(14);
      float x[8], y[8];
#pragma unroll
      for (int i = 0; i < 8; i++) { x[i] = lds32f(aRld + i * 256); y[i] = lds32f(aRld + i * 256 + 32); }
      unsigned u = pack_bf16(((x[0] + x[1]) + (x[2] + x[3])) + ((x[4] + x[5]) + (x[6] + x[7])), ((y[0] + y[1]) + (y[2] + y[3])) + ((y[4] + y[5]) + (y[6] + y[7])));
      if (u == 0) u = 0x80000000u;
      asm volatile("st.relaxed.gpu.global.u32 [%0], %1;" ::"l"(pub + c * 128 + (oPub >> 2)), "r"(u) : "memory");
      RSTAMP(15);
    }
    mbar_wait(bar + 8 * MB_KVF, par);
    {
      const char* src = pub + oPub;
      uint4 a, b; unsigned it = 0;
      while (true) {
        a = ldv4_relaxed(src); b = ldv4_relaxed(src + 4096);
        unsigned z = min(min(min(a.x, a.y), min(a.z, a.w)), min(min(b.x, b.y), min(b.z, b.w)));
        if (z) break;
        spin_check(it);
      }
      sts128(aMem, a); sts128(aMem + 512, b);
    }
  }
}

__device__ __forceinline__ void rec_ring(const Maps& maps, unsigned sb) {
  const int c = blockIdx.x, h = c >> 1, j = c & 1;
  const unsigned bar = sb + SM_BAR;
  const int lane = threadIdx.x & 31;
  if (lane == 0) {
    mbar_expect_tx(bar + 8 * MB_W0, 131072);
    for (int kb = 0; kb < 8; kb++) tma_load_2d(sb + R_WO + kb * 8192, &maps.wq, h * 128 + j * 64, kb * 64, bar + 8 * MB_W0);
    for (int kb = 0; kb < 8; kb++) tma_load_2d(sb + R_T1 + kb * 8192, &maps.wk, h * 128 + j * 64, kb * 64, bar + 8 * MB_W0);
    mbar_expect_tx(bar + 8 * MB_W1, 65536);
    for (int kb = 0; kb < 8; kb++) tma_load_2d(sb + R_T2 + kb * 8192, &maps.wv, h * 128 + j * 64, kb * 64, bar + 8 * MB_W1);
  }
  __syncwarp();
  bar_sync(2, 288);
  if (lane == 0) {
    fence_proxy_async_smem();
    for (int s = 0; s < NSEG; s++) {
      unsigned slot = s & (RING_N - 1);
      if ((s & 3) == 0 && !DBGMODE) {
        wait_flag_ge(&g_flags.qkv[(s >> 2) * 48 + 16 + (h >> 1)], 1);
        wait_flag_ge(&g_flags.qkv[(s >> 2) * 48 + 32 + (h >> 1)], 1);
        fence_proxy_async();
      }
      if (s >= RING_N) mbar_wait_sleep(bar + 8 * (MB_EMPTY + slot), ((s / RING_N) - 1) & 1);
      unsigned dst = sb + R_RING + slot * RING_BYTES, mb = bar + 8 * (MB_FULL + slot);
      mbar_expect_tx(mb, RING_BYTES);
      tma_load_2d(dst, &maps.qkv_ld, HD + h * 128 + j * 64, s * SEG, mb);
      tma_load_2d(dst + 4096, &maps.qkv_ld, 2 * HD + h * 128, s * SEG, mb);
      tma_load_2d(dst + 8192, &maps.qkv_ld, 2 * HD + h * 128 + 64, s * SEG, mb);
    }
  }
}
__device__ __forceinline__ void rec_copy(unsigned sb) {
  const int c = blockIdx.x, h = c >> 1, j = c & 1;
  const unsigned bar = sb + SM_BAR;
  const int lane = threadIdx.x & 31;
  for (int s = 0; s < NSEG; s++) {
    mbar_wait_sleep(bar + 8 * MB_KVR, s & 1);
    uint4 k0 = lds128(sb + R_KS + (lane >> 3) * 144 + (lane & 7) * 16), k1 = lds128(sb + R_KS + (4 + (lane >> 3)) * 144 + (lane & 7) * 16);
    uint2 v[4];
#pragma unroll
    for (int i = 0; i < 4; i++) v[i] = lds64(sb + R_VM + (j * 4 + i) * 256 + lane * 8);
    __syncwarp();
    if (lane == 0) mbar_arrive(bar + 8 * MB_KVF);
    bf16* kd = g_km + ((size_t)(s * NH + h) * NMEM) * DH + j * 64;
    *reinterpret_cast<uint4*>(kd + (lane >> 3) * DH + (lane & 7) * 8) = k0;
    *reinterpret_cast<uint4*>(kd + (4 + (lane >> 3)) * DH + (lane & 7) * 8) = k1;
    unsigned* vd = reinterpret_cast<unsigned*>(g_vmt) + ((size_t)(s * NH + h) * DH + j * 64) * 4;
#pragma unroll
    for (int i = 0; i < 4; i++) { vd[(i * 16) * 4 + lane] = v[i].x; vd[(i * 16 + 8) * 4 + lane] = v[i].y; }
    __threadfence();
    __syncwarp();
    if (lane == 0) st_release(&g_flags.rec[c], s + 1);
  }
}

__device__ __forceinline__ void bulk_producer(const Maps& maps, unsigned sb, int* misc) {
  const unsigned bar = sb + SM_BAR;
  unsigned st = 0, ph = 0, seq = 0;
  while (true) {
    int idx = (int)atomicAdd(&g_flags.ctr, 1u);
    if (idx >= N_ITEMS) {
      mbar_wait(bar + 8 * (MB_EMPTY + st), ph ^ 1);
      misc[seq & 3] = -1;
      mbar_arrive(bar + 8 * (MB_FULL + st));
      break;
    }
    ISTAMP(idx, 0);
    Item it = decode_item(idx);
    const CUtensorMap *ma, *mb_; int ka = 0, kbr = 0, nb0 = it.c * 256;
    if (it.type == T_QKV) { ma = &maps.xn; mb_ = it.c < 16 ? &maps.wq : (it.c < 32 ? &maps.wk : &maps.wv); nb0 = (it.c & 15) * 256; }
    else if (it.type == T_M1) { ma = &maps.y; mb_ = &maps.w1; }
    else if (it.type == T_M2) { ma = &maps.h1; mb_ = &maps.w2; wait_flag_ge(&g_flags.h1[it.b], 7); }
    else if (it.type == T_OUT) { ma = &maps.o; mb_ = &maps.wo; ka = kbr = it.ks * 1024; wait_flag_ge(&g_flags.o[it.b * 4 + it.ks], 4); wait_flag_ge(&g_flags.g[it.b], 2); }
    else {
      ma = mb_ = &maps.qkv_ld;
      wait_flag_ge(&g_flags.qkv[it.b * 48 + it.c], 1); wait_flag_ge(&g_flags.qkv[it.b * 48 + 16 + it.c], 1); wait_flag_ge(&g_flags.qkv[it.b * 48 + 32 + it.c], 1);
      for (int i = 0; i < 4; i++) wait_flag_ge(&g_flags.rec[it.c * 4 + i], it.b * 4 + 4);
    }
    fence_proxy_async();
    ISTAMP(idx, 1);
    const int nkb = item_nkb(it.type);
    for (int kb = 0; kb < nkb; kb++) {
      mbar_wait(bar + 8 * (MB_EMPTY + st), ph ^ 1);
      if (kb == 0) { misc[seq & 3] = idx; seq++; }
      unsigned dst = sb + st * STAGE_BYTES, mb = bar + 8 * (MB_FULL + st);
      mbar_expect_tx(mb, STAGE_BYTES);
      if (it.type == T_ATT) {
        int head = it.c * 2 + (kb >> 1), row = it.b * 128 + (kb & 1) * 64;
        for (int i = 0; i < 12; i++) tma_load_2d(dst + i * 4096, ma, (i >> 2) * HD + head * 128 + (i & 1) * 64, row + ((i >> 1) & 1) * 32, mb);
      } else {
        tma_load_2d(dst, ma, ka + kb * 64, it.b * 128, mb);
        for (int i = 0; i < 4; i++) tma_load_2d(dst + 16384 + i * 8192, mb_, nb0 + i * 64, kbr + kb * 64, mb);
      }
      if (++st == NSTAGE) { st = 0; ph ^= 1; }
    }
  }
}
__device__ __forceinline__ void bulk_store(const Maps& maps, unsigned sb, volatile int* misc) {
  const unsigned bar = sb + SM_BAR;
  unsigned ph = 0;
  while (true) {
    mbar_wait(bar + 8 * MB_STGF, ph); ph ^= 1;
    int idx = misc[4];
    if (idx < 0) break;
    Item it = decode_item(idx);
    const CUtensorMap* mp = it.type == T_QKV ? &maps.qkv_st : (it.type == T_M1 ? &maps.h1 : (it.type == T_M2 ? &maps.g : &maps.o));
    unsigned* flag = it.type == T_QKV ? &g_flags.qkv[it.b * 48 + it.c] : (it.type == T_M1 ? &g_flags.h1[it.b] : (it.type == T_M2 ? &g_flags.g[it.b] : &g_flags.o[it.b * 4 + (it.c >> 2)]));
    for (int i = 0; i < 4; i++) tma_store_2d(mp, sb + B_STG + i * 16384, it.c * 256 + i * 64, it.b * 128);
    asm volatile("cp.async.bulk.commit_group;" ::: "memory");
    asm volatile("cp.async.bulk.wait_group.read 0;" ::: "memory");
    mbar_arrive(bar + 8 * MB_STGE);
    asm volatile("cp.async.bulk.wait_group 0;" ::: "memory");
    fence_proxy_async();
    __threadfence();
    red_release_add(flag, 1);
    ISTAMP(idx, 3);
  }
}
__device__ __forceinline__ float gelu_t(float x) {
  float u = 0.7978845608028654f * (x + 0.044715f * x * x * x);
  return __fdividef(x, 1.0f + __expf(-2.0f * u));
}
__device__ __forceinline__ float silu_f(float x) { return __fdividef(x, 1.0f + __expf(-x)); }

__device__ __forceinline__ void bulk_att_stage(unsigned sa, unsigned stg, int b, int hp, int kb, int w, int lane) {
  const int g = lane >> 2, tq = lane & 3, m = lane >> 3, r8 = lane & 7;
  const int seg = w >> 2, mt = (w >> 1) & 1, eh = w & 1;
  const int head = hp * 2 + (kb >> 1), sg = b * 4 + (kb & 1) * 2 + seg;
  const unsigned* kmp = reinterpret_cast<const unsigned*>(g_km + ((size_t)(sg * NH + head) * NMEM + g) * DH) + tq;
  const unsigned* vmp = reinterpret_cast<const unsigned*>(g_vmt) + ((size_t)(sg * NH + head) * DH + eh * 64) * 4 + lane;
  unsigned km[16], vm[8];
#pragma unroll
  for (int i = 0; i < 16; i++) km[i] = __ldcg(kmp + i * 4);
#pragma unroll
  for (int i = 0; i < 8; i++) vm[i] = __ldcg(vmp + i * 32);
  float s[5][4];
#pragma unroll
  for (int i = 0; i < 5; i++) { s[i][0] = s[i][1] = s[i][2] = s[i][3] = 0; }
  const unsigned qb = sa + (0 * 2 + seg) * 8192, kbs = sa + (1 * 2 + seg) * 8192, vb = sa + (2 * 2 + seg) * 8192 + eh * 4096;
  unsigned qa[8][4];
#pragma unroll
  for (int ks = 0; ks < 8; ks++) {
    int row = mt * 16 + (m & 1) * 8 + r8;
    ldsm_x4(qa[ks], qb + (ks >> 2) * 4096 + row * 128 + ((((ks & 3) * 2 + (m >> 1)) ^ r8) << 4));
    unsigned kf[4];
    int krow = (m >> 1) * 8 + r8;
    unsigned ka = kbs + (ks >> 2) * 4096 + krow * 128 + ((((ks & 3) * 2 + (m & 1)) ^ r8) << 4);
    ldsm_x4(kf, ka);
    mma16816(s[0], qa[ks], kf[0], kf[1]); mma16816(s[1], qa[ks], kf[2], kf[3]);
    if (mt) { ldsm_x4(kf, ka + 2048); mma16816(s[2], qa[ks], kf[0], kf[1]); mma16816(s[3], qa[ks], kf[2], kf[3]); }
  }
#pragma unroll
  for (int ks = 0; ks < 8; ks++) mma16816(s[4], qa[ks], km[2 * ks], km[2 * ks + 1]);
  float mx0 = -INFINITY, mx1 = -INFINITY;
  const int t0 = mt * 16 + g, t1 = t0 + 8;
#pragma unroll
  for (int i = 0; i < 5; i++) {
#pragma unroll
    for (int e = 0; e < 4; e++) {
      float v = bf16r(bf16r(s[i][e]) * SCALE_QK);
      if (i < 4) { int kj = i * 8 + 2 * tq + (e & 1); if (kj > (e < 2 ? t0 : t1)) v = -INFINITY; }
      s[i][e] = v;
      if (e < 2) mx0 = fmaxf(mx0, v); else mx1 = fmaxf(mx1, v);
    }
  }
  mx0 = fmaxf(mx0, __shfl_xor_sync(~0u, mx0, 1)); mx0 = fmaxf(mx0, __shfl_xor_sync(~0u, mx0, 2));
  mx1 = fmaxf(mx1, __shfl_xor_sync(~0u, mx1, 1)); mx1 = fmaxf(mx1, __shfl_xor_sync(~0u, mx1, 2));
  float sm0 = 0, sm1 = 0;
#pragma unroll
  for (int i = 0; i < 5; i++) {
    s[i][0] = __expf(s[i][0] - mx0); s[i][1] = __expf(s[i][1] - mx0); s[i][2] = __expf(s[i][2] - mx1); s[i][3] = __expf(s[i][3] - mx1);
    sm0 += s[i][0] + s[i][1]; sm1 += s[i][2] + s[i][3];
  }
  sm0 += __shfl_xor_sync(~0u, sm0, 1); sm0 += __shfl_xor_sync(~0u, sm0, 2);
  sm1 += __shfl_xor_sync(~0u, sm1, 1); sm1 += __shfl_xor_sync(~0u, sm1, 2);
  const float i0 = __fdividef(1.0f, sm0), i1 = __fdividef(1.0f, sm1);
  unsigned pa[2][4], pm0, pm1;
#pragma unroll
  for (int kk = 0; kk < 2; kk++) {
    pa[kk][0] = pack_bf16(s[2 * kk][0] * i0, s[2 * kk][1] * i0); pa[kk][1] = pack_bf16(s[2 * kk][2] * i1, s[2 * kk][3] * i1);
    pa[kk][2] = pack_bf16(s[2 * kk + 1][0] * i0, s[2 * kk + 1][1] * i0); pa[kk][3] = pack_bf16(s[2 * kk + 1][2] * i1, s[2 * kk + 1][3] * i1);
  }
  pm0 = pack_bf16(s[4][0] * i0, s[4][1] * i0); pm1 = pack_bf16(s[4][2] * i1, s[4][3] * i1);
  const int orow = (kb & 1) * 64 + seg * 32 + mt * 16 + (m & 1) * 8 + r8;
  const unsigned ob = stg + ((kb >> 1) * 2 + eh) * 16384 + orow * 128;
#pragma unroll
  for (int cp = 0; cp < 4; cp++) {
    float o0[4] = {0, 0, 0, 0}, o1[4] = {0, 0, 0, 0};
    mma1688(o0, pm0, pm1, vm[2 * cp]); mma1688(o1, pm0, pm1, vm[2 * cp + 1]);
    unsigned vf[4];
    int row = (m & 1) * 8 + r8;
    unsigned va = vb + row * 128 + (((cp * 2 + (m >> 1)) ^ r8) << 4);
    ldsm_x4_t(vf, va);
    mma16816(o0, pa[0], vf[0], vf[1]); mma16816(o1, pa[0], vf[2], vf[3]);
    if (mt) { ldsm_x4_t(vf, va + 2048); mma16816(o0, pa[1], vf[0], vf[1]); mma16816(o1, pa[1], vf[2], vf[3]); }
    stsm_x4(ob + (((cp * 2 + (m >> 1)) ^ r8) << 4), pack_bf16(o0[0], o0[1]), pack_bf16(o0[2], o0[3]), pack_bf16(o1[0], o1[1]), pack_bf16(o1[2], o1[3]));
  }
}

__device__ __forceinline__ void bulk_worker(unsigned sb, volatile int* misc, const bf16* __restrict__ x, const bf16* __restrict__ b1, const bf16* __restrict__ b2, bf16* __restrict__ out) {
  const int t = threadIdx.x, lane = t & 31, w = t >> 5, wg = w >> 2, g = lane >> 2, tq = lane & 3, m = lane >> 3, r8 = lane & 7;
  const unsigned bar = sb + SM_BAR;
  unsigned st = 0, ph = 0, seq = 0, sph = 0;
  float d[128];
  while (true) {
    mbar_wait(bar + 8 * (MB_FULL + st), ph);
    const int idx = misc[seq & 3]; seq++;
    if (idx < 0 || idx >= N_ITEMS) break;
    if (t == 0) ISTAMP(idx, 2);
    const Item it = decode_item(idx);
    const int nkb = item_nkb(it.type);
    if (it.type == T_ATT) {
      mbar_wait(bar + 8 * MB_STGE, sph ^ 1);
      for (int kb = 0; kb < 4; kb++) {
        if (kb) mbar_wait(bar + 8 * (MB_FULL + st), ph);
        bulk_att_stage(sb + st * STAGE_BYTES, sb + B_STG, it.b, it.c, kb, w, lane);
        __syncwarp();
        if (lane == 0) mbar_arrive(bar + 8 * (MB_EMPTY + st));
        if (++st == NSTAGE) { st = 0; ph ^= 1; }
      }
      if (t == 0) misc[4] = idx;
      fence_proxy_async_smem();
      mbar_arrive(bar + 8 * MB_STGF); sph ^= 1;
      continue;
    }
    unsigned pst = 0;
    for (int kb = 0; kb < nkb; kb++) {
      if (kb) mbar_wait(bar + 8 * (MB_FULL + st), ph);
      unsigned sa = sb + st * STAGE_BYTES;
      uint64_t ad = mkdesc(sa + wg * 8192, 16, 1024), bd = mkdesc(sa + 16384, 8192, 1024);
      asm volatile("wgmma.fence.sync.aligned;" ::: "memory");
#pragma unroll
      for (int k = 0; k < 4; k++) wgmma_n256(d, ad + k * 2, bd + k * 128, (kb | k) != 0);
      asm volatile("wgmma.commit_group.sync.aligned;" ::: "memory");
      if (kb) {
        asm volatile("wgmma.wait_group.sync.aligned 1;" ::: "memory");
        if (lane == 0) mbar_arrive(bar + 8 * (MB_EMPTY + pst));
      }
      pst = st;
      if (++st == NSTAGE) { st = 0; ph ^= 1; }
    }
    asm volatile("wgmma.wait_group.sync.aligned 0;" ::: "memory");
    if (lane == 0) mbar_arrive(bar + 8 * (MB_EMPTY + pst));
    if (it.type == T_OUT) {
      const int row = it.b * 128 + w * 16 + g, col = it.c * 256 + 2 * tq;
      float* pp = g_opart + ((size_t)it.ks * S_TOK + row) * DM + col;
#pragma unroll
      for (int i = 0; i < 32; i++) {
        __stcg(reinterpret_cast<float2*>(pp + i * 8), make_float2(d[4 * i], d[4 * i + 1]));
        __stcg(reinterpret_cast<float2*>(pp + 8 * DM + i * 8), make_float2(d[4 * i + 2], d[4 * i + 3]));
      }
      __threadfence();
      bar_sync(1, 256);
      if (t == 0) misc[5] = (int)atomicAdd(&g_flags.p[it.b * 2 + it.c], 1u);
      bar_sync(1, 256);
      if (misc[5] == 3) {
        __threadfence();
        const float* p0 = g_opart + (size_t)row * DM + col;
#pragma unroll 4
        for (int i = 0; i < 64; i++) {
          size_t off = (size_t)(i & 1) * 8 * DM + (i >> 1) * 8;
          float2 a = __ldcg(reinterpret_cast<const float2*>(p0 + off)), b = __ldcg(reinterpret_cast<const float2*>(p0 + off + (size_t)S_TOK * DM));
          float2 c = __ldcg(reinterpret_cast<const float2*>(p0 + off + (size_t)2 * S_TOK * DM)), e = __ldcg(reinterpret_cast<const float2*>(p0 + off + (size_t)3 * S_TOK * DM));
          size_t o = (size_t)row * DM + col + off;
          unsigned gv = __ldcg(reinterpret_cast<const unsigned*>(g_g + o)), xv = __ldg(reinterpret_cast<const unsigned*>(x + o));
          float s0 = bf16r((a.x + b.x) + (c.x + e.x)), s1 = bf16r((a.y + b.y) + (c.y + e.y));
          *reinterpret_cast<unsigned*>(out + o) = pack_bf16(bf_lo(xv) + bf16r(s0 * bf_lo(gv)), bf_hi(xv) + bf16r(s1 * bf_hi(gv)));
        }
      }
      bar_sync(1, 256);
      if (t == 0) ISTAMP(idx, 3);
      continue;
    }
    if (it.type != T_QKV) {
      const unsigned* bp = reinterpret_cast<const unsigned*>((it.type == T_M1 ? b1 : b2) + it.c * 256) + tq;
#pragma unroll
      for (int i = 0; i < 32; i++) {
        unsigned bv = __ldg(bp + i * 4);
        float lo = bf_lo(bv), hi = bf_hi(bv);
        float x0 = bf16r(bf16r(d[4 * i]) + lo), x1 = bf16r(bf16r(d[4 * i + 1]) + hi), x2 = bf16r(bf16r(d[4 * i + 2]) + lo), x3 = bf16r(bf16r(d[4 * i + 3]) + hi);
        if (it.type == T_M1) { d[4 * i] = gelu_t(x0); d[4 * i + 1] = gelu_t(x1); d[4 * i + 2] = gelu_t(x2); d[4 * i + 3] = gelu_t(x3); }
        else { d[4 * i] = silu_f(x0); d[4 * i + 1] = silu_f(x1); d[4 * i + 2] = silu_f(x2); d[4 * i + 3] = silu_f(x3); }
      }
    }
    mbar_wait(bar + 8 * MB_STGE, sph ^ 1);
    {
      const unsigned ob = sb + B_STG + (w * 16 + (m & 1) * 8 + r8) * 128;
#pragma unroll
      for (int i = 0; i < 16; i++)
        stsm_x4(ob + (i >> 2) * 16384 + ((((i & 3) * 2 + (m >> 1)) ^ r8) << 4), pack_bf16(d[8 * i], d[8 * i + 1]), pack_bf16(d[8 * i + 2], d[8 * i + 3]),
                pack_bf16(d[8 * i + 4], d[8 * i + 5]), pack_bf16(d[8 * i + 6], d[8 * i + 7]));
    }
    if (t == 0) misc[4] = idx;
    fence_proxy_async_smem();
    mbar_arrive(bar + 8 * MB_STGF); sph ^= 1;
  }
  mbar_wait(bar + 8 * MB_STGE, sph ^ 1);
  if (t == 0) misc[4] = -1;
  mbar_arrive(bar + 8 * MB_STGF);
}

__global__ void __cluster_dims__(2, 1, 1) __launch_bounds__(384, 1)
k_main(const __grid_constant__ Maps maps, const bf16* __restrict__ x, const bf16* __restrict__ mem0, const bf16* __restrict__ b1, const bf16* __restrict__ b2, bf16* __restrict__ out) {
  extern __shared__ unsigned char smem_raw[];
  const unsigned sraw = smem_u32(smem_raw);
  const unsigned sb = (sraw + 1023u) & ~1023u;
  int* misc = reinterpret_cast<int*>(smem_raw + (sb - sraw) + SM_MISC);
  const int w = threadIdx.x >> 5;
  const bool rec = blockIdx.x < NREC;
  if (threadIdx.x == 0) {
    const unsigned bar = sb + SM_BAR;
    for (int i = 0; i < 8; i++) { mbar_init(bar + 8 * (MB_FULL + i), 1); mbar_init(bar + 8 * (MB_EMPTY + i), rec ? 1 : 8); }
    mbar_init(bar + 8 * MB_STGF, 256); mbar_init(bar + 8 * MB_STGE, 1);
    for (int i = MB_W0; i <= MB_KVF; i++) mbar_init(bar + 8 * i, 1);
    asm volatile("fence.mbarrier_init.release.cluster;" ::: "memory");
  }
  __syncthreads();
  asm volatile("barrier.cluster.arrive.release.aligned;\nbarrier.cluster.wait.acquire.aligned;" ::: "memory");
  if (DBGMODE && !rec) return;
  if (w >= 8) {
    asm volatile("setmaxnreg.dec.sync.aligned.u32 24;");
    if (rec) { if (w == 8) rec_ring(maps, sb); else if (w == 9) rec_copy(sb); }
    else if ((threadIdx.x & 31) == 0) { if (w == 8) bulk_producer(maps, sb, misc); else if (w == 9) bulk_store(maps, sb, misc); }
  } else {
    if (rec) { asm volatile("setmaxnreg.inc.sync.aligned.u32 240;"); rec_worker(maps, sb, mem0); }
    else { asm volatile("setmaxnreg.inc.sync.aligned.u32 240;"); bulk_worker(sb, misc, x, b1, b2, out); }
  }
}

typedef CUresult (*EncFn)(CUtensorMap*, CUtensorMapDataType, cuuint32_t, void*, const cuuint64_t*, const cuuint64_t*, const cuuint32_t*, const cuuint32_t*,
                          CUtensorMapInterleave, CUtensorMapSwizzle, CUtensorMapL2promotion, CUtensorMapFloatOOBfill);
static void mk_map(EncFn enc, CUtensorMap* m, const void* ptr, uint64_t rows, uint64_t cols, uint32_t box_rows) {
  cuuint64_t dims[2] = {cols, rows}; cuuint64_t strides[1] = {cols * 2};
  cuuint32_t box[2] = {64, box_rows}, es[2] = {1, 1};
  enc(m, CU_TENSOR_MAP_DATA_TYPE_BFLOAT16, 2, const_cast<void*>(ptr), dims, strides, box, es, CU_TENSOR_MAP_INTERLEAVE_NONE, CU_TENSOR_MAP_SWIZZLE_128B,
      CU_TENSOR_MAP_L2_PROMOTION_L2_256B, CU_TENSOR_MAP_FLOAT_OOB_FILL_NONE);
}
extern "C" void kernel_launch(void* const* d_in, const int* in_sizes, int n_in, void* d_out, int out_size) {
  static EncFn enc = nullptr;
  static void *p_xn, *p_y, *p_h1, *p_o, *p_qkv, *p_g;
  if (!enc) {
    void* fn = nullptr; cudaDriverEntryPointQueryResult qr;
    cudaGetDriverEntryPoint("cuTensorMapEncodeTiled", &fn, cudaEnableDefault, &qr);
    enc = (EncFn)fn;
    cudaGetSymbolAddress(&p_xn, g_xn); cudaGetSymbolAddress(&p_y, g_y); cudaGetSymbolAddress(&p_h1, g_h1);
    cudaGetSymbolAddress(&p_o, g_o); cudaGetSymbolAddress(&p_qkv, g_qkv); cudaGetSymbolAddress(&p_g, g_g);
    cudaFuncSetAttribute(k_main, cudaFuncAttributeMaxDynamicSharedMemorySize, SMEM_TOTAL);
  }
  Maps maps;
  mk_map(enc, &maps.xn, p_xn, S_TOK, DM, 128); mk_map(enc, &maps.y, p_y, S_TOK, DM, 128); mk_map(enc, &maps.h1, p_h1, S_TOK, FF, 128);
  mk_map(enc, &maps.o, p_o, S_TOK, HD, 128); mk_map(enc, &maps.qkv_st, p_qkv, S_TOK, 3 * HD, 128); mk_map(enc, &maps.qkv_ld, p_qkv, S_TOK, 3 * HD, 32);
  mk_map(enc, &maps.g, p_g, S_TOK, DM, 128);
  mk_map(enc, &maps.wq, d_in[2], DM, HD, 64); mk_map(enc, &maps.wk, d_in[3], DM, HD, 64); mk_map(enc, &maps.wv, d_in[4], DM, HD, 64);
  mk_map(enc, &maps.wo, d_in[5], HD, DM, 64); mk_map(enc, &maps.w1, d_in[8], DM, FF, 64); mk_map(enc, &maps.w2, d_in[10], FF, DM, 64);
  cudaStream_t st = cudaStreamPerThread;
  k_pre<<<256, 256, 0, st>>>((const bf16*)d_in[0]);
  k_main<<<NCTA, 384, SMEM_TOTAL, st>>>(maps, (const bf16*)d_in[0], (const bf16*)d_in[1], (const bf16*)d_in[9], (const bf16*)d_in[11], (bf16*)d_out);
}
```

```cpp
#include <cuda_runtime.h>
#include <cuda_bf16.h>
#include <cuda.h>
#include <stdint.h>

typedef __nv_bfloat16 bf16;

#define S_TOK 2048
#define DM 512
#define NH 32
#define DH 128
#define HD 4096
#define NMEM 8
#define SEG 32
#define NSEG 64
#define FF 1792
#define NBLK 16
#define NREC 64
#define NCTA 132
#define NBULK (NCTA - NREC)

__device__ __align__(1024) bf16 g_xn[S_TOK * DM];
__device__ __align__(1024) bf16 g_y[S_TOK * DM];
__device__ __align__(1024) bf16 g_qkv[(size_t)S_TOK * 3 * HD];
__device__ __align__(1024) bf16 g_h1[S_TOK * FF];
__device__ __align__(1024) bf16 g_g[S_TOK * DM];
__device__ __align__(1024) bf16 g_o[(size_t)S_TOK * HD];
__device__ __align__(1024) bf16 g_km[NSEG * NH * NMEM * DH];
__device__ __align__(1024) bf16 g_vmt[NSEG * NH * DH * NMEM];
__device__ __align__(1024) float g_opart[(size_t)4 * S_TOK * DM];
__device__ __align__(1024) unsigned g_part[2 * NREC * NH * 64];
__device__ __align__(1024) unsigned g_pub[NSEG * 2048];
struct Flags {
  unsigned qkv[NBLK * 48];
  unsigned h1[NBLK];
  unsigned g[NBLK];
  unsigned o[NBLK * 4];
  unsigned p[NBLK * 2];
  unsigned ctr;
  unsigned rec[NREC];
  unsigned abort_;
};
__device__ __align__(1024) Flags g_flags;

#define RSTAMP(k)
#define DBGMODE 0
#define ISTAMP(i, k)
__device__ __forceinline__ unsigned smem_u32(const void* p) { return (unsigned)__cvta_generic_to_shared(p); }
__device__ __forceinline__ float bf16r(float x) { unsigned u; asm("cvt.rn.bf16x2.f32 %0, %1, %2;" : "=r"(u) : "f"(x), "f"(0.0f)); return __uint_as_float(u); }
__device__ __forceinline__ unsigned pack_bf16(float lo, float hi) {
  __nv_bfloat162 v = __floats2bfloat162_rn(lo, hi);
  return *reinterpret_cast<unsigned*>(&v);
}
__device__ __forceinline__ float bf_lo(unsigned u) { return __uint_as_float(u << 16); }
__device__ __forceinline__ float bf_hi(unsigned u) { return __uint_as_float(u & 0xffff0000u); }

#define SPIN_LIMIT (1u << 20)
#define TRAP_IF(x) if ((x) > SPIN_LIMIT) { asm volatile("st.global.u32 [%0], %1;" ::"l"(0ull), "r"(0u) : "memory"); break; }
__device__ __forceinline__ unsigned ld_acquire(const unsigned* p) {
  unsigned v; asm volatile("ld.acquire.gpu.global.u32 %0, [%1];" : "=r"(v) : "l"(p) : "memory"); return v;
}
__device__ __forceinline__ unsigned ld_relaxed(const unsigned* p) {
  unsigned v; asm volatile("ld.relaxed.gpu.global.u32 %0, [%1];" : "=r"(v) : "l"(p) : "memory"); return v;
}
__device__ __forceinline__ void red_release_add(unsigned* p, unsigned v) {
  asm volatile("red.release.gpu.global.add.u32 [%0], %1;" ::"l"(p), "r"(v) : "memory");
}
__device__ __forceinline__ void st_release(unsigned* p, unsigned v) {
  asm volatile("st.release.gpu.global.u32 [%0], %1;" ::"l"(p), "r"(v) : "memory");
}
__device__ __forceinline__ void wait_flag_ge(const unsigned* p, unsigned target) {
  unsigned it = 0;
  while (ld_acquire(p) < target) {
    __nanosleep(64);
    TRAP_IF(++it);
  }
}
__device__ __forceinline__ uint4 ldv4_relaxed(const void* p) {
  uint4 a; asm volatile("ld.relaxed.gpu.global.v4.u32 {%0,%1,%2,%3}, [%4];" : "=r"(a.x), "=r"(a.y), "=r"(a.z), "=r"(a.w) : "l"(p) : "memory"); return a;
}
__device__ __forceinline__ void mbar_init(unsigned mb, unsigned cnt) { asm volatile("mbarrier.init.shared::cta.b64 [%0], %1;" ::"r"(mb), "r"(cnt) : "memory"); }
__device__ __forceinline__ void mbar_expect_tx(unsigned mb, unsigned bytes) { asm volatile("mbarrier.arrive.expect_tx.shared::cta.b64 _, [%0], %1;" ::"r"(mb), "r"(bytes) : "memory"); }
__device__ __forceinline__ void mbar_arrive(unsigned mb) { asm volatile("mbarrier.arrive.shared::cta.b64 _, [%0];" ::"r"(mb) : "memory"); }
__device__ __forceinline__ void mbar_wait(unsigned mb, unsigned parity) {
  unsigned ok, it = 0;
  while (true) {
    asm volatile("{.reg .pred p; mbarrier.try_wait.parity.shared::cta.b64 p, [%1], %2; selp.u32 %0,1,0,p;}" : "=r"(ok) : "r"(mb), "r"(parity) : "memory");
    if (ok) break;
    TRAP_IF(++it);
  }
}
__device__ __forceinline__ void mbar_wait_sleep(unsigned mb, unsigned parity) {
  unsigned ok, it = 0;
  while (true) {
    asm volatile("{.reg .pred p; mbarrier.test_wait.parity.shared::cta.b64 p, [%1], %2; selp.u32 %0,1,0,p;}" : "=r"(ok) : "r"(mb), "r"(parity) : "memory");
    if (ok) break;
    __nanosleep(200);
    TRAP_IF(++it);
  }
}
__device__ __forceinline__ float ex2f(float x) { float y; asm("ex2.approx.ftz.f32 %0, %1;" : "=f"(y) : "f"(x)); return y; }
__device__ __forceinline__ int opaque_tid() { int t = threadIdx.x; t = __shfl_sync(~0u, t, t & 31); return t; }
#define LOG2E 1.4426950408889634f
__device__ __forceinline__ void mbar_wait_cluster(unsigned mb, unsigned parity) {
  unsigned ok, it = 0;
  while (true) {
    asm volatile("{.reg .pred p; mbarrier.try_wait.parity.acquire.cluster.shared::cta.b64 p, [%1], %2; selp.u32 %0,1,0,p;}" : "=r"(ok) : "r"(mb), "r"(parity) : "memory");
    if (ok) break;
    TRAP_IF(++it);
  }
}
__device__ __forceinline__ void bar_sync(int id, int n) { asm volatile("bar.sync %0, %1;" ::"r"(id), "r"(n) : "memory"); }
__device__ __forceinline__ void bar_arrive(int id, int n) { asm volatile("bar.arrive %0, %1;" ::"r"(id), "r"(n) : "memory"); }
__device__ __forceinline__ void tma_load_2d(unsigned dst, const CUtensorMap* map, int c0, int c1, unsigned mb) {
  asm volatile("cp.async.bulk.tensor.2d.shared::cluster.global.mbarrier::complete_tx::bytes [%0], [%1, {%3, %4}], [%2];"
               ::"r"(dst), "l"((uint64_t)map), "r"(mb), "r"(c0), "r"(c1) : "memory");
}
__device__ __forceinline__ void tma_store_2d(const CUtensorMap* map, unsigned src, int c0, int c1) {
  asm volatile("cp.async.bulk.tensor.2d.global.shared::cta.bulk_group [%0, {%2, %3}], [%1];"
               ::"l"((uint64_t)map), "r"(src), "r"(c0), "r"(c1) : "memory");
}
__device__ __forceinline__ void fence_proxy_async() { asm volatile("fence.proxy.async;" ::: "memory"); }
__device__ __forceinline__ void fence_proxy_async_smem() { asm volatile("fence.proxy.async.shared::cta;" ::: "memory"); }
__device__ __forceinline__ void ldsm_x4(unsigned* r, unsigned addr) {
  asm volatile("ldmatrix.sync.aligned.m8n8.x4.shared.b16 {%0,%1,%2,%3}, [%4];" : "=r"(r[0]), "=r"(r[1]), "=r"(r[2]), "=r"(r[3]) : "r"(addr) : "memory");
}
__device__ __forceinline__ void ldsm_x4_t(unsigned* r, unsigned addr) {
  asm volatile("ldmatrix.sync.aligned.m8n8.x4.trans.shared.b16 {%0,%1,%2,%3}, [%4];" : "=r"(r[0]), "=r"(r[1]), "=r"(r[2]), "=r"(r[3]) : "r"(addr) : "memory");
}
__device__ __forceinline__ void stsm_x2_t(unsigned addr, unsigned r0, unsigned r1) {
  asm volatile("stmatrix.sync.aligned.m8n8.x2.trans.shared.b16 [%0], {%1,%2};" ::"r"(addr), "r"(r0), "r"(r1) : "memory");
}
__device__ __forceinline__ void stsm_x4(unsigned addr, unsigned r0, unsigned r1, unsigned r2, unsigned r3) {
  asm volatile("stmatrix.sync.aligned.m8n8.x4.shared.b16 [%0], {%1,%2,%3,%4};" ::"r"(addr), "r"(r0), "r"(r1), "r"(r2), "r"(r3) : "memory");
}
__device__ __forceinline__ void mma16816(float* d, const unsigned* a, unsigned b0, unsigned b1) {
  asm volatile("mma.sync.aligned.m16n8k16.row.col.f32.bf16.bf16.f32 {%0,%1,%2,%3}, {%4,%5,%6,%7}, {%8,%9}, {%0,%1,%2,%3};"
               : "+f"(d[0]), "+f"(d[1]), "+f"(d[2]), "+f"(d[3]) : "r"(a[0]), "r"(a[1]), "r"(a[2]), "r"(a[3]), "r"(b0), "r"(b1));
}
__device__ __forceinline__ void mma1688(float* d, unsigned a0, unsigned a1, unsigned b0) {
  asm volatile("mma.sync.aligned.m16n8k8.row.col.f32.bf16.bf16.f32 {%0,%1,%2,%3}, {%4,%5}, {%6}, {%0,%1,%2,%3};"
               : "+f"(d[0]), "+f"(d[1]), "+f"(d[2]), "+f"(d[3]) : "r"(a0), "r"(a1), "r"(b0));
}
__device__ __forceinline__ uint64_t mkdesc(unsigned addr, unsigned lbo, unsigned sbo) {
  return (uint64_t)((addr >> 4) & 0x3fff) | ((uint64_t)(lbo >> 4) << 16) | ((uint64_t)(sbo >> 4) << 32) | (1ull << 62);
}
#define R8(b) "+f"(d[b]), "+f"(d[b + 1]), "+f"(d[b + 2]), "+f"(d[b + 3]), "+f"(d[b + 4]), "+f"(d[b + 5]), "+f"(d[b + 6]), "+f"(d[b + 7])
#define R32(b) R8(b), R8(b + 8), R8(b + 16), R8(b + 24)
__device__ __forceinline__ void wgmma_n256(float* d, uint64_t ad, uint64_t bd, int acc) {
  asm volatile(
      "{.reg .pred p; setp.ne.b32 p, %130, 0;\n"
      "wgmma.mma_async.sync.aligned.m64n256k16.f32.bf16.bf16 "
      "{%0,%1,%2,%3,%4,%5,%6,%7,%8,%9,%10,%11,%12,%13,%14,%15,%16,%17,%18,%19,%20,%21,%22,%23,%24,%25,%26,%27,%28,%29,%30,%31,"
      "%32,%33,%34,%35,%36,%37,%38,%39,%40,%41,%42,%43,%44,%45,%46,%47,%48,%49,%50,%51,%52,%53,%54,%55,%56,%57,%58,%59,%60,%61,%62,%63,"
      "%64,%65,%66,%67,%68,%69,%70,%71,%72,%73,%74,%75,%76,%77,%78,%79,%80,%81,%82,%83,%84,%85,%86,%87,%88,%89,%90,%91,%92,%93,%94,%95,"
      "%96,%97,%98,%99,%100,%101,%102,%103,%104,%105,%106,%107,%108,%109,%110,%111,%112,%113,%114,%115,%116,%117,%118,%119,%120,%121,%122,%123,%124,%125,%126,%127},"
      "%128, %129, p, 1, 1, 0, 1;}\n"
      : R32(0), R32(32), R32(64), R32(96)
      : "l"(ad), "l"(bd), "r"(acc));
}

__device__ __forceinline__ void ln16(const float* x, float* o) {
  float s = 0;
#pragma unroll
  for (int i = 0; i < 16; i++) s += x[i];
#pragma unroll
  for (int of = 16; of > 0; of >>= 1) s += __shfl_xor_sync(~0u, s, of);
  float mean = s * (1.0f / DM);
  float v = 0;
#pragma unroll
  for (int i = 0; i < 16; i++) { float dd = x[i] - mean; v += dd * dd; }
#pragma unroll
  for (int of = 16; of > 0; of >>= 1) v += __shfl_xor_sync(~0u, v, of);
  float mb = bf16r(mean);
  float vb = bf16r(v * (1.0f / DM));
  float den = bf16r(sqrtf(bf16r(vb + 1e-5f)));
#pragma unroll
  for (int i = 0; i < 16; i++) o[i] = bf16r(__fdiv_rn(bf16r(x[i] - mb), den));
}
__global__ void __launch_bounds__(256) k_pre(const bf16* __restrict__ x) {
  int t = threadIdx.x, lane = t & 31, w = t >> 5;
  int row = blockIdx.x * 8 + w;
  const uint4* src = reinterpret_cast<const uint4*>(x + (size_t)row * DM);
  uint4 a = src[lane], b = src[lane + 32];
  unsigned u[8] = {a.x, a.y, a.z, a.w, b.x, b.y, b.z, b.w};
  float f[16], o[16], o2[16];
#pragma unroll
  for (int i = 0; i < 8; i++) { f[2 * i] = bf_lo(u[i]); f[2 * i + 1] = bf_hi(u[i]); }
  ln16(f, o);
  ln16(o, o2);
  uint4* d1 = reinterpret_cast<uint4*>(g_xn + (size_t)row * DM);
  uint4* d2 = reinterpret_cast<uint4*>(g_y + (size_t)row * DM);
  d1[lane] = make_uint4(pack_bf16(o[0], o[1]), pack_bf16(o[2], o[3]), pack_bf16(o[4], o[5]), pack_bf16(o[6], o[7]));
  d1[lane + 32] = make_uint4(pack_bf16(o[8], o[9]), pack_bf16(o[10], o[11]), pack_bf16(o[12], o[13]), pack_bf16(o[14], o[15]));
  d2[lane] = make_uint4(pack_bf16(o2[0], o2[1]), pack_bf16(o2[2], o2[3]), pack_bf16(o2[4], o2[5]), pack_bf16(o2[6], o2[7]));
  d2[lane + 32] = make_uint4(pack_bf16(o2[8], o2[9]), pack_bf16(o2[10], o2[11]), pack_bf16(o2[12], o2[13]), pack_bf16(o2[14], o2[15]));
  int gt = blockIdx.x * 256 + t;
  uint4 z = make_uint4(0, 0, 0, 0);
  reinterpret_cast<uint4*>(g_part)[gt] = z;
  if (gt < NSEG * 2048 / 4) reinterpret_cast<uint4*>(g_pub)[gt] = z;
  if (gt < (int)(sizeof(Flags) / 4)) reinterpret_cast<unsigned*>(&g_flags)[gt] = 0;
}

struct Maps { CUtensorMap xn, y, h1, o, qkv_st, qkv_ld, g, wq, wk, wv, wo, w1, w2; };

#define NSTAGE 3
#define STAGE_BYTES 49152
#define B_STG (NSTAGE * STAGE_BYTES)
#define R_WO 0
#define R_T1 65536
#define R_T2 131072
#define R_RING 65536
#define RING_N 4
#define RING_BYTES 12288
#define R_MEM 196608
#define R_QS (R_MEM + 8448)
#define R_KS (R_QS + 1152)
#define R_OS (R_KS + 1152)
#define R_SOWN (R_OS + 2176)
#define R_SPEER (R_SOWN + 1280)
#define R_VM (R_SPEER + 1280)
#define R_VRED (R_VM + 2048)
#define R_RED (R_VRED + 6144)
#define SM_BAR (R_RED + 2048)
#define SMEM_TOTAL (SM_BAR + 256 + 1024)
#define MB_FULL 0
#define MB_EMPTY 8
#define MB_STGF 16
#define MB_STGE 17
#define MB_W0 18
#define MB_W1 19
#define MB_WO 20
#define MB_S 21
#define MB_V 22
#define MB_KVR 23
#define MB_KVF 24
#define SM_MISC (SM_BAR + 208)

#define N_KV 512
#define I_Q 512
#define I_M1 768
#define I_M2 880
#define I_POST 912
#define N_ITEMS 1296
enum { T_QKV = 0, T_M1 = 1, T_M2 = 2, T_ATT = 3, T_OUT = 4 };
struct Item { int type, b, c, ks; };
__device__ __forceinline__ Item decode_item(int i) {
  Item it; it.ks = 0;
  if (i < N_KV) { it.type = T_QKV; it.b = i >> 5; it.c = 16 + (i & 31); }
  else if (i < I_M1) { it.type = T_QKV; it.b = (i - I_Q) >> 4; it.c = (i - I_Q) & 15; }
  else if (i < I_M2) { it.type = T_M1; it.b = (i - I_M1) / 7; it.c = (i - I_M1) % 7; }
  else if (i < I_POST) { it.type = T_M2; it.b = (i - I_M2) >> 1; it.c = (i - I_M2) & 1; }
  else {
    int x = i - I_POST;
    if (x < 16) { it.type = T_ATT; it.b = 0; it.c = x; }
    else {
      x -= 16; int p = 1 + x / 24, r = x % 24;
      if (p < 16 && r < 16) { it.type = T_ATT; it.b = p; it.c = r; }
      else { if (p < 16) r -= 16; it.type = T_OUT; it.b = p - 1; it.c = r & 1; it.ks = r >> 1; }
    }
  }
  return it;
}
__device__ __forceinline__ int item_nkb(int type) { return type == T_M2 ? 28 : (type == T_OUT ? 16 : (type == T_ATT ? 4 : 8)); }

__device__ __forceinline__ void st_async_b64(unsigned raddr, unsigned lo, unsigned hi, unsigned rmb) {
  asm volatile("st.async.weak.shared::cluster.mbarrier::complete_tx::bytes.v2.b32 [%0], {%1,%2}, [%3];" ::"r"(raddr), "r"(lo), "r"(hi), "r"(rmb) : "memory");
}
__device__ __forceinline__ unsigned mapa(unsigned a, unsigned rank) {
  unsigned r; asm volatile("mapa.shared::cluster.u32 %0, %1, %2;" : "=r"(r) : "r"(a), "r"(rank)); return r;
}
__device__ __forceinline__ void sts64(unsigned a, unsigned x, unsigned y) { asm volatile("st.shared.v2.b32 [%0], {%1,%2};" ::"r"(a), "r"(x), "r"(y) : "memory"); }
__device__ __forceinline__ void sts128(unsigned a, uint4 v) { asm volatile("st.shared.v4.b32 [%0], {%1,%2,%3,%4};" ::"r"(a), "r"(v.x), "r"(v.y), "r"(v.z), "r"(v.w) : "memory"); }
__device__ __forceinline__ uint2 lds64(unsigned a) { uint2 v; asm volatile("ld.shared.v2.b32 {%0,%1}, [%2];" : "=r"(v.x), "=r"(v.y) : "r"(a) : "memory"); return v; }
__device__ __forceinline__ uint4 lds128(unsigned a) { uint4 v; asm volatile("ld.shared.v4.b32 {%0,%1,%2,%3}, [%4];" : "=r"(v.x), "=r"(v.y), "=r"(v.z), "=r"(v.w) : "r"(a) : "memory"); return v; }
__device__ __forceinline__ float lds32f(unsigned a) { float v; asm volatile("ld.shared.f32 %0, [%1];" : "=f"(v) : "r"(a) : "memory"); return v; }
#define spin_check(it) TRAP_IF(++it)
#define D_RED 300
#define D_PUB 400
#define DELAY(n) do { unsigned c0_, c1_; asm volatile("mov.u32 %0, %%clock;" : "=r"(c0_)); do { asm volatile("mov.u32 %0, %%clock;" : "=r"(c1_)); } while (c1_ - c0_ < (n)); } while (0)
#define SCALE_QK 0.08838834764831845f

__device__ __forceinline__ void rec_worker(const Maps& maps, unsigned sb, const bf16* __restrict__ mem0) {
  const int c = blockIdx.x, h = c >> 1, j = c & 1;
  const int t = opaque_tid(), lane = t & 31, w = t >> 5, g = lane >> 2, tq = lane & 3;
  const int m = lane >> 3, r8 = lane & 7, kh = w >> 2, et = w & 3;
  const unsigned bar = sb + SM_BAR;
  unsigned wq[16][4], wk[16][4], wo[8][4];
  const unsigned woff = (kh * 4) * 8192 + ((m >> 1) * 8 + r8) * 128 + (((et * 2 + (m & 1)) ^ r8) << 4);
  mbar_wait(bar + 8 * MB_W0, 0);
#pragma unroll
  for (int i = 0; i < 16; i++) {
    ldsm_x4_t(wq[i], sb + R_WO + woff + (i >> 2) * 8192 + (i & 3) * 2048);
    ldsm_x4_t(wk[i], sb + R_T1 + woff + (i >> 2) * 8192 + (i & 3) * 2048);
  }
  bar_sync(2, 288);
  if (t == 0) {
    fence_proxy_async_smem();
    mbar_expect_tx(bar + 8 * MB_WO, 65536);
    for (int kb = 0; kb < 2; kb++)
      for (int cb = 0; cb < 4; cb++) tma_load_2d(sb + R_WO + (kb * 4 + cb) * 8192, &maps.wo, j * 256 + cb * 64, h * 128 + kb * 64, bar + 8 * MB_WO);
  }
  mbar_wait(bar + 8 * MB_W1, 0);
  const unsigned pV = sb + R_T2 + woff;
  const unsigned peer = j ^ 1;
#define KEEP(x) x = __shfl_sync(~0u, x, lane)
  unsigned pA = sb + R_MEM + r8 * 1040 + m * 16 + kh * 512;
  unsigned pW0 = sb + R_WO + (w >> 1) * 8192 + ((m >> 1) * 8 + r8) * 128 + ((((w & 1) * 4 + (m & 1)) ^ r8) << 4);
  unsigned pW1 = pW0 ^ 32;
  unsigned pVk = pV;
  unsigned aMem = sb + R_MEM + (t & 7) * 1040 + (t >> 3) * 16;
  unsigned aX = sb + R_VRED + et * 512 + lane * 16;
  unsigned aQKst = sb + (kh ? R_KS : R_QS) + r8 * 144 + (et * 16 + (m & 1) * 8) * 2;
  unsigned aL8 = sb + lane * 8;
  unsigned aSl = mapa(sb + R_SOWN + w * 256 + lane * 8, j), aSr = mapa(sb + R_SPEER + w * 256 + lane * 8, peer);
  unsigned aVl = mapa(sb + R_VM + (j * 4 + et) * 256 + lane * 8, j), aVr = mapa(sb + R_VM + (j * 4 + et) * 256 + lane * 8, peer);
  const unsigned mbSl = mapa(bar + 8 * MB_S, j), mbSr = mapa(bar + 8 * MB_S, peer), mbVl = mbSl + 8, mbVr = mbSr + 8;
  unsigned aQ = sb + R_QS + r8 * 144 + m * 16;
  unsigned oKx = (et * 8 + r8) * 128 + ((m ^ r8) << 4);
  unsigned oVx = 4096 + (et >> 1) * 4096 + ((m >> 1) * 8 + r8) * 128 + ((((et & 1) * 4 + (m & 1)) ^ r8) << 4);
  unsigned aOst = sb + R_OS + r8 * 272 + (et * 32 + m * 8) * 2;
  unsigned aOld = sb + R_OS + r8 * 272 + m * 16;
  unsigned aVm = sb + R_VM + et * 512 + lane * 8;
  unsigned aRst = sb + R_RED + w * 256 + lane * 16;
  unsigned aRld = sb + R_RED + tq * 64 + g * 4;
  unsigned oPd = ((32 * j + 4 * w) * NH + h) * 256 + g * 32 + tq * 8;
  unsigned oPs = (c * NH + 4 * w) * 256 + lane * 16;
  unsigned oPub = t * 16;
  KEEP(pA); KEEP(pW0); KEEP(pW1); KEEP(pVk); KEEP(aMem); KEEP(aX); KEEP(aQKst); KEEP(aL8); KEEP(aSl); KEEP(aSr); KEEP(aVl); KEEP(aVr); KEEP(aQ); KEEP(oKx); KEEP(oVx);
  KEEP(aOst); KEEP(aOld); KEEP(aVm); KEEP(aRst); KEEP(aRld); KEEP(oPd); KEEP(oPs); KEEP(oPub);
  mbar_wait(bar + 8 * MB_WO, 0);
#pragma unroll
  for (int ks = 0; ks < 4; ks++) { ldsm_x4_t(wo[2 * ks], pW0 + ks * 2048); ldsm_x4_t(wo[2 * ks + 1], pW1 + ks * 2048); }
#pragma unroll
  for (int u = 0; u < 2; u++) {
    int i = t + 256 * u;
    uint4 v = __ldg(reinterpret_cast<const uint4*>(mem0) + i);
    sts128(sb + R_MEM + (i >> 6) * 1040 + (i & 63) * 16, v);
  }
  if (t == 0) { mbar_expect_tx(bar + 8 * MB_S, 2560); mbar_expect_tx(bar + 8 * MB_V, 2048); }

#pragma unroll 1
  for (int s = 0;; s++) {
    const unsigned par = s & 1;
    const unsigned slot = s & (RING_N - 1), rpar = (s / RING_N) & 1;
    const unsigned ring = sb + R_RING + slot * RING_BYTES;
    RSTAMP(1);
    bar_sync(1, 256);
    RSTAMP(2);
    float aq[4] = {0, 0, 0, 0}, ak[4] = {0, 0, 0, 0}, av[4] = {0, 0, 0, 0};
#pragma unroll
    for (int i = 0; i < 8; i++) {
      unsigned b[4], f[4], f0[4];
      ldsm_x4(b, pA + i * 64);
      ldsm_x4_t(f0, pVk + (i >> 1) * 8192 + (i & 1) * 4096);
      ldsm_x4_t(f, pVk + (i >> 1) * 8192 + (i & 1) * 4096 + 2048);
      mma16816(aq, wq[2 * i], b[0], b[1]); mma16816(ak, wk[2 * i], b[0], b[1]); mma16816(av, f0, b[0], b[1]);
      mma16816(aq, wq[2 * i + 1], b[2], b[3]); mma16816(ak, wk[2 * i + 1], b[2], b[3]); mma16816(av, f, b[2], b[3]);
    }
    RSTAMP(3);
#define STSF4(a, v) asm volatile("st.shared.v4.f32 [%0], {%1,%2,%3,%4};" ::"r"(a), "f"(v[0]), "f"(v[1]), "f"(v[2]), "f"(v[3]) : "memory")
    unsigned f[8][4];
#define WO_PREFETCH() do { _Pragma("unroll") for (int i = 0; i < 4; i++) { ldsm_x4_t(f[2 * i], pW0 + 32768 + i * 2048); ldsm_x4_t(f[2 * i + 1], pW1 + 32768 + i * 2048); } } while (0)
    if (kh) {
      STSF4(aX, aq);
      bar_sync(4 + et, 64);
      uint4 o = lds128(aX + 2048), o2 = lds128(aX + 4096);
      stsm_x2_t(aQKst, pack_bf16(ak[0] + __uint_as_float(o.x), ak[1] + __uint_as_float(o.y)), pack_bf16(ak[2] + __uint_as_float(o.z), ak[3] + __uint_as_float(o.w)));
      bar_arrive(1, 256);
      unsigned x = pack_bf16(av[0] + __uint_as_float(o2.x), av[1] + __uint_as_float(o2.y)), y = pack_bf16(av[2] + __uint_as_float(o2.z), av[3] + __uint_as_float(o2.w));
      st_async_b64(aVr, x, y, mbVr);
      st_async_b64(aVl, x, y, mbVl);
      mbar_wait(bar + 8 * (MB_FULL + slot), rpar);
      unsigned vx[4][4];
      ldsm_x4_t(vx[0], ring + oVx); ldsm_x4_t(vx[1], ring + oVx + 2048); ldsm_x4_t(vx[2], ring + (oVx ^ 32)); ldsm_x4_t(vx[3], ring + (oVx ^ 32) + 2048);
      mbar_wait(bar + 8 * MB_S, par);
      float sc[10];
#pragma unroll
      for (int i = 0; i < 5; i++) {
        uint2 o = lds64(aL8 + R_SOWN + i * 256), p = lds64(aL8 + R_SPEER + i * 256);
        sc[2 * i] = __uint_as_float(o.x) + __uint_as_float(p.x); sc[2 * i + 1] = __uint_as_float(o.y) + __uint_as_float(p.y);
      }
      mbar_wait(bar + 8 * MB_V, par);
      uint2 vm0 = lds64(aVm), vm1 = lds64(aVm + 256);
      float mx = fmaxf(fmaxf(fmaxf(sc[0], sc[1]), fmaxf(sc[2], sc[3])), fmaxf(fmaxf(fmaxf(sc[4], sc[5]), fmaxf(sc[6], sc[7])), fmaxf(sc[8], sc[9])));
      mx = fmaxf(mx, __shfl_xor_sync(~0u, mx, 1)); mx = fmaxf(mx, __shfl_xor_sync(~0u, mx, 2));
      const float nm = -mx * (SCALE_QK * LOG2E);
#pragma unroll
      for (int i = 0; i < 10; i++) sc[i] = ex2f(fmaf(sc[i], SCALE_QK * LOG2E, nm));
      float sum = (((sc[0] + sc[1]) + (sc[2] + sc[3])) + ((sc[4] + sc[5]) + (sc[6] + sc[7]))) + (sc[8] + sc[9]);
      sum += __shfl_xor_sync(~0u, sum, 1); sum += __shfl_xor_sync(~0u, sum, 2);
      float inv; asm("rcp.approx.ftz.f32 %0, %1;" : "=f"(inv) : "f"(sum));
      unsigned p[5];
#pragma unroll
      for (int i = 0; i < 5; i++) p[i] = pack_bf16(sc[2 * i] * inv, sc[2 * i + 1] * inv);
      float o0[4] = {0, 0, 0, 0}, o1[4] = {0, 0, 0, 0}, o3[4] = {0, 0, 0, 0}, o4[4] = {0, 0, 0, 0};
      mma16816(o0, vx[0], p[0], p[1]); mma16816(o3, vx[2], p[0], p[1]); mma16816(o1, vx[1], p[2], p[3]); mma16816(o4, vx[3], p[2], p[3]);
      mma1688(o0, vm0.x, vm0.y, p[4]); mma1688(o3, vm1.x, vm1.y, p[4]);
      if (s == NSEG - 1) { if (t == 128) mbar_arrive(bar + 8 * MB_KVR); break; }
      asm volatile("stmatrix.sync.aligned.m8n8.x4.trans.shared.b16 [%0], {%1,%2,%3,%4};" ::"r"(aOst), "r"(pack_bf16(o0[0] + o1[0], o0[1] + o1[1])), "r"(pack_bf16(o0[2] + o1[2], o0[3] + o1[3])),
                   "r"(pack_bf16(o3[0] + o4[0], o3[1] + o4[1])), "r"(pack_bf16(o3[2] + o4[2], o3[3] + o4[3])) : "memory");
      bar_sync(1, 256);
      WO_PREFETCH();
    } else {
      STSF4(aX + 2048, ak); STSF4(aX + 4096, av);
      unsigned kb[8];
      mbar_wait(bar + 8 * (MB_FULL + slot), rpar);
      ldsm_x4(kb, ring + oKx); ldsm_x4(kb + 4, ring + (oKx ^ 64));
      bar_sync(4 + et, 64);
      uint4 o = lds128(aX);
      stsm_x2_t(aQKst, pack_bf16(aq[0] + __uint_as_float(o.x), aq[1] + __uint_as_float(o.y)), pack_bf16(aq[2] + __uint_as_float(o.z), aq[3] + __uint_as_float(o.w)));
      RSTAMP(4);
      bar_sync(1, 256);
      RSTAMP(5);
      unsigned qa[8], km[8];
      ldsm_x4(qa, aQ); ldsm_x4(qa + 4, aQ + 64);
      if (w == 3) { ldsm_x4(km, aQ + 1152); ldsm_x4(km + 4, aQ + 1152 + 64); }
      float s0[4] = {0, 0, 0, 0}, s1[4] = {0, 0, 0, 0};
      unsigned af[4][4];
#pragma unroll
      for (int i = 0; i < 4; i++) { af[i][0] = qa[2 * i]; af[i][1] = 0; af[i][2] = qa[2 * i + 1]; af[i][3] = 0; }
      mma16816(s0, af[0], kb[0], kb[1]); mma16816(s1, af[1], kb[2], kb[3]);
      mma16816(s0, af[2], kb[4], kb[5]); mma16816(s1, af[3], kb[6], kb[7]);
      if (w == 3) {
        float m0[4] = {0, 0, 0, 0}, m1[4] = {0, 0, 0, 0};
        mma16816(m0, af[0], km[0], km[1]); mma16816(m1, af[1], km[2], km[3]);
        mma16816(m0, af[2], km[4], km[5]); mma16816(m1, af[3], km[6], km[7]);
        unsigned x = __float_as_uint(m0[0] + m1[0]), y = __float_as_uint(m0[1] + m1[1]);
        st_async_b64(aSr + 256, x, y, mbSr); st_async_b64(aSl + 256, x, y, mbSl);
      }
      unsigned x = __float_as_uint(s0[0] + s1[0]), y = __float_as_uint(s0[1] + s1[1]);
      st_async_b64(aSr, x, y, mbSr); st_async_b64(aSl, x, y, mbSl);
      RSTAMP(6);
      if (s == NSEG - 1) break;
      WO_PREFETCH();
      RSTAMP(7); RSTAMP(8); RSTAMP(9); RSTAMP(10);
      bar_sync(1, 256);
    }
    RSTAMP(11);
    float d0[4] = {0, 0, 0, 0}, d1[4] = {0, 0, 0, 0}, e0[4] = {0, 0, 0, 0}, e1[4] = {0, 0, 0, 0};
    unsigned ob[4][4];
#pragma unroll
    for (int k2 = 0; k2 < 4; k2++) ldsm_x4(ob[k2], aOld + k2 * 64);
    mma16816(d0, wo[0], ob[0][0], ob[0][1]); mma16816(d1, wo[1], ob[0][0], ob[0][1]);
    mma16816(e0, wo[2], ob[0][2], ob[0][3]); mma16816(e1, wo[3], ob[0][2], ob[0][3]);
    mma16816(d0, wo[4], ob[1][0], ob[1][1]); mma16816(d1, wo[5], ob[1][0], ob[1][1]);
    mma16816(e0, wo[6], ob[1][2], ob[1][3]); mma16816(e1, wo[7], ob[1][2], ob[1][3]);
    mma16816(d0, f[0], ob[2][0], ob[2][1]); mma16816(d1, f[1], ob[2][0], ob[2][1]);
    mma16816(e0, f[2], ob[2][2], ob[2][3]); mma16816(e1, f[3], ob[2][2], ob[2][3]);
    mma16816(d0, f[4], ob[3][0], ob[3][1]); mma16816(d1, f[5], ob[3][0], ob[3][1]);
    mma16816(e0, f[6], ob[3][2], ob[3][3]); mma16816(e1, f[7], ob[3][2], ob[3][3]);
    const unsigned tag = ((s >> 1) & 1) ^ 1;
    const char* pbase = reinterpret_cast<const char*>(g_part) + par * (NREC * NH * 256);
    {
      const char* dst = pbase + oPd;
#define PST(ptr, x, y) asm volatile("st.relaxed.gpu.global.v2.u32 [%0], {%1,%2};" ::"l"(ptr), "r"((__float_as_uint(x) & ~1u) | tag), "r"((__float_as_uint(y) & ~1u) | tag) : "memory")
      PST(dst, d0[0] + e0[0], d0[1] + e0[1]); PST(dst + NH * 256, d0[2] + e0[2], d0[3] + e0[3]);
      PST(dst + 2 * NH * 256, d1[0] + e1[0], d1[1] + e1[1]); PST(dst + 3 * NH * 256, d1[2] + e1[2], d1[3] + e1[3]);
    }
    RSTAMP(12);
    if (t == 128) {
      mbar_arrive(bar + 8 * (MB_EMPTY + slot)); mbar_arrive(bar + 8 * MB_KVR);
      mbar_expect_tx(bar + 8 * MB_S, 2560); mbar_expect_tx(bar + 8 * MB_V, 2048);
    }
    {
      const char* src = pbase + oPs;
      uint4 a, b; unsigned it = 0;
      DELAY(D_RED);
      while (true) {
        a = ldv4_relaxed(src); b = ldv4_relaxed(src + 512);
        unsigned z = ((a.x ^ tag) | (a.y ^ tag)) | ((a.z ^ tag) | (a.w ^ tag)) | ((b.x ^ tag) | (b.y ^ tag)) | ((b.z ^ tag) | (b.w ^ tag));
        if (!(z & 1u)) break;
        spin_check(it);
      }
      RSTAMP(13);
      float r0 = __uint_as_float(a.x) + __uint_as_float(b.x), r1 = __uint_as_float(a.y) + __uint_as_float(b.y);
      float r2 = __uint_as_float(a.z) + __uint_as_float(b.z), r3 = __uint_as_float(a.w) + __uint_as_float(b.w);
      __syncwarp();
      r0 += __shfl_xor_sync(~0u, r0, 16); r1 += __shfl_xor_sync(~0u, r1, 16); r2 += __shfl_xor_sync(~0u, r2, 16); r3 += __shfl_xor_sync(~0u, r3, 16);
      if (lane < 16) asm volatile("st.shared.v4.f32 [%0], {%1,%2,%3,%4};" ::"r"(aRst), "f"(r0), "f"(r1), "f"(r2), "f"(r3) : "memory");
    }
    const char* pub = reinterpret_cast<const char*>(g_pub) + (s + 1) * 8192;
    bar_sync(3, 256);
    if (w == 0) {
      RSTAMP(14);
      float x[8], y[8];
#pragma unroll
      for (int i = 0; i < 8; i++) { x[i] = lds32f(aRld + i * 256); y[i] = lds32f(aRld + i * 256 + 32); }
      unsigned u = pack_bf16(((x[0] + x[1]) + (x[2] + x[3])) + ((x[4] + x[5]) + (x[6] + x[7])), ((y[0] + y[1]) + (y[2] + y[3])) + ((y[4] + y[5]) + (y[6] + y[7])));
      if (u == 0) u = 0x80000000u;
      asm volatile("st.relaxed.gpu.global.u32 [%0], %1;" ::"l"(pub + c * 128 + (oPub >> 2)), "r"(u) : "memory");
      RSTAMP(15);
    }
    mbar_wait(bar + 8 * MB_KVF, par);
    {
      const char* src = pub + oPub;
      uint4 a, b; unsigned it = 0;
      DELAY(D_PUB);
      while (true) {
        a = ldv4_relaxed(src); b = ldv4_relaxed(src + 4096);
        unsigned z = min(min(min(a.x, a.y), min(a.z, a.w)), min(min(b.x, b.y), min(b.z, b.w)));
        if (z) break;
        spin_check(it);
      }
      sts128(aMem, a); sts128(aMem + 512, b);
    }
  }
}

__device__ __forceinline__ void rec_ring(const Maps& maps, unsigned sb) {
  const int c = blockIdx.x, h = c >> 1, j = c & 1;
  const unsigned bar = sb + SM_BAR;
  const int lane = threadIdx.x & 31;
  if (lane == 0) {
    mbar_expect_tx(bar + 8 * MB_W0, 131072);
    for (int kb = 0; kb < 8; kb++) tma_load_2d(sb + R_WO + kb * 8192, &maps.wq, h * 128 + j * 64, kb * 64, bar + 8 * MB_W0);
    for (int kb = 0; kb < 8; kb++) tma_load_2d(sb + R_T1 + kb * 8192, &maps.wk, h * 128 + j * 64, kb * 64, bar + 8 * MB_W0);
    mbar_expect_tx(bar + 8 * MB_W1, 65536);
    for (int kb = 0; kb < 8; kb++) tma_load_2d(sb + R_T2 + kb * 8192, &maps.wv, h * 128 + j * 64, kb * 64, bar + 8 * MB_W1);
  }
  __syncwarp();
  bar_sync(2, 288);
  if (lane == 0) {
    fence_proxy_async_smem();
    for (int s = 0; s < NSEG; s++) {
      unsigned slot = s & (RING_N - 1);
      if ((s & 3) == 0 && !DBGMODE) {
        wait_flag_ge(&g_flags.qkv[(s >> 2) * 48 + 16 + (h >> 1)], 1);
        wait_flag_ge(&g_flags.qkv[(s >> 2) * 48 + 32 + (h >> 1)], 1);
        fence_proxy_async();
      }
      if (s >= RING_N) mbar_wait_sleep(bar + 8 * (MB_EMPTY + slot), ((s / RING_N) - 1) & 1);
      unsigned dst = sb + R_RING + slot * RING_BYTES, mb = bar + 8 * (MB_FULL + slot);
      mbar_expect_tx(mb, RING_BYTES);
      tma_load_2d(dst, &maps.qkv_ld, HD + h * 128 + j * 64, s * SEG, mb);
      tma_load_2d(dst + 4096, &maps.qkv_ld, 2 * HD + h * 128, s * SEG, mb);
      tma_load_2d(dst + 8192, &maps.qkv_ld, 2 * HD + h * 128 + 64, s * SEG, mb);
    }
  }
}
__device__ __forceinline__ void rec_copy(unsigned sb) {
  const int c = blockIdx.x, h = c >> 1, j = c & 1;
  const unsigned bar = sb + SM_BAR;
  const int lane = threadIdx.x & 31;
  for (int s = 0; s < NSEG; s++) {
    mbar_wait_sleep(bar + 8 * MB_KVR, s & 1);
    uint4 k0 = lds128(sb + R_KS + (lane >> 3) * 144 + (lane & 7) * 16), k1 = lds128(sb + R_KS + (4 + (lane >> 3)) * 144 + (lane & 7) * 16);
    uint2 v[4];
#pragma unroll
    for (int i = 0; i < 4; i++) v[i] = lds64(sb + R_VM + (j * 4 + i) * 256 + lane * 8);
    __syncwarp();
    if (lane == 0) mbar_arrive(bar + 8 * MB_KVF);
    bf16* kd = g_km + ((size_t)(s * NH + h) * NMEM) * DH + j * 64;
    *reinterpret_cast<uint4*>(kd + (lane >> 3) * DH + (lane & 7) * 8) = k0;
    *reinterpret_cast<uint4*>(kd + (4 + (lane >> 3)) * DH + (lane & 7) * 8) = k1;
    unsigned* vd = reinterpret_cast<unsigned*>(g_vmt) + ((size_t)(s * NH + h) * DH + j * 64) * 4;
#pragma unroll
    for (int i = 0; i < 4; i++) { vd[(i * 16) * 4 + lane] = v[i].x; vd[(i * 16 + 8) * 4 + lane] = v[i].y; }
    __threadfence();
    __syncwarp();
    if (lane == 0) st_release(&g_flags.rec[c], s + 1);
  }
}

__device__ __forceinline__ void bulk_producer(const Maps& maps, unsigned sb, int* misc) {
  const unsigned bar = sb + SM_BAR;
  unsigned st = 0, ph = 0, seq = 0;
  while (true) {
    int idx = (int)atomicAdd(&g_flags.ctr, 1u);
    if (idx >= N_ITEMS) {
      mbar_wait(bar + 8 * (MB_EMPTY + st), ph ^ 1);
      misc[seq & 3] = -1;
      mbar_arrive(bar + 8 * (MB_FULL + st));
      break;
    }
    ISTAMP(idx, 0);
    Item it = decode_item(idx);
    const CUtensorMap *ma, *mb_; int ka = 0, kbr = 0, nb0 = it.c * 256;
    if (it.type == T_QKV) { ma = &maps.xn; mb_ = it.c < 16 ? &maps.wq : (it.c < 32 ? &maps.wk : &maps.wv); nb0 = (it.c & 15) * 256; }
    else if (it.type == T_M1) { ma = &maps.y; mb_ = &maps.w1; }
    else if (it.type == T_M2) { ma = &maps.h1; mb_ = &maps.w2; wait_flag_ge(&g_flags.h1[it.b], 7); }
    else if (it.type == T_OUT) { ma = &maps.o; mb_ = &maps.wo; ka = kbr = it.ks * 1024; wait_flag_ge(&g_flags.o[it.b * 4 + it.ks], 4); wait_flag_ge(&g_flags.g[it.b], 2); }
    else {
      ma = mb_ = &maps.qkv_ld;
      wait_flag_ge(&g_flags.qkv[it.b * 48 + it.c], 1); wait_flag_ge(&g_flags.qkv[it.b * 48 + 16 + it.c], 1); wait_flag_ge(&g_flags.qkv[it.b * 48 + 32 + it.c], 1);
      for (int i = 0; i < 4; i++) wait_flag_ge(&g_flags.rec[it.c * 4 + i], it.b * 4 + 4);
    }
    fence_proxy_async();
    ISTAMP(idx, 1);
    const int nkb = item_nkb(it.type);
    for (int kb = 0; kb < nkb; kb++) {
      mbar_wait(bar + 8 * (MB_EMPTY + st), ph ^ 1);
      if (kb == 0) { misc[seq & 3] = idx; seq++; }
      unsigned dst = sb + st * STAGE_BYTES, mb = bar + 8 * (MB_FULL + st);
      mbar_expect_tx(mb, STAGE_BYTES);
      if (it.type == T_ATT) {
        int head = it.c * 2 + (kb >> 1), row = it.b * 128 + (kb & 1) * 64;
        for (int i = 0; i < 12; i++) tma_load_2d(dst + i * 4096, ma, (i >> 2) * HD + head * 128 + (i & 1) * 64, row + ((i >> 1) & 1) * 32, mb);
      } else {
        tma_load_2d(dst, ma, ka + kb * 64, it.b * 128, mb);
        for (int i = 0; i < 4; i++) tma_load_2d(dst + 16384 + i * 8192, mb_, nb0 + i * 64, kbr + kb * 64, mb);
      }
      if (++st == NSTAGE) { st = 0; ph ^= 1; }
    }
  }
}
__device__ __forceinline__ void bulk_store(const Maps& maps, unsigned sb, volatile int* misc) {
  const unsigned bar = sb + SM_BAR;
  unsigned ph = 0;
  while (true) {
    mbar_wait(bar + 8 * MB_STGF, ph); ph ^= 1;
    int idx = misc[4];
    if (idx < 0) break;
    Item it = decode_item(idx);
    const CUtensorMap* mp = it.type == T_QKV ? &maps.qkv_st : (it.type == T_M1 ? &maps.h1 : (it.type == T_M2 ? &maps.g : &maps.o));
    unsigned* flag = it.type == T_QKV ? &g_flags.qkv[it.b * 48 + it.c] : (it.type == T_M1 ? &g_flags.h1[it.b] : (it.type == T_M2 ? &g_flags.g[it.b] : &g_flags.o[it.b * 4 + (it.c >> 2)]));
    for (int i = 0; i < 4; i++) tma_store_2d(mp, sb + B_STG + i * 16384, it.c * 256 + i * 64, it.b * 128);
    asm volatile("cp.async.bulk.commit_group;" ::: "memory");
    asm volatile("cp.async.bulk.wait_group.read 0;" ::: "memory");
    mbar_arrive(bar + 8 * MB_STGE);
    asm volatile("cp.async.bulk.wait_group 0;" ::: "memory");
    fence_proxy_async();
    __threadfence();
    red_release_add(flag, 1);
    ISTAMP(idx, 3);
  }
}
__device__ __forceinline__ float gelu_t(float x) {
  float u = 0.7978845608028654f * (x + 0.044715f * x * x * x);
  return __fdividef(x, 1.0f + __expf(-2.0f * u));
}
__device__ __forceinline__ float silu_f(float x) { return __fdividef(x, 1.0f + __expf(-x)); }

__device__ __forceinline__ void bulk_att_stage(unsigned sa, unsigned stg, int b, int hp, int kb, int w, int lane) {
  const int g = lane >> 2, tq = lane & 3, m = lane >> 3, r8 = lane & 7;
  const int seg = w >> 2, mt = (w >> 1) & 1, eh = w & 1;
  const int head = hp * 2 + (kb >> 1), sg = b * 4 + (kb & 1) * 2 + seg;
  const unsigned* kmp = reinterpret_cast<const unsigned*>(g_km + ((size_t)(sg * NH + head) * NMEM + g) * DH) + tq;
  const unsigned* vmp = reinterpret_cast<const unsigned*>(g_vmt) + ((size_t)(sg * NH + head) * DH + eh * 64) * 4 + lane;
  unsigned km[16], vm[8];
#pragma unroll
  for (int i = 0; i < 16; i++) km[i] = __ldcg(kmp + i * 4);
#pragma unroll
  for (int i = 0; i < 8; i++) vm[i] = __ldcg(vmp + i * 32);
  float s[5][4];
#pragma unroll
  for (int i = 0; i < 5; i++) { s[i][0] = s[i][1] = s[i][2] = s[i][3] = 0; }
  const unsigned qb = sa + (0 * 2 + seg) * 8192, kbs = sa + (1 * 2 + seg) * 8192, vb = sa + (2 * 2 + seg) * 8192 + eh * 4096;
  unsigned qa[8][4];
#pragma unroll
  for (int ks = 0; ks < 8; ks++) {
    int row = mt * 16 + (m & 1) * 8 + r8;
    ldsm_x4(qa[ks], qb + (ks >> 2) * 4096 + row * 128 + ((((ks & 3) * 2 + (m >> 1)) ^ r8) << 4));
    unsigned kf[4];
    int krow = (m >> 1) * 8 + r8;
    unsigned ka = kbs + (ks >> 2) * 4096 + krow * 128 + ((((ks & 3) * 2 + (m & 1)) ^ r8) << 4);
    ldsm_x4(kf, ka);
    mma16816(s[0], qa[ks], kf[0], kf[1]); mma16816(s[1], qa[ks], kf[2], kf[3]);
    if (mt) { ldsm_x4(kf, ka + 2048); mma16816(s[2], qa[ks], kf[0], kf[1]); mma16816(s[3], qa[ks], kf[2], kf[3]); }
  }
#pragma unroll
  for (int ks = 0; ks < 8; ks++) mma16816(s[4], qa[ks], km[2 * ks], km[2 * ks + 1]);
  float mx0 = -INFINITY, mx1 = -INFINITY;
  const int t0 = mt * 16 + g, t1 = t0 + 8;
#pragma unroll
  for (int i = 0; i < 5; i++) {
#pragma unroll
    for (int e = 0; e < 4; e++) {
      float v = bf16r(bf16r(s[i][e]) * SCALE_QK);
      if (i < 4) { int kj = i * 8 + 2 * tq + (e & 1); if (kj > (e < 2 ? t0 : t1)) v = -INFINITY; }
      s[i][e] = v;
      if (e < 2) mx0 = fmaxf(mx0, v); else mx1 = fmaxf(mx1, v);
    }
  }
  mx0 = fmaxf(mx0, __shfl_xor_sync(~0u, mx0, 1)); mx0 = fmaxf(mx0, __shfl_xor_sync(~0u, mx0, 2));
  mx1 = fmaxf(mx1, __shfl_xor_sync(~0u, mx1, 1)); mx1 = fmaxf(mx1, __shfl_xor_sync(~0u, mx1, 2));
  float sm0 = 0, sm1 = 0;
#pragma unroll
  for (int i = 0; i < 5; i++) {
    s[i][0] = __expf(s[i][0] - mx0); s[i][1] = __expf(s[i][1] - mx0); s[i][2] = __expf(s[i][2] - mx1); s[i][3] = __expf(s[i][3] - mx1);
    sm0 += s[i][0] + s[i][1]; sm1 += s[i][2] + s[i][3];
  }
  sm0 += __shfl_xor_sync(~0u, sm0, 1); sm0 += __shfl_xor_sync(~0u, sm0, 2);
  sm1 += __shfl_xor_sync(~0u, sm1, 1); sm1 += __shfl_xor_sync(~0u, sm1, 2);
  const float i0 = __fdividef(1.0f, sm0), i1 = __fdividef(1.0f, sm1);
  unsigned pa[2][4], pm0, pm1;
#pragma unroll
  for (int kk = 0; kk < 2; kk++) {
    pa[kk][0] = pack_bf16(s[2 * kk][0] * i0, s[2 * kk][1] * i0); pa[kk][1] = pack_bf16(s[2 * kk][2] * i1, s[2 * kk][3] * i1);
    pa[kk][2] = pack_bf16(s[2 * kk + 1][0] * i0, s[2 * kk + 1][1] * i0); pa[kk][3] = pack_bf16(s[2 * kk + 1][2] * i1, s[2 * kk + 1][3] * i1);
  }
  pm0 = pack_bf16(s[4][0] * i0, s[4][1] * i0); pm1 = pack_bf16(s[4][2] * i1, s[4][3] * i1);
  const int orow = (kb & 1) * 64 + seg * 32 + mt * 16 + (m & 1) * 8 + r8;
  const unsigned ob = stg + ((kb >> 1) * 2 + eh) * 16384 + orow * 128;
#pragma unroll
  for (int cp = 0; cp < 4; cp++) {
    float o0[4] = {0, 0, 0, 0}, o1[4] = {0, 0, 0, 0};
    mma1688(o0, pm0, pm1, vm[2 * cp]); mma1688(o1, pm0, pm1, vm[2 * cp + 1]);
    unsigned vf[4];
    int row = (m & 1) * 8 + r8;
    unsigned va = vb + row * 128 + (((cp * 2 + (m >> 1)) ^ r8) << 4);
    ldsm_x4_t(vf, va);
    mma16816(o0, pa[0], vf[0], vf[1]); mma16816(o1, pa[0], vf[2], vf[3]);
    if (mt) { ldsm_x4_t(vf, va + 2048); mma16816(o0, pa[1], vf[0], vf[1]); mma16816(o1, pa[1], vf[2], vf[3]); }
    stsm_x4(ob + (((cp * 2 + (m >> 1)) ^ r8) << 4), pack_bf16(o0[0], o0[1]), pack_bf16(o0[2], o0[3]), pack_bf16(o1[0], o1[1]), pack_bf16(o1[2], o1[3]));
  }
}

__device__ __forceinline__ void bulk_worker(unsigned sb, volatile int* misc, const bf16* __restrict__ x, const bf16* __restrict__ b1, const bf16* __restrict__ b2, bf16* __restrict__ out) {
  const int t = threadIdx.x, lane = t & 31, w = t >> 5, wg = w >> 2, g = lane >> 2, tq = lane & 3, m = lane >> 3, r8 = lane & 7;
  const unsigned bar = sb + SM_BAR;
  unsigned st = 0, ph = 0, seq = 0, sph = 0;
  float d[128];
  while (true) {
    mbar_wait(bar + 8 * (MB_FULL + st), ph);
    const int idx = misc[seq & 3]; seq++;
    if (idx < 0 || idx >= N_ITEMS) break;
    if (t == 0) ISTAMP(idx, 2);
    const Item it = decode_item(idx);
    const int nkb = item_nkb(it.type);
    if (it.type == T_ATT) {
      mbar_wait(bar + 8 * MB_STGE, sph ^ 1);
      for (int kb = 0; kb < 4; kb++) {
        if (kb) mbar_wait(bar + 8 * (MB_FULL + st), ph);
        bulk_att_stage(sb + st * STAGE_BYTES, sb + B_STG, it.b, it.c, kb, w, lane);
        __syncwarp();
        if (lane == 0) mbar_arrive(bar + 8 * (MB_EMPTY + st));
        if (++st == NSTAGE) { st = 0; ph ^= 1; }
      }
      if (t == 0) misc[4] = idx;
      fence_proxy_async_smem();
      mbar_arrive(bar + 8 * MB_STGF); sph ^= 1;
      continue;
    }
    unsigned pst = 0;
    for (int kb = 0; kb < nkb; kb++) {
      if (kb) mbar_wait(bar + 8 * (MB_FULL + st), ph);
      unsigned sa = sb + st * STAGE_BYTES;
      uint64_t ad = mkdesc(sa + wg * 8192, 16, 1024), bd = mkdesc(sa + 16384, 8192, 1024);
      asm volatile("wgmma.fence.sync.aligned;" ::: "memory");
#pragma unroll
      for (int k = 0; k < 4; k++) wgmma_n256(d, ad + k * 2, bd + k * 128, (kb | k) != 0);
      asm volatile("wgmma.commit_group.sync.aligned;" ::: "memory");
      if (kb) {
        asm volatile("wgmma.wait_group.sync.aligned 1;" ::: "memory");
        if (lane == 0) mbar_arrive(bar + 8 * (MB_EMPTY + pst));
      }
      pst = st;
      if (++st == NSTAGE) { st = 0; ph ^= 1; }
    }
    asm volatile("wgmma.wait_group.sync.aligned 0;" ::: "memory");
    if (lane == 0) mbar_arrive(bar + 8 * (MB_EMPTY + pst));
    if (it.type == T_OUT) {
      const int row = it.b * 128 + w * 16 + g, col = it.c * 256 + 2 * tq;
      float* pp = g_opart + ((size_t)it.ks * S_TOK + row) * DM + col;
#pragma unroll
      for (int i = 0; i < 32; i++) {
        __stcg(reinterpret_cast<float2*>(pp + i * 8), make_float2(d[4 * i], d[4 * i + 1]));
        __stcg(reinterpret_cast<float2*>(pp + 8 * DM + i * 8), make_float2(d[4 * i + 2], d[4 * i + 3]));
      }
      __threadfence();
      bar_sync(1, 256);
      if (t == 0) misc[5] = (int)atomicAdd(&g_flags.p[it.b * 2 + it.c], 1u);
      bar_sync(1, 256);
      if (misc[5] == 3) {
        __threadfence();
        const float* p0 = g_opart + (size_t)row * DM + col;
#pragma unroll 4
        for (int i = 0; i < 64; i++) {
          size_t off = (size_t)(i & 1) * 8 * DM + (i >> 1) * 8;
          float2 a = __ldcg(reinterpret_cast<const float2*>(p0 + off)), b = __ldcg(reinterpret_cast<const float2*>(p0 + off + (size_t)S_TOK * DM));
          float2 c = __ldcg(reinterpret_cast<const float2*>(p0 + off + (size_t)2 * S_TOK * DM)), e = __ldcg(reinterpret_cast<const float2*>(p0 + off + (size_t)3 * S_TOK * DM));
          size_t o = (size_t)row * DM + col + off;
          unsigned gv = __ldcg(reinterpret_cast<const unsigned*>(g_g + o)), xv = __ldg(reinterpret_cast<const unsigned*>(x + o));
          float s0 = bf16r((a.x + b.x) + (c.x + e.x)), s1 = bf16r((a.y + b.y) + (c.y + e.y));
          *reinterpret_cast<unsigned*>(out + o) = pack_bf16(bf_lo(xv) + bf16r(s0 * bf_lo(gv)), bf_hi(xv) + bf16r(s1 * bf_hi(gv)));
        }
      }
      bar_sync(1, 256);
      if (t == 0) ISTAMP(idx, 3);
      continue;
    }
    if (it.type != T_QKV) {
      const unsigned* bp = reinterpret_cast<const unsigned*>((it.type == T_M1 ? b1 : b2) + it.c * 256) + tq;
#pragma unroll
      for (int i = 0; i < 32; i++) {
        unsigned bv = __ldg(bp + i * 4);
        float lo = bf_lo(bv), hi = bf_hi(bv);
        float x0 = bf16r(bf16r(d[4 * i]) + lo), x1 = bf16r(bf16r(d[4 * i + 1]) + hi), x2 = bf16r(bf16r(d[4 * i + 2]) + lo), x3 = bf16r(bf16r(d[4 * i + 3]) + hi);
        if (it.type == T_M1) { d[4 * i] = gelu_t(x0); d[4 * i + 1] = gelu_t(x1); d[4 * i + 2] = gelu_t(x2); d[4 * i + 3] = gelu_t(x3); }
        else { d[4 * i] = silu_f(x0); d[4 * i + 1] = silu_f(x1); d[4 * i + 2] = silu_f(x2); d[4 * i + 3] = silu_f(x3); }
      }
    }
    mbar_wait(bar + 8 * MB_STGE, sph ^ 1);
    {
      const unsigned ob = sb + B_STG + (w * 16 + (m & 1) * 8 + r8) * 128;
#pragma unroll
      for (int i = 0; i < 16; i++)
        stsm_x4(ob + (i >> 2) * 16384 + ((((i & 3) * 2 + (m >> 1)) ^ r8) << 4), pack_bf16(d[8 * i], d[8 * i + 1]), pack_bf16(d[8 * i + 2], d[8 * i + 3]),
                pack_bf16(d[8 * i + 4], d[8 * i + 5]), pack_bf16(d[8 * i + 6], d[8 * i + 7]));
    }
    if (t == 0) misc[4] = idx;
    fence_proxy_async_smem();
    mbar_arrive(bar + 8 * MB_STGF); sph ^= 1;
  }
  mbar_wait(bar + 8 * MB_STGE, sph ^ 1);
  if (t == 0) misc[4] = -1;
  mbar_arrive(bar + 8 * MB_STGF);
}

__global__ void __cluster_dims__(2, 1, 1) __launch_bounds__(384, 1)
k_main(const __grid_constant__ Maps maps, const bf16* __restrict__ x, const bf16* __restrict__ mem0, const bf16* __restrict__ b1, const bf16* __restrict__ b2, bf16* __restrict__ out) {
  extern __shared__ unsigned char smem_raw[];
  const unsigned sraw = smem_u32(smem_raw);
  const unsigned sb = (sraw + 1023u) & ~1023u;
  int* misc = reinterpret_cast<int*>(smem_raw + (sb - sraw) + SM_MISC);
  const int w = threadIdx.x >> 5;
  const bool rec = blockIdx.x < NREC;
  if (threadIdx.x == 0) {
    const unsigned bar = sb + SM_BAR;
    for (int i = 0; i < 8; i++) { mbar_init(bar + 8 * (MB_FULL + i), 1); mbar_init(bar + 8 * (MB_EMPTY + i), rec ? 1 : 8); }
    mbar_init(bar + 8 * MB_STGF, 256); mbar_init(bar + 8 * MB_STGE, 1);
    for (int i = MB_W0; i <= MB_KVF; i++) mbar_init(bar + 8 * i, 1);
    asm volatile("fence.mbarrier_init.release.cluster;" ::: "memory");
  }
  __syncthreads();
  asm volatile("barrier.cluster.arrive.release.aligned;\nbarrier.cluster.wait.acquire.aligned;" ::: "memory");
  if (DBGMODE && !rec) return;
  if (w >= 8) {
    asm volatile("setmaxnreg.dec.sync.aligned.u32 24;");
    if (rec) { if (w == 8) rec_ring(maps, sb); else if (w == 9) rec_copy(sb); }
    else if ((threadIdx.x & 31) == 0) { if (w == 8) bulk_producer(maps, sb, misc); else if (w == 9) bulk_store(maps, sb, misc); }
  } else {
    if (rec) { asm volatile("setmaxnreg.inc.sync.aligned.u32 240;"); rec_worker(maps, sb, mem0); }
    else { asm volatile("setmaxnreg.inc.sync.aligned.u32 240;"); bulk_worker(sb, misc, x, b1, b2, out); }
  }
}

typedef CUresult (*EncFn)(CUtensorMap*, CUtensorMapDataType, cuuint32_t, void*, const cuuint64_t*, const cuuint64_t*, const cuuint32_t*, const cuuint32_t*,
                          CUtensorMapInterleave, CUtensorMapSwizzle, CUtensorMapL2promotion, CUtensorMapFloatOOBfill);
static void mk_map(EncFn enc, CUtensorMap* m, const void* ptr, uint64_t rows, uint64_t cols, uint32_t box_rows) {
  cuuint64_t dims[2] = {cols, rows}; cuuint64_t strides[1] = {cols * 2};
  cuuint32_t box[2] = {64, box_rows}, es[2] = {1, 1};
  enc(m, CU_TENSOR_MAP_DATA_TYPE_BFLOAT16, 2, const_cast<void*>(ptr), dims, strides, box, es, CU_TENSOR_MAP_INTERLEAVE_NONE, CU_TENSOR_MAP_SWIZZLE_128B,
      CU_TENSOR_MAP_L2_PROMOTION_L2_256B, CU_TENSOR_MAP_FLOAT_OOB_FILL_NONE);
}
extern "C" void kernel_launch(void* const* d_in, const int* in_sizes, int n_in, void* d_out, int out_size) {
  static EncFn enc = nullptr;
  static void *p_xn, *p_y, *p_h1, *p_o, *p_qkv, *p_g;
  if (!enc) {
    void* fn = nullptr; cudaDriverEntryPointQueryResult qr;
    cudaGetDriverEntryPoint("cuTensorMapEncodeTiled", &fn, cudaEnableDefault, &qr);
    enc = (EncFn)fn;
    cudaGetSymbolAddress(&p_xn, g_xn); cudaGetSymbolAddress(&p_y, g_y); cudaGetSymbolAddress(&p_h1, g_h1);
    cudaGetSymbolAddress(&p_o, g_o); cudaGetSymbolAddress(&p_qkv, g_qkv); cudaGetSymbolAddress(&p_g, g_g);
    cudaFuncSetAttribute(k_main, cudaFuncAttributeMaxDynamicSharedMemorySize, SMEM_TOTAL);
  }
  Maps maps;
  mk_map(enc, &maps.xn, p_xn, S_TOK, DM, 128); mk_map(enc, &maps.y, p_y, S_TOK, DM, 128); mk_map(enc, &maps.h1, p_h1, S_TOK, FF, 128);
  mk_map(enc, &maps.o, p_o, S_TOK, HD, 128); mk_map(enc, &maps.qkv_st, p_qkv, S_TOK, 3 * HD, 128); mk_map(enc, &maps.qkv_ld, p_qkv, S_TOK, 3 * HD, 32);
  mk_map(enc, &maps.g, p_g, S_TOK, DM, 128);
  mk_map(enc, &maps.wq, d_in[2], DM, HD, 64); mk_map(enc, &maps.wk, d_in[3], DM, HD, 64); mk_map(enc, &maps.wv, d_in[4], DM, HD, 64);
  mk_map(enc, &maps.wo, d_in[5], HD, DM, 64); mk_map(enc, &maps.w1, d_in[8], DM, FF, 64); mk_map(enc, &maps.w2, d_in[10], FF, DM, 64);
  cudaStream_t st = cudaStreamPerThread;
  k_pre<<<256, 256, 0, st>>>((const bf16*)d_in[0]);
  k_main<<<NCTA, 384, SMEM_TOTAL, st>>>(maps, (const bf16*)d_in[0], (const bf16*)d_in[1], (const bf16*)d_in[9], (const bf16*)d_in[11], (bf16*)d_out);
}
```

```cpp
#include <cuda_runtime.h>
#include <cuda_bf16.h>
#include <cuda.h>
#include <stdint.h>

typedef __nv_bfloat16 bf16;

#define S_TOK 2048
#define DM 512
#define NH 32
#define DH 128
#define HD 4096
#define NMEM 8
#define SEG 32
#define NSEG 64
#define FF 1792
#define NBLK 16
#define NREC 64
#define NCTA 132
#define NBULK (NCTA - NREC)

__device__ __align__(1024) bf16 g_xn[S_TOK * DM];
__device__ __align__(1024) bf16 g_y[S_TOK * DM];
__device__ __align__(1024) bf16 g_qkv[(size_t)S_TOK * 3 * HD];
__device__ __align__(1024) bf16 g_h1[S_TOK * FF];
__device__ __align__(1024) bf16 g_g[S_TOK * DM];
__device__ __align__(1024) bf16 g_o[(size_t)S_TOK * HD];
__device__ __align__(1024) bf16 g_km[NSEG * NH * NMEM * DH];
__device__ __align__(1024) bf16 g_vmt[NSEG * NH * DH * NMEM];
__device__ __align__(1024) float g_opart[(size_t)4 * S_TOK * DM];
__device__ __align__(1024) unsigned g_part[2 * NREC * NH * 64];
__device__ __align__(1024) unsigned g_pub[NSEG * 2048];
struct Flags {
  unsigned qkv[NBLK * 48];
  unsigned h1[NBLK];
  unsigned g[NBLK];
  unsigned o[NBLK * 4];
  unsigned p[NBLK * 2];
  unsigned ctr;
  unsigned rec[NREC];
  unsigned abort_;
};
__device__ __align__(1024) Flags g_flags;

#define RSTAMP(k)
#define DBGMODE 0
#define ISTAMP(i, k)
__device__ __forceinline__ unsigned smem_u32(const void* p) { return (unsigned)__cvta_generic_to_shared(p); }
__device__ __forceinline__ float bf16r(float x) { unsigned u; asm("cvt.rn.bf16x2.f32 %0, %1, %2;" : "=r"(u) : "f"(x), "f"(0.0f)); return __uint_as_float(u); }
__device__ __forceinline__ unsigned pack_bf16(float lo, float hi) {
  __nv_bfloat162 v = __floats2bfloat162_rn(lo, hi);
  return *reinterpret_cast<unsigned*>(&v);
}
__device__ __forceinline__ float bf_lo(unsigned u) { return __uint_as_float(u << 16); }
__device__ __forceinline__ float bf_hi(unsigned u) { return __uint_as_float(u & 0xffff0000u); }

#define SPIN_LIMIT (1u << 20)
#define TRAP_IF(x) if ((x) > SPIN_LIMIT) { asm volatile("st.global.u32 [%0], %1;" ::"l"(0ull), "r"(0u) : "memory"); break; }
__device__ __forceinline__ unsigned ld_acquire(const unsigned* p) {
  unsigned v; asm volatile("ld.acquire.gpu.global.u32 %0, [%1];" : "=r"(v) : "l"(p) : "memory"); return v;
}
__device__ __forceinline__ unsigned ld_relaxed(const unsigned* p) {
  unsigned v; asm volatile("ld.relaxed.gpu.global.u32 %0, [%1];" : "=r"(v) : "l"(p) : "memory"); return v;
}
__device__ __forceinline__ void red_release_add(unsigned* p, unsigned v) {
  asm volatile("red.release.gpu.global.add.u32 [%0], %1;" ::"l"(p), "r"(v) : "memory");
}
__device__ __forceinline__ void st_release(unsigned* p, unsigned v) {
  asm volatile("st.release.gpu.global.u32 [%0], %1;" ::"l"(p), "r"(v) : "memory");
}
__device__ __forceinline__ void wait_flag_ge(const unsigned* p, unsigned target) {
  unsigned it = 0;
  while (ld_acquire(p) < target) {
    __nanosleep(64);
    TRAP_IF(++it);
  }
}
__device__ __forceinline__ uint4 ldv4_relaxed(const void* p) {
  uint4 a; asm volatile("ld.relaxed.gpu.global.v4.u32 {%0,%1,%2,%3}, [%4];" : "=r"(a.x), "=r"(a.y), "=r"(a.z), "=r"(a.w) : "l"(p) : "memory"); return a;
}
__device__ __forceinline__ void mbar_init(unsigned mb, unsigned cnt) { asm volatile("mbarrier.init.shared::cta.b64 [%0], %1;" ::"r"(mb), "r"(cnt) : "memory"); }
__device__ __forceinline__ void mbar_expect_tx(unsigned mb, unsigned bytes) { asm volatile("mbarrier.arrive.expect_tx.shared::cta.b64 _, [%0], %1;" ::"r"(mb), "r"(bytes) : "memory"); }
__device__ __forceinline__ void mbar_arrive(unsigned mb) { asm volatile("mbarrier.arrive.shared::cta.b64 _, [%0];" ::"r"(mb) : "memory"); }
__device__ __forceinline__ void mbar_wait(unsigned mb, unsigned parity) {
  unsigned ok, it = 0;
  while (true) {
    asm volatile("{.reg .pred p; mbarrier.try_wait.parity.shared::cta.b64 p, [%1], %2; selp.u32 %0,1,0,p;}" : "=r"(ok) : "r"(mb), "r"(parity) : "memory");
    if (ok) break;
    TRAP_IF(++it);
  }
}
__device__ __forceinline__ void mbar_wait_sleep(unsigned mb, unsigned parity) {
  unsigned ok, it = 0;
  while (true) {
    asm volatile("{.reg .pred p; mbarrier.test_wait.parity.shared::cta.b64 p, [%1], %2; selp.u32 %0,1,0,p;}" : "=r"(ok) : "r"(mb), "r"(parity) : "memory");
    if (ok) break;
    __nanosleep(200);
    TRAP_IF(++it);
  }
}
__device__ __forceinline__ float ex2f(float x) { float y; asm("ex2.approx.ftz.f32 %0, %1;" : "=f"(y) : "f"(x)); return y; }
__device__ __forceinline__ int opaque_tid() { int t = threadIdx.x; t = __shfl_sync(~0u, t, t & 31); return t; }
#define LOG2E 1.4426950408889634f
__device__ __forceinline__ void mbar_wait_cluster(unsigned mb, unsigned parity) {
  unsigned ok, it = 0;
  while (true) {
    asm volatile("{.reg .pred p; mbarrier.try_wait.parity.acquire.cluster.shared::cta.b64 p, [%1], %2; selp.u32 %0,1,0,p;}" : "=r"(ok) : "r"(mb), "r"(parity) : "memory");
    if (ok) break;
    TRAP_IF(++it);
  }
}
__device__ __forceinline__ void bar_sync(int id, int n) { asm volatile("bar.sync %0, %1;" ::"r"(id), "r"(n) : "memory"); }
__device__ __forceinline__ void bar_arrive(int id, int n) { asm volatile("bar.arrive %0, %1;" ::"r"(id), "r"(n) : "memory"); }
__device__ __forceinline__ void tma_load_2d(unsigned dst, const CUtensorMap* map, int c0, int c1, unsigned mb) {
  asm volatile("cp.async.bulk.tensor.2d.shared::cluster.global.mbarrier::complete_tx::bytes [%0], [%1, {%3, %4}], [%2];"
               ::"r"(dst), "l"((uint64_t)map), "r"(mb), "r"(c0), "r"(c1) : "memory");
}
__device__ __forceinline__ void tma_store_2d(const CUtensorMap* map, unsigned src, int c0, int c1) {
  asm volatile("cp.async.bulk.tensor.2d.global.shared::cta.bulk_group [%0, {%2, %3}], [%1];"
               ::"l"((uint64_t)map), "r"(src), "r"(c0), "r"(c1) : "memory");
}
__device__ __forceinline__ void fence_proxy_async() { asm volatile("fence.proxy.async;" ::: "memory"); }
__device__ __forceinline__ void fence_proxy_async_smem() { asm volatile("fence.proxy.async.shared::cta;" ::: "memory"); }
__device__ __forceinline__ void ldsm_x4(unsigned* r, unsigned addr) {
  asm volatile("ldmatrix.sync.aligned.m8n8.x4.shared.b16 {%0,%1,%2,%3}, [%4];" : "=r"(r[0]), "=r"(r[1]), "=r"(r[2]), "=r"(r[3]) : "r"(addr) : "memory");
}
__device__ __forceinline__ void ldsm_x4_t(unsigned* r, unsigned addr) {
  asm volatile("ldmatrix.sync.aligned.m8n8.x4.trans.shared.b16 {%0,%1,%2,%3}, [%4];" : "=r"(r[0]), "=r"(r[1]), "=r"(r[2]), "=r"(r[3]) : "r"(addr) : "memory");
}
__device__ __forceinline__ void stsm_x2_t(unsigned addr, unsigned r0, unsigned r1) {
  asm volatile("stmatrix.sync.aligned.m8n8.x2.trans.shared.b16 [%0], {%1,%2};" ::"r"(addr), "r"(r0), "r"(r1) : "memory");
}
__device__ __forceinline__ void stsm_x4(unsigned addr, unsigned r0, unsigned r1, unsigned r2, unsigned r3) {
  asm volatile("stmatrix.sync.aligned.m8n8.x4.shared.b16 [%0], {%1,%2,%3,%4};" ::"r"(addr), "r"(r0), "r"(r1), "r"(r2), "r"(r3) : "memory");
}
__device__ __forceinline__ void mma16816(float* d, const unsigned* a, unsigned b0, unsigned b1) {
  asm volatile("mma.sync.aligned.m16n8k16.row.col.f32.bf16.bf16.f32 {%0,%1,%2,%3}, {%4,%5,%6,%7}, {%8,%9}, {%0,%1,%2,%3};"
               : "+f"(d[0]), "+f"(d[1]), "+f"(d[2]), "+f"(d[3]) : "r"(a[0]), "r"(a[1]), "r"(a[2]), "r"(a[3]), "r"(b0), "r"(b1));
}
__device__ __forceinline__ void mma1688(float* d, unsigned a0, unsigned a1, unsigned b0) {
  asm volatile("mma.sync.aligned.m16n8k8.row.col.f32.bf16.bf16.f32 {%0,%1,%2,%3}, {%4,%5}, {%6}, {%0,%1,%2,%3};"
               : "+f"(d[0]), "+f"(d[1]), "+f"(d[2]), "+f"(d[3]) : "r"(a0), "r"(a1), "r"(b0));
}
__device__ __forceinline__ uint64_t mkdesc(unsigned addr, unsigned lbo, unsigned sbo) {
  return (uint64_t)((addr >> 4) & 0x3fff) | ((uint64_t)(lbo >> 4) << 16) | ((uint64_t)(sbo >> 4) << 32) | (1ull << 62);
}
#define R8(b) "+f"(d[b]), "+f"(d[b + 1]), "+f"(d[b + 2]), "+f"(d[b + 3]), "+f"(d[b + 4]), "+f"(d[b + 5]), "+f"(d[b + 6]), "+f"(d[b + 7])
#define R32(b) R8(b), R8(b + 8), R8(b + 16), R8(b + 24)
__device__ __forceinline__ void wgmma_n256(float* d, uint64_t ad, uint64_t bd, int acc) {
  asm volatile(
      "{.reg .pred p; setp.ne.b32 p, %130, 0;\n"
      "wgmma.mma_async.sync.aligned.m64n256k16.f32.bf16.bf16 "
      "{%0,%1,%2,%3,%4,%5,%6,%7,%8,%9,%10,%11,%12,%13,%14,%15,%16,%17,%18,%19,%20,%21,%22,%23,%24,%25,%26,%27,%28,%29,%30,%31,"
      "%32,%33,%34,%35,%36,%37,%38,%39,%40,%41,%42,%43,%44,%45,%46,%47,%48,%49,%50,%51,%52,%53,%54,%55,%56,%57,%58,%59,%60,%61,%62,%63,"
      "%64,%65,%66,%67,%68,%69,%70,%71,%72,%73,%74,%75,%76,%77,%78,%79,%80,%81,%82,%83,%84,%85,%86,%87,%88,%89,%90,%91,%92,%93,%94,%95,"
      "%96,%97,%98,%99,%100,%101,%102,%103,%104,%105,%106,%107,%108,%109,%110,%111,%112,%113,%114,%115,%116,%117,%118,%119,%120,%121,%122,%123,%124,%125,%126,%127},"
      "%128, %129, p, 1, 1, 0, 1;}\n"
      : R32(0), R32(32), R32(64), R32(96)
      : "l"(ad), "l"(bd), "r"(acc));
}

__device__ __forceinline__ void ln16(const float* x, float* o) {
  float s = 0;
#pragma unroll
  for (int i = 0; i < 16; i++) s += x[i];
#pragma unroll
  for (int of = 16; of > 0; of >>= 1) s += __shfl_xor_sync(~0u, s, of);
  float mean = s * (1.0f / DM);
  float v = 0;
#pragma unroll
  for (int i = 0; i < 16; i++) { float dd = x[i] - mean; v += dd * dd; }
#pragma unroll
  for (int of = 16; of > 0; of >>= 1) v += __shfl_xor_sync(~0u, v, of);
  float mb = bf16r(mean);
  float vb = bf16r(v * (1.0f / DM));
  float den = bf16r(sqrtf(bf16r(vb + 1e-5f)));
#pragma unroll
  for (int i = 0; i < 16; i++) o[i] = bf16r(__fdiv_rn(bf16r(x[i] - mb), den));
}
__global__ void __launch_bounds__(256) k_pre(const bf16* __restrict__ x) {
  int t = threadIdx.x, lane = t & 31, w = t >> 5;
  int row = blockIdx.x * 8 + w;
  const uint4* src = reinterpret_cast<const uint4*>(x + (size_t)row * DM);
  uint4 a = src[lane], b = src[lane + 32];
  unsigned u[8] = {a.x, a.y, a.z, a.w, b.x, b.y, b.z, b.w};
  float f[16], o[16], o2[16];
#pragma unroll
  for (int i = 0; i < 8; i++) { f[2 * i] = bf_lo(u[i]); f[2 * i + 1] = bf_hi(u[i]); }
  ln16(f, o);
  ln16(o, o2);
  uint4* d1 = reinterpret_cast<uint4*>(g_xn + (size_t)row * DM);
  uint4* d2 = reinterpret_cast<uint4*>(g_y + (size_t)row * DM);
  d1[lane] = make_uint4(pack_bf16(o[0], o[1]), pack_bf16(o[2], o[3]), pack_bf16(o[4], o[5]), pack_bf16(o[6], o[7]));
  d1[lane + 32] = make_uint4(pack_bf16(o[8], o[9]), pack_bf16(o[10], o[11]), pack_bf16(o[12], o[13]), pack_bf16(o[14], o[15]));
  d2[lane] = make_uint4(pack_bf16(o2[0], o2[1]), pack_bf16(o2[2], o2[3]), pack_bf16(o2[4], o2[5]), pack_bf16(o2[6], o2[7]));
  d2[lane + 32] = make_uint4(pack_bf16(o2[8], o2[9]), pack_bf16(o2[10], o2[11]), pack_bf16(o2[12], o2[13]), pack_bf16(o2[14], o2[15]));
  int gt = blockIdx.x * 256 + t;
  uint4 z = make_uint4(0, 0, 0, 0);
  reinterpret_cast<uint4*>(g_part)[gt] = z;
  if (gt < NSEG * 2048 / 4) reinterpret_cast<uint4*>(g_pub)[gt] = z;
  if (gt < (int)(sizeof(Flags) / 4)) reinterpret_cast<unsigned*>(&g_flags)[gt] = 0;
}

struct Maps { CUtensorMap xn, y, h1, o, qkv_st, qkv_ld, g, wq, wk, wv, wo, w1, w2; };

#define NSTAGE 3
#define STAGE_BYTES 49152
#define B_STG (NSTAGE * STAGE_BYTES)
#define R_WO 0
#define R_T1 65536
#define R_T2 131072
#define R_RING 65536
#define RING_N 4
#define RING_BYTES 12288
#define R_MEM 196608
#define R_QS (R_MEM + 8448)
#define R_KS (R_QS + 1152)
#define R_OS (R_KS + 1152)
#define R_SOWN (R_OS + 2176)
#define R_SPEER (R_SOWN + 1280)
#define R_VM (R_SPEER + 1280)
#define R_VRED (R_VM + 2048)
#define R_RED (R_VRED + 6144)
#define SM_BAR (R_RED + 2048)
#define SMEM_TOTAL (SM_BAR + 256 + 1024)
#define MB_FULL 0
#define MB_EMPTY 8
#define MB_STGF 16
#define MB_STGE 17
#define MB_W0 18
#define MB_W1 19
#define MB_WO 20
#define MB_S 21
#define MB_V 22
#define MB_KVR 23
#define MB_KVF 24
#define SM_MISC (SM_BAR + 208)

#define N_KV 512
#define I_Q 512
#define I_M1 768
#define I_M2 880
#define I_POST 912
#define N_ITEMS 1296
enum { T_QKV = 0, T_M1 = 1, T_M2 = 2, T_ATT = 3, T_OUT = 4 };
struct Item { int type, b, c, ks; };
__device__ __forceinline__ Item decode_item(int i) {
  Item it; it.ks = 0;
  if (i < N_KV) { it.type = T_QKV; it.b = i >> 5; it.c = 16 + (i & 31); }
  else if (i < I_M1) { it.type = T_QKV; it.b = (i - I_Q) >> 4; it.c = (i - I_Q) & 15; }
  else if (i < I_M2) { it.type = T_M1; it.b = (i - I_M1) / 7; it.c = (i - I_M1) % 7; }
  else if (i < I_POST) { it.type = T_M2; it.b = (i - I_M2) >> 1; it.c = (i - I_M2) & 1; }
  else {
    int x = i - I_POST;
    if (x < 16) { it.type = T_ATT; it.b = 0; it.c = x; }
    else {
      x -= 16; int p = 1 + x / 24, r = x % 24;
      if (p < 16 && r < 16) { it.type = T_ATT; it.b = p; it.c = r; }
      else { if (p < 16) r -= 16; it.type = T_OUT; it.b = p - 1; it.c = r & 1; it.ks = r >> 1; }
    }
  }
  return it;
}
__device__ __forceinline__ int item_nkb(int type) { return type == T_M2 ? 28 : (type == T_OUT ? 16 : (type == T_ATT ? 4 : 8)); }

__device__ __forceinline__ void st_async_b64(unsigned raddr, unsigned lo, unsigned hi, unsigned rmb) {
  asm volatile("st.async.weak.shared::cluster.mbarrier::complete_tx::bytes.v2.b32 [%0], {%1,%2}, [%3];" ::"r"(raddr), "r"(lo), "r"(hi), "r"(rmb) : "memory");
}
__device__ __forceinline__ unsigned mapa(unsigned a, unsigned rank) {
  unsigned r; asm volatile("mapa.shared::cluster.u32 %0, %1, %2;" : "=r"(r) : "r"(a), "r"(rank)); return r;
}
__device__ __forceinline__ void sts64(unsigned a, unsigned x, unsigned y) { asm volatile("st.shared.v2.b32 [%0], {%1,%2};" ::"r"(a), "r"(x), "r"(y) : "memory"); }
__device__ __forceinline__ void sts128(unsigned a, uint4 v) { asm volatile("st.shared.v4.b32 [%0], {%1,%2,%3,%4};" ::"r"(a), "r"(v.x), "r"(v.y), "r"(v.z), "r"(v.w) : "memory"); }
__device__ __forceinline__ uint2 lds64(unsigned a) { uint2 v; asm volatile("ld.shared.v2.b32 {%0,%1}, [%2];" : "=r"(v.x), "=r"(v.y) : "r"(a) : "memory"); return v; }
__device__ __forceinline__ uint4 lds128(unsigned a) { uint4 v; asm volatile("ld.shared.v4.b32 {%0,%1,%2,%3}, [%4];" : "=r"(v.x), "=r"(v.y), "=r"(v.z), "=r"(v.w) : "r"(a) : "memory"); return v; }
__device__ __forceinline__ float lds32f(unsigned a) { float v; asm volatile("ld.shared.f32 %0, [%1];" : "=f"(v) : "r"(a) : "memory"); return v; }
#define spin_check(it) TRAP_IF(++it)
#define D_RED 300
#define D_PUB 400
#define DELAY(n) do { unsigned c0_, c1_; asm volatile("mov.u32 %0, %%clock;" : "=r"(c0_)); do { asm volatile("mov.u32 %0, %%clock;" : "=r"(c1_)); } while (c1_ - c0_ < (n)); } while (0)
#define SCALE_QK 0.08838834764831845f

__device__ __forceinline__ void rec_worker(const Maps& maps, unsigned sb, const bf16* __restrict__ mem0) {
  const int c = blockIdx.x, h = c >> 1, j = c & 1;
  const int t = opaque_tid(), lane = t & 31, w = t >> 5, g = lane >> 2, tq = lane & 3;
  const int m = lane >> 3, r8 = lane & 7, kh = w >> 2, et = w & 3;
  const unsigned bar = sb + SM_BAR;
  unsigned wq[16][4], wk[16][4], wo[8][4];
  const unsigned woff = (kh * 4) * 8192 + ((m >> 1) * 8 + r8) * 128 + (((et * 2 + (m & 1)) ^ r8) << 4);
  mbar_wait(bar + 8 * MB_W0, 0);
#pragma unroll
  for (int i = 0; i < 16; i++) {
    ldsm_x4_t(wq[i], sb + R_WO + woff + (i >> 2) * 8192 + (i & 3) * 2048);
    ldsm_x4_t(wk[i], sb + R_T1 + woff + (i >> 2) * 8192 + (i & 3) * 2048);
  }
  bar_sync(2, 288);
  if (t == 0) {
    fence_proxy_async_smem();
    mbar_expect_tx(bar + 8 * MB_WO, 65536);
    for (int kb = 0; kb < 2; kb++)
      for (int cb = 0; cb < 4; cb++) tma_load_2d(sb + R_WO + (kb * 4 + cb) * 8192, &maps.wo, j * 256 + cb * 64, h * 128 + kb * 64, bar + 8 * MB_WO);
  }
  mbar_wait(bar + 8 * MB_W1, 0);
  const unsigned pV = sb + R_T2 + woff;
  const unsigned peer = j ^ 1;
#define KEEP(x) x = __shfl_sync(~0u, x, lane)
  unsigned pA = sb + R_MEM + r8 * 1040 + m * 16 + kh * 512;
  unsigned pW0 = sb + R_WO + (w >> 1) * 8192 + ((m >> 1) * 8 + r8) * 128 + ((((w & 1) * 4 + (m & 1)) ^ r8) << 4);
  unsigned pW1 = pW0 ^ 32;
  unsigned pVk = pV;
  unsigned aMem = sb + R_MEM + (t & 7) * 1040 + (t >> 3) * 16;
  unsigned aX = sb + R_VRED + et * 512 + lane * 16;
  unsigned aQKst = sb + (kh ? R_KS : R_QS) + r8 * 144 + (et * 16 + (m & 1) * 8) * 2;
  unsigned aL8 = sb + lane * 8;
  unsigned aSl = mapa(sb + R_SOWN + w * 256 + lane * 8, j), aSr = mapa(sb + R_SPEER + w * 256 + lane * 8, peer);
  unsigned aVl = mapa(sb + R_VM + (j * 4 + et) * 256 + lane * 8, j), aVr = mapa(sb + R_VM + (j * 4 + et) * 256 + lane * 8, peer);
  const unsigned mbSl = mapa(bar + 8 * MB_S, j), mbSr = mapa(bar + 8 * MB_S, peer), mbVl = mbSl + 8, mbVr = mbSr + 8;
  unsigned aQ = sb + R_QS + r8 * 144 + m * 16;
  unsigned oKx = (et * 8 + r8) * 128 + ((m ^ r8) << 4);
  unsigned oVx = 4096 + (et >> 1) * 4096 + ((m >> 1) * 8 + r8) * 128 + ((((et & 1) * 4 + (m & 1)) ^ r8) << 4);
  unsigned aOst = sb + R_OS + r8 * 272 + (et * 32 + m * 8) * 2;
  unsigned aOld = sb + R_OS + r8 * 272 + m * 16;
  unsigned aVm = sb + R_VM + et * 512 + lane * 8;
  unsigned aRst = sb + R_RED + w * 256 + lane * 16;
  unsigned aRld = sb + R_RED + tq * 64 + g * 4;
  unsigned oPd = ((32 * j + 4 * w) * NH + h) * 256 + g * 32 + tq * 8;
  unsigned oPs = (c * NH + 4 * w) * 256 + lane * 16;
  unsigned oPub = t * 16;
  KEEP(pA); KEEP(pW0); KEEP(pW1); KEEP(pVk); KEEP(aX); KEEP(aQKst); KEEP(aL8); KEEP(aSl); KEEP(aSr); KEEP(aVl); KEEP(aVr); KEEP(aQ); KEEP(oKx); KEEP(oVx);
  KEEP(aOst); KEEP(aOld); KEEP(aVm); KEEP(oPd);
  mbar_wait(bar + 8 * MB_WO, 0);
#pragma unroll
  for (int ks = 0; ks < 4; ks++) { ldsm_x4_t(wo[2 * ks], pW0 + ks * 2048); ldsm_x4_t(wo[2 * ks + 1], pW1 + ks * 2048); }
#pragma unroll
  for (int u = 0; u < 2; u++) {
    int i = t + 256 * u;
    uint4 v = __ldg(reinterpret_cast<const uint4*>(mem0) + i);
    sts128(sb + R_MEM + (i >> 6) * 1040 + (i & 63) * 16, v);
  }
  if (t == 0) { mbar_expect_tx(bar + 8 * MB_S, 2560); mbar_expect_tx(bar + 8 * MB_V, 2048); }

#pragma unroll 1
  for (int s = 0;; s++) {
    const unsigned par = s & 1;
    const unsigned slot = s & (RING_N - 1), rpar = (s / RING_N) & 1;
    const unsigned ring = sb + R_RING + slot * RING_BYTES;
    RSTAMP(1);
    bar_sync(1, 256);
    RSTAMP(2);
    float aq[4] = {0, 0, 0, 0}, ak[4] = {0, 0, 0, 0}, av[4] = {0, 0, 0, 0};
#pragma unroll
    for (int i = 0; i < 8; i++) {
      unsigned b[4], f[4], f0[4];
      ldsm_x4(b, pA + i * 64);
      ldsm_x4_t(f0, pVk + (i >> 1) * 8192 + (i & 1) * 4096);
      ldsm_x4_t(f, pVk + (i >> 1) * 8192 + (i & 1) * 4096 + 2048);
      mma16816(aq, wq[2 * i], b[0], b[1]); mma16816(ak, wk[2 * i], b[0], b[1]); mma16816(av, f0, b[0], b[1]);
      mma16816(aq, wq[2 * i + 1], b[2], b[3]); mma16816(ak, wk[2 * i + 1], b[2], b[3]); mma16816(av, f, b[2], b[3]);
    }
    RSTAMP(3);
#define STSF4(a, v) asm volatile("st.shared.v4.f32 [%0], {%1,%2,%3,%4};" ::"r"(a), "f"(v[0]), "f"(v[1]), "f"(v[2]), "f"(v[3]) : "memory")
    unsigned f[8][4];
#define NPRE 2
#define WO_PREFETCH() do { _Pragma("unroll") for (int i = 0; i < NPRE; i++) { ldsm_x4_t(f[2 * i], pW0 + 32768 + i * 2048); ldsm_x4_t(f[2 * i + 1], pW1 + 32768 + i * 2048); } } while (0)
    if (kh) {
      STSF4(aX, aq);
      bar_sync(4 + et, 64);
      uint4 o = lds128(aX + 2048), o2 = lds128(aX + 4096);
      stsm_x2_t(aQKst, pack_bf16(ak[0] + __uint_as_float(o.x), ak[1] + __uint_as_float(o.y)), pack_bf16(ak[2] + __uint_as_float(o.z), ak[3] + __uint_as_float(o.w)));
      bar_arrive(1, 256);
      unsigned x = pack_bf16(av[0] + __uint_as_float(o2.x), av[1] + __uint_as_float(o2.y)), y = pack_bf16(av[2] + __uint_as_float(o2.z), av[3] + __uint_as_float(o2.w));
      st_async_b64(aVr, x, y, mbVr);
      st_async_b64(aVl, x, y, mbVl);
      mbar_wait(bar + 8 * (MB_FULL + slot), rpar);
      unsigned vx[4][4];
      ldsm_x4_t(vx[0], ring + oVx); ldsm_x4_t(vx[1], ring + oVx + 2048); ldsm_x4_t(vx[2], ring + (oVx ^ 32)); ldsm_x4_t(vx[3], ring + (oVx ^ 32) + 2048);
      mbar_wait(bar + 8 * MB_S, par);
      float sc[10];
#pragma unroll
      for (int i = 0; i < 5; i++) {
        uint2 o = lds64(aL8 + R_SOWN + i * 256), p = lds64(aL8 + R_SPEER + i * 256);
        sc[2 * i] = __uint_as_float(o.x) + __uint_as_float(p.x); sc[2 * i + 1] = __uint_as_float(o.y) + __uint_as_float(p.y);
      }
      mbar_wait(bar + 8 * MB_V, par);
      uint2 vm0 = lds64(aVm), vm1 = lds64(aVm + 256);
      float mx = fmaxf(fmaxf(fmaxf(sc[0], sc[1]), fmaxf(sc[2], sc[3])), fmaxf(fmaxf(fmaxf(sc[4], sc[5]), fmaxf(sc[6], sc[7])), fmaxf(sc[8], sc[9])));
      mx = fmaxf(mx, __shfl_xor_sync(~0u, mx, 1)); mx = fmaxf(mx, __shfl_xor_sync(~0u, mx, 2));
      const float nm = -mx * (SCALE_QK * LOG2E);
#pragma unroll
      for (int i = 0; i < 10; i++) sc[i] = ex2f(fmaf(sc[i], SCALE_QK * LOG2E, nm));
      float sum = (((sc[0] + sc[1]) + (sc[2] + sc[3])) + ((sc[4] + sc[5]) + (sc[6] + sc[7]))) + (sc[8] + sc[9]);
      sum += __shfl_xor_sync(~0u, sum, 1); sum += __shfl_xor_sync(~0u, sum, 2);
      float inv; asm("rcp.approx.ftz.f32 %0, %1;" : "=f"(inv) : "f"(sum));
      unsigned p[5];
#pragma unroll
      for (int i = 0; i < 5; i++) p[i] = pack_bf16(sc[2 * i] * inv, sc[2 * i + 1] * inv);
      float o0[4] = {0, 0, 0, 0}, o1[4] = {0, 0, 0, 0}, o3[4] = {0, 0, 0, 0}, o4[4] = {0, 0, 0, 0};
      mma16816(o0, vx[0], p[0], p[1]); mma16816(o3, vx[2], p[0], p[1]); mma16816(o1, vx[1], p[2], p[3]); mma16816(o4, vx[3], p[2], p[3]);
      mma1688(o0, vm0.x, vm0.y, p[4]); mma1688(o3, vm1.x, vm1.y, p[4]);
      if (s == NSEG - 1) { if (t == 128) mbar_arrive(bar + 8 * MB_KVR); break; }
      asm volatile("stmatrix.sync.aligned.m8n8.x4.trans.shared.b16 [%0], {%1,%2,%3,%4};" ::"r"(aOst), "r"(pack_bf16(o0[0] + o1[0], o0[1] + o1[1])), "r"(pack_bf16(o0[2] + o1[2], o0[3] + o1[3])),
                   "r"(pack_bf16(o3[0] + o4[0], o3[1] + o4[1])), "r"(pack_bf16(o3[2] + o4[2], o3[3] + o4[3])) : "memory");
      bar_sync(1, 256);
      WO_PREFETCH();
    } else {
      STSF4(aX + 2048, ak); STSF4(aX + 4096, av);
      unsigned kb[8];
      mbar_wait(bar + 8 * (MB_FULL + slot), rpar);
      ldsm_x4(kb, ring + oKx); ldsm_x4(kb + 4, ring + (oKx ^ 64));
      bar_sync(4 + et, 64);
      uint4 o = lds128(aX);
      stsm_x2_t(aQKst, pack_bf16(aq[0] + __uint_as_float(o.x), aq[1] + __uint_as_float(o.y)), pack_bf16(aq[2] + __uint_as_float(o.z), aq[3] + __uint_as_float(o.w)));
      RSTAMP(4);
      bar_sync(1, 256);
      RSTAMP(5);
      unsigned qa[8], km[8];
      ldsm_x4(qa, aQ); ldsm_x4(qa + 4, aQ + 64);
      if (w == 3) { ldsm_x4(km, aQ + 1152); ldsm_x4(km + 4, aQ + 1152 + 64); }
      float s0[4] = {0, 0, 0, 0}, s1[4] = {0, 0, 0, 0};
      unsigned af[4][4];
#pragma unroll
      for (int i = 0; i < 4; i++) { af[i][0] = qa[2 * i]; af[i][1] = 0; af[i][2] = qa[2 * i + 1]; af[i][3] = 0; }
      mma16816(s0, af[0], kb[0], kb[1]); mma16816(s1, af[1], kb[2], kb[3]);
      mma16816(s0, af[2], kb[4], kb[5]); mma16816(s1, af[3], kb[6], kb[7]);
      if (w == 3) {
        float m0[4] = {0, 0, 0, 0}, m1[4] = {0, 0, 0, 0};
        mma16816(m0, af[0], km[0], km[1]); mma16816(m1, af[1], km[2], km[3]);
        mma16816(m0, af[2], km[4], km[5]); mma16816(m1, af[3], km[6], km[7]);
        unsigned x = __float_as_uint(m0[0] + m1[0]), y = __float_as_uint(m0[1] + m1[1]);
        st_async_b64(aSr + 256, x, y, mbSr); st_async_b64(aSl + 256, x, y, mbSl);
      }
      unsigned x = __float_as_uint(s0[0] + s1[0]), y = __float_as_uint(s0[1] + s1[1]);
      st_async_b64(aSr, x, y, mbSr); st_async_b64(aSl, x, y, mbSl);
      RSTAMP(6);
      if (s == NSEG - 1) break;
      WO_PREFETCH();
      RSTAMP(7); RSTAMP(8); RSTAMP(9); RSTAMP(10);
      bar_sync(1, 256);
    }
    RSTAMP(11);
    float d0[4] = {0, 0, 0, 0}, d1[4] = {0, 0, 0, 0}, e0[4] = {0, 0, 0, 0}, e1[4] = {0, 0, 0, 0};
    unsigned ob[4][4];
#pragma unroll
    for (int k2 = 0; k2 < 4; k2++) ldsm_x4(ob[k2], aOld + k2 * 64);
#pragma unroll
    for (int i = NPRE; i < 4; i++) { ldsm_x4_t(f[2 * i], pW0 + 32768 + i * 2048); ldsm_x4_t(f[2 * i + 1], pW1 + 32768 + i * 2048); }
    mma16816(d0, wo[0], ob[0][0], ob[0][1]); mma16816(d1, wo[1], ob[0][0], ob[0][1]);
    mma16816(e0, wo[2], ob[0][2], ob[0][3]); mma16816(e1, wo[3], ob[0][2], ob[0][3]);
    mma16816(d0, wo[4], ob[1][0], ob[1][1]); mma16816(d1, wo[5], ob[1][0], ob[1][1]);
    mma16816(e0, wo[6], ob[1][2], ob[1][3]); mma16816(e1, wo[7], ob[1][2], ob[1][3]);
    mma16816(d0, f[0], ob[2][0], ob[2][1]); mma16816(d1, f[1], ob[2][0], ob[2][1]);
    mma16816(e0, f[2], ob[2][2], ob[2][3]); mma16816(e1, f[3], ob[2][2], ob[2][3]);
    mma16816(d0, f[4], ob[3][0], ob[3][1]); mma16816(d1, f[5], ob[3][0], ob[3][1]);
    mma16816(e0, f[6], ob[3][2], ob[3][3]); mma16816(e1, f[7], ob[3][2], ob[3][3]);
    const unsigned tag = ((s >> 1) & 1) ^ 1;
    const char* pbase = reinterpret_cast<const char*>(g_part) + par * (NREC * NH * 256);
    {
      const char* dst = pbase + oPd;
#define PST(ptr, x, y) asm volatile("st.relaxed.gpu.global.v2.u32 [%0], {%1,%2};" ::"l"(ptr), "r"((__float_as_uint(x) & ~1u) | tag), "r"((__float_as_uint(y) & ~1u) | tag) : "memory")
      PST(dst, d0[0] + e0[0], d0[1] + e0[1]); PST(dst + NH * 256, d0[2] + e0[2], d0[3] + e0[3]);
      PST(dst + 2 * NH * 256, d1[0] + e1[0], d1[1] + e1[1]); PST(dst + 3 * NH * 256, d1[2] + e1[2], d1[3] + e1[3]);
    }
    RSTAMP(12);
    if (t == 128) {
      mbar_arrive(bar + 8 * (MB_EMPTY + slot)); mbar_arrive(bar + 8 * MB_KVR);
      mbar_expect_tx(bar + 8 * MB_S, 2560); mbar_expect_tx(bar + 8 * MB_V, 2048);
    }
    {
      const char* src = pbase + oPs;
      uint4 a, b; unsigned it = 0;
      DELAY(D_RED);
      while (true) {
        a = ldv4_relaxed(src); b = ldv4_relaxed(src + 512);
        unsigned z = ((a.x ^ tag) | (a.y ^ tag)) | ((a.z ^ tag) | (a.w ^ tag)) | ((b.x ^ tag) | (b.y ^ tag)) | ((b.z ^ tag) | (b.w ^ tag));
        if (!(z & 1u)) break;
        spin_check(it);
      }
      RSTAMP(13);
      float r0 = __uint_as_float(a.x) + __uint_as_float(b.x), r1 = __uint_as_float(a.y) + __uint_as_float(b.y);
      float r2 = __uint_as_float(a.z) + __uint_as_float(b.z), r3 = __uint_as_float(a.w) + __uint_as_float(b.w);
      __syncwarp();
      r0 += __shfl_xor_sync(~0u, r0, 16); r1 += __shfl_xor_sync(~0u, r1, 16); r2 += __shfl_xor_sync(~0u, r2, 16); r3 += __shfl_xor_sync(~0u, r3, 16);
      if (lane < 16) asm volatile("st.shared.v4.f32 [%0], {%1,%2,%3,%4};" ::"r"(aRst), "f"(r0), "f"(r1), "f"(r2), "f"(r3) : "memory");
    }
    const char* pub = reinterpret_cast<const char*>(g_pub) + (s + 1) * 8192;
    bar_sync(3, 256);
    if (w == 0) {
      RSTAMP(14);
      float x[8], y[8];
#pragma unroll
      for (int i = 0; i < 8; i++) { x[i] = lds32f(aRld + i * 256); y[i] = lds32f(aRld + i * 256 + 32); }
      unsigned u = pack_bf16(((x[0] + x[1]) + (x[2] + x[3])) + ((x[4] + x[5]) + (x[6] + x[7])), ((y[0] + y[1]) + (y[2] + y[3])) + ((y[4] + y[5]) + (y[6] + y[7])));
      if (u == 0) u = 0x80000000u;
      asm volatile("st.relaxed.gpu.global.u32 [%0], %1;" ::"l"(pub + c * 128 + (oPub >> 2)), "r"(u) : "memory");
      RSTAMP(15);
    }
    mbar_wait(bar + 8 * MB_KVF, par);
    {
      const char* src = pub + oPub;
      uint4 a, b; unsigned it = 0;
      DELAY(D_PUB);
      while (true) {
        a = ldv4_relaxed(src); b = ldv4_relaxed(src + 4096);
        unsigned z = min(min(min(a.x, a.y), min(a.z, a.w)), min(min(b.x, b.y), min(b.z, b.w)));
        if (z) break;
        spin_check(it);
      }
      sts128(aMem, a); sts128(aMem + 512, b);
    }
  }
}

__device__ __forceinline__ void rec_ring(const Maps& maps, unsigned sb) {
  const int c = blockIdx.x, h = c >> 1, j = c & 1;
  const unsigned bar = sb + SM_BAR;
  const int lane = threadIdx.x & 31;
  if (lane == 0) {
    mbar_expect_tx(bar + 8 * MB_W0, 131072);
    for (int kb = 0; kb < 8; kb++) tma_load_2d(sb + R_WO + kb * 8192, &maps.wq, h * 128 + j * 64, kb * 64, bar + 8 * MB_W0);
    for (int kb = 0; kb < 8; kb++) tma_load_2d(sb + R_T1 + kb * 8192, &maps.wk, h * 128 + j * 64, kb * 64, bar + 8 * MB_W0);
    mbar_expect_tx(bar + 8 * MB_W1, 65536);
    for (int kb = 0; kb < 8; kb++) tma_load_2d(sb + R_T2 + kb * 8192, &maps.wv, h * 128 + j * 64, kb * 64, bar + 8 * MB_W1);
  }
  __syncwarp();
  bar_sync(2, 288);
  if (lane == 0) {
    fence_proxy_async_smem();
    for (int s = 0; s < NSEG; s++) {
      unsigned slot = s & (RING_N - 1);
      if ((s & 3) == 0 && !DBGMODE) {
        wait_flag_ge(&g_flags.qkv[(s >> 2) * 48 + 16 + (h >> 1)], 1);
        wait_flag_ge(&g_flags.qkv[(s >> 2) * 48 + 32 + (h >> 1)], 1);
        fence_proxy_async();
      }
      if (s >= RING_N) mbar_wait_sleep(bar + 8 * (MB_EMPTY + slot), ((s / RING_N) - 1) & 1);
      unsigned dst = sb + R_RING + slot * RING_BYTES, mb = bar + 8 * (MB_FULL + slot);
      mbar_expect_tx(mb, RING_BYTES);
      tma_load_2d(dst, &maps.qkv_ld, HD + h * 128 + j * 64, s * SEG, mb);
      tma_load_2d(dst + 4096, &maps.qkv_ld, 2 * HD + h * 128, s * SEG, mb);
      tma_load_2d(dst + 8192, &maps.qkv_ld, 2 * HD + h * 128 + 64, s * SEG, mb);
    }
  }
}
__device__ __forceinline__ void rec_copy(unsigned sb) {
  const int c = blockIdx.x, h = c >> 1, j = c & 1;
  const unsigned bar = sb + SM_BAR;
  const int lane = threadIdx.x & 31;
  for (int s = 0; s < NSEG; s++) {
    mbar_wait_sleep(bar + 8 * MB_KVR, s & 1);
    uint4 k0 = lds128(sb + R_KS + (lane >> 3) * 144 + (lane & 7) * 16), k1 = lds128(sb + R_KS + (4 + (lane >> 3)) * 144 + (lane & 7) * 16);
    uint2 v[4];
#pragma unroll
    for (int i = 0; i < 4; i++) v[i] = lds64(sb + R_VM + (j * 4 + i) * 256 + lane * 8);
    __syncwarp();
    if (lane == 0) mbar_arrive(bar + 8 * MB_KVF);
    bf16* kd = g_km + ((size_t)(s * NH + h) * NMEM) * DH + j * 64;
    *reinterpret_cast<uint4*>(kd + (lane >> 3) * DH + (lane & 7) * 8) = k0;
    *reinterpret_cast<uint4*>(kd + (4 + (lane >> 3)) * DH + (lane & 7) * 8) = k1;
    unsigned* vd = reinterpret_cast<unsigned*>(g_vmt) + ((size_t)(s * NH + h) * DH + j * 64) * 4;
#pragma unroll
    for (int i = 0; i < 4; i++) { vd[(i * 16) * 4 + lane] = v[i].x; vd[(i * 16 + 8) * 4 + lane] = v[i].y; }
    __threadfence();
    __syncwarp();
    if (lane == 0) st_release(&g_flags.rec[c], s + 1);
  }
}

__device__ __forceinline__ void bulk_producer(const Maps& maps, unsigned sb, int* misc) {
  const unsigned bar = sb + SM_BAR;
  unsigned st = 0, ph = 0, seq = 0;
  while (true) {
    int idx = (int)atomicAdd(&g_flags.ctr, 1u);
    if (idx >= N_ITEMS) {
      mbar_wait(bar + 8 * (MB_EMPTY + st), ph ^ 1);
      misc[seq & 3] = -1;
      mbar_arrive(bar + 8 * (MB_FULL + st));
      break;
    }
    ISTAMP(idx, 0);
    Item it = decode_item(idx);
    const CUtensorMap *ma, *mb_; int ka = 0, kbr = 0, nb0 = it.c * 256;
    if (it.type == T_QKV) { ma = &maps.xn; mb_ = it.c < 16 ? &maps.wq : (it.c < 32 ? &maps.wk : &maps.wv); nb0 = (it.c & 15) * 256; }
    else if (it.type == T_M1) { ma = &maps.y; mb_ = &maps.w1; }
    else if (it.type == T_M2) { ma = &maps.h1; mb_ = &maps.w2; wait_flag_ge(&g_flags.h1[it.b], 7); }
    else if (it.type == T_OUT) { ma = &maps.o; mb_ = &maps.wo; ka = kbr = it.ks * 1024; wait_flag_ge(&g_flags.o[it.b * 4 + it.ks], 4); wait_flag_ge(&g_flags.g[it.b], 2); }
    else {
      ma = mb_ = &maps.qkv_ld;
      wait_flag_ge(&g_flags.qkv[it.b * 48 + it.c], 1); wait_flag_ge(&g_flags.qkv[it.b * 48 + 16 + it.c], 1); wait_flag_ge(&g_flags.qkv[it.b * 48 + 32 + it.c], 1);
      for (int i = 0; i < 4; i++) wait_flag_ge(&g_flags.rec[it.c * 4 + i], it.b * 4 + 4);
    }
    fence_proxy_async();
    ISTAMP(idx, 1);
    const int nkb = item_nkb(it.type);
    for (int kb = 0; kb < nkb; kb++) {
      mbar_wait(bar + 8 * (MB_EMPTY + st), ph ^ 1);
      if (kb == 0) { misc[seq & 3] = idx; seq++; }
      unsigned dst = sb + st * STAGE_BYTES, mb = bar + 8 * (MB_FULL + st);
      mbar_expect_tx(mb, STAGE_BYTES);
      if (it.type == T_ATT) {
        int head = it.c * 2 + (kb >> 1), row = it.b * 128 + (kb & 1) * 64;
        for (int i = 0; i < 12; i++) tma_load_2d(dst + i * 4096, ma, (i >> 2) * HD + head * 128 + (i & 1) * 64, row + ((i >> 1) & 1) * 32, mb);
      } else {
        tma_load_2d(dst, ma, ka + kb * 64, it.b * 128, mb);
        for (int i = 0; i < 4; i++) tma_load_2d(dst + 16384 + i * 8192, mb_, nb0 + i * 64, kbr + kb * 64, mb);
      }
      if (++st == NSTAGE) { st = 0; ph ^= 1; }
    }
  }
}
__device__ __forceinline__ void bulk_store(const Maps& maps, unsigned sb, volatile int* misc) {
  const unsigned bar = sb + SM_BAR;
  unsigned ph = 0;
  while (true) {
    mbar_wait(bar + 8 * MB_STGF, ph); ph ^= 1;
    int idx = misc[4];
    if (idx < 0) break;
    Item it = decode_item(idx);
    const CUtensorMap* mp = it.type == T_QKV ? &maps.qkv_st : (it.type == T_M1 ? &maps.h1 : (it.type == T_M2 ? &maps.g : &maps.o));
    unsigned* flag = it.type == T_QKV ? &g_flags.qkv[it.b * 48 + it.c] : (it.type == T_M1 ? &g_flags.h1[it.b] : (it.type == T_M2 ? &g_flags.g[it.b] : &g_flags.o[it.b * 4 + (it.c >> 2)]));
    for (int i = 0; i < 4; i++) tma_store_2d(mp, sb + B_STG + i * 16384, it.c * 256 + i * 64, it.b * 128);
    asm volatile("cp.async.bulk.commit_group;" ::: "memory");
    asm volatile("cp.async.bulk.wait_group.read 0;" ::: "memory");
    mbar_arrive(bar + 8 * MB_STGE);
    asm volatile("cp.async.bulk.wait_group 0;" ::: "memory");
    fence_proxy_async();
    __threadfence();
    red_release_add(flag, 1);
    ISTAMP(idx, 3);
  }
}
__device__ __forceinline__ float gelu_t(float x) {
  float u = 0.7978845608028654f * (x + 0.044715f * x * x * x);
  return __fdividef(x, 1.0f + __expf(-2.0f * u));
}
__device__ __forceinline__ float silu_f(float x) { return __fdividef(x, 1.0f + __expf(-x)); }

__device__ __forceinline__ void bulk_att_stage(unsigned sa, unsigned stg, int b, int hp, int kb, int w, int lane) {
  const int g = lane >> 2, tq = lane & 3, m = lane >> 3, r8 = lane & 7;
  const int seg = w >> 2, mt = (w >> 1) & 1, eh = w & 1;
  const int head = hp * 2 + (kb >> 1), sg = b * 4 + (kb & 1) * 2 + seg;
  const unsigned* kmp = reinterpret_cast<const unsigned*>(g_km + ((size_t)(sg * NH + head) * NMEM + g) * DH) + tq;
  const unsigned* vmp = reinterpret_cast<const unsigned*>(g_vmt) + ((size_t)(sg * NH + head) * DH + eh * 64) * 4 + lane;
  unsigned km[16], vm[8];
#pragma unroll
  for (int i = 0; i < 16; i++) km[i] = __ldcg(kmp + i * 4);
#pragma unroll
  for (int i = 0; i < 8; i++) vm[i] = __ldcg(vmp + i * 32);
  float s[5][4];
#pragma unroll
  for (int i = 0; i < 5; i++) { s[i][0] = s[i][1] = s[i][2] = s[i][3] = 0; }
  const unsigned qb = sa + (0 * 2 + seg) * 8192, kbs = sa + (1 * 2 + seg) * 8192, vb = sa + (2 * 2 + seg) * 8192 + eh * 4096;
  unsigned qa[8][4];
#pragma unroll
  for (int ks = 0; ks < 8; ks++) {
    int row = mt * 16 + (m & 1) * 8 + r8;
    ldsm_x4(qa[ks], qb + (ks >> 2) * 4096 + row * 128 + ((((ks & 3) * 2 + (m >> 1)) ^ r8) << 4));
    unsigned kf[4];
    int krow = (m >> 1) * 8 + r8;
    unsigned ka = kbs + (ks >> 2) * 4096 + krow * 128 + ((((ks & 3) * 2 + (m & 1)) ^ r8) << 4);
    ldsm_x4(kf, ka);
    mma16816(s[0], qa[ks], kf[0], kf[1]); mma16816(s[1], qa[ks], kf[2], kf[3]);
    if (mt) { ldsm_x4(kf, ka + 2048); mma16816(s[2], qa[ks], kf[0], kf[1]); mma16816(s[3], qa[ks], kf[2], kf[3]); }
  }
#pragma unroll
  for (int ks = 0; ks < 8; ks++) mma16816(s[4], qa[ks], km[2 * ks], km[2 * ks + 1]);
  float mx0 = -INFINITY, mx1 = -INFINITY;
  const int t0 = mt * 16 + g, t1 = t0 + 8;
#pragma unroll
  for (int i = 0; i < 5; i++) {
#pragma unroll
    for (int e = 0; e < 4; e++) {
      float v = bf16r(bf16r(s[i][e]) * SCALE_QK);
      if (i < 4) { int kj = i * 8 + 2 * tq + (e & 1); if (kj > (e < 2 ? t0 : t1)) v = -INFINITY; }
      s[i][e] = v;
      if (e < 2) mx0 = fmaxf(mx0, v); else mx1 = fmaxf(mx1, v);
    }
  }
  mx0 = fmaxf(mx0, __shfl_xor_sync(~0u, mx0, 1)); mx0 = fmaxf(mx0, __shfl_xor_sync(~0u, mx0, 2));
  mx1 = fmaxf(mx1, __shfl_xor_sync(~0u, mx1, 1)); mx1 = fmaxf(mx1, __shfl_xor_sync(~0u, mx1, 2));
  float sm0 = 0, sm1 = 0;
#pragma unroll
  for (int i = 0; i < 5; i++) {
    s[i][0] = __expf(s[i][0] - mx0); s[i][1] = __expf(s[i][1] - mx0); s[i][2] = __expf(s[i][2] - mx1); s[i][3] = __expf(s[i][3] - mx1);
    sm0 += s[i][0] + s[i][1]; sm1 += s[i][2] + s[i][3];
  }
  sm0 += __shfl_xor_sync(~0u, sm0, 1); sm0 += __shfl_xor_sync(~0u, sm0, 2);
  sm1 += __shfl_xor_sync(~0u, sm1, 1); sm1 += __shfl_xor_sync(~0u, sm1, 2);
  const float i0 = __fdividef(1.0f, sm0), i1 = __fdividef(1.0f, sm1);
  unsigned pa[2][4], pm0, pm1;
#pragma unroll
  for (int kk = 0; kk < 2; kk++) {
    pa[kk][0] = pack_bf16(s[2 * kk][0] * i0, s[2 * kk][1] * i0); pa[kk][1] = pack_bf16(s[2 * kk][2] * i1, s[2 * kk][3] * i1);
    pa[kk][2] = pack_bf16(s[2 * kk + 1][0] * i0, s[2 * kk + 1][1] * i0); pa[kk][3] = pack_bf16(s[2 * kk + 1][2] * i1, s[2 * kk + 1][3] * i1);
  }
  pm0 = pack_bf16(s[4][0] * i0, s[4][1] * i0); pm1 = pack_bf16(s[4][2] * i1, s[4][3] * i1);
  const int orow = (kb & 1) * 64 + seg * 32 + mt * 16 + (m & 1) * 8 + r8;
  const unsigned ob = stg + ((kb >> 1) * 2 + eh) * 16384 + orow * 128;
#pragma unroll
  for (int cp = 0; cp < 4; cp++) {
    float o0[4] = {0, 0, 0, 0}, o1[4] = {0, 0, 0, 0};
    mma1688(o0, pm0, pm1, vm[2 * cp]); mma1688(o1, pm0, pm1, vm[2 * cp + 1]);
    unsigned vf[4];
    int row = (m & 1) * 8 + r8;
    unsigned va = vb + row * 128 + (((cp * 2 + (m >> 1)) ^ r8) << 4);
    ldsm_x4_t(vf, va);
    mma16816(o0, pa[0], vf[0], vf[1]); mma16816(o1, pa[0], vf[2], vf[3]);
    if (mt) { ldsm_x4_t(vf, va + 2048); mma16816(o0, pa[1], vf[0], vf[1]); mma16816(o1, pa[1], vf[2], vf[3]); }
    stsm_x4(ob + (((cp * 2 + (m >> 1)) ^ r8) << 4), pack_bf16(o0[0], o0[1]), pack_bf16(o0[2], o0[3]), pack_bf16(o1[0], o1[1]), pack_bf16(o1[2], o1[3]));
  }
}

__device__ __forceinline__ void bulk_worker(unsigned sb, volatile int* misc, const bf16* __restrict__ x, const bf16* __restrict__ b1, const bf16* __restrict__ b2, bf16* __restrict__ out) {
  const int t = threadIdx.x, lane = t & 31, w = t >> 5, wg = w >> 2, g = lane >> 2, tq = lane & 3, m = lane >> 3, r8 = lane & 7;
  const unsigned bar = sb + SM_BAR;
  unsigned st = 0, ph = 0, seq = 0, sph = 0;
  float d[128];
  while (true) {
    mbar_wait(bar + 8 * (MB_FULL + st), ph);
    const int idx = misc[seq & 3]; seq++;
    if (idx < 0 || idx >= N_ITEMS) break;
    if (t == 0) ISTAMP(idx, 2);
    const Item it = decode_item(idx);
    const int nkb = item_nkb(it.type);
    if (it.type == T_ATT) {
      mbar_wait(bar + 8 * MB_STGE, sph ^ 1);
      for (int kb = 0; kb < 4; kb++) {
        if (kb) mbar_wait(bar + 8 * (MB_FULL + st), ph);
        bulk_att_stage(sb + st * STAGE_BYTES, sb + B_STG, it.b, it.c, kb, w, lane);
        __syncwarp();
        if (lane == 0) mbar_arrive(bar + 8 * (MB_EMPTY + st));
        if (++st == NSTAGE) { st = 0; ph ^= 1; }
      }
      if (t == 0) misc[4] = idx;
      fence_proxy_async_smem();
      mbar_arrive(bar + 8 * MB_STGF); sph ^= 1;
      continue;
    }
    unsigned pst = 0;
    for (int kb = 0; kb < nkb; kb++) {
      if (kb) mbar_wait(bar + 8 * (MB_FULL + st), ph);
      unsigned sa = sb + st * STAGE_BYTES;
      uint64_t ad = mkdesc(sa + wg * 8192, 16, 1024), bd = mkdesc(sa + 16384, 8192, 1024);
      asm volatile("wgmma.fence.sync.aligned;" ::: "memory");
#pragma unroll
      for (int k = 0; k < 4; k++) wgmma_n256(d, ad + k * 2, bd + k * 128, (kb | k) != 0);
      asm volatile("wgmma.commit_group.sync.aligned;" ::: "memory");
      if (kb) {
        asm volatile("wgmma.wait_group.sync.aligned 1;" ::: "memory");
        if (lane == 0) mbar_arrive(bar + 8 * (MB_EMPTY + pst));
      }
      pst = st;
      if (++st == NSTAGE) { st = 0; ph ^= 1; }
    }
    asm volatile("wgmma.wait_group.sync.aligned 0;" ::: "memory");
    if (lane == 0) mbar_arrive(bar + 8 * (MB_EMPTY + pst));
    if (it.type == T_OUT) {
      const int row = it.b * 128 + w * 16 + g, col = it.c * 256 + 2 * tq;
      float* pp = g_opart + ((size_t)it.ks * S_TOK + row) * DM + col;
#pragma unroll
      for (int i = 0; i < 32; i++) {
        __stcg(reinterpret_cast<float2*>(pp + i * 8), make_float2(d[4 * i], d[4 * i + 1]));
        __stcg(reinterpret_cast<float2*>(pp + 8 * DM + i * 8), make_float2(d[4 * i + 2], d[4 * i + 3]));
      }
      __threadfence();
      bar_sync(1, 256);
      if (t == 0) misc[5] = (int)atomicAdd(&g_flags.p[it.b * 2 + it.c], 1u);
      bar_sync(1, 256);
      if (misc[5] == 3) {
        __threadfence();
        const float* p0 = g_opart + (size_t)row * DM + col;
#pragma unroll 4
        for (int i = 0; i < 64; i++) {
          size_t off = (size_t)(i & 1) * 8 * DM + (i >> 1) * 8;
          float2 a = __ldcg(reinterpret_cast<const float2*>(p0 + off)), b = __ldcg(reinterpret_cast<const float2*>(p0 + off + (size_t)S_TOK * DM));
          float2 c = __ldcg(reinterpret_cast<const float2*>(p0 + off + (size_t)2 * S_TOK * DM)), e = __ldcg(reinterpret_cast<const float2*>(p0 + off + (size_t)3 * S_TOK * DM));
          size_t o = (size_t)row * DM + col + off;
          unsigned gv = __ldcg(reinterpret_cast<const unsigned*>(g_g + o)), xv = __ldg(reinterpret_cast<const unsigned*>(x + o));
          float s0 = bf16r((a.x + b.x) + (c.x + e.x)), s1 = bf16r((a.y + b.y) + (c.y + e.y));
          *reinterpret_cast<unsigned*>(out + o) = pack_bf16(bf_lo(xv) + bf16r(s0 * bf_lo(gv)), bf_hi(xv) + bf16r(s1 * bf_hi(gv)));
        }
      }
      bar_sync(1, 256);
      if (t == 0) ISTAMP(idx, 3);
      continue;
    }
    if (it.type != T_QKV) {
      const unsigned* bp = reinterpret_cast<const unsigned*>((it.type == T_M1 ? b1 : b2) + it.c * 256) + tq;
#pragma unroll
      for (int i = 0; i < 32; i++) {
        unsigned bv = __ldg(bp + i * 4);
        float lo = bf_lo(bv), hi = bf_hi(bv);
        float x0 = bf16r(bf16r(d[4 * i]) + lo), x1 = bf16r(bf16r(d[4 * i + 1]) + hi), x2 = bf16r(bf16r(d[4 * i + 2]) + lo), x3 = bf16r(bf16r(d[4 * i + 3]) + hi);
        if (it.type == T_M1) { d[4 * i] = gelu_t(x0); d[4 * i + 1] = gelu_t(x1); d[4 * i + 2] = gelu_t(x2); d[4 * i + 3] = gelu_t(x3); }
        else { d[4 * i] = silu_f(x0); d[4 * i + 1] = silu_f(x1); d[4 * i + 2] = silu_f(x2); d[4 * i + 3] = silu_f(x3); }
      }
    }
    mbar_wait(bar + 8 * MB_STGE, sph ^ 1);
    {
      const unsigned ob = sb + B_STG + (w * 16 + (m & 1) * 8 + r8) * 128;
#pragma unroll
      for (int i = 0; i < 16; i++)
        stsm_x4(ob + (i >> 2) * 16384 + ((((i & 3) * 2 + (m >> 1)) ^ r8) << 4), pack_bf16(d[8 * i], d[8 * i + 1]), pack_bf16(d[8 * i + 2], d[8 * i + 3]),
                pack_bf16(d[8 * i + 4], d[8 * i + 5]), pack_bf16(d[8 * i + 6], d[8 * i + 7]));
    }
    if (t == 0) misc[4] = idx;
    fence_proxy_async_smem();
    mbar_arrive(bar + 8 * MB_STGF); sph ^= 1;
  }
  mbar_wait(bar + 8 * MB_STGE, sph ^ 1);
  if (t == 0) misc[4] = -1;
  mbar_arrive(bar + 8 * MB_STGF);
}

__global__ void __cluster_dims__(2, 1, 1) __launch_bounds__(384, 1)
k_main(const __grid_constant__ Maps maps, const bf16* __restrict__ x, const bf16* __restrict__ mem0, const bf16* __restrict__ b1, const bf16* __restrict__ b2, bf16* __restrict__ out) {
  extern __shared__ unsigned char smem_raw[];
  const unsigned sraw = smem_u32(smem_raw);
  const unsigned sb = (sraw + 1023u) & ~1023u;
  int* misc = reinterpret_cast<int*>(smem_raw + (sb - sraw) + SM_MISC);
  const int w = threadIdx.x >> 5;
  const bool rec = blockIdx.x < NREC;
  if (threadIdx.x == 0) {
    const unsigned bar = sb + SM_BAR;
    for (int i = 0; i < 8; i++) { mbar_init(bar + 8 * (MB_FULL + i), 1); mbar_init(bar + 8 * (MB_EMPTY + i), rec ? 1 : 8); }
    mbar_init(bar + 8 * MB_STGF, 256); mbar_init(bar + 8 * MB_STGE, 1);
    for (int i = MB_W0; i <= MB_KVF; i++) mbar_init(bar + 8 * i, 1);
    asm volatile("fence.mbarrier_init.release.cluster;" ::: "memory");
  }
  __syncthreads();
  asm volatile("barrier.cluster.arrive.release.aligned;\nbarrier.cluster.wait.acquire.aligned;" ::: "memory");
  if (DBGMODE && !rec) return;
  if (w >= 8) {
    asm volatile("setmaxnreg.dec.sync.aligned.u32 24;");
    if (rec) { if (w == 8) rec_ring(maps, sb); else if (w == 9) rec_copy(sb); }
    else if ((threadIdx.x & 31) == 0) { if (w == 8) bulk_producer(maps, sb, misc); else if (w == 9) bulk_store(maps, sb, misc); }
  } else {
    if (rec) { asm volatile("setmaxnreg.inc.sync.aligned.u32 240;"); rec_worker(maps, sb, mem0); }
    else { asm volatile("setmaxnreg.inc.sync.aligned.u32 240;"); bulk_worker(sb, misc, x, b1, b2, out); }
  }
}

typedef CUresult (*EncFn)(CUtensorMap*, CUtensorMapDataType, cuuint32_t, void*, const cuuint64_t*, const cuuint64_t*, const cuuint32_t*, const cuuint32_t*,
                          CUtensorMapInterleave, CUtensorMapSwizzle, CUtensorMapL2promotion, CUtensorMapFloatOOBfill);
static void mk_map(EncFn enc, CUtensorMap* m, const void* ptr, uint64_t rows, uint64_t cols, uint32_t box_rows) {
  cuuint64_t dims[2] = {cols, rows}; cuuint64_t strides[1] = {cols * 2};
  cuuint32_t box[2] = {64, box_rows}, es[2] = {1, 1};
  enc(m, CU_TENSOR_MAP_DATA_TYPE_BFLOAT16, 2, const_cast<void*>(ptr), dims, strides, box, es, CU_TENSOR_MAP_INTERLEAVE_NONE, CU_TENSOR_MAP_SWIZZLE_128B,
      CU_TENSOR_MAP_L2_PROMOTION_L2_256B, CU_TENSOR_MAP_FLOAT_OOB_FILL_NONE);
}
extern "C" void kernel_launch(void* const* d_in, const int* in_sizes, int n_in, void* d_out, int out_size) {
  static EncFn enc = nullptr;
  static void *p_xn, *p_y, *p_h1, *p_o, *p_qkv, *p_g;
  if (!enc) {
    void* fn = nullptr; cudaDriverEntryPointQueryResult qr;
    cudaGetDriverEntryPoint("cuTensorMapEncodeTiled", &fn, cudaEnableDefault, &qr);
    enc = (EncFn)fn;
    cudaGetSymbolAddress(&p_xn, g_xn); cudaGetSymbolAddress(&p_y, g_y); cudaGetSymbolAddress(&p_h1, g_h1);
    cudaGetSymbolAddress(&p_o, g_o); cudaGetSymbolAddress(&p_qkv, g_qkv); cudaGetSymbolAddress(&p_g, g_g);
    cudaFuncSetAttribute(k_main, cudaFuncAttributeMaxDynamicSharedMemorySize, SMEM_TOTAL);
  }
  Maps maps;
  mk_map(enc, &maps.xn, p_xn, S_TOK, DM, 128); mk_map(enc, &maps.y, p_y, S_TOK, DM, 128); mk_map(enc, &maps.h1, p_h1, S_TOK, FF, 128);
  mk_map(enc, &maps.o, p_o, S_TOK, HD, 128); mk_map(enc, &maps.qkv_st, p_qkv, S_TOK, 3 * HD, 128); mk_map(enc, &maps.qkv_ld, p_qkv, S_TOK, 3 * HD, 32);
  mk_map(enc, &maps.g, p_g, S_TOK, DM, 128);
  mk_map(enc, &maps.wq, d_in[2], DM, HD, 64); mk_map(enc, &maps.wk, d_in[3], DM, HD, 64); mk_map(enc, &maps.wv, d_in[4], DM, HD, 64);
  mk_map(enc, &maps.wo, d_in[5], HD, DM, 64); mk_map(enc, &maps.w1, d_in[8], DM, FF, 64); mk_map(enc, &maps.w2, d_in[10], FF, DM, 64);
  cudaStream_t st = cudaStreamPerThread;
  k_pre<<<256, 256, 0, st>>>((const bf16*)d_in[0]);
  k_main<<<NCTA, 384, SMEM_TOTAL, st>>>(maps, (const bf16*)d_in[0], (const bf16*)d_in[1], (const bf16*)d_in[9], (const bf16*)d_in[11], (bf16*)d_out);
}
```

```cpp
#include <cuda_runtime.h>
#include <cuda_bf16.h>
#include <cuda.h>
#include <stdint.h>

typedef __nv_bfloat16 bf16;

#define S_TOK 2048
#define DM 512
#define NH 32
#define DH 128
#define HD 4096
#define NMEM 8
#define SEG 32
#define NSEG 64
#define FF 1792
#define NBLK 16
#define NREC 64
#define NCTA 132
#define NBULK (NCTA - NREC)

__device__ __align__(1024) bf16 g_xn[S_TOK * DM];
__device__ __align__(1024) bf16 g_y[S_TOK * DM];
__device__ __align__(1024) bf16 g_qkv[(size_t)S_TOK * 3 * HD];
__device__ __align__(1024) bf16 g_h1[S_TOK * FF];
__device__ __align__(1024) bf16 g_g[S_TOK * DM];
__device__ __align__(1024) bf16 g_o[(size_t)S_TOK * HD];
__device__ __align__(1024) bf16 g_km[NSEG * NH * NMEM * DH];
__device__ __align__(1024) bf16 g_vmt[NSEG * NH * DH * NMEM];
__device__ __align__(1024) float g_opart[(size_t)4 * S_TOK * DM];
__device__ __align__(1024) float g_opl[(size_t)16 * 128 * DM];
__device__ __align__(1024) unsigned g_part[2 * NREC * NH * 64];
__device__ __align__(1024) unsigned g_pub[NSEG * 2048];
struct Flags {
  unsigned qkv[NBLK * 48];
  unsigned h1[NBLK];
  unsigned g[NBLK];
  unsigned o[NBLK * 4];
  unsigned p[NBLK];
  unsigned o16[16];
  unsigned ctr;
  unsigned rec[NREC];
  unsigned abort_;
};
__device__ __align__(1024) Flags g_flags;

#define RSTAMP(k)
#define DBGMODE 0
#define ISTAMP(i, k)
__device__ __forceinline__ unsigned smem_u32(const void* p) { return (unsigned)__cvta_generic_to_shared(p); }
__device__ __forceinline__ float bf16r(float x) { unsigned u; asm("cvt.rn.bf16x2.f32 %0, %1, %2;" : "=r"(u) : "f"(x), "f"(0.0f)); return __uint_as_float(u); }
__device__ __forceinline__ unsigned pack_bf16(float lo, float hi) {
  __nv_bfloat162 v = __floats2bfloat162_rn(lo, hi);
  return *reinterpret_cast<unsigned*>(&v);
}
__device__ __forceinline__ float bf_lo(unsigned u) { return __uint_as_float(u << 16); }
__device__ __forceinline__ float bf_hi(unsigned u) { return __uint_as_float(u & 0xffff0000u); }

#define SPIN_LIMIT (1u << 20)
#define TRAP_IF(x) if ((x) > SPIN_LIMIT) { asm volatile("st.global.u32 [%0], %1;" ::"l"(0ull), "r"(0u) : "memory"); break; }
__device__ __forceinline__ unsigned ld_acquire(const unsigned* p) {
  unsigned v; asm volatile("ld.acquire.gpu.global.u32 %0, [%1];" : "=r"(v) : "l"(p) : "memory"); return v;
}
__device__ __forceinline__ unsigned ld_relaxed(const unsigned* p) {
  unsigned v; asm volatile("ld.relaxed.gpu.global.u32 %0, [%1];" : "=r"(v) : "l"(p) : "memory"); return v;
}
__device__ __forceinline__ void red_release_add(unsigned* p, unsigned v) {
  asm volatile("red.release.gpu.global.add.u32 [%0], %1;" ::"l"(p), "r"(v) : "memory");
}
__device__ __forceinline__ void st_release(unsigned* p, unsigned v) {
  asm volatile("st.release.gpu.global.u32 [%0], %1;" ::"l"(p), "r"(v) : "memory");
}
__device__ __forceinline__ void wait_flag_ge(const unsigned* p, unsigned target) {
  unsigned it = 0;
  while (ld_acquire(p) < target) {
    __nanosleep(64);
    TRAP_IF(++it);
  }
}
__device__ __forceinline__ uint4 ldv4_relaxed(const void* p) {
  uint4 a; asm volatile("ld.relaxed.gpu.global.v4.u32 {%0,%1,%2,%3}, [%4];" : "=r"(a.x), "=r"(a.y), "=r"(a.z), "=r"(a.w) : "l"(p) : "memory"); return a;
}
__device__ __forceinline__ void mbar_init(unsigned mb, unsigned cnt) { asm volatile("mbarrier.init.shared::cta.b64 [%0], %1;" ::"r"(mb), "r"(cnt) : "memory"); }
__device__ __forceinline__ void mbar_expect_tx(unsigned mb, unsigned bytes) { asm volatile("mbarrier.arrive.expect_tx.shared::cta.b64 _, [%0], %1;" ::"r"(mb), "r"(bytes) : "memory"); }
__device__ __forceinline__ void mbar_arrive(unsigned mb) { asm volatile("mbarrier.arrive.shared::cta.b64 _, [%0];" ::"r"(mb) : "memory"); }
__device__ __forceinline__ void mbar_wait(unsigned mb, unsigned parity) {
  unsigned ok, it = 0;
  while (true) {
    asm volatile("{.reg .pred p; mbarrier.try_wait.parity.shared::cta.b64 p, [%1], %2; selp.u32 %0,1,0,p;}" : "=r"(ok) : "r"(mb), "r"(parity) : "memory");
    if (ok) break;
    TRAP_IF(++it);
  }
}
__device__ __forceinline__ void mbar_wait_sleep(unsigned mb, unsigned parity) {
  unsigned ok, it = 0;
  while (true) {
    asm volatile("{.reg .pred p; mbarrier.test_wait.parity.shared::cta.b64 p, [%1], %2; selp.u32 %0,1,0,p;}" : "=r"(ok) : "r"(mb), "r"(parity) : "memory");
    if (ok) break;
    __nanosleep(200);
    TRAP_IF(++it);
  }
}
__device__ __forceinline__ float ex2f(float x) { float y; asm("ex2.approx.ftz.f32 %0, %1;" : "=f"(y) : "f"(x)); return y; }
__device__ __forceinline__ int opaque_tid() { int t = threadIdx.x; t = __shfl_sync(~0u, t, t & 31); return t; }
#define LOG2E 1.4426950408889634f
__device__ __forceinline__ void mbar_wait_cluster(unsigned mb, unsigned parity) {
  unsigned ok, it = 0;
  while (true) {
    asm volatile("{.reg .pred p; mbarrier.try_wait.parity.acquire.cluster.shared::cta.b64 p, [%1], %2; selp.u32 %0,1,0,p;}" : "=r"(ok) : "r"(mb), "r"(parity) : "memory");
    if (ok) break;
    TRAP_IF(++it);
  }
}
__device__ __forceinline__ void bar_sync(int id, int n) { asm volatile("bar.sync %0, %1;" ::"r"(id), "r"(n) : "memory"); }
__device__ __forceinline__ void bar_arrive(int id, int n) { asm volatile("bar.arrive %0, %1;" ::"r"(id), "r"(n) : "memory"); }
__device__ __forceinline__ void tma_load_2d(unsigned dst, const CUtensorMap* map, int c0, int c1, unsigned mb) {
  asm volatile("cp.async.bulk.tensor.2d.shared::cluster.global.mbarrier::complete_tx::bytes [%0], [%1, {%3, %4}], [%2];"
               ::"r"(dst), "l"((uint64_t)map), "r"(mb), "r"(c0), "r"(c1) : "memory");
}
__device__ __forceinline__ void tma_store_2d(const CUtensorMap* map, unsigned src, int c0, int c1) {
  asm volatile("cp.async.bulk.tensor.2d.global.shared::cta.bulk_group [%0, {%2, %3}], [%1];"
               ::"l"((uint64_t)map), "r"(src), "r"(c0), "r"(c1) : "memory");
}
__device__ __forceinline__ void fence_proxy_async() { asm volatile("fence.proxy.async;" ::: "memory"); }
__device__ __forceinline__ void fence_proxy_async_smem() { asm volatile("fence.proxy.async.shared::cta;" ::: "memory"); }
__device__ __forceinline__ void ldsm_x4(unsigned* r, unsigned addr) {
  asm volatile("ldmatrix.sync.aligned.m8n8.x4.shared.b16 {%0,%1,%2,%3}, [%4];" : "=r"(r[0]), "=r"(r[1]), "=r"(r[2]), "=r"(r[3]) : "r"(addr) : "memory");
}
__device__ __forceinline__ void ldsm_x4_t(unsigned* r, unsigned addr) {
  asm volatile("ldmatrix.sync.aligned.m8n8.x4.trans.shared.b16 {%0,%1,%2,%3}, [%4];" : "=r"(r[0]), "=r"(r[1]), "=r"(r[2]), "=r"(r[3]) : "r"(addr) : "memory");
}
__device__ __forceinline__ void stsm_x2_t(unsigned addr, unsigned r0, unsigned r1) {
  asm volatile("stmatrix.sync.aligned.m8n8.x2.trans.shared.b16 [%0], {%1,%2};" ::"r"(addr), "r"(r0), "r"(r1) : "memory");
}
__device__ __forceinline__ void stsm_x4(unsigned addr, unsigned r0, unsigned r1, unsigned r2, unsigned r3) {
  asm volatile("stmatrix.sync.aligned.m8n8.x4.shared.b16 [%0], {%1,%2,%3,%4};" ::"r"(addr), "r"(r0), "r"(r1), "r"(r2), "r"(r3) : "memory");
}
__device__ __forceinline__ void mma16816(float* d, const unsigned* a, unsigned b0, unsigned b1) {
  asm volatile("mma.sync.aligned.m16n8k16.row.col.f32.bf16.bf16.f32 {%0,%1,%2,%3}, {%4,%5,%6,%7}, {%8,%9}, {%0,%1,%2,%3};"
               : "+f"(d[0]), "+f"(d[1]), "+f"(d[2]), "+f"(d[3]) : "r"(a[0]), "r"(a[1]), "r"(a[2]), "r"(a[3]), "r"(b0), "r"(b1));
}
__device__ __forceinline__ void mma1688(float* d, unsigned a0, unsigned a1, unsigned b0) {
  asm volatile("mma.sync.aligned.m16n8k8.row.col.f32.bf16.bf16.f32 {%0,%1,%2,%3}, {%4,%5}, {%6}, {%0,%1,%2,%3};"
               : "+f"(d[0]), "+f"(d[1]), "+f"(d[2]), "+f"(d[3]) : "r"(a0), "r"(a1), "r"(b0));
}
__device__ __forceinline__ uint64_t mkdesc(unsigned addr, unsigned lbo, unsigned sbo) {
  return (uint64_t)((addr >> 4) & 0x3fff) | ((uint64_t)(lbo >> 4) << 16) | ((uint64_t)(sbo >> 4) << 32) | (1ull << 62);
}
#define R8(b) "+f"(d[b]), "+f"(d[b + 1]), "+f"(d[b + 2]), "+f"(d[b + 3]), "+f"(d[b + 4]), "+f"(d[b + 5]), "+f"(d[b + 6]), "+f"(d[b + 7])
#define R32(b) R8(b), R8(b + 8), R8(b + 16), R8(b + 24)
__device__ __forceinline__ void wgmma_n256(float* d, uint64_t ad, uint64_t bd, int acc) {
  asm volatile(
      "{.reg .pred p; setp.ne.b32 p, %130, 0;\n"
      "wgmma.mma_async.sync.aligned.m64n256k16.f32.bf16.bf16 "
      "{%0,%1,%2,%3,%4,%5,%6,%7,%8,%9,%10,%11,%12,%13,%14,%15,%16,%17,%18,%19,%20,%21,%22,%23,%24,%25,%26,%27,%28,%29,%30,%31,"
      "%32,%33,%34,%35,%36,%37,%38,%39,%40,%41,%42,%43,%44,%45,%46,%47,%48,%49,%50,%51,%52,%53,%54,%55,%56,%57,%58,%59,%60,%61,%62,%63,"
      "%64,%65,%66,%67,%68,%69,%70,%71,%72,%73,%74,%75,%76,%77,%78,%79,%80,%81,%82,%83,%84,%85,%86,%87,%88,%89,%90,%91,%92,%93,%94,%95,"
      "%96,%97,%98,%99,%100,%101,%102,%103,%104,%105,%106,%107,%108,%109,%110,%111,%112,%113,%114,%115,%116,%117,%118,%119,%120,%121,%122,%123,%124,%125,%126,%127},"
      "%128, %129, p, 1, 1, 0, 1;}\n"
      : R32(0), R32(32), R32(64), R32(96)
      : "l"(ad), "l"(bd), "r"(acc));
}

__device__ __forceinline__ void ln16(const float* x, float* o) {
  float s = 0;
#pragma unroll
  for (int i = 0; i < 16; i++) s += x[i];
#pragma unroll
  for (int of = 16; of > 0; of >>= 1) s += __shfl_xor_sync(~0u, s, of);
  float mean = s * (1.0f / DM);
  float v = 0;
#pragma unroll
  for (int i = 0; i < 16; i++) { float dd = x[i] - mean; v += dd * dd; }
#pragma unroll
  for (int of = 16; of > 0; of >>= 1) v += __shfl_xor_sync(~0u, v, of);
  float mb = bf16r(mean);
  float vb = bf16r(v * (1.0f / DM));
  float den = bf16r(sqrtf(bf16r(vb + 1e-5f)));
#pragma unroll
  for (int i = 0; i < 16; i++) o[i] = bf16r(__fdiv_rn(bf16r(x[i] - mb), den));
}
__global__ void __launch_bounds__(256) k_pre(const bf16* __restrict__ x) {
  int t = threadIdx.x, lane = t & 31, w = t >> 5;
  int row = blockIdx.x * 8 + w;
  const uint4* src = reinterpret_cast<const uint4*>(x + (size_t)row * DM);
  uint4 a = src[lane], b = src[lane + 32];
  unsigned u[8] = {a.x, a.y, a.z, a.w, b.x, b.y, b.z, b.w};
  float f[16], o[16], o2[16];
#pragma unroll
  for (int i = 0; i < 8; i++) { f[2 * i] = bf_lo(u[i]); f[2 * i + 1] = bf_hi(u[i]); }
  ln16(f, o);
  ln16(o, o2);
  uint4* d1 = reinterpret_cast<uint4*>(g_xn + (size_t)row * DM);
  uint4* d2 = reinterpret_cast<uint4*>(g_y + (size_t)row * DM);
  d1[lane] = make_uint4(pack_bf16(o[0], o[1]), pack_bf16(o[2], o[3]), pack_bf16(o[4], o[5]), pack_bf16(o[6], o[7]));
  d1[lane + 32] = make_uint4(pack_bf16(o[8], o[9]), pack_bf16(o[10], o[11]), pack_bf16(o[12], o[13]), pack_bf16(o[14], o[15]));
  d2[lane] = make_uint4(pack_bf16(o2[0], o2[1]), pack_bf16(o2[2], o2[3]), pack_bf16(o2[4], o2[5]), pack_bf16(o2[6], o2[7]));
  d2[lane + 32] = make_uint4(pack_bf16(o2[8], o2[9]), pack_bf16(o2[10], o2[11]), pack_bf16(o2[12], o2[13]), pack_bf16(o2[14], o2[15]));
  int gt = blockIdx.x * 256 + t;
  uint4 z = make_uint4(0, 0, 0, 0);
  reinterpret_cast<uint4*>(g_part)[gt] = z;
  if (gt < NSEG * 2048 / 4) reinterpret_cast<uint4*>(g_pub)[gt] = z;
  if (gt < (int)(sizeof(Flags) / 4)) reinterpret_cast<unsigned*>(&g_flags)[gt] = 0;
}

struct Maps { CUtensorMap xn, y, h1, o, qkv_st, qkv_ld, g, wq, wk, wv, wo, w1, w2; };

#define NSTAGE 3
#define STAGE_BYTES 49152
#define B_STG (NSTAGE * STAGE_BYTES)
#define R_WO 0
#define R_T1 65536
#define R_T2 131072
#define R_RING 65536
#define RING_N 4
#define RING_BYTES 12288
#define R_MEM 196608
#define R_QS (R_MEM + 8448)
#define R_KS (R_QS + 1152)
#define R_OS (R_KS + 1152)
#define R_SOWN (R_OS + 2176)
#define R_SPEER (R_SOWN + 1280)
#define R_VM (R_SPEER + 1280)
#define R_VRED (R_VM + 2048)
#define R_RED (R_VRED + 6144)
#define SM_BAR (R_RED + 2048)
#define SMEM_TOTAL (SM_BAR + 256 + 1024)
#define MB_FULL 0
#define MB_EMPTY 8
#define MB_STGF 16
#define MB_STGE 17
#define MB_W0 18
#define MB_W1 19
#define MB_WO 20
#define MB_S 21
#define MB_V 22
#define MB_KVR 23
#define MB_KVF 24
#define SM_MISC (SM_BAR + 208)

#define N_KV 512
#define I_Q 512
#define I_M1 768
#define I_M2 880
#define I_POST 912
#define I_TAIL (I_POST + 16 + 24 + 14 * 32)
#define N_ITEMS (I_TAIL + 8 + 32 + 64)
enum { T_QKV = 0, T_M1 = 1, T_M2 = 2, T_ATT = 3, T_OUT = 4, T_OUTL = 5, T_RED = 6, T_REDL = 7 };
struct Item { int type, b, c, ks; };
__device__ __forceinline__ Item decode_item(int i) {
  Item it; it.ks = 0;
  if (i < N_KV) { it.type = T_QKV; it.b = i >> 5; it.c = 16 + (i & 31); }
  else if (i < I_M1) { it.type = T_QKV; it.b = (i - I_Q) >> 4; it.c = (i - I_Q) & 15; }
  else if (i < I_M2) { it.type = T_M1; it.b = (i - I_M1) / 7; it.c = (i - I_M1) % 7; }
  else if (i < I_POST) { it.type = T_M2; it.b = (i - I_M2) >> 1; it.c = (i - I_M2) & 1; }
  else if (i < I_TAIL) {
    int x = i - I_POST, p, r;
    if (x < 16) { p = 0; r = x; } else if (x < 40) { p = 1; r = x - 16; } else { p = 2 + ((x - 40) >> 5); r = (x - 40) & 31; }
    if (r < 16) { it.type = T_ATT; it.b = p; it.c = r; }
    else if (r < 24) { it.type = T_OUT; it.b = p - 1; it.c = r & 1; it.ks = (r - 16) >> 1; }
    else { it.type = T_RED; it.b = p - 2; it.c = r - 24; }
  } else {
    int x = i - I_TAIL;
    if (x < 8) { it.type = T_RED; it.b = 14; it.c = x; }
    else if (x < 40) { it.type = T_OUTL; it.b = 15; it.c = x & 1; it.ks = (x - 8) >> 1; }
    else { it.type = T_REDL; it.b = 15; it.c = x - 40; }
  }
  return it;
}
__device__ __forceinline__ int item_nkb(int type) { return type == T_M2 ? 28 : (type == T_OUT ? 16 : (type >= T_RED ? 1 : (type >= T_ATT ? 4 : 8))); }

__device__ __forceinline__ void st_async_b64(unsigned raddr, unsigned lo, unsigned hi, unsigned rmb) {
  asm volatile("st.async.weak.shared::cluster.mbarrier::complete_tx::bytes.v2.b32 [%0], {%1,%2}, [%3];" ::"r"(raddr), "r"(lo), "r"(hi), "r"(rmb) : "memory");
}
__device__ __forceinline__ unsigned mapa(unsigned a, unsigned rank) {
  unsigned r; asm volatile("mapa.shared::cluster.u32 %0, %1, %2;" : "=r"(r) : "r"(a), "r"(rank)); return r;
}
__device__ __forceinline__ void sts64(unsigned a, unsigned x, unsigned y) { asm volatile("st.shared.v2.b32 [%0], {%1,%2};" ::"r"(a), "r"(x), "r"(y) : "memory"); }
__device__ __forceinline__ void sts128(unsigned a, uint4 v) { asm volatile("st.shared.v4.b32 [%0], {%1,%2,%3,%4};" ::"r"(a), "r"(v.x), "r"(v.y), "r"(v.z), "r"(v.w) : "memory"); }
__device__ __forceinline__ uint2 lds64(unsigned a) { uint2 v; asm volatile("ld.shared.v2.b32 {%0,%1}, [%2];" : "=r"(v.x), "=r"(v.y) : "r"(a) : "memory"); return v; }
__device__ __forceinline__ uint4 lds128(unsigned a) { uint4 v; asm volatile("ld.shared.v4.b32 {%0,%1,%2,%3}, [%4];" : "=r"(v.x), "=r"(v.y), "=r"(v.z), "=r"(v.w) : "r"(a) : "memory"); return v; }
__device__ __forceinline__ float lds32f(unsigned a) { float v; asm volatile("ld.shared.f32 %0, [%1];" : "=f"(v) : "r"(a) : "memory"); return v; }
#define spin_check(it) TRAP_IF(++it)
#define POLLV 0
#define BAR8 0
#define D_STAG 150
#define D_RED 0
#define D_PUB 0
#define DELAY(n) do { unsigned c0_, c1_; asm volatile("mov.u32 %0, %%clock;" : "=r"(c0_)); do { asm volatile("mov.u32 %0, %%clock;" : "=r"(c1_)); } while (c1_ - c0_ < (n)); } while (0)
#define SCALE_QK 0.08838834764831845f

__device__ __forceinline__ void rec_worker(const Maps& maps, unsigned sb, const bf16* __restrict__ mem0) {
  const int c = blockIdx.x, h = c >> 1, j = c & 1;
  const int t = opaque_tid(), lane = t & 31, w = t >> 5, g = lane >> 2, tq = lane & 3;
  const int m = lane >> 3, r8 = lane & 7, kh = w >> 2, et = w & 3;
  const unsigned bar = sb + SM_BAR;
  unsigned wq[16][4], wk[16][4], wo[8][4];
  const unsigned woff = (kh * 4) * 8192 + ((m >> 1) * 8 + r8) * 128 + (((et * 2 + (m & 1)) ^ r8) << 4);
  mbar_wait(bar + 8 * MB_W0, 0);
#pragma unroll
  for (int i = 0; i < 16; i++) {
    ldsm_x4_t(wq[i], sb + R_WO + woff + (i >> 2) * 8192 + (i & 3) * 2048);
    ldsm_x4_t(wk[i], sb + R_T1 + woff + (i >> 2) * 8192 + (i & 3) * 2048);
  }
  bar_sync(2, 288);
  if (t == 0) {
    fence_proxy_async_smem();
    mbar_expect_tx(bar + 8 * MB_WO, 65536);
    for (int kb = 0; kb < 2; kb++)
      for (int cb = 0; cb < 4; cb++) tma_load_2d(sb + R_WO + (kb * 4 + cb) * 8192, &maps.wo, j * 256 + cb * 64, h * 128 + kb * 64, bar + 8 * MB_WO);
  }
  mbar_wait(bar + 8 * MB_W1, 0);
  const unsigned pV = sb + R_T2 + woff;
  const unsigned peer = j ^ 1;
#define KEEP(x) x = __shfl_sync(~0u, x, lane)
  unsigned pA = sb + R_MEM + r8 * 1040 + m * 16 + kh * 512;
  unsigned pW0 = sb + R_WO + (w >> 1) * 8192 + ((m >> 1) * 8 + r8) * 128 + ((((w & 1) * 4 + (m & 1)) ^ r8) << 4);
  unsigned pW1 = pW0 ^ 32;
  unsigned pVk = pV;
  unsigned aMem = sb + R_MEM + (t & 7) * 1040 + (t >> 3) * 16;
  unsigned aX = sb + R_VRED + et * 512 + lane * 16;
  unsigned aQKst = sb + (kh ? R_KS : R_QS) + r8 * 144 + (et * 16 + (m & 1) * 8) * 2;
  unsigned aL8 = sb + lane * 8;
  unsigned aSl = mapa(sb + R_SOWN + w * 256 + lane * 8, j), aSr = mapa(sb + R_SPEER + w * 256 + lane * 8, peer);
  unsigned aVl = mapa(sb + R_VM + (j * 4 + et) * 256 + lane * 8, j), aVr = mapa(sb + R_VM + (j * 4 + et) * 256 + lane * 8, peer);
  const unsigned mbSl = mapa(bar + 8 * MB_S, j), mbSr = mapa(bar + 8 * MB_S, peer), mbVl = mbSl + 8, mbVr = mbSr + 8;
  unsigned aQ = sb + R_QS + r8 * 144 + m * 16;
  unsigned oKx = (et * 8 + r8) * 128 + ((m ^ r8) << 4);
  unsigned oVx = 4096 + (et >> 1) * 4096 + ((m >> 1) * 8 + r8) * 128 + ((((et & 1) * 4 + (m & 1)) ^ r8) << 4);
  unsigned aOst = sb + R_OS + r8 * 272 + (et * 32 + m * 8) * 2;
  unsigned aOld = sb + R_OS + r8 * 272 + m * 16;
  unsigned aVm = sb + R_VM + et * 512 + lane * 8;
  unsigned aRst = sb + R_RED + w * 256 + lane * 16;
  unsigned aRld = sb + R_RED + tq * 64 + g * 4;
  unsigned oPd = ((32 * j + 4 * w) * NH + h) * 256 + g * 32 + tq * 8;
  unsigned oPs = (c * NH + 4 * w) * 256 + lane * 16;
  unsigned oPub = t * 16;
  KEEP(pA); KEEP(pW0); KEEP(pW1); KEEP(pVk); KEEP(aX); KEEP(aQKst); KEEP(aL8); KEEP(aSl); KEEP(aSr); KEEP(aVl); KEEP(aVr); KEEP(aQ); KEEP(oKx); KEEP(oVx);
  KEEP(aOst); KEEP(aOld); KEEP(aVm); KEEP(oPd);
  mbar_wait(bar + 8 * MB_WO, 0);
#pragma unroll
  for (int ks = 0; ks < 4; ks++) { ldsm_x4_t(wo[2 * ks], pW0 + ks * 2048); ldsm_x4_t(wo[2 * ks + 1], pW1 + ks * 2048); }
#pragma unroll
  for (int u = 0; u < 2; u++) {
    int i = t + 256 * u;
    uint4 v = __ldg(reinterpret_cast<const uint4*>(mem0) + i);
    sts128(sb + R_MEM + (i >> 6) * 1040 + (i & 63) * 16, v);
  }
  if (t == 0) { mbar_expect_tx(bar + 8 * MB_S, 2560); mbar_expect_tx(bar + 8 * MB_V, 2048); }

#pragma unroll 1
  for (int s = 0;; s++) {
    const unsigned par = s & 1;
    const unsigned slot = s & (RING_N - 1), rpar = (s / RING_N) & 1;
    const unsigned ring = sb + R_RING + slot * RING_BYTES;
    RSTAMP(1);
    bar_sync(1, 256);
    RSTAMP(2);
    float aq[4] = {0, 0, 0, 0}, ak[4] = {0, 0, 0, 0}, av[4] = {0, 0, 0, 0};
#pragma unroll
    for (int i = 0; i < 8; i++) {
      unsigned b[4], f[4], f0[4];
      ldsm_x4(b, pA + i * 64);
      ldsm_x4_t(f0, pVk + (i >> 1) * 8192 + (i & 1) * 4096);
      ldsm_x4_t(f, pVk + (i >> 1) * 8192 + (i & 1) * 4096 + 2048);
      mma16816(aq, wq[2 * i], b[0], b[1]); mma16816(ak, wk[2 * i], b[0], b[1]); mma16816(av, f0, b[0], b[1]);
      mma16816(aq, wq[2 * i + 1], b[2], b[3]); mma16816(ak, wk[2 * i + 1], b[2], b[3]); mma16816(av, f, b[2], b[3]);
    }
    RSTAMP(3);
#define STSF4(a, v) asm volatile("st.shared.v4.f32 [%0], {%1,%2,%3,%4};" ::"r"(a), "f"(v[0]), "f"(v[1]), "f"(v[2]), "f"(v[3]) : "memory")
    unsigned f[8][4];
#define NPRE 2
#define WO_PREFETCH() do { _Pragma("unroll") for (int i = 0; i < NPRE; i++) { ldsm_x4_t(f[2 * i], pW0 + 32768 + i * 2048); ldsm_x4_t(f[2 * i + 1], pW1 + 32768 + i * 2048); } } while (0)
    if (kh) {
      STSF4(aX, aq);
      bar_sync(4 + et, 64);
      uint4 o = lds128(aX + 2048), o2 = lds128(aX + 4096);
      stsm_x2_t(aQKst, pack_bf16(ak[0] + __uint_as_float(o.x), ak[1] + __uint_as_float(o.y)), pack_bf16(ak[2] + __uint_as_float(o.z), ak[3] + __uint_as_float(o.w)));
      bar_arrive(1, 256);
      unsigned x = pack_bf16(av[0] + __uint_as_float(o2.x), av[1] + __uint_as_float(o2.y)), y = pack_bf16(av[2] + __uint_as_float(o2.z), av[3] + __uint_as_float(o2.w));
      st_async_b64(aVr, x, y, mbVr);
      st_async_b64(aVl, x, y, mbVl);
      mbar_wait(bar + 8 * (MB_FULL + slot), rpar);
      unsigned vx[4][4];
      ldsm_x4_t(vx[0], ring + oVx); ldsm_x4_t(vx[1], ring + oVx + 2048); ldsm_x4_t(vx[2], ring + (oVx ^ 32)); ldsm_x4_t(vx[3], ring + (oVx ^ 32) + 2048);
      RSTAMP(4); RSTAMP(5); RSTAMP(6); RSTAMP(7);
      mbar_wait(bar + 8 * MB_S, par);
      RSTAMP(8);
      float sc[10];
#pragma unroll
      for (int i = 0; i < 5; i++) {
        uint2 o = lds64(aL8 + R_SOWN + i * 256), p = lds64(aL8 + R_SPEER + i * 256);
        sc[2 * i] = __uint_as_float(o.x) + __uint_as_float(p.x); sc[2 * i + 1] = __uint_as_float(o.y) + __uint_as_float(p.y);
      }
      mbar_wait(bar + 8 * MB_V, par);
      uint2 vm0 = lds64(aVm), vm1 = lds64(aVm + 256);
      float mx = fmaxf(fmaxf(fmaxf(sc[0], sc[1]), fmaxf(sc[2], sc[3])), fmaxf(fmaxf(fmaxf(sc[4], sc[5]), fmaxf(sc[6], sc[7])), fmaxf(sc[8], sc[9])));
      mx = fmaxf(mx, __shfl_xor_sync(~0u, mx, 1)); mx = fmaxf(mx, __shfl_xor_sync(~0u, mx, 2));
      const float nm = -mx * (SCALE_QK * LOG2E);
#pragma unroll
      for (int i = 0; i < 10; i++) sc[i] = ex2f(fmaf(sc[i], SCALE_QK * LOG2E, nm));
      float sum = (((sc[0] + sc[1]) + (sc[2] + sc[3])) + ((sc[4] + sc[5]) + (sc[6] + sc[7]))) + (sc[8] + sc[9]);
      sum += __shfl_xor_sync(~0u, sum, 1); sum += __shfl_xor_sync(~0u, sum, 2);
      float inv; asm("rcp.approx.ftz.f32 %0, %1;" : "=f"(inv) : "f"(sum));
      unsigned p[5];
#pragma unroll
      for (int i = 0; i < 5; i++) p[i] = pack_bf16(sc[2 * i] * inv, sc[2 * i + 1] * inv);
      RSTAMP(9);
      float o0[4] = {0, 0, 0, 0}, o1[4] = {0, 0, 0, 0}, o3[4] = {0, 0, 0, 0}, o4[4] = {0, 0, 0, 0};
      mma16816(o0, vx[0], p[0], p[1]); mma16816(o3, vx[2], p[0], p[1]); mma16816(o1, vx[1], p[2], p[3]); mma16816(o4, vx[3], p[2], p[3]);
      mma1688(o0, vm0.x, vm0.y, p[4]); mma1688(o3, vm1.x, vm1.y, p[4]);
      if (s == NSEG - 1) { if (t == 128) mbar_arrive(bar + 8 * MB_KVR); break; }
      asm volatile("stmatrix.sync.aligned.m8n8.x4.trans.shared.b16 [%0], {%1,%2,%3,%4};" ::"r"(aOst), "r"(pack_bf16(o0[0] + o1[0], o0[1] + o1[1])), "r"(pack_bf16(o0[2] + o1[2], o0[3] + o1[3])),
                   "r"(pack_bf16(o3[0] + o4[0], o3[1] + o4[1])), "r"(pack_bf16(o3[2] + o4[2], o3[3] + o4[3])) : "memory");
      RSTAMP(10);
      bar_sync(1, 256);
      WO_PREFETCH();
    } else {
      STSF4(aX + 2048, ak); STSF4(aX + 4096, av);
      unsigned kb[8];
      mbar_wait(bar + 8 * (MB_FULL + slot), rpar);
      ldsm_x4(kb, ring + oKx); ldsm_x4(kb + 4, ring + (oKx ^ 64));
      bar_sync(4 + et, 64);
      uint4 o = lds128(aX);
      stsm_x2_t(aQKst, pack_bf16(aq[0] + __uint_as_float(o.x), aq[1] + __uint_as_float(o.y)), pack_bf16(aq[2] + __uint_as_float(o.z), aq[3] + __uint_as_float(o.w)));
      RSTAMP(4);
      bar_sync(1, 256);
      RSTAMP(5);
      unsigned qa[8], km[8];
      ldsm_x4(qa, aQ); ldsm_x4(qa + 4, aQ + 64);
      if (w == 3) { ldsm_x4(km, aQ + 1152); ldsm_x4(km + 4, aQ + 1152 + 64); }
      float s0[4] = {0, 0, 0, 0}, s1[4] = {0, 0, 0, 0};
      unsigned af[4][4];
#pragma unroll
      for (int i = 0; i < 4; i++) { af[i][0] = qa[2 * i]; af[i][1] = 0; af[i][2] = qa[2 * i + 1]; af[i][3] = 0; }
      mma16816(s0, af[0], kb[0], kb[1]); mma16816(s1, af[1], kb[2], kb[3]);
      mma16816(s0, af[2], kb[4], kb[5]); mma16816(s1, af[3], kb[6], kb[7]);
      if (w == 3) {
        float m0[4] = {0, 0, 0, 0}, m1[4] = {0, 0, 0, 0};
        mma16816(m0, af[0], km[0], km[1]); mma16816(m1, af[1], km[2], km[3]);
        mma16816(m0, af[2], km[4], km[5]); mma16816(m1, af[3], km[6], km[7]);
        unsigned x = __float_as_uint(m0[0] + m1[0]), y = __float_as_uint(m0[1] + m1[1]);
        st_async_b64(aSr + 256, x, y, mbSr); st_async_b64(aSl + 256, x, y, mbSl);
      }
      unsigned x = __float_as_uint(s0[0] + s1[0]), y = __float_as_uint(s0[1] + s1[1]);
      st_async_b64(aSr, x, y, mbSr); st_async_b64(aSl, x, y, mbSl);
      RSTAMP(6);
      if (s == NSEG - 1) break;
      WO_PREFETCH();
      RSTAMP(7); RSTAMP(8); RSTAMP(9); RSTAMP(10);
      bar_sync(1, 256);
    }
    RSTAMP(11);
    float d0[4] = {0, 0, 0, 0}, d1[4] = {0, 0, 0, 0}, e0[4] = {0, 0, 0, 0}, e1[4] = {0, 0, 0, 0};
    unsigned ob[4][4];
#pragma unroll
    for (int k2 = 0; k2 < 4; k2++) ldsm_x4(ob[k2], aOld + k2 * 64);
#pragma unroll
    for (int i = NPRE; i < 4; i++) { ldsm_x4_t(f[2 * i], pW0 + 32768 + i * 2048); ldsm_x4_t(f[2 * i + 1], pW1 + 32768 + i * 2048); }
    mma16816(d0, wo[0], ob[0][0], ob[0][1]); mma16816(d1, wo[1], ob[0][0], ob[0][1]);
    mma16816(e0, wo[2], ob[0][2], ob[0][3]); mma16816(e1, wo[3], ob[0][2], ob[0][3]);
    mma16816(d0, wo[4], ob[1][0], ob[1][1]); mma16816(d1, wo[5], ob[1][0], ob[1][1]);
    mma16816(e0, wo[6], ob[1][2], ob[1][3]); mma16816(e1, wo[7], ob[1][2], ob[1][3]);
    mma16816(d0, f[0], ob[2][0], ob[2][1]); mma16816(d1, f[1], ob[2][0], ob[2][1]);
    mma16816(e0, f[2], ob[2][2], ob[2][3]); mma16816(e1, f[3], ob[2][2], ob[2][3]);
    mma16816(d0, f[4], ob[3][0], ob[3][1]); mma16816(d1, f[5], ob[3][0], ob[3][1]);
    mma16816(e0, f[6], ob[3][2], ob[3][3]); mma16816(e1, f[7], ob[3][2], ob[3][3]);
    const unsigned tag = ((s >> 1) & 1) ^ 1;
    const char* pbase = reinterpret_cast<const char*>(g_part) + par * (NREC * NH * 256);
    {
      const char* dst = pbase + oPd;
#define PST(ptr, x, y) asm volatile("st.relaxed.gpu.global.v2.u32 [%0], {%1,%2};" ::"l"(ptr), "r"((__float_as_uint(x) & ~1u) | tag), "r"((__float_as_uint(y) & ~1u) | tag) : "memory")
      PST(dst, d0[0] + e0[0], d0[1] + e0[1]); PST(dst + NH * 256, d0[2] + e0[2], d0[3] + e0[3]);
      PST(dst + 2 * NH * 256, d1[0] + e1[0], d1[1] + e1[1]); PST(dst + 3 * NH * 256, d1[2] + e1[2], d1[3] + e1[3]);
    }
    RSTAMP(12);
    if (t == 128) {
      mbar_arrive(bar + 8 * (MB_EMPTY + slot)); mbar_arrive(bar + 8 * MB_KVR);
      mbar_expect_tx(bar + 8 * MB_S, 2560); mbar_expect_tx(bar + 8 * MB_V, 2048);
    }
    {
      const char* src = pbase + oPs;
      uint4 a, b; unsigned it = 0;
#define OKT(a, b) (!((((a.x ^ tag) | (a.y ^ tag)) | ((a.z ^ tag) | (a.w ^ tag)) | ((b.x ^ tag) | (b.y ^ tag)) | ((b.z ^ tag) | (b.w ^ tag))) & 1u))
#define OKZ(a, b) (min(min(min(a.x, a.y), min(a.z, a.w)), min(min(b.x, b.y), min(b.z, b.w))) != 0)
#define POLL(OK, off) while (true) { a = ldv4_relaxed(src); b = ldv4_relaxed(src + off); if (OK(a, b)) break; spin_check(it); }
      POLL(OKT, 512);
      RSTAMP(13);
      float r0 = __uint_as_float(a.x) + __uint_as_float(b.x), r1 = __uint_as_float(a.y) + __uint_as_float(b.y);
      float r2 = __uint_as_float(a.z) + __uint_as_float(b.z), r3 = __uint_as_float(a.w) + __uint_as_float(b.w);
      __syncwarp();
      r0 += __shfl_xor_sync(~0u, r0, 16); r1 += __shfl_xor_sync(~0u, r1, 16); r2 += __shfl_xor_sync(~0u, r2, 16); r3 += __shfl_xor_sync(~0u, r3, 16);
      if (lane < 16) asm volatile("st.shared.v4.f32 [%0], {%1,%2,%3,%4};" ::"r"(aRst), "f"(r0), "f"(r1), "f"(r2), "f"(r3) : "memory");
    }
    const char* pub = reinterpret_cast<const char*>(g_pub) + (s + 1) * 8192;
    if (w != 0) { bar_arrive(3, 256); if (BAR8) bar_sync(8, 256); }
    else {
      bar_sync(3, 256);
      RSTAMP(14);
      float x[8], y[8];
#pragma unroll
      for (int i = 0; i < 8; i++) { x[i] = lds32f(aRld + i * 256); y[i] = lds32f(aRld + i * 256 + 32); }
      unsigned u = pack_bf16(((x[0] + x[1]) + (x[2] + x[3])) + ((x[4] + x[5]) + (x[6] + x[7])), ((y[0] + y[1]) + (y[2] + y[3])) + ((y[4] + y[5]) + (y[6] + y[7])));
      if (u == 0) u = 0x80000000u;
      asm volatile("st.relaxed.gpu.global.u32 [%0], %1;" ::"l"(pub + c * 128 + (oPub >> 2)), "r"(u) : "memory");
      if (BAR8) bar_arrive(8, 256);
    }
    RSTAMP(15);
    mbar_wait(bar + 8 * MB_KVF, par);
    {
      const char* src = pub + oPub;
      uint4 a, b; unsigned it = 0;
      POLL(OKZ, 4096);
      sts128(aMem, a); sts128(aMem + 512, b);
    }
  }
}

__device__ __forceinline__ void rec_ring(const Maps& maps, unsigned sb) {
  const int c = blockIdx.x, h = c >> 1, j = c & 1;
  const unsigned bar = sb + SM_BAR;
  const int lane = threadIdx.x & 31;
  if (lane == 0) {
    mbar_expect_tx(bar + 8 * MB_W0, 131072);
    for (int kb = 0; kb < 8; kb++) tma_load_2d(sb + R_WO + kb * 8192, &maps.wq, h * 128 + j * 64, kb * 64, bar + 8 * MB_W0);
    for (int kb = 0; kb < 8; kb++) tma_load_2d(sb + R_T1 + kb * 8192, &maps.wk, h * 128 + j * 64, kb * 64, bar + 8 * MB_W0);
    mbar_expect_tx(bar + 8 * MB_W1, 65536);
    for (int kb = 0; kb < 8; kb++) tma_load_2d(sb + R_T2 + kb * 8192, &maps.wv, h * 128 + j * 64, kb * 64, bar + 8 * MB_W1);
  }
  __syncwarp();
  bar_sync(2, 288);
  if (lane == 0) {
    fence_proxy_async_smem();
    for (int s = 0; s < NSEG; s++) {
      unsigned slot = s & (RING_N - 1);
      if ((s & 3) == 0 && !DBGMODE) {
        wait_flag_ge(&g_flags.qkv[(s >> 2) * 48 + 16 + (h >> 1)], 1);
        wait_flag_ge(&g_flags.qkv[(s >> 2) * 48 + 32 + (h >> 1)], 1);
        fence_proxy_async();
      }
      if (s >= RING_N) mbar_wait_sleep(bar + 8 * (MB_EMPTY + slot), ((s / RING_N) - 1) & 1);
      unsigned dst = sb + R_RING + slot * RING_BYTES, mb = bar + 8 * (MB_FULL + slot);
      mbar_expect_tx(mb, RING_BYTES);
      tma_load_2d(dst, &maps.qkv_ld, HD + h * 128 + j * 64, s * SEG, mb);
      tma_load_2d(dst + 4096, &maps.qkv_ld, 2 * HD + h * 128, s * SEG, mb);
      tma_load_2d(dst + 8192, &maps.qkv_ld, 2 * HD + h * 128 + 64, s * SEG, mb);
    }
  }
}
__device__ __forceinline__ void rec_copy(unsigned sb) {
  const int c = blockIdx.x, h = c >> 1, j = c & 1;
  const unsigned bar = sb + SM_BAR;
  const int lane = threadIdx.x & 31;
  for (int s = 0; s < NSEG; s++) {
    mbar_wait_sleep(bar + 8 * MB_KVR, s & 1);
    uint4 k0 = lds128(sb + R_KS + (lane >> 3) * 144 + (lane & 7) * 16), k1 = lds128(sb + R_KS + (4 + (lane >> 3)) * 144 + (lane & 7) * 16);
    uint2 v[4];
#pragma unroll
    for (int i = 0; i < 4; i++) v[i] = lds64(sb + R_VM + (j * 4 + i) * 256 + lane * 8);
    __syncwarp();
    if (lane == 0) mbar_arrive(bar + 8 * MB_KVF);
    bf16* kd = g_km + ((size_t)(s * NH + h) * NMEM) * DH + j * 64;
    *reinterpret_cast<uint4*>(kd + (lane >> 3) * DH + (lane & 7) * 8) = k0;
    *reinterpret_cast<uint4*>(kd + (4 + (lane >> 3)) * DH + (lane & 7) * 8) = k1;
    unsigned* vd = reinterpret_cast<unsigned*>(g_vmt) + ((size_t)(s * NH + h) * DH + j * 64) * 4;
#pragma unroll
    for (int i = 0; i < 4; i++) { vd[(i * 16) * 4 + lane] = v[i].x; vd[(i * 16 + 8) * 4 + lane] = v[i].y; }
    __syncwarp();
    if (lane == 0) st_release(&g_flags.rec[c], s + 1);
  }
}

__device__ __forceinline__ void bulk_producer(const Maps& maps, unsigned sb, int* misc) {
  const unsigned bar = sb + SM_BAR;
  unsigned st = 0, ph = 0, seq = 0;
  while (true) {
    int idx = (int)atomicAdd(&g_flags.ctr, 1u);
    if (idx >= N_ITEMS) {
      mbar_wait(bar + 8 * (MB_EMPTY + st), ph ^ 1);
      misc[seq & 3] = -1;
      mbar_arrive(bar + 8 * (MB_FULL + st));
      break;
    }
    ISTAMP(idx, 0);
    Item it = decode_item(idx);
    const CUtensorMap *ma, *mb_; int ka = 0, kbr = 0, nb0 = it.c * 256;
    if (it.type == T_QKV) { ma = &maps.xn; mb_ = it.c < 16 ? &maps.wq : (it.c < 32 ? &maps.wk : &maps.wv); nb0 = (it.c & 15) * 256; }
    else if (it.type == T_M1) { ma = &maps.y; mb_ = &maps.w1; }
    else if (it.type == T_M2) { ma = &maps.h1; mb_ = &maps.w2; wait_flag_ge(&g_flags.h1[it.b], 7); }
    else if (it.type == T_OUT) { ma = &maps.o; mb_ = &maps.wo; ka = kbr = it.ks * 1024; wait_flag_ge(&g_flags.o[it.b * 4 + it.ks], 4); }
    else if (it.type == T_OUTL) { ma = &maps.o; mb_ = &maps.wo; ka = kbr = it.ks * 256; wait_flag_ge(&g_flags.o16[it.ks], 1); }
    else if (it.type >= T_RED) { ma = mb_ = &maps.o; wait_flag_ge(&g_flags.g[it.b], 2); wait_flag_ge(&g_flags.p[it.b], it.type == T_RED ? 8 : 32); }
    else {
      ma = mb_ = &maps.qkv_ld;
      wait_flag_ge(&g_flags.qkv[it.b * 48 + it.c], 1); wait_flag_ge(&g_flags.qkv[it.b * 48 + 16 + it.c], 1); wait_flag_ge(&g_flags.qkv[it.b * 48 + 32 + it.c], 1);
      for (int i = 0; i < 4; i++) wait_flag_ge(&g_flags.rec[it.c * 4 + i], it.b * 4 + 2);
    }
    fence_proxy_async();
    ISTAMP(idx, 1);
    const int nkb = item_nkb(it.type);
    for (int kb = 0; kb < nkb; kb++) {
      mbar_wait(bar + 8 * (MB_EMPTY + st), ph ^ 1);
      if (kb == 0) { misc[seq & 3] = idx; seq++; }
      unsigned dst = sb + st * STAGE_BYTES, mb = bar + 8 * (MB_FULL + st);
      if (it.type >= T_RED) { mbar_arrive(mb); if (++st == NSTAGE) { st = 0; ph ^= 1; } break; }
      if (it.type == T_ATT && kb == 2) for (int i = 0; i < 4; i++) wait_flag_ge(&g_flags.rec[it.c * 4 + i], it.b * 4 + 4);
      mbar_expect_tx(mb, STAGE_BYTES);
      if (it.type == T_ATT) {
        int head = it.c * 2 + (kb & 1), row = it.b * 128 + (kb >> 1) * 64;
        for (int i = 0; i < 12; i++) tma_load_2d(dst + i * 4096, ma, (i >> 2) * HD + head * 128 + (i & 1) * 64, row + ((i >> 1) & 1) * 32, mb);
      } else {
        tma_load_2d(dst, ma, ka + kb * 64, it.b * 128, mb);
        for (int i = 0; i < 4; i++) tma_load_2d(dst + 16384 + i * 8192, mb_, nb0 + i * 64, kbr + kb * 64, mb);
      }
      if (++st == NSTAGE) { st = 0; ph ^= 1; }
    }
  }
}
__device__ __forceinline__ void bulk_store(const Maps& maps, unsigned sb, volatile int* misc) {
  const unsigned bar = sb + SM_BAR;
  unsigned ph = 0;
  while (true) {
    mbar_wait(bar + 8 * MB_STGF, ph); ph ^= 1;
    int idx = misc[4];
    if (idx < 0) break;
    Item it = decode_item(idx);
    const CUtensorMap* mp = it.type == T_QKV ? &maps.qkv_st : (it.type == T_M1 ? &maps.h1 : (it.type == T_M2 ? &maps.g : &maps.o));
    unsigned* flag = it.type == T_QKV ? &g_flags.qkv[it.b * 48 + it.c] : (it.type == T_M1 ? &g_flags.h1[it.b] : (it.type == T_M2 ? &g_flags.g[it.b] : (it.b == 15 ? &g_flags.o16[it.c] : &g_flags.o[it.b * 4 + (it.c >> 2)])));
    for (int i = 0; i < 4; i++) tma_store_2d(mp, sb + B_STG + i * 16384, it.c * 256 + i * 64, it.b * 128);
    asm volatile("cp.async.bulk.commit_group;" ::: "memory");
    asm volatile("cp.async.bulk.wait_group.read 0;" ::: "memory");
    mbar_arrive(bar + 8 * MB_STGE);
    asm volatile("cp.async.bulk.wait_group 0;" ::: "memory");
    fence_proxy_async();
    red_release_add(flag, 1);
    ISTAMP(idx, 3);
  }
}
__device__ __forceinline__ float gelu_t(float x) {
  float u = 0.7978845608028654f * (x + 0.044715f * x * x * x);
  return __fdividef(x, 1.0f + __expf(-2.0f * u));
}
__device__ __forceinline__ float silu_f(float x) { return __fdividef(x, 1.0f + __expf(-x)); }

__device__ __forceinline__ void final_out(bf16* __restrict__ out, const bf16* __restrict__ x, size_t o, float4 s) {
  uint2 gv = __ldcg(reinterpret_cast<const uint2*>(g_g + o)), xv = __ldg(reinterpret_cast<const uint2*>(x + o));
  uint2 r;
  r.x = pack_bf16(bf_lo(xv.x) + bf16r(bf16r(s.x) * bf_lo(gv.x)), bf_hi(xv.x) + bf16r(bf16r(s.y) * bf_hi(gv.x)));
  r.y = pack_bf16(bf_lo(xv.y) + bf16r(bf16r(s.z) * bf_lo(gv.y)), bf_hi(xv.y) + bf16r(bf16r(s.w) * bf_hi(gv.y)));
  *reinterpret_cast<uint2*>(out + o) = r;
}
__device__ __forceinline__ void bulk_att_stage(unsigned sa, unsigned stg, int b, int hp, int kb, int w, int lane) {
  const int g = lane >> 2, tq = lane & 3, m = lane >> 3, r8 = lane & 7;
  const int seg = w >> 2, mt = (w >> 1) & 1, eh = w & 1;
  const int head = hp * 2 + (kb & 1), sg = b * 4 + (kb >> 1) * 2 + seg;
  const unsigned* kmp = reinterpret_cast<const unsigned*>(g_km + ((size_t)(sg * NH + head) * NMEM + g) * DH) + tq;
  const unsigned* vmp = reinterpret_cast<const unsigned*>(g_vmt) + ((size_t)(sg * NH + head) * DH + eh * 64) * 4 + lane;
  unsigned km[16], vm[8];
#pragma unroll
  for (int i = 0; i < 16; i++) km[i] = __ldcg(kmp + i * 4);
#pragma unroll
  for (int i = 0; i < 8; i++) vm[i] = __ldcg(vmp + i * 32);
  float s[5][4];
#pragma unroll
  for (int i = 0; i < 5; i++) { s[i][0] = s[i][1] = s[i][2] = s[i][3] = 0; }
  const unsigned qb = sa + (0 * 2 + seg) * 8192, kbs = sa + (1 * 2 + seg) * 8192, vb = sa + (2 * 2 + seg) * 8192 + eh * 4096;
  unsigned qa[8][4];
#pragma unroll
  for (int ks = 0; ks < 8; ks++) {
    int row = mt * 16 + (m & 1) * 8 + r8;
    ldsm_x4(qa[ks], qb + (ks >> 2) * 4096 + row * 128 + ((((ks & 3) * 2 + (m >> 1)) ^ r8) << 4));
    unsigned kf[4];
    int krow = (m >> 1) * 8 + r8;
    unsigned ka = kbs + (ks >> 2) * 4096 + krow * 128 + ((((ks & 3) * 2 + (m & 1)) ^ r8) << 4);
    ldsm_x4(kf, ka);
    mma16816(s[0], qa[ks], kf[0], kf[1]); mma16816(s[1], qa[ks], kf[2], kf[3]);
    if (mt) { ldsm_x4(kf, ka + 2048); mma16816(s[2], qa[ks], kf[0], kf[1]); mma16816(s[3], qa[ks], kf[2], kf[3]); }
  }
#pragma unroll
  for (int ks = 0; ks < 8; ks++) mma16816(s[4], qa[ks], km[2 * ks], km[2 * ks + 1]);
  float mx0 = -INFINITY, mx1 = -INFINITY;
  const int t0 = mt * 16 + g, t1 = t0 + 8;
#pragma unroll
  for (int i = 0; i < 5; i++) {
#pragma unroll
    for (int e = 0; e < 4; e++) {
      float v = s[i][e];
      if (i < 4) { int kj = i * 8 + 2 * tq + (e & 1); if (kj > (e < 2 ? t0 : t1)) v = -INFINITY; }
      s[i][e] = v;
      if (e < 2) mx0 = fmaxf(mx0, v); else mx1 = fmaxf(mx1, v);
    }
  }
  mx0 = fmaxf(mx0, __shfl_xor_sync(~0u, mx0, 1)); mx0 = fmaxf(mx0, __shfl_xor_sync(~0u, mx0, 2));
  mx1 = fmaxf(mx1, __shfl_xor_sync(~0u, mx1, 1)); mx1 = fmaxf(mx1, __shfl_xor_sync(~0u, mx1, 2));
  float sm0 = 0, sm1 = 0;
#pragma unroll
  for (int i = 0; i < 5; i++) {
    s[i][0] = ex2f((s[i][0] - mx0) * (SCALE_QK * LOG2E)); s[i][1] = ex2f((s[i][1] - mx0) * (SCALE_QK * LOG2E));
    s[i][2] = ex2f((s[i][2] - mx1) * (SCALE_QK * LOG2E)); s[i][3] = ex2f((s[i][3] - mx1) * (SCALE_QK * LOG2E));
    sm0 += s[i][0] + s[i][1]; sm1 += s[i][2] + s[i][3];
  }
  sm0 += __shfl_xor_sync(~0u, sm0, 1); sm0 += __shfl_xor_sync(~0u, sm0, 2);
  sm1 += __shfl_xor_sync(~0u, sm1, 1); sm1 += __shfl_xor_sync(~0u, sm1, 2);
  const float i0 = __fdividef(1.0f, sm0), i1 = __fdividef(1.0f, sm1);
  unsigned pa[2][4], pm0, pm1;
#pragma unroll
  for (int kk = 0; kk < 2; kk++) {
    pa[kk][0] = pack_bf16(s[2 * kk][0] * i0, s[2 * kk][1] * i0); pa[kk][1] = pack_bf16(s[2 * kk][2] * i1, s[2 * kk][3] * i1);
    pa[kk][2] = pack_bf16(s[2 * kk + 1][0] * i0, s[2 * kk + 1][1] * i0); pa[kk][3] = pack_bf16(s[2 * kk + 1][2] * i1, s[2 * kk + 1][3] * i1);
  }
  pm0 = pack_bf16(s[4][0] * i0, s[4][1] * i0); pm1 = pack_bf16(s[4][2] * i1, s[4][3] * i1);
  const int orow = (kb >> 1) * 64 + seg * 32 + mt * 16 + (m & 1) * 8 + r8;
  const unsigned ob = stg + ((kb & 1) * 2 + eh) * 16384 + orow * 128;
#pragma unroll
  for (int cp = 0; cp < 4; cp++) {
    float o0[4] = {0, 0, 0, 0}, o1[4] = {0, 0, 0, 0};
    mma1688(o0, pm0, pm1, vm[2 * cp]); mma1688(o1, pm0, pm1, vm[2 * cp + 1]);
    unsigned vf[4];
    int row = (m & 1) * 8 + r8;
    unsigned va = vb + row * 128 + (((cp * 2 + (m >> 1)) ^ r8) << 4);
    ldsm_x4_t(vf, va);
    mma16816(o0, pa[0], vf[0], vf[1]); mma16816(o1, pa[0], vf[2], vf[3]);
    if (mt) { ldsm_x4_t(vf, va + 2048); mma16816(o0, pa[1], vf[0], vf[1]); mma16816(o1, pa[1], vf[2], vf[3]); }
    stsm_x4(ob + (((cp * 2 + (m >> 1)) ^ r8) << 4), pack_bf16(o0[0], o0[1]), pack_bf16(o0[2], o0[3]), pack_bf16(o1[0], o1[1]), pack_bf16(o1[2], o1[3]));
  }
}

__device__ __forceinline__ void bulk_worker(unsigned sb, volatile int* misc, const bf16* __restrict__ x, const bf16* __restrict__ b1, const bf16* __restrict__ b2, bf16* __restrict__ out) {
  const int t = threadIdx.x, lane = t & 31, w = t >> 5, wg = w >> 2, g = lane >> 2, tq = lane & 3, m = lane >> 3, r8 = lane & 7;
  const unsigned bar = sb + SM_BAR;
  unsigned st = 0, ph = 0, seq = 0, sph = 0;
  float d[128];
  while (true) {
    mbar_wait(bar + 8 * (MB_FULL + st), ph);
    const int idx = misc[seq & 3]; seq++;
    if (idx < 0 || idx >= N_ITEMS) break;
    if (t == 0) ISTAMP(idx, 2);
    const Item it = decode_item(idx);
    const int nkb = item_nkb(it.type);
    if (it.type == T_ATT) {
      mbar_wait(bar + 8 * MB_STGE, sph ^ 1);
      for (int kb = 0; kb < 4; kb++) {
        if (kb) mbar_wait(bar + 8 * (MB_FULL + st), ph);
        bulk_att_stage(sb + st * STAGE_BYTES, sb + B_STG, it.b, it.c, kb, w, lane);
        __syncwarp();
        if (lane == 0) mbar_arrive(bar + 8 * (MB_EMPTY + st));
        if (++st == NSTAGE) { st = 0; ph ^= 1; }
      }
      if (t == 0) misc[4] = idx;
      fence_proxy_async_smem();
      mbar_arrive(bar + 8 * MB_STGF); sph ^= 1;
      continue;
    }
    if (it.type >= T_RED) {
      __syncwarp();
      if (lane == 0) mbar_arrive(bar + 8 * (MB_EMPTY + st));
      if (++st == NSTAGE) { st = 0; ph ^= 1; }
      if (it.type == T_RED) {
#pragma unroll 2
        for (int i = 0; i < 8; i++) {
          size_t o = ((size_t)it.b * 128 + it.c * 16 + i * 2 + (t >> 7)) * DM + (t & 127) * 4;
          float4 a = __ldcg(reinterpret_cast<const float4*>(g_opart + o)), b = __ldcg(reinterpret_cast<const float4*>(g_opart + o + (size_t)S_TOK * DM));
          float4 c = __ldcg(reinterpret_cast<const float4*>(g_opart + o + (size_t)2 * S_TOK * DM)), e = __ldcg(reinterpret_cast<const float4*>(g_opart + o + (size_t)3 * S_TOK * DM));
          final_out(out, x, o, make_float4((a.x + b.x) + (c.x + e.x), (a.y + b.y) + (c.y + e.y), (a.z + b.z) + (c.z + e.z), (a.w + b.w) + (c.w + e.w)));
        }
      } else {
        size_t ol = ((size_t)it.c * 2 + (t >> 7)) * DM + (t & 127) * 4;
        float4 v[16];
#pragma unroll
        for (int i = 0; i < 16; i++) v[i] = __ldcg(reinterpret_cast<const float4*>(g_opl + ol + (size_t)i * 128 * DM));
#pragma unroll
        for (int st2 = 1; st2 < 16; st2 <<= 1)
#pragma unroll
          for (int i = 0; i < 16; i += 2 * st2) { v[i].x += v[i + st2].x; v[i].y += v[i + st2].y; v[i].z += v[i + st2].z; v[i].w += v[i + st2].w; }
        final_out(out, x, ol + (size_t)15 * 128 * DM, v[0]);
      }
      if (t == 0) ISTAMP(idx, 3);
      continue;
    }
    unsigned pst = 0;
    for (int kb = 0; kb < nkb; kb++) {
      if (kb) mbar_wait(bar + 8 * (MB_FULL + st), ph);
      unsigned sa = sb + st * STAGE_BYTES;
      uint64_t ad = mkdesc(sa + wg * 8192, 16, 1024), bd = mkdesc(sa + 16384, 8192, 1024);
      asm volatile("wgmma.fence.sync.aligned;" ::: "memory");
#pragma unroll
      for (int k = 0; k < 4; k++) wgmma_n256(d, ad + k * 2, bd + k * 128, (kb | k) != 0);
      asm volatile("wgmma.commit_group.sync.aligned;" ::: "memory");
      if (kb) {
        asm volatile("wgmma.wait_group.sync.aligned 1;" ::: "memory");
        if (lane == 0) mbar_arrive(bar + 8 * (MB_EMPTY + pst));
      }
      pst = st;
      if (++st == NSTAGE) { st = 0; ph ^= 1; }
    }
    asm volatile("wgmma.wait_group.sync.aligned 0;" ::: "memory");
    if (lane == 0) mbar_arrive(bar + 8 * (MB_EMPTY + pst));
    if (it.type >= T_OUT) {
      const int col = it.c * 256 + 2 * tq;
      float* pp = it.type == T_OUT ? g_opart + ((size_t)it.ks * S_TOK + it.b * 128 + w * 16 + g) * DM + col : g_opl + ((size_t)it.ks * 128 + w * 16 + g) * DM + col;
#pragma unroll
      for (int i = 0; i < 32; i++) {
        __stcg(reinterpret_cast<float2*>(pp + i * 8), make_float2(d[4 * i], d[4 * i + 1]));
        __stcg(reinterpret_cast<float2*>(pp + 8 * DM + i * 8), make_float2(d[4 * i + 2], d[4 * i + 3]));
      }
      bar_sync(1, 256);
      if (t == 0) { red_release_add(&g_flags.p[it.b], 1); ISTAMP(idx, 3); }
      continue;
    }
    if (it.type != T_QKV) {
      const unsigned* bp = reinterpret_cast<const unsigned*>((it.type == T_M1 ? b1 : b2) + it.c * 256) + tq;
#pragma unroll
      for (int i = 0; i < 32; i++) {
        unsigned bv = __ldg(bp + i * 4);
        float lo = bf_lo(bv), hi = bf_hi(bv);
        float x0 = bf16r(bf16r(d[4 * i]) + lo), x1 = bf16r(bf16r(d[4 * i + 1]) + hi), x2 = bf16r(bf16r(d[4 * i + 2]) + lo), x3 = bf16r(bf16r(d[4 * i + 3]) + hi);
        if (it.type == T_M1) { d[4 * i] = gelu_t(x0); d[4 * i + 1] = gelu_t(x1); d[4 * i + 2] = gelu_t(x2); d[4 * i + 3] = gelu_t(x3); }
        else { d[4 * i] = silu_f(x0); d[4 * i + 1] = silu_f(x1); d[4 * i + 2] = silu_f(x2); d[4 * i + 3] = silu_f(x3); }
      }
    }
    mbar_wait(bar + 8 * MB_STGE, sph ^ 1);
    {
      const unsigned ob = sb + B_STG + (w * 16 + (m & 1) * 8 + r8) * 128;
#pragma unroll
      for (int i = 0; i < 16; i++)
        stsm_x4(ob + (i >> 2) * 16384 + ((((i & 3) * 2 + (m >> 1)) ^ r8) << 4), pack_bf16(d[8 * i], d[8 * i + 1]), pack_bf16(d[8 * i + 2], d[8 * i + 3]),
                pack_bf16(d[8 * i + 4], d[8 * i + 5]), pack_bf16(d[8 * i + 6], d[8 * i + 7]));
    }
    if (t == 0) misc[4] = idx;
    fence_proxy_async_smem();
    mbar_arrive(bar + 8 * MB_STGF); sph ^= 1;
  }
  mbar_wait(bar + 8 * MB_STGE, sph ^ 1);
  if (t == 0) misc[4] = -1;
  mbar_arrive(bar + 8 * MB_STGF);
}

__global__ void __cluster_dims__(2, 1, 1) __launch_bounds__(384, 1)
k_main(const __grid_constant__ Maps maps, const bf16* __restrict__ x, const bf16* __restrict__ mem0, const bf16* __restrict__ b1, const bf16* __restrict__ b2, bf16* __restrict__ out) {
  extern __shared__ unsigned char smem_raw[];
  const unsigned sraw = smem_u32(smem_raw);
  const unsigned sb = (sraw + 1023u) & ~1023u;
  int* misc = reinterpret_cast<int*>(smem_raw + (sb - sraw) + SM_MISC);
  const int w = threadIdx.x >> 5;
  const bool rec = blockIdx.x < NREC;
  if (threadIdx.x == 0) {
    const unsigned bar = sb + SM_BAR;
    for (int i = 0; i < 8; i++) { mbar_init(bar + 8 * (MB_FULL + i), 1); mbar_init(bar + 8 * (MB_EMPTY + i), rec ? 1 : 8); }
    mbar_init(bar + 8 * MB_STGF, 256); mbar_init(bar + 8 * MB_STGE, 1);
    for (int i = MB_W0; i <= MB_KVF; i++) mbar_init(bar + 8 * i, 1);
    asm volatile("fence.mbarrier_init.release.cluster;" ::: "memory");
  }
  __syncthreads();
  asm volatile("barrier.cluster.arrive.release.aligned;\nbarrier.cluster.wait.acquire.aligned;" ::: "memory");
  if (DBGMODE && !rec) return;
  if (w >= 8) {
    asm volatile("setmaxnreg.dec.sync.aligned.u32 24;");
    if (rec) { if (w == 8) rec_ring(maps, sb); else if (w == 9) rec_copy(sb); }
    else if ((threadIdx.x & 31) == 0) { if (w == 8) bulk_producer(maps, sb, misc); else if (w == 9) bulk_store(maps, sb, misc); }
  } else {
    if (rec) { asm volatile("setmaxnreg.inc.sync.aligned.u32 240;"); rec_worker(maps, sb, mem0); }
    else { asm volatile("setmaxnreg.inc.sync.aligned.u32 240;"); bulk_worker(sb, misc, x, b1, b2, out); }
  }
}

typedef CUresult (*EncFn)(CUtensorMap*, CUtensorMapDataType, cuuint32_t, void*, const cuuint64_t*, const cuuint64_t*, const cuuint32_t*, const cuuint32_t*,
                          CUtensorMapInterleave, CUtensorMapSwizzle, CUtensorMapL2promotion, CUtensorMapFloatOOBfill);
static void mk_map(EncFn enc, CUtensorMap* m, const void* ptr, uint64_t rows, uint64_t cols, uint32_t box_rows) {
  cuuint64_t dims[2] = {cols, rows}; cuuint64_t strides[1] = {cols * 2};
  cuuint32_t box[2] = {64, box_rows}, es[2] = {1, 1};
  enc(m, CU_TENSOR_MAP_DATA_TYPE_BFLOAT16, 2, const_cast<void*>(ptr), dims, strides, box, es, CU_TENSOR_MAP_INTERLEAVE_NONE, CU_TENSOR_MAP_SWIZZLE_128B,
      CU_TENSOR_MAP_L2_PROMOTION_L2_256B, CU_TENSOR_MAP_FLOAT_OOB_FILL_NONE);
}
extern "C" void kernel_launch(void* const* d_in, const int* in_sizes, int n_in, void* d_out, int out_size) {
  static EncFn enc = nullptr;
  static void *p_xn, *p_y, *p_h1, *p_o, *p_qkv, *p_g;
  if (!enc) {
    void* fn = nullptr; cudaDriverEntryPointQueryResult qr;
    cudaGetDriverEntryPoint("cuTensorMapEncodeTiled", &fn, cudaEnableDefault, &qr);
    enc = (EncFn)fn;
    cudaGetSymbolAddress(&p_xn, g_xn); cudaGetSymbolAddress(&p_y, g_y); cudaGetSymbolAddress(&p_h1, g_h1);
    cudaGetSymbolAddress(&p_o, g_o); cudaGetSymbolAddress(&p_qkv, g_qkv); cudaGetSymbolAddress(&p_g, g_g);
    cudaFuncSetAttribute(k_main, cudaFuncAttributeMaxDynamicSharedMemorySize, SMEM_TOTAL);
  }
  Maps maps;
  mk_map(enc, &maps.xn, p_xn, S_TOK, DM, 128); mk_map(enc, &maps.y, p_y, S_TOK, DM, 128); mk_map(enc, &maps.h1, p_h1, S_TOK, FF, 128);
  mk_map(enc, &maps.o, p_o, S_TOK, HD, 128); mk_map(enc, &maps.qkv_st, p_qkv, S_TOK, 3 * HD, 128); mk_map(enc, &maps.qkv_ld, p_qkv, S_TOK, 3 * HD, 32);
  mk_map(enc, &maps.g, p_g, S_TOK, DM, 128);
  mk_map(enc, &maps.wq, d_in[2], DM, HD, 64); mk_map(enc, &maps.wk, d_in[3], DM, HD, 64); mk_map(enc, &maps.wv, d_in[4], DM, HD, 64);
  mk_map(enc, &maps.wo, d_in[5], HD, DM, 64); mk_map(enc, &maps.w1, d_in[8], DM, FF, 64); mk_map(enc, &maps.w2, d_in[10], FF, DM, 64);
  cudaStream_t st = cudaStreamPerThread;
  k_pre<<<256, 256, 0, st>>>((const bf16*)d_in[0]);
  k_main<<<NCTA, 384, SMEM_TOTAL, st>>>(maps, (const bf16*)d_in[0], (const bf16*)d_in[1], (const bf16*)d_in[9], (const bf16*)d_in[11], (bf16*)d_out);
}
```

```cpp
#include <cuda_runtime.h>
#include <cuda_bf16.h>
#include <cuda.h>
#include <stdint.h>

typedef __nv_bfloat16 bf16;

#define S_TOK 2048
#define DM 512
#define NH 32
#define DH 128
#define HD 4096
#define NMEM 8
#define SEG 32
#define NSEG 64
#define FF 1792
#define NBLK 16
#define NREC 64
#define CLS 8

__device__ __align__(1024) bf16 g_xn[S_TOK * DM];
__device__ __align__(1024) bf16 g_y[S_TOK * DM];
__device__ __align__(1024) bf16 g_qkv[(size_t)S_TOK * 3 * HD];
__device__ __align__(1024) bf16 g_h1[S_TOK * FF];
__device__ __align__(1024) bf16 g_g[S_TOK * DM];
__device__ __align__(1024) bf16 g_o[(size_t)S_TOK * HD];
__device__ __align__(1024) bf16 g_km[NSEG * NH * NMEM * DH];
__device__ __align__(1024) bf16 g_vmt[NSEG * NH * DH * NMEM];
__device__ __align__(1024) float g_opart[(size_t)4 * S_TOK * DM];
__device__ __align__(1024) float g_opl[(size_t)16 * 128 * DM];
__device__ __align__(1024) unsigned g_part[2 * 8 * 8 * 512];
struct Flags {
  unsigned qkv[NBLK * 48];
  unsigned h1[NBLK];
  unsigned g[NBLK];
  unsigned o[NBLK * 4];
  unsigned p[NBLK];
  unsigned o16[16];
  unsigned ctr;
  unsigned rec[NREC];
  unsigned abort_;
};
__device__ __align__(1024) Flags g_flags;

#define RSTAMP(k)
#define DBGMODE 0
#define ISTAMP(i, k)
__device__ __forceinline__ unsigned smem_u32(const void* p) { return (unsigned)__cvta_generic_to_shared(p); }
__device__ __forceinline__ float bf16r(float x) { unsigned u; asm("cvt.rn.bf16x2.f32 %0, %1, %2;" : "=r"(u) : "f"(x), "f"(0.0f)); return __uint_as_float(u); }
__device__ __forceinline__ unsigned pack_bf16(float lo, float hi) {
  __nv_bfloat162 v = __floats2bfloat162_rn(lo, hi);
  return *reinterpret_cast<unsigned*>(&v);
}
__device__ __forceinline__ float bf_lo(unsigned u) { return __uint_as_float(u << 16); }
__device__ __forceinline__ float bf_hi(unsigned u) { return __uint_as_float(u & 0xffff0000u); }

#define SPIN_LIMIT (1u << 20)
#define TRAP_IF(x) if ((x) > SPIN_LIMIT) { asm volatile("st.global.u32 [%0], %1;" ::"l"(0ull), "r"(0u) : "memory"); break; }
__device__ __forceinline__ unsigned ld_acquire(const unsigned* p) {
  unsigned v; asm volatile("ld.acquire.gpu.global.u32 %0, [%1];" : "=r"(v) : "l"(p) : "memory"); return v;
}
__device__ __forceinline__ unsigned ld_relaxed(const unsigned* p) {
  unsigned v; asm volatile("ld.relaxed.gpu.global.u32 %0, [%1];" : "=r"(v) : "l"(p) : "memory"); return v;
}
__device__ __forceinline__ void red_release_add(unsigned* p, unsigned v) {
  asm volatile("red.release.gpu.global.add.u32 [%0], %1;" ::"l"(p), "r"(v) : "memory");
}
__device__ __forceinline__ void st_release(unsigned* p, unsigned v) {
  asm volatile("st.release.gpu.global.u32 [%0], %1;" ::"l"(p), "r"(v) : "memory");
}
__device__ __forceinline__ void wait_flag_ge(const unsigned* p, unsigned target) {
  unsigned it = 0;
  while (ld_acquire(p) < target) {
    __nanosleep(64);
    TRAP_IF(++it);
  }
}
__device__ __forceinline__ uint4 ldv4_relaxed(const void* p) {
  uint4 a; asm volatile("ld.relaxed.gpu.global.v4.u32 {%0,%1,%2,%3}, [%4];" : "=r"(a.x), "=r"(a.y), "=r"(a.z), "=r"(a.w) : "l"(p) : "memory"); return a;
}
__device__ __forceinline__ uint2 ldv2_relaxed(const void* p) {
  uint2 a; asm volatile("ld.relaxed.gpu.global.v2.u32 {%0,%1}, [%2];" : "=r"(a.x), "=r"(a.y) : "l"(p) : "memory"); return a;
}
__device__ __forceinline__ void mbar_init(unsigned mb, unsigned cnt) { asm volatile("mbarrier.init.shared::cta.b64 [%0], %1;" ::"r"(mb), "r"(cnt) : "memory"); }
__device__ __forceinline__ void mbar_expect_tx(unsigned mb, unsigned bytes) { asm volatile("mbarrier.arrive.expect_tx.shared::cta.b64 _, [%0], %1;" ::"r"(mb), "r"(bytes) : "memory"); }
__device__ __forceinline__ void mbar_arrive(unsigned mb) { asm volatile("mbarrier.arrive.shared::cta.b64 _, [%0];" ::"r"(mb) : "memory"); }
__device__ __forceinline__ void mbar_wait(unsigned mb, unsigned parity) {
  unsigned ok, it = 0;
  while (true) {
    asm volatile("{.reg .pred p; mbarrier.try_wait.parity.shared::cta.b64 p, [%1], %2; selp.u32 %0,1,0,p;}" : "=r"(ok) : "r"(mb), "r"(parity) : "memory");
    if (ok) break;
    TRAP_IF(++it);
  }
}
__device__ __forceinline__ void mbar_wait_sleep(unsigned mb, unsigned parity) {
  unsigned ok, it = 0;
  while (true) {
    asm volatile("{.reg .pred p; mbarrier.test_wait.parity.shared::cta.b64 p, [%1], %2; selp.u32 %0,1,0,p;}" : "=r"(ok) : "r"(mb), "r"(parity) : "memory");
    if (ok) break;
    __nanosleep(200);
    TRAP_IF(++it);
  }
}
__device__ __forceinline__ float ex2f(float x) { float y; asm("ex2.approx.ftz.f32 %0, %1;" : "=f"(y) : "f"(x)); return y; }
__device__ __forceinline__ int opaque_tid() { int t = threadIdx.x; t = __shfl_sync(~0u, t, t & 31); return t; }
#define LOG2E 1.4426950408889634f
__device__ __forceinline__ void mbar_wait_cluster(unsigned mb, unsigned parity) {
  unsigned ok, it = 0;
  while (true) {
    asm volatile("{.reg .pred p; mbarrier.try_wait.parity.acquire.cluster.shared::cta.b64 p, [%1], %2; selp.u32 %0,1,0,p;}" : "=r"(ok) : "r"(mb), "r"(parity) : "memory");
    if (ok) break;
    TRAP_IF(++it);
  }
}
__device__ __forceinline__ void bar_sync(int id, int n) { asm volatile("bar.sync %0, %1;" ::"r"(id), "r"(n) : "memory"); }
__device__ __forceinline__ void bar_arrive(int id, int n) { asm volatile("bar.arrive %0, %1;" ::"r"(id), "r"(n) : "memory"); }
__device__ __forceinline__ void tma_load_2d(unsigned dst, const CUtensorMap* map, int c0, int c1, unsigned mb) {
  asm volatile("cp.async.bulk.tensor.2d.shared::cluster.global.mbarrier::complete_tx::bytes [%0], [%1, {%3, %4}], [%2];"
               ::"r"(dst), "l"((uint64_t)map), "r"(mb), "r"(c0), "r"(c1) : "memory");
}
__device__ __forceinline__ void tma_store_2d(const CUtensorMap* map, unsigned src, int c0, int c1) {
  asm volatile("cp.async.bulk.tensor.2d.global.shared::cta.bulk_group [%0, {%2, %3}], [%1];"
               ::"l"((uint64_t)map), "r"(src), "r"(c0), "r"(c1) : "memory");
}
__device__ __forceinline__ void fence_proxy_async() { asm volatile("fence.proxy.async;" ::: "memory"); }
__device__ __forceinline__ void fence_proxy_async_smem() { asm volatile("fence.proxy.async.shared::cta;" ::: "memory"); }
__device__ __forceinline__ void ldsm_x4(unsigned* r, unsigned addr) {
  asm volatile("ldmatrix.sync.aligned.m8n8.x4.shared.b16 {%0,%1,%2,%3}, [%4];" : "=r"(r[0]), "=r"(r[1]), "=r"(r[2]), "=r"(r[3]) : "r"(addr) : "memory");
}
__device__ __forceinline__ void ldsm_x4_t(unsigned* r, unsigned addr) {
  asm volatile("ldmatrix.sync.aligned.m8n8.x4.trans.shared.b16 {%0,%1,%2,%3}, [%4];" : "=r"(r[0]), "=r"(r[1]), "=r"(r[2]), "=r"(r[3]) : "r"(addr) : "memory");
}
__device__ __forceinline__ void stsm_x2_t(unsigned addr, unsigned r0, unsigned r1) {
  asm volatile("stmatrix.sync.aligned.m8n8.x2.trans.shared.b16 [%0], {%1,%2};" ::"r"(addr), "r"(r0), "r"(r1) : "memory");
}
__device__ __forceinline__ void stsm_x4(unsigned addr, unsigned r0, unsigned r1, unsigned r2, unsigned r3) {
  asm volatile("stmatrix.sync.aligned.m8n8.x4.shared.b16 [%0], {%1,%2,%3,%4};" ::"r"(addr), "r"(r0), "r"(r1), "r"(r2), "r"(r3) : "memory");
}
__device__ __forceinline__ void mma16816(float* d, const unsigned* a, unsigned b0, unsigned b1) {
  asm volatile("mma.sync.aligned.m16n8k16.row.col.f32.bf16.bf16.f32 {%0,%1,%2,%3}, {%4,%5,%6,%7}, {%8,%9}, {%0,%1,%2,%3};"
               : "+f"(d[0]), "+f"(d[1]), "+f"(d[2]), "+f"(d[3]) : "r"(a[0]), "r"(a[1]), "r"(a[2]), "r"(a[3]), "r"(b0), "r"(b1));
}
__device__ __forceinline__ void mma1688(float* d, unsigned a0, unsigned a1, unsigned b0) {
  asm volatile("mma.sync.aligned.m16n8k8.row.col.f32.bf16.bf16.f32 {%0,%1,%2,%3}, {%4,%5}, {%6}, {%0,%1,%2,%3};"
               : "+f"(d[0]), "+f"(d[1]), "+f"(d[2]), "+f"(d[3]) : "r"(a0), "r"(a1), "r"(b0));
}
__device__ __forceinline__ uint64_t mkdesc(unsigned addr, unsigned lbo, unsigned sbo) {
  return (uint64_t)((addr >> 4) & 0x3fff) | ((uint64_t)(lbo >> 4) << 16) | ((uint64_t)(sbo >> 4) << 32) | (1ull << 62);
}
#define R8(b) "+f"(d[b]), "+f"(d[b + 1]), "+f"(d[b + 2]), "+f"(d[b + 3]), "+f"(d[b + 4]), "+f"(d[b + 5]), "+f"(d[b + 6]), "+f"(d[b + 7])
#define R32(b) R8(b), R8(b + 8), R8(b + 16), R8(b + 24)
__device__ __forceinline__ void wgmma_n256(float* d, uint64_t ad, uint64_t bd, int acc) {
  asm volatile(
      "{.reg .pred p; setp.ne.b32 p, %130, 0;\n"
      "wgmma.mma_async.sync.aligned.m64n256k16.f32.bf16.bf16 "
      "{%0,%1,%2,%3,%4,%5,%6,%7,%8,%9,%10,%11,%12,%13,%14,%15,%16,%17,%18,%19,%20,%21,%22,%23,%24,%25,%26,%27,%28,%29,%30,%31,"
      "%32,%33,%34,%35,%36,%37,%38,%39,%40,%41,%42,%43,%44,%45,%46,%47,%48,%49,%50,%51,%52,%53,%54,%55,%56,%57,%58,%59,%60,%61,%62,%63,"
      "%64,%65,%66,%67,%68,%69,%70,%71,%72,%73,%74,%75,%76,%77,%78,%79,%80,%81,%82,%83,%84,%85,%86,%87,%88,%89,%90,%91,%92,%93,%94,%95,"
      "%96,%97,%98,%99,%100,%101,%102,%103,%104,%105,%106,%107,%108,%109,%110,%111,%112,%113,%114,%115,%116,%117,%118,%119,%120,%121,%122,%123,%124,%125,%126,%127},"
      "%128, %129, p, 1, 1, 0, 1;}\n"
      : R32(0), R32(32), R32(64), R32(96)
      : "l"(ad), "l"(bd), "r"(acc));
}

__device__ __forceinline__ void ln16(const float* x, float* o) {
  float s = 0;
#pragma unroll
  for (int i = 0; i < 16; i++) s += x[i];
#pragma unroll
  for (int of = 16; of > 0; of >>= 1) s += __shfl_xor_sync(~0u, s, of);
  float mean = s * (1.0f / DM);
  float v = 0;
#pragma unroll
  for (int i = 0; i < 16; i++) { float dd = x[i] - mean; v += dd * dd; }
#pragma unroll
  for (int of = 16; of > 0; of >>= 1) v += __shfl_xor_sync(~0u, v, of);
  float mb = bf16r(mean);
  float vb = bf16r(v * (1.0f / DM));
  float den = bf16r(sqrtf(bf16r(vb + 1e-5f)));
#pragma unroll
  for (int i = 0; i < 16; i++) o[i] = bf16r(__fdiv_rn(bf16r(x[i] - mb), den));
}
__global__ void __launch_bounds__(256) k_pre(const bf16* __restrict__ x) {
  int t = threadIdx.x, lane = t & 31, w = t >> 5;
  int row = blockIdx.x * 8 + w;
  const uint4* src = reinterpret_cast<const uint4*>(x + (size_t)row * DM);
  uint4 a = src[lane], b = src[lane + 32];
  unsigned u[8] = {a.x, a.y, a.z, a.w, b.x, b.y, b.z, b.w};
  float f[16], o[16], o2[16];
#pragma unroll
  for (int i = 0; i < 8; i++) { f[2 * i] = bf_lo(u[i]); f[2 * i + 1] = bf_hi(u[i]); }
  ln16(f, o);
  ln16(o, o2);
  uint4* d1 = reinterpret_cast<uint4*>(g_xn + (size_t)row * DM);
  uint4* d2 = reinterpret_cast<uint4*>(g_y + (size_t)row * DM);
  d1[lane] = make_uint4(pack_bf16(o[0], o[1]), pack_bf16(o[2], o[3]), pack_bf16(o[4], o[5]), pack_bf16(o[6], o[7]));
  d1[lane + 32] = make_uint4(pack_bf16(o[8], o[9]), pack_bf16(o[10], o[11]), pack_bf16(o[12], o[13]), pack_bf16(o[14], o[15]));
  d2[lane] = make_uint4(pack_bf16(o2[0], o2[1]), pack_bf16(o2[2], o2[3]), pack_bf16(o2[4], o2[5]), pack_bf16(o2[6], o2[7]));
  d2[lane + 32] = make_uint4(pack_bf16(o2[8], o2[9]), pack_bf16(o2[10], o2[11]), pack_bf16(o2[12], o2[13]), pack_bf16(o2[14], o2[15]));
  int gt = blockIdx.x * 256 + t;
  uint4 z = make_uint4(0, 0, 0, 0);
  if (gt < 16384) reinterpret_cast<uint4*>(g_part)[gt] = z;
  if (gt < (int)(sizeof(Flags) / 4)) reinterpret_cast<unsigned*>(&g_flags)[gt] = 0;
}

struct Maps { CUtensorMap xn, y, h1, o, qkv_st, qkv_ld, g, wq, wk, wv, wo, w1, w2; };

#define NSTAGE 3
#define STAGE_BYTES 49152
#define B_STG (NSTAGE * STAGE_BYTES)
#define R_WO 0
#define R_T1 65536
#define R_T2 131072
#define R_RING 65536
#define RING_N 4
#define RING_BYTES 12288
#define R_MEM 196608
#define R_QS (R_MEM + 8448)
#define R_KS (R_QS + 1152)
#define R_OS (R_KS + 1152)
#define R_SOWN (R_OS + 2176)
#define R_SPEER (R_SOWN + 1280)
#define R_VM (R_SPEER + 1280)
#define R_VRED (R_VM + 2048)
#define R_RS (R_VRED + 6144)
#define SM_BAR (R_RS + 8192)
#define SMEM_TOTAL (SM_BAR + 256 + 1024)
#define MB_FULL 0
#define MB_EMPTY 8
#define MB_STGF 16
#define MB_STGE 17
#define MB_W0 18
#define MB_W1 19
#define MB_WO 20
#define MB_S 21
#define MB_V 22
#define MB_KVR 23
#define MB_KVF 24
#define MB_RS 25
#define MB_AG 26
#define SM_MISC (SM_BAR + 224)

#define N_KV 512
#define I_Q 512
#define I_M1 768
#define I_M2 880
#define I_POST 912
#define I_TAIL (I_POST + 16 + 24 + 14 * 32)
#define N_ITEMS (I_TAIL + 8 + 32 + 64)
enum { T_QKV = 0, T_M1 = 1, T_M2 = 2, T_ATT = 3, T_OUT = 4, T_OUTL = 5, T_RED = 6, T_REDL = 7 };
struct Item { int type, b, c, ks; };
__device__ __forceinline__ Item decode_item(int i) {
  Item it; it.ks = 0;
  if (i < N_KV) { it.type = T_QKV; it.b = i >> 5; it.c = 16 + (i & 31); }
  else if (i < I_M1) { it.type = T_QKV; it.b = (i - I_Q) >> 4; it.c = (i - I_Q) & 15; }
  else if (i < I_M2) { it.type = T_M1; it.b = (i - I_M1) / 7; it.c = (i - I_M1) % 7; }
  else if (i < I_POST) { it.type = T_M2; it.b = (i - I_M2) >> 1; it.c = (i - I_M2) & 1; }
  else if (i < I_TAIL) {
    int x = i - I_POST, p, r;
    if (x < 16) { p = 0; r = x; } else if (x < 40) { p = 1; r = x - 16; } else { p = 2 + ((x - 40) >> 5); r = (x - 40) & 31; }
    if (r < 16) { it.type = T_ATT; it.b = p; it.c = r; }
    else if (r < 24) { it.type = T_OUT; it.b = p - 1; it.c = r & 1; it.ks = (r - 16) >> 1; }
    else { it.type = T_RED; it.b = p - 2; it.c = r - 24; }
  } else {
    int x = i - I_TAIL;
    if (x < 8) { it.type = T_RED; it.b = 14; it.c = x; }
    else if (x < 40) { it.type = T_OUTL; it.b = 15; it.c = x & 1; it.ks = (x - 8) >> 1; }
    else { it.type = T_REDL; it.b = 15; it.c = x - 40; }
  }
  return it;
}
__device__ __forceinline__ int item_nkb(int type) { return type == T_M2 ? 28 : (type == T_OUT ? 16 : (type >= T_RED ? 1 : (type >= T_ATT ? 4 : 8))); }

__device__ __forceinline__ void st_async_b64(unsigned raddr, unsigned lo, unsigned hi, unsigned rmb) {
  asm volatile("st.async.weak.shared::cluster.mbarrier::complete_tx::bytes.v2.b32 [%0], {%1,%2}, [%3];" ::"r"(raddr), "r"(lo), "r"(hi), "r"(rmb) : "memory");
}
__device__ __forceinline__ void st_async_b32(unsigned raddr, unsigned v, unsigned rmb) {
  asm volatile("st.async.weak.shared::cluster.mbarrier::complete_tx::bytes.b32 [%0], %1, [%2];" ::"r"(raddr), "r"(v), "r"(rmb) : "memory");
}
__device__ __forceinline__ unsigned mapa(unsigned a, unsigned rank) {
  unsigned r; asm volatile("mapa.shared::cluster.u32 %0, %1, %2;" : "=r"(r) : "r"(a), "r"(rank)); return r;
}
__device__ __forceinline__ void sts64(unsigned a, unsigned x, unsigned y) { asm volatile("st.shared.v2.b32 [%0], {%1,%2};" ::"r"(a), "r"(x), "r"(y) : "memory"); }
__device__ __forceinline__ void sts128(unsigned a, uint4 v) { asm volatile("st.shared.v4.b32 [%0], {%1,%2,%3,%4};" ::"r"(a), "r"(v.x), "r"(v.y), "r"(v.z), "r"(v.w) : "memory"); }
__device__ __forceinline__ uint2 lds64(unsigned a) { uint2 v; asm volatile("ld.shared.v2.b32 {%0,%1}, [%2];" : "=r"(v.x), "=r"(v.y) : "r"(a) : "memory"); return v; }
__device__ __forceinline__ uint4 lds128(unsigned a) { uint4 v; asm volatile("ld.shared.v4.b32 {%0,%1,%2,%3}, [%4];" : "=r"(v.x), "=r"(v.y), "=r"(v.z), "=r"(v.w) : "r"(a) : "memory"); return v; }
__device__ __forceinline__ float lds32f(unsigned a) { float v; asm volatile("ld.shared.f32 %0, [%1];" : "=f"(v) : "r"(a) : "memory"); return v; }
#define spin_check(it) TRAP_IF(++it)
#define POLLV 0
#define BAR8 0
#define D_STAG 150
#define D_RED 0
#define D_PUB 0
#define DELAY(n) do { unsigned c0_, c1_; asm volatile("mov.u32 %0, %%clock;" : "=r"(c0_)); do { asm volatile("mov.u32 %0, %%clock;" : "=r"(c1_)); } while (c1_ - c0_ < (n)); } while (0)
#define SCALE_QK 0.08838834764831845f

__device__ __forceinline__ void rec_worker(const Maps& maps, unsigned sb, const bf16* __restrict__ mem0) {
  const int c = blockIdx.x, h = c >> 1, j = c & 1;
  const int t = opaque_tid(), lane = t & 31, w = t >> 5, g = lane >> 2, tq = lane & 3;
  const int m = lane >> 3, r8 = lane & 7, kh = w >> 2, et = w & 3;
  const unsigned bar = sb + SM_BAR;
  unsigned wq[16][4], wk[16][4], wo[8][4];
  const unsigned woff = (kh * 4) * 8192 + ((m >> 1) * 8 + r8) * 128 + (((et * 2 + (m & 1)) ^ r8) << 4);
  mbar_wait(bar + 8 * MB_W0, 0);
#pragma unroll
  for (int i = 0; i < 16; i++) {
    ldsm_x4_t(wq[i], sb + R_WO + woff + (i >> 2) * 8192 + (i & 3) * 2048);
    ldsm_x4_t(wk[i], sb + R_T1 + woff + (i >> 2) * 8192 + (i & 3) * 2048);
  }
  bar_sync(2, 288);
  if (t == 0) {
    fence_proxy_async_smem();
    mbar_expect_tx(bar + 8 * MB_WO, 65536);
    for (int kb = 0; kb < 2; kb++)
      for (int cb = 0; cb < 4; cb++) tma_load_2d(sb + R_WO + (kb * 4 + cb) * 8192, &maps.wo, j * 256 + cb * 64, h * 128 + kb * 64, bar + 8 * MB_WO);
  }
  mbar_wait(bar + 8 * MB_W1, 0);
  const unsigned pV = sb + R_T2 + woff;
  const unsigned rk = c & 7, peer = rk ^ 1, cl = c >> 3;
#define KEEP(x) x = __shfl_sync(~0u, x, lane)
  unsigned pA = sb + R_MEM + kh * 4096 + lane * 16;
  unsigned pW0 = sb + R_WO + (w >> 1) * 8192 + ((m >> 1) * 8 + r8) * 128 + ((((w & 1) * 4 + (m & 1)) ^ r8) << 4);
  unsigned pW1 = pW0 ^ 32;
  unsigned pVk = pV;
  unsigned aX = sb + R_VRED + et * 512 + lane * 16;
  unsigned aQKst = sb + (kh ? R_KS : R_QS) + r8 * 144 + (et * 16 + (m & 1) * 8) * 2;
  unsigned aL8 = sb + lane * 8;
  unsigned aSl = mapa(sb + R_SOWN + w * 256 + lane * 8, rk), aSr = mapa(sb + R_SPEER + w * 256 + lane * 8, peer);
  unsigned aVl = mapa(sb + R_VM + (j * 4 + et) * 256 + lane * 8, rk), aVr = mapa(sb + R_VM + (j * 4 + et) * 256 + lane * 8, peer);
  const unsigned mbSl = mapa(bar + 8 * MB_S, rk), mbSr = mapa(bar + 8 * MB_S, peer), mbVl = mbSl + 8, mbVr = mbSr + 8;
  unsigned aQ = sb + R_QS + r8 * 144 + m * 16;
  unsigned oKx = (et * 8 + r8) * 128 + ((m ^ r8) << 4);
  unsigned oVx = 4096 + (et >> 1) * 4096 + ((m >> 1) * 8 + r8) * 128 + ((((et & 1) * 4 + (m & 1)) ^ r8) << 4);
  unsigned aOst = sb + R_OS + r8 * 272 + (et * 32 + m * 8) * 2;
  unsigned aOld = sb + R_OS + r8 * 272 + m * 16;
  unsigned aVm = sb + R_VM + et * 512 + lane * 8;
  unsigned aRSr = mapa(sb + R_RS + (h & 3) * 2048 + (w & 1) * 1024 + lane * 8, j * 4 + (w >> 1));
  unsigned mbRSr = mapa(bar + 8 * MB_RS, j * 4 + (w >> 1));
  unsigned t8 = t * 8;
  KEEP(pA); KEEP(pW0); KEEP(pW1); KEEP(pVk); KEEP(aX); KEEP(aQKst); KEEP(aL8); KEEP(aSl); KEEP(aSr); KEEP(aVl); KEEP(aVr); KEEP(aQ); KEEP(oKx); KEEP(oVx);
  KEEP(aOst); KEEP(aOld); KEEP(aVm); KEEP(aRSr); KEEP(mbRSr); KEEP(t8);
  mbar_wait(bar + 8 * MB_WO, 0);
#pragma unroll
  for (int ks = 0; ks < 4; ks++) { ldsm_x4_t(wo[2 * ks], pW0 + ks * 2048); ldsm_x4_t(wo[2 * ks + 1], pW1 + ks * 2048); }
  {
    unsigned v[8];
#pragma unroll
    for (int q = 0; q < 8; q++) v[q] = __ldg(reinterpret_cast<const unsigned*>(mem0) + q * 256 + t);
    sts128(sb + R_MEM + t * 32, make_uint4(__byte_perm(v[0], v[1], 0x5410), __byte_perm(v[2], v[3], 0x5410), __byte_perm(v[4], v[5], 0x5410), __byte_perm(v[6], v[7], 0x5410)));
    sts128(sb + R_MEM + t * 32 + 16, make_uint4(__byte_perm(v[0], v[1], 0x7632), __byte_perm(v[2], v[3], 0x7632), __byte_perm(v[4], v[5], 0x7632), __byte_perm(v[6], v[7], 0x7632)));
  }
  bar_sync(1, 256);

#pragma unroll 1
  for (int s = 0;; s++) {
    const unsigned par = s & 1;
    const unsigned slot = s & (RING_N - 1), rpar = (s / RING_N) & 1;
    const unsigned ring = sb + R_RING + slot * RING_BYTES;
    RSTAMP(1);
    RSTAMP(2);
    float aq[4] = {0, 0, 0, 0}, ak[4] = {0, 0, 0, 0}, av[4] = {0, 0, 0, 0};
#pragma unroll
    for (int i = 0; i < 8; i++) {
      unsigned b[4], f[4], f0[4];
      ldsm_x4_t(b, pA + i * 512);
      ldsm_x4_t(f0, pVk + (i >> 1) * 8192 + (i & 1) * 4096);
      ldsm_x4_t(f, pVk + (i >> 1) * 8192 + (i & 1) * 4096 + 2048);
      mma16816(aq, wq[2 * i], b[0], b[1]); mma16816(ak, wk[2 * i], b[0], b[1]); mma16816(av, f0, b[0], b[1]);
      mma16816(aq, wq[2 * i + 1], b[2], b[3]); mma16816(ak, wk[2 * i + 1], b[2], b[3]); mma16816(av, f, b[2], b[3]);
    }
    RSTAMP(3);
#define STSF4(a, v) asm volatile("st.shared.v4.f32 [%0], {%1,%2,%3,%4};" ::"r"(a), "f"(v[0]), "f"(v[1]), "f"(v[2]), "f"(v[3]) : "memory")
    unsigned f[8][4];
#define NPRE 2
#define WO_PREFETCH() do { _Pragma("unroll") for (int i = 0; i < NPRE; i++) { ldsm_x4_t(f[2 * i], pW0 + 32768 + i * 2048); ldsm_x4_t(f[2 * i + 1], pW1 + 32768 + i * 2048); } } while (0)
    if (kh) {
      STSF4(aX, aq);
      bar_sync(4 + et, 64);
      uint4 o = lds128(aX + 2048), o2 = lds128(aX + 4096);
      stsm_x2_t(aQKst, pack_bf16(ak[0] + __uint_as_float(o.x), ak[1] + __uint_as_float(o.y)), pack_bf16(ak[2] + __uint_as_float(o.z), ak[3] + __uint_as_float(o.w)));
      bar_arrive(1, 256);
      unsigned x = pack_bf16(av[0] + __uint_as_float(o2.x), av[1] + __uint_as_float(o2.y)), y = pack_bf16(av[2] + __uint_as_float(o2.z), av[3] + __uint_as_float(o2.w));
      st_async_b64(aVr, x, y, mbVr);
      st_async_b64(aVl, x, y, mbVl);
      mbar_wait(bar + 8 * (MB_FULL + slot), rpar);
      unsigned vx[4][4];
      ldsm_x4_t(vx[0], ring + oVx); ldsm_x4_t(vx[1], ring + oVx + 2048); ldsm_x4_t(vx[2], ring + (oVx ^ 32)); ldsm_x4_t(vx[3], ring + (oVx ^ 32) + 2048);
      RSTAMP(4); RSTAMP(5); RSTAMP(6); RSTAMP(7);
      mbar_wait(bar + 8 * MB_S, par);
      RSTAMP(8);
      float sc[10];
#pragma unroll
      for (int i = 0; i < 5; i++) {
        uint2 o = lds64(aL8 + R_SOWN + i * 256), p = lds64(aL8 + R_SPEER + i * 256);
        sc[2 * i] = __uint_as_float(o.x) + __uint_as_float(p.x); sc[2 * i + 1] = __uint_as_float(o.y) + __uint_as_float(p.y);
      }
      mbar_wait(bar + 8 * MB_V, par);
      uint2 vm0 = lds64(aVm), vm1 = lds64(aVm + 256);
      float mx = fmaxf(fmaxf(fmaxf(sc[0], sc[1]), fmaxf(sc[2], sc[3])), fmaxf(fmaxf(fmaxf(sc[4], sc[5]), fmaxf(sc[6], sc[7])), fmaxf(sc[8], sc[9])));
      mx = fmaxf(mx, __shfl_xor_sync(~0u, mx, 1)); mx = fmaxf(mx, __shfl_xor_sync(~0u, mx, 2));
      const float nm = -mx * (SCALE_QK * LOG2E);
#pragma unroll
      for (int i = 0; i < 10; i++) sc[i] = ex2f(fmaf(sc[i], SCALE_QK * LOG2E, nm));
      float sum = (((sc[0] + sc[1]) + (sc[2] + sc[3])) + ((sc[4] + sc[5]) + (sc[6] + sc[7]))) + (sc[8] + sc[9]);
      sum += __shfl_xor_sync(~0u, sum, 1); sum += __shfl_xor_sync(~0u, sum, 2);
      float inv; asm("rcp.approx.ftz.f32 %0, %1;" : "=f"(inv) : "f"(sum));
      unsigned p[5];
#pragma unroll
      for (int i = 0; i < 5; i++) p[i] = pack_bf16(sc[2 * i] * inv, sc[2 * i + 1] * inv);
      RSTAMP(9);
      float o0[4] = {0, 0, 0, 0}, o1[4] = {0, 0, 0, 0}, o3[4] = {0, 0, 0, 0}, o4[4] = {0, 0, 0, 0};
      mma16816(o0, vx[0], p[0], p[1]); mma16816(o3, vx[2], p[0], p[1]); mma16816(o1, vx[1], p[2], p[3]); mma16816(o4, vx[3], p[2], p[3]);
      mma1688(o0, vm0.x, vm0.y, p[4]); mma1688(o3, vm1.x, vm1.y, p[4]);
      if (s == NSEG - 1) { if (t == 128) mbar_arrive(bar + 8 * MB_KVR); break; }
      asm volatile("stmatrix.sync.aligned.m8n8.x4.trans.shared.b16 [%0], {%1,%2,%3,%4};" ::"r"(aOst), "r"(pack_bf16(o0[0] + o1[0], o0[1] + o1[1])), "r"(pack_bf16(o0[2] + o1[2], o0[3] + o1[3])),
                   "r"(pack_bf16(o3[0] + o4[0], o3[1] + o4[1])), "r"(pack_bf16(o3[2] + o4[2], o3[3] + o4[3])) : "memory");
      RSTAMP(10);
      bar_sync(1, 256);
      WO_PREFETCH();
    } else {
      STSF4(aX + 2048, ak); STSF4(aX + 4096, av);
      unsigned kb[8];
      mbar_wait(bar + 8 * (MB_FULL + slot), rpar);
      ldsm_x4(kb, ring + oKx); ldsm_x4(kb + 4, ring + (oKx ^ 64));
      bar_sync(4 + et, 64);
      uint4 o = lds128(aX);
      stsm_x2_t(aQKst, pack_bf16(aq[0] + __uint_as_float(o.x), aq[1] + __uint_as_float(o.y)), pack_bf16(aq[2] + __uint_as_float(o.z), aq[3] + __uint_as_float(o.w)));
      RSTAMP(4);
      bar_sync(1, 256);
      RSTAMP(5);
      unsigned qa[8], km[8];
      ldsm_x4(qa, aQ); ldsm_x4(qa + 4, aQ + 64);
      if (w == 3) { ldsm_x4(km, aQ + 1152); ldsm_x4(km + 4, aQ + 1152 + 64); }
      float s0[4] = {0, 0, 0, 0}, s1[4] = {0, 0, 0, 0};
      unsigned af[4][4];
#pragma unroll
      for (int i = 0; i < 4; i++) { af[i][0] = qa[2 * i]; af[i][1] = 0; af[i][2] = qa[2 * i + 1]; af[i][3] = 0; }
      mma16816(s0, af[0], kb[0], kb[1]); mma16816(s1, af[1], kb[2], kb[3]);
      mma16816(s0, af[2], kb[4], kb[5]); mma16816(s1, af[3], kb[6], kb[7]);
      if (w == 3) {
        float m0[4] = {0, 0, 0, 0}, m1[4] = {0, 0, 0, 0};
        mma16816(m0, af[0], km[0], km[1]); mma16816(m1, af[1], km[2], km[3]);
        mma16816(m0, af[2], km[4], km[5]); mma16816(m1, af[3], km[6], km[7]);
        unsigned x = __float_as_uint(m0[0] + m1[0]), y = __float_as_uint(m0[1] + m1[1]);
        st_async_b64(aSr + 256, x, y, mbSr); st_async_b64(aSl + 256, x, y, mbSl);
      }
      unsigned x = __float_as_uint(s0[0] + s1[0]), y = __float_as_uint(s0[1] + s1[1]);
      st_async_b64(aSr, x, y, mbSr); st_async_b64(aSl, x, y, mbSl);
      RSTAMP(6);
      if (s == NSEG - 1) break;
      WO_PREFETCH();
      RSTAMP(7); RSTAMP(8); RSTAMP(9); RSTAMP(10);
      bar_sync(1, 256);
    }
    RSTAMP(11);
    float d0[4] = {0, 0, 0, 0}, d1[4] = {0, 0, 0, 0}, e0[4] = {0, 0, 0, 0}, e1[4] = {0, 0, 0, 0};
    unsigned ob[4][4];
#pragma unroll
    for (int k2 = 0; k2 < 4; k2++) ldsm_x4(ob[k2], aOld + k2 * 64);
#pragma unroll
    for (int i = NPRE; i < 4; i++) { ldsm_x4_t(f[2 * i], pW0 + 32768 + i * 2048); ldsm_x4_t(f[2 * i + 1], pW1 + 32768 + i * 2048); }
    mma16816(d0, wo[0], ob[0][0], ob[0][1]); mma16816(d1, wo[1], ob[0][0], ob[0][1]);
    mma16816(e0, wo[2], ob[0][2], ob[0][3]); mma16816(e1, wo[3], ob[0][2], ob[0][3]);
    mma16816(d0, wo[4], ob[1][0], ob[1][1]); mma16816(d1, wo[5], ob[1][0], ob[1][1]);
    mma16816(e0, wo[6], ob[1][2], ob[1][3]); mma16816(e1, wo[7], ob[1][2], ob[1][3]);
    mma16816(d0, f[0], ob[2][0], ob[2][1]); mma16816(d1, f[1], ob[2][0], ob[2][1]);
    mma16816(e0, f[2], ob[2][2], ob[2][3]); mma16816(e1, f[3], ob[2][2], ob[2][3]);
    mma16816(d0, f[4], ob[3][0], ob[3][1]); mma16816(d1, f[5], ob[3][0], ob[3][1]);
    mma16816(e0, f[6], ob[3][2], ob[3][3]); mma16816(e1, f[7], ob[3][2], ob[3][3]);
    st_async_b64(aRSr, __float_as_uint(d0[0] + e0[0]), __float_as_uint(d0[1] + e0[1]), mbRSr);
    st_async_b64(aRSr + 256, __float_as_uint(d0[2] + e0[2]), __float_as_uint(d0[3] + e0[3]), mbRSr);
    st_async_b64(aRSr + 512, __float_as_uint(d1[0] + e1[0]), __float_as_uint(d1[1] + e1[1]), mbRSr);
    st_async_b64(aRSr + 768, __float_as_uint(d1[2] + e1[2]), __float_as_uint(d1[3] + e1[3]), mbRSr);
    RSTAMP(12);
    if (t == 128) {
      mbar_arrive(bar + 8 * (MB_EMPTY + slot)); mbar_arrive(bar + 8 * MB_KVR);
      mbar_expect_tx(bar + 8 * MB_S, 2560); mbar_expect_tx(bar + 8 * MB_V, 2048);
    }
    const unsigned tag = ((s >> 1) & 1) ^ 1;
    const char* gp = reinterpret_cast<const char*>(g_part) + (par * 8 + rk) * 16384 + t8;
    unsigned mbA[8];
#pragma unroll
    for (int i = 0; i < 8; i++) mbA[i] = mapa(bar + 8 * MB_AG, i);
    const unsigned dlt = (R_MEM + rk * 1024) - (SM_BAR + 8 * MB_AG) + (t8 >> 1);
    mbar_wait(bar + 8 * MB_RS, par);
    RSTAMP(13);
    uint2 a[8];
    {
      uint2 x0 = lds64(sb + R_RS + t8), x1 = lds64(sb + R_RS + 2048 + t8), x2 = lds64(sb + R_RS + 4096 + t8), x3 = lds64(sb + R_RS + 6144 + t8);
      float r0 = (__uint_as_float(x0.x) + __uint_as_float(x1.x)) + (__uint_as_float(x2.x) + __uint_as_float(x3.x));
      float r1 = (__uint_as_float(x0.y) + __uint_as_float(x1.y)) + (__uint_as_float(x2.y) + __uint_as_float(x3.y));
      a[0].x = (__float_as_uint(r0) & ~1u) | tag; a[0].y = (__float_as_uint(r1) & ~1u) | tag;
      asm volatile("st.relaxed.gpu.global.v2.u32 [%0], {%1,%2};" ::"l"(gp + cl * 2048), "r"(a[0].x), "r"(a[0].y) : "memory");
    }
    RSTAMP(14);
    if (t == 128) mbar_expect_tx(bar + 8 * MB_RS, 8192);
    {
      unsigned it = 0;
      while (true) {
#pragma unroll
        for (int i = 1; i < 8; i++) a[i] = ldv2_relaxed(gp + (cl ^ i) * 2048);
        unsigned an = a[1].x & a[1].y, orr = a[1].x | a[1].y;
#pragma unroll
        for (int i = 2; i < 8; i++) { an &= a[i].x & a[i].y; orr |= a[i].x | a[i].y; }
        if (((tag ? an : ~orr) & 1u) != 0) break;
        spin_check(it);
      }
    }
    RSTAMP(15);
    {
#define AF(i, c) __uint_as_float(a[i].c)
      unsigned u = pack_bf16(((AF(0, x) + AF(1, x)) + (AF(2, x) + AF(3, x))) + ((AF(4, x) + AF(5, x)) + (AF(6, x) + AF(7, x))),
                             ((AF(0, y) + AF(1, y)) + (AF(2, y) + AF(3, y))) + ((AF(4, y) + AF(5, y)) + (AF(6, y) + AF(7, y))));
      __syncwarp();
#pragma unroll
      for (int i = 0; i < 8; i++) st_async_b32(mbA[i] + dlt, u, mbA[i]);
    }
    mbar_wait(bar + 8 * MB_KVF, par);
    mbar_wait(bar + 8 * MB_AG, par);
    if (t == 128) mbar_expect_tx(bar + 8 * MB_AG, 8192);
  }
}

__device__ __forceinline__ void rec_ring(const Maps& maps, unsigned sb) {
  const int c = blockIdx.x, h = c >> 1, j = c & 1;
  const unsigned bar = sb + SM_BAR;
  const int lane = threadIdx.x & 31;
  if (lane == 0) {
    mbar_expect_tx(bar + 8 * MB_W0, 131072);
    for (int kb = 0; kb < 8; kb++) tma_load_2d(sb + R_WO + kb * 8192, &maps.wq, h * 128 + j * 64, kb * 64, bar + 8 * MB_W0);
    for (int kb = 0; kb < 8; kb++) tma_load_2d(sb + R_T1 + kb * 8192, &maps.wk, h * 128 + j * 64, kb * 64, bar + 8 * MB_W0);
    mbar_expect_tx(bar + 8 * MB_W1, 65536);
    for (int kb = 0; kb < 8; kb++) tma_load_2d(sb + R_T2 + kb * 8192, &maps.wv, h * 128 + j * 64, kb * 64, bar + 8 * MB_W1);
  }
  __syncwarp();
  bar_sync(2, 288);
  if (lane == 0) {
    fence_proxy_async_smem();
    for (int s = 0; s < NSEG; s++) {
      unsigned slot = s & (RING_N - 1);
      if ((s & 3) == 0 && !DBGMODE) {
        wait_flag_ge(&g_flags.qkv[(s >> 2) * 48 + 16 + (h >> 1)], 1);
        wait_flag_ge(&g_flags.qkv[(s >> 2) * 48 + 32 + (h >> 1)], 1);
        fence_proxy_async();
      }
      if (s >= RING_N) mbar_wait_sleep(bar + 8 * (MB_EMPTY + slot), ((s / RING_N) - 1) & 1);
      unsigned dst = sb + R_RING + slot * RING_BYTES, mb = bar + 8 * (MB_FULL + slot);
      mbar_expect_tx(mb, RING_BYTES);
      tma_load_2d(dst, &maps.qkv_ld, HD + h * 128 + j * 64, s * SEG, mb);
      tma_load_2d(dst + 4096, &maps.qkv_ld, 2 * HD + h * 128, s * SEG, mb);
      tma_load_2d(dst + 8192, &maps.qkv_ld, 2 * HD + h * 128 + 64, s * SEG, mb);
    }
  }
}
__device__ __forceinline__ void rec_copy(unsigned sb) {
  const int c = blockIdx.x, h = c >> 1, j = c & 1;
  const unsigned bar = sb + SM_BAR;
  const int lane = threadIdx.x & 31;
  for (int s = 0; s < NSEG; s++) {
    mbar_wait_sleep(bar + 8 * MB_KVR, s & 1);
    uint4 k0 = lds128(sb + R_KS + (lane >> 3) * 144 + (lane & 7) * 16), k1 = lds128(sb + R_KS + (4 + (lane >> 3)) * 144 + (lane & 7) * 16);
    uint2 v[4];
#pragma unroll
    for (int i = 0; i < 4; i++) v[i] = lds64(sb + R_VM + (j * 4 + i) * 256 + lane * 8);
    __syncwarp();
    if (lane == 0) mbar_arrive(bar + 8 * MB_KVF);
    bf16* kd = g_km + ((size_t)(s * NH + h) * NMEM) * DH + j * 64;
    *reinterpret_cast<uint4*>(kd + (lane >> 3) * DH + (lane & 7) * 8) = k0;
    *reinterpret_cast<uint4*>(kd + (4 + (lane >> 3)) * DH + (lane & 7) * 8) = k1;
    unsigned* vd = reinterpret_cast<unsigned*>(g_vmt) + ((size_t)(s * NH + h) * DH + j * 64) * 4;
#pragma unroll
    for (int i = 0; i < 4; i++) { vd[(i * 16) * 4 + lane] = v[i].x; vd[(i * 16 + 8) * 4 + lane] = v[i].y; }
    __syncwarp();
    if (lane == 0) st_release(&g_flags.rec[c], s + 1);
  }
}

__device__ __forceinline__ void bulk_producer(const Maps& maps, unsigned sb, int* misc) {
  const unsigned bar = sb + SM_BAR;
  unsigned st = 0, ph = 0, seq = 0;
  while (true) {
    int idx = (int)atomicAdd(&g_flags.ctr, 1u);
    if (idx >= N_ITEMS) {
      mbar_wait(bar + 8 * (MB_EMPTY + st), ph ^ 1);
      misc[seq & 3] = -1;
      mbar_arrive(bar + 8 * (MB_FULL + st));
      break;
    }
    ISTAMP(idx, 0);
    Item it = decode_item(idx);
    const CUtensorMap *ma, *mb_; int ka = 0, kbr = 0, nb0 = it.c * 256;
    if (it.type == T_QKV) { ma = &maps.xn; mb_ = it.c < 16 ? &maps.wq : (it.c < 32 ? &maps.wk : &maps.wv); nb0 = (it.c & 15) * 256; }
    else if (it.type == T_M1) { ma = &maps.y; mb_ = &maps.w1; }
    else if (it.type == T_M2) { ma = &maps.h1; mb_ = &maps.w2; wait_flag_ge(&g_flags.h1[it.b], 7); }
    else if (it.type == T_OUT) { ma = &maps.o; mb_ = &maps.wo; ka = kbr = it.ks * 1024; wait_flag_ge(&g_flags.o[it.b * 4 + it.ks], 4); }
    else if (it.type == T_OUTL) { ma = &maps.o; mb_ = &maps.wo; ka = kbr = it.ks * 256; wait_flag_ge(&g_flags.o16[it.ks], 1); }
    else if (it.type >= T_RED) { ma = mb_ = &maps.o; wait_flag_ge(&g_flags.g[it.b], 2); wait_flag_ge(&g_flags.p[it.b], it.type == T_RED ? 8 : 32); }
    else {
      ma = mb_ = &maps.qkv_ld;
      wait_flag_ge(&g_flags.qkv[it.b * 48 + it.c], 1); wait_flag_ge(&g_flags.qkv[it.b * 48 + 16 + it.c], 1); wait_flag_ge(&g_flags.qkv[it.b * 48 + 32 + it.c], 1);
      for (int i = 0; i < 4; i++) wait_flag_ge(&g_flags.rec[it.c * 4 + i], it.b * 4 + 2);
    }
    fence_proxy_async();
    ISTAMP(idx, 1);
    const int nkb = item_nkb(it.type);
    for (int kb = 0; kb < nkb; kb++) {
      mbar_wait(bar + 8 * (MB_EMPTY + st), ph ^ 1);
      if (kb == 0) { misc[seq & 3] = idx; seq++; }
      unsigned dst = sb + st * STAGE_BYTES, mb = bar + 8 * (MB_FULL + st);
      if (it.type >= T_RED) { mbar_arrive(mb); if (++st == NSTAGE) { st = 0; ph ^= 1; } break; }
      if (it.type == T_ATT && kb == 2) for (int i = 0; i < 4; i++) wait_flag_ge(&g_flags.rec[it.c * 4 + i], it.b * 4 + 4);
      mbar_expect_tx(mb, STAGE_BYTES);
      if (it.type == T_ATT) {
        int head = it.c * 2 + (kb & 1), row = it.b * 128 + (kb >> 1) * 64;
        for (int i = 0; i < 12; i++) tma_load_2d(dst + i * 4096, ma, (i >> 2) * HD + head * 128 + (i & 1) * 64, row + ((i >> 1) & 1) * 32, mb);
      } else {
        tma_load_2d(dst, ma, ka + kb * 64, it.b * 128, mb);
        for (int i = 0; i < 4; i++) tma_load_2d(dst + 16384 + i * 8192, mb_, nb0 + i * 64, kbr + kb * 64, mb);
      }
      if (++st == NSTAGE) { st = 0; ph ^= 1; }
    }
  }
}
__device__ __forceinline__ void bulk_store(const Maps& maps, unsigned sb, volatile int* misc) {
  const unsigned bar = sb + SM_BAR;
  unsigned ph = 0;
  while (true) {
    mbar_wait(bar + 8 * MB_STGF, ph); ph ^= 1;
    int idx = misc[4];
    if (idx < 0) break;
    Item it = decode_item(idx);
    const CUtensorMap* mp = it.type == T_QKV ? &maps.qkv_st : (it.type == T_M1 ? &maps.h1 : (it.type == T_M2 ? &maps.g : &maps.o));
    unsigned* flag = it.type == T_QKV ? &g_flags.qkv[it.b * 48 + it.c] : (it.type == T_M1 ? &g_flags.h1[it.b] : (it.type == T_M2 ? &g_flags.g[it.b] : (it.b == 15 ? &g_flags.o16[it.c] : &g_flags.o[it.b * 4 + (it.c >> 2)])));
    for (int i = 0; i < 4; i++) tma_store_2d(mp, sb + B_STG + i * 16384, it.c * 256 + i * 64, it.b * 128);
    asm volatile("cp.async.bulk.commit_group;" ::: "memory");
    asm volatile("cp.async.bulk.wait_group.read 0;" ::: "memory");
    mbar_arrive(bar + 8 * MB_STGE);
    asm volatile("cp.async.bulk.wait_group 0;" ::: "memory");
    fence_proxy_async();
    red_release_add(flag, 1);
    ISTAMP(idx, 3);
  }
}
__device__ __forceinline__ float gelu_t(float x) {
  float u = 0.7978845608028654f * (x + 0.044715f * x * x * x);
  return __fdividef(x, 1.0f + __expf(-2.0f * u));
}
__device__ __forceinline__ float silu_f(float x) { return __fdividef(x, 1.0f + __expf(-x)); }

__device__ __forceinline__ void final_out(bf16* __restrict__ out, const bf16* __restrict__ x, size_t o, float4 s) {
  uint2 gv = __ldcg(reinterpret_cast<const uint2*>(g_g + o)), xv = __ldg(reinterpret_cast<const uint2*>(x + o));
  uint2 r;
  r.x = pack_bf16(bf_lo(xv.x) + bf16r(bf16r(s.x) * bf_lo(gv.x)), bf_hi(xv.x) + bf16r(bf16r(s.y) * bf_hi(gv.x)));
  r.y = pack_bf16(bf_lo(xv.y) + bf16r(bf16r(s.z) * bf_lo(gv.y)), bf_hi(xv.y) + bf16r(bf16r(s.w) * bf_hi(gv.y)));
  *reinterpret_cast<uint2*>(out + o) = r;
}
__device__ __forceinline__ void bulk_att_stage(unsigned sa, unsigned stg, int b, int hp, int kb, int w, int lane) {
  const int g = lane >> 2, tq = lane & 3, m = lane >> 3, r8 = lane & 7;
  const int seg = w >> 2, mt = (w >> 1) & 1, eh = w & 1;
  const int head = hp * 2 + (kb & 1), sg = b * 4 + (kb >> 1) * 2 + seg;
  const unsigned* kmp = reinterpret_cast<const unsigned*>(g_km + ((size_t)(sg * NH + head) * NMEM + g) * DH) + tq;
  const unsigned* vmp = reinterpret_cast<const unsigned*>(g_vmt) + ((size_t)(sg * NH + head) * DH + eh * 64) * 4 + lane;
  unsigned km[16], vm[8];
#pragma unroll
  for (int i = 0; i < 16; i++) km[i] = __ldcg(kmp + i * 4);
#pragma unroll
  for (int i = 0; i < 8; i++) vm[i] = __ldcg(vmp + i * 32);
  float s[5][4];
#pragma unroll
  for (int i = 0; i < 5; i++) { s[i][0] = s[i][1] = s[i][2] = s[i][3] = 0; }
  const unsigned qb = sa + (0 * 2 + seg) * 8192, kbs = sa + (1 * 2 + seg) * 8192, vb = sa + (2 * 2 + seg) * 8192 + eh * 4096;
  unsigned qa[8][4];
#pragma unroll
  for (int ks = 0; ks < 8; ks++) {
    int row = mt * 16 + (m & 1) * 8 + r8;
    ldsm_x4(qa[ks], qb + (ks >> 2) * 4096 + row * 128 + ((((ks & 3) * 2 + (m >> 1)) ^ r8) << 4));
    unsigned kf[4];
    int krow = (m >> 1) * 8 + r8;
    unsigned ka = kbs + (ks >> 2) * 4096 + krow * 128 + ((((ks & 3) * 2 + (m & 1)) ^ r8) << 4);
    ldsm_x4(kf, ka);
    mma16816(s[0], qa[ks], kf[0], kf[1]); mma16816(s[1], qa[ks], kf[2], kf[3]);
    if (mt) { ldsm_x4(kf, ka + 2048); mma16816(s[2], qa[ks], kf[0], kf[1]); mma16816(s[3], qa[ks], kf[2], kf[3]); }
  }
#pragma unroll
  for (int ks = 0; ks < 8; ks++) mma16816(s[4], qa[ks], km[2 * ks], km[2 * ks + 1]);
  float mx0 = -INFINITY, mx1 = -INFINITY;
  const int t0 = mt * 16 + g, t1 = t0 + 8;
#pragma unroll
  for (int i = 0; i < 5; i++) {
#pragma unroll
    for (int e = 0; e < 4; e++) {
      float v = s[i][e];
      if (i < 4) { int kj = i * 8 + 2 * tq + (e & 1); if (kj > (e < 2 ? t0 : t1)) v = -INFINITY; }
      s[i][e] = v;
      if (e < 2) mx0 = fmaxf(mx0, v); else mx1 = fmaxf(mx1, v);
    }
  }
  mx0 = fmaxf(mx0, __shfl_xor_sync(~0u, mx0, 1)); mx0 = fmaxf(mx0, __shfl_xor_sync(~0u, mx0, 2));
  mx1 = fmaxf(mx1, __shfl_xor_sync(~0u, mx1, 1)); mx1 = fmaxf(mx1, __shfl_xor_sync(~0u, mx1, 2));
  float sm0 = 0, sm1 = 0;
#pragma unroll
  for (int i = 0; i < 5; i++) {
    s[i][0] = ex2f((s[i][0] - mx0) * (SCALE_QK * LOG2E)); s[i][1] = ex2f((s[i][1] - mx0) * (SCALE_QK * LOG2E));
    s[i][2] = ex2f((s[i][2] - mx1) * (SCALE_QK * LOG2E)); s[i][3] = ex2f((s[i][3] - mx1) * (SCALE_QK * LOG2E));
    sm0 += s[i][0] + s[i][1]; sm1 += s[i][2] + s[i][3];
  }
  sm0 += __shfl_xor_sync(~0u, sm0, 1); sm0 += __shfl_xor_sync(~0u, sm0, 2);
  sm1 += __shfl_xor_sync(~0u, sm1, 1); sm1 += __shfl_xor_sync(~0u, sm1, 2);
  const float i0 = __fdividef(1.0f, sm0), i1 = __fdividef(1.0f, sm1);
  unsigned pa[2][4], pm0, pm1;
#pragma unroll
  for (int kk = 0; kk < 2; kk++) {
    pa[kk][0] = pack_bf16(s[2 * kk][0] * i0, s[2 * kk][1] * i0); pa[kk][1] = pack_bf16(s[2 * kk][2] * i1, s[2 * kk][3] * i1);
    pa[kk][2] = pack_bf16(s[2 * kk + 1][0] * i0, s[2 * kk + 1][1] * i0); pa[kk][3] = pack_bf16(s[2 * kk + 1][2] * i1, s[2 * kk + 1][3] * i1);
  }
  pm0 = pack_bf16(s[4][0] * i0, s[4][1] * i0); pm1 = pack_bf16(s[4][2] * i1, s[4][3] * i1);
  const int orow = (kb >> 1) * 64 + seg * 32 + mt * 16 + (m & 1) * 8 + r8;
  const unsigned ob = stg + ((kb & 1) * 2 + eh) * 16384 + orow * 128;
#pragma unroll
  for (int cp = 0; cp < 4; cp++) {
    float o0[4] = {0, 0, 0, 0}, o1[4] = {0, 0, 0, 0};
    mma1688(o0, pm0, pm1, vm[2 * cp]); mma1688(o1, pm0, pm1, vm[2 * cp + 1]);
    unsigned vf[4];
    int row = (m & 1) * 8 + r8;
    unsigned va = vb + row * 128 + (((cp * 2 + (m >> 1)) ^ r8) << 4);
    ldsm_x4_t(vf, va);
    mma16816(o0, pa[0], vf[0], vf[1]); mma16816(o1, pa[0], vf[2], vf[3]);
    if (mt) { ldsm_x4_t(vf, va + 2048); mma16816(o0, pa[1], vf[0], vf[1]); mma16816(o1, pa[1], vf[2], vf[3]); }
    stsm_x4(ob + (((cp * 2 + (m >> 1)) ^ r8) << 4), pack_bf16(o0[0], o0[1]), pack_bf16(o0[2], o0[3]), pack_bf16(o1[0], o1[1]), pack_bf16(o1[2], o1[3]));
  }
}

__device__ __forceinline__ void bulk_worker(unsigned sb, volatile int* misc, const bf16* __restrict__ x, const bf16* __restrict__ b1, const bf16* __restrict__ b2, bf16* __restrict__ out) {
  const int t = threadIdx.x, lane = t & 31, w = t >> 5, wg = w >> 2, g = lane >> 2, tq = lane & 3, m = lane >> 3, r8 = lane & 7;
  const unsigned bar = sb + SM_BAR;
  unsigned st = 0, ph = 0, seq = 0, sph = 0;
  float d[128];
  while (true) {
    mbar_wait(bar + 8 * (MB_FULL + st), ph);
    const int idx = misc[seq & 3]; seq++;
    if (idx < 0 || idx >= N_ITEMS) break;
    if (t == 0) ISTAMP(idx, 2);
    const Item it = decode_item(idx);
    const int nkb = item_nkb(it.type);
    if (it.type == T_ATT) {
      mbar_wait(bar + 8 * MB_STGE, sph ^ 1);
      for (int kb = 0; kb < 4; kb++) {
        if (kb) mbar_wait(bar + 8 * (MB_FULL + st), ph);
        bulk_att_stage(sb + st * STAGE_BYTES, sb + B_STG, it.b, it.c, kb, w, lane);
        __syncwarp();
        if (lane == 0) mbar_arrive(bar + 8 * (MB_EMPTY + st));
        if (++st == NSTAGE) { st = 0; ph ^= 1; }
      }
      if (t == 0) misc[4] = idx;
      fence_proxy_async_smem();
      mbar_arrive(bar + 8 * MB_STGF); sph ^= 1;
      continue;
    }
    if (it.type >= T_RED) {
      __syncwarp();
      if (lane == 0) mbar_arrive(bar + 8 * (MB_EMPTY + st));
      if (++st == NSTAGE) { st = 0; ph ^= 1; }
      if (it.type == T_RED) {
#pragma unroll 2
        for (int i = 0; i < 8; i++) {
          size_t o = ((size_t)it.b * 128 + it.c * 16 + i * 2 + (t >> 7)) * DM + (t & 127) * 4;
          float4 a = __ldcg(reinterpret_cast<const float4*>(g_opart + o)), b = __ldcg(reinterpret_cast<const float4*>(g_opart + o + (size_t)S_TOK * DM));
          float4 c = __ldcg(reinterpret_cast<const float4*>(g_opart + o + (size_t)2 * S_TOK * DM)), e = __ldcg(reinterpret_cast<const float4*>(g_opart + o + (size_t)3 * S_TOK * DM));
          final_out(out, x, o, make_float4((a.x + b.x) + (c.x + e.x), (a.y + b.y) + (c.y + e.y), (a.z + b.z) + (c.z + e.z), (a.w + b.w) + (c.w + e.w)));
        }
      } else {
        size_t ol = ((size_t)it.c * 2 + (t >> 7)) * DM + (t & 127) * 4;
        float4 v[16];
#pragma unroll
        for (int i = 0; i < 16; i++) v[i] = __ldcg(reinterpret_cast<const float4*>(g_opl + ol + (size_t)i * 128 * DM));
#pragma unroll
        for (int st2 = 1; st2 < 16; st2 <<= 1)
#pragma unroll
          for (int i = 0; i < 16; i += 2 * st2) { v[i].x += v[i + st2].x; v[i].y += v[i + st2].y; v[i].z += v[i + st2].z; v[i].w += v[i + st2].w; }
        final_out(out, x, ol + (size_t)15 * 128 * DM, v[0]);
      }
      if (t == 0) ISTAMP(idx, 3);
      continue;
    }
    unsigned pst = 0;
    for (int kb = 0; kb < nkb; kb++) {
      if (kb) mbar_wait(bar + 8 * (MB_FULL + st), ph);
      unsigned sa = sb + st * STAGE_BYTES;
      uint64_t ad = mkdesc(sa + wg * 8192, 16, 1024), bd = mkdesc(sa + 16384, 8192, 1024);
      asm volatile("wgmma.fence.sync.aligned;" ::: "memory");
#pragma unroll
      for (int k = 0; k < 4; k++) wgmma_n256(d, ad + k * 2, bd + k * 128, (kb | k) != 0);
      asm volatile("wgmma.commit_group.sync.aligned;" ::: "memory");
      if (kb) {
        asm volatile("wgmma.wait_group.sync.aligned 1;" ::: "memory");
        if (lane == 0) mbar_arrive(bar + 8 * (MB_EMPTY + pst));
      }
      pst = st;
      if (++st == NSTAGE) { st = 0; ph ^= 1; }
    }
    asm volatile("wgmma.wait_group.sync.aligned 0;" ::: "memory");
    if (lane == 0) mbar_arrive(bar + 8 * (MB_EMPTY + pst));
    if (it.type >= T_OUT) {
      const int col = it.c * 256 + 2 * tq;
      float* pp = it.type == T_OUT ? g_opart + ((size_t)it.ks * S_TOK + it.b * 128 + w * 16 + g) * DM + col : g_opl + ((size_t)it.ks * 128 + w * 16 + g) * DM + col;
#pragma unroll
      for (int i = 0; i < 32; i++) {
        __stcg(reinterpret_cast<float2*>(pp + i * 8), make_float2(d[4 * i], d[4 * i + 1]));
        __stcg(reinterpret_cast<float2*>(pp + 8 * DM + i * 8), make_float2(d[4 * i + 2], d[4 * i + 3]));
      }
      bar_sync(1, 256);
      if (t == 0) { red_release_add(&g_flags.p[it.b], 1); ISTAMP(idx, 3); }
      continue;
    }
    if (it.type != T_QKV) {
      const unsigned* bp = reinterpret_cast<const unsigned*>((it.type == T_M1 ? b1 : b2) + it.c * 256) + tq;
#pragma unroll
      for (int i = 0; i < 32; i++) {
        unsigned bv = __ldg(bp + i * 4);
        float lo = bf_lo(bv), hi = bf_hi(bv);
        float x0 = bf16r(bf16r(d[4 * i]) + lo), x1 = bf16r(bf16r(d[4 * i + 1]) + hi), x2 = bf16r(bf16r(d[4 * i + 2]) + lo), x3 = bf16r(bf16r(d[4 * i + 3]) + hi);
        if (it.type == T_M1) { d[4 * i] = gelu_t(x0); d[4 * i + 1] = gelu_t(x1); d[4 * i + 2] = gelu_t(x2); d[4 * i + 3] = gelu_t(x3); }
        else { d[4 * i] = silu_f(x0); d[4 * i + 1] = silu_f(x1); d[4 * i + 2] = silu_f(x2); d[4 * i + 3] = silu_f(x3); }
      }
    }
    mbar_wait(bar + 8 * MB_STGE, sph ^ 1);
    {
      const unsigned ob = sb + B_STG + (w * 16 + (m & 1) * 8 + r8) * 128;
#pragma unroll
      for (int i = 0; i < 16; i++)
        stsm_x4(ob + (i >> 2) * 16384 + ((((i & 3) * 2 + (m >> 1)) ^ r8) << 4), pack_bf16(d[8 * i], d[8 * i + 1]), pack_bf16(d[8 * i + 2], d[8 * i + 3]),
                pack_bf16(d[8 * i + 4], d[8 * i + 5]), pack_bf16(d[8 * i + 6], d[8 * i + 7]));
    }
    if (t == 0) misc[4] = idx;
    fence_proxy_async_smem();
    mbar_arrive(bar + 8 * MB_STGF); sph ^= 1;
  }
  mbar_wait(bar + 8 * MB_STGE, sph ^ 1);
  if (t == 0) misc[4] = -1;
  mbar_arrive(bar + 8 * MB_STGF);
}

__global__ void __cluster_dims__(CLS, 1, 1) __launch_bounds__(384, 1)
k_main(const __grid_constant__ Maps maps, const bf16* __restrict__ x, const bf16* __restrict__ mem0, const bf16* __restrict__ b1, const bf16* __restrict__ b2, bf16* __restrict__ out) {
  extern __shared__ unsigned char smem_raw[];
  const unsigned sraw = smem_u32(smem_raw);
  const unsigned sb = (sraw + 1023u) & ~1023u;
  int* misc = reinterpret_cast<int*>(smem_raw + (sb - sraw) + SM_MISC);
  const int w = threadIdx.x >> 5;
  const bool rec = blockIdx.x < NREC;
  if (threadIdx.x == 0) {
    const unsigned bar = sb + SM_BAR;
    for (int i = 0; i < 8; i++) { mbar_init(bar + 8 * (MB_FULL + i), 1); mbar_init(bar + 8 * (MB_EMPTY + i), rec ? 1 : 8); }
    mbar_init(bar + 8 * MB_STGF, 256); mbar_init(bar + 8 * MB_STGE, 1);
    for (int i = MB_W0; i <= MB_AG; i++) mbar_init(bar + 8 * i, 1);
    if (rec) { mbar_expect_tx(bar + 8 * MB_S, 2560); mbar_expect_tx(bar + 8 * MB_V, 2048); mbar_expect_tx(bar + 8 * MB_RS, 8192); mbar_expect_tx(bar + 8 * MB_AG, 8192); }
    asm volatile("fence.mbarrier_init.release.cluster;" ::: "memory");
  }
  __syncthreads();
  asm volatile("barrier.cluster.arrive.release.aligned;\nbarrier.cluster.wait.acquire.aligned;" ::: "memory");
  if (DBGMODE && !rec) return;
  if (w >= 8) {
    asm volatile("setmaxnreg.dec.sync.aligned.u32 24;");
    if (rec) { if (w == 8) rec_ring(maps, sb); else if (w == 9) rec_copy(sb); }
    else if ((threadIdx.x & 31) == 0) { if (w == 8) bulk_producer(maps, sb, misc); else if (w == 9) bulk_store(maps, sb, misc); }
  } else {
    if (rec) { asm volatile("setmaxnreg.inc.sync.aligned.u32 240;"); rec_worker(maps, sb, mem0); }
    else { asm volatile("setmaxnreg.inc.sync.aligned.u32 240;"); bulk_worker(sb, misc, x, b1, b2, out); }
  }
}

typedef CUresult (*EncFn)(CUtensorMap*, CUtensorMapDataType, cuuint32_t, void*, const cuuint64_t*, const cuuint64_t*, const cuuint32_t*, const cuuint32_t*,
                          CUtensorMapInterleave, CUtensorMapSwizzle, CUtensorMapL2promotion, CUtensorMapFloatOOBfill);
static void mk_map(EncFn enc, CUtensorMap* m, const void* ptr, uint64_t rows, uint64_t cols, uint32_t box_rows) {
  cuuint64_t dims[2] = {cols, rows}; cuuint64_t strides[1] = {cols * 2};
  cuuint32_t box[2] = {64, box_rows}, es[2] = {1, 1};
  enc(m, CU_TENSOR_MAP_DATA_TYPE_BFLOAT16, 2, const_cast<void*>(ptr), dims, strides, box, es, CU_TENSOR_MAP_INTERLEAVE_NONE, CU_TENSOR_MAP_SWIZZLE_128B,
      CU_TENSOR_MAP_L2_PROMOTION_L2_256B, CU_TENSOR_MAP_FLOAT_OOB_FILL_NONE);
}
extern "C" void kernel_launch(void* const* d_in, const int* in_sizes, int n_in, void* d_out, int out_size) {
  static EncFn enc = nullptr;
  static int ncl = 0;
  static void *p_xn, *p_y, *p_h1, *p_o, *p_qkv, *p_g;
  if (!enc) {
    void* fn = nullptr; cudaDriverEntryPointQueryResult qr;
    cudaGetDriverEntryPoint("cuTensorMapEncodeTiled", &fn, cudaEnableDefault, &qr);
    enc = (EncFn)fn;
    cudaGetSymbolAddress(&p_xn, g_xn); cudaGetSymbolAddress(&p_y, g_y); cudaGetSymbolAddress(&p_h1, g_h1);
    cudaGetSymbolAddress(&p_o, g_o); cudaGetSymbolAddress(&p_qkv, g_qkv); cudaGetSymbolAddress(&p_g, g_g);
    cudaFuncSetAttribute(k_main, cudaFuncAttributeMaxDynamicSharedMemorySize, SMEM_TOTAL);
    cudaLaunchConfig_t cfg = {}; cfg.gridDim = dim3(128); cfg.blockDim = dim3(384); cfg.dynamicSmemBytes = SMEM_TOTAL;
    cudaLaunchAttribute at[1]; at[0].id = cudaLaunchAttributeClusterDimension; at[0].val.clusterDim.x = CLS; at[0].val.clusterDim.y = 1; at[0].val.clusterDim.z = 1;
    cfg.attrs = at; cfg.numAttrs = 1;
    if (cudaOccupancyMaxActiveClusters(&ncl, k_main, &cfg) != cudaSuccess) { cudaGetLastError(); ncl = 14; }
    ncl = ncl > 16 ? 16 : (ncl < 9 ? 9 : ncl);
  }
  Maps maps;
  mk_map(enc, &maps.xn, p_xn, S_TOK, DM, 128); mk_map(enc, &maps.y, p_y, S_TOK, DM, 128); mk_map(enc, &maps.h1, p_h1, S_TOK, FF, 128);
  mk_map(enc, &maps.o, p_o, S_TOK, HD, 128); mk_map(enc, &maps.qkv_st, p_qkv, S_TOK, 3 * HD, 128); mk_map(enc, &maps.qkv_ld, p_qkv, S_TOK, 3 * HD, 32);
  mk_map(enc, &maps.g, p_g, S_TOK, DM, 128);
  mk_map(enc, &maps.wq, d_in[2], DM, HD, 64); mk_map(enc, &maps.wk, d_in[3], DM, HD, 64); mk_map(enc, &maps.wv, d_in[4], DM, HD, 64);
  mk_map(enc, &maps.wo, d_in[5], HD, DM, 64); mk_map(enc, &maps.w1, d_in[8], DM, FF, 64); mk_map(enc, &maps.w2, d_in[10], FF, DM, 64);
  cudaStream_t st = cudaStreamPerThread;
  k_pre<<<256, 256, 0, st>>>((const bf16*)d_in[0]);
  k_main<<<ncl * CLS, 384, SMEM_TOTAL, st>>>(maps, (const bf16*)d_in[0], (const bf16*)d_in[1], (const bf16*)d_in[9], (const bf16*)d_in[11], (bf16*)d_out);
}
```

```cpp
#include <cuda_runtime.h>
#include <cuda_bf16.h>
#include <cuda.h>
#include <stdint.h>

typedef __nv_bfloat16 bf16;

#define S_TOK 2048
#define DM 512
#define NH 32
#define DH 128
#define HD 4096
#define NMEM 8
#define SEG 32
#define NSEG 64
#define FF 1792
#define NBLK 16
#define NREC 64
#define CLS 8

__device__ __align__(1024) bf16 g_xn[S_TOK * DM];
__device__ __align__(1024) bf16 g_y[S_TOK * DM];
__device__ __align__(1024) bf16 g_qkv[(size_t)S_TOK * 3 * HD];
__device__ __align__(1024) bf16 g_h1[S_TOK * FF];
__device__ __align__(1024) bf16 g_g[S_TOK * DM];
__device__ __align__(1024) bf16 g_o[(size_t)S_TOK * HD];
__device__ __align__(1024) bf16 g_km[NSEG * NH * NMEM * DH];
__device__ __align__(1024) bf16 g_vmt[NSEG * NH * DH * NMEM];
__device__ __align__(1024) float g_opart[(size_t)4 * S_TOK * DM];
__device__ __align__(1024) float g_opl[(size_t)16 * 128 * DM];
__device__ __align__(1024) unsigned g_part[2 * 8 * 8 * 512];
struct Flags {
  unsigned qkv[NBLK * 48];
  unsigned h1[NBLK];
  unsigned g[NBLK];
  unsigned o[NBLK * 4];
  unsigned p[NBLK];
  unsigned o16[16];
  unsigned ctr;
  unsigned rec[NREC];
  unsigned abort_;
};
__device__ __align__(1024) Flags g_flags;

#define RSTAMP(k)
#define DBGMODE 0
#define ISTAMP(i, k)
__device__ __forceinline__ unsigned smem_u32(const void* p) { return (unsigned)__cvta_generic_to_shared(p); }
__device__ __forceinline__ float bf16r(float x) { unsigned u; asm("cvt.rn.bf16x2.f32 %0, %1, %2;" : "=r"(u) : "f"(x), "f"(0.0f)); return __uint_as_float(u); }
__device__ __forceinline__ unsigned pack_bf16(float lo, float hi) {
  __nv_bfloat162 v = __floats2bfloat162_rn(lo, hi);
  return *reinterpret_cast<unsigned*>(&v);
}
__device__ __forceinline__ float bf_lo(unsigned u) { return __uint_as_float(u << 16); }
__device__ __forceinline__ float bf_hi(unsigned u) { return __uint_as_float(u & 0xffff0000u); }

#define SPIN_LIMIT (1u << 20)
#define TRAP_IF(x) if ((x) > SPIN_LIMIT) { asm volatile("st.global.u32 [%0], %1;" ::"l"(0ull), "r"(0u) : "memory"); break; }
__device__ __forceinline__ unsigned ld_acquire(const unsigned* p) {
  unsigned v; asm volatile("ld.acquire.gpu.global.u32 %0, [%1];" : "=r"(v) : "l"(p) : "memory"); return v;
}
__device__ __forceinline__ unsigned ld_relaxed(const unsigned* p) {
  unsigned v; asm volatile("ld.relaxed.gpu.global.u32 %0, [%1];" : "=r"(v) : "l"(p) : "memory"); return v;
}
__device__ __forceinline__ void red_release_add(unsigned* p, unsigned v) {
  asm volatile("red.release.gpu.global.add.u32 [%0], %1;" ::"l"(p), "r"(v) : "memory");
}
__device__ __forceinline__ void st_release(unsigned* p, unsigned v) {
  asm volatile("st.release.gpu.global.u32 [%0], %1;" ::"l"(p), "r"(v) : "memory");
}
__device__ __forceinline__ void wait_flag_ge(const unsigned* p, unsigned target) {
  unsigned it = 0;
  while (ld_acquire(p) < target) {
    __nanosleep(64);
    TRAP_IF(++it);
  }
}
__device__ __forceinline__ uint4 ldv4_relaxed(const void* p) {
  uint4 a; asm volatile("ld.relaxed.gpu.global.v4.u32 {%0,%1,%2,%3}, [%4];" : "=r"(a.x), "=r"(a.y), "=r"(a.z), "=r"(a.w) : "l"(p) : "memory"); return a;
}
__device__ __forceinline__ uint2 ldv2_relaxed(const void* p) {
  uint2 a; asm volatile("ld.relaxed.gpu.global.v2.u32 {%0,%1}, [%2];" : "=r"(a.x), "=r"(a.y) : "l"(p) : "memory"); return a;
}
__device__ __forceinline__ void mbar_init(unsigned mb, unsigned cnt) { asm volatile("mbarrier.init.shared::cta.b64 [%0], %1;" ::"r"(mb), "r"(cnt) : "memory"); }
__device__ __forceinline__ void mbar_expect_tx(unsigned mb, unsigned bytes) { asm volatile("mbarrier.arrive.expect_tx.shared::cta.b64 _, [%0], %1;" ::"r"(mb), "r"(bytes) : "memory"); }
__device__ __forceinline__ void mbar_arrive(unsigned mb) { asm volatile("mbarrier.arrive.shared::cta.b64 _, [%0];" ::"r"(mb) : "memory"); }
__device__ __forceinline__ void mbar_wait(unsigned mb, unsigned parity) {
  unsigned ok, it = 0;
  while (true) {
    asm volatile("{.reg .pred p; mbarrier.try_wait.parity.shared::cta.b64 p, [%1], %2; selp.u32 %0,1,0,p;}" : "=r"(ok) : "r"(mb), "r"(parity) : "memory");
    if (ok) break;
    TRAP_IF(++it);
  }
}
__device__ __forceinline__ void mbar_wait_sleep(unsigned mb, unsigned parity) {
  unsigned ok, it = 0;
  while (true) {
    asm volatile("{.reg .pred p; mbarrier.test_wait.parity.shared::cta.b64 p, [%1], %2; selp.u32 %0,1,0,p;}" : "=r"(ok) : "r"(mb), "r"(parity) : "memory");
    if (ok) break;
    __nanosleep(200);
    TRAP_IF(++it);
  }
}
__device__ __forceinline__ float ex2f(float x) { float y; asm("ex2.approx.ftz.f32 %0, %1;" : "=f"(y) : "f"(x)); return y; }
__device__ __forceinline__ int opaque_tid() { int t = threadIdx.x; t = __shfl_sync(~0u, t, t & 31); return t; }
#define LOG2E 1.4426950408889634f
__device__ __forceinline__ void mbar_wait_cluster(unsigned mb, unsigned parity) {
  unsigned ok, it = 0;
  while (true) {
    asm volatile("{.reg .pred p; mbarrier.try_wait.parity.acquire.cluster.shared::cta.b64 p, [%1], %2; selp.u32 %0,1,0,p;}" : "=r"(ok) : "r"(mb), "r"(parity) : "memory");
    if (ok) break;
    TRAP_IF(++it);
  }
}
__device__ __forceinline__ void bar_sync(int id, int n) { asm volatile("bar.sync %0, %1;" ::"r"(id), "r"(n) : "memory"); }
__device__ __forceinline__ void bar_arrive(int id, int n) { asm volatile("bar.arrive %0, %1;" ::"r"(id), "r"(n) : "memory"); }
__device__ __forceinline__ void tma_load_2d(unsigned dst, const CUtensorMap* map, int c0, int c1, unsigned mb) {
  asm volatile("cp.async.bulk.tensor.2d.shared::cluster.global.mbarrier::complete_tx::bytes [%0], [%1, {%3, %4}], [%2];"
               ::"r"(dst), "l"((uint64_t)map), "r"(mb), "r"(c0), "r"(c1) : "memory");
}
__device__ __forceinline__ void tma_store_2d(const CUtensorMap* map, unsigned src, int c0, int c1) {
  asm volatile("cp.async.bulk.tensor.2d.global.shared::cta.bulk_group [%0, {%2, %3}], [%1];"
               ::"l"((uint64_t)map), "r"(src), "r"(c0), "r"(c1) : "memory");
}
__device__ __forceinline__ void fence_proxy_async() { asm volatile("fence.proxy.async;" ::: "memory"); }
__device__ __forceinline__ void fence_proxy_async_smem() { asm volatile("fence.proxy.async.shared::cta;" ::: "memory"); }
__device__ __forceinline__ void ldsm_x4(unsigned* r, unsigned addr) {
  asm volatile("ldmatrix.sync.aligned.m8n8.x4.shared.b16 {%0,%1,%2,%3}, [%4];" : "=r"(r[0]), "=r"(r[1]), "=r"(r[2]), "=r"(r[3]) : "r"(addr) : "memory");
}
__device__ __forceinline__ void ldsm_x4_t(unsigned* r, unsigned addr) {
  asm volatile("ldmatrix.sync.aligned.m8n8.x4.trans.shared.b16 {%0,%1,%2,%3}, [%4];" : "=r"(r[0]), "=r"(r[1]), "=r"(r[2]), "=r"(r[3]) : "r"(addr) : "memory");
}
__device__ __forceinline__ void stsm_x2_t(unsigned addr, unsigned r0, unsigned r1) {
  asm volatile("stmatrix.sync.aligned.m8n8.x2.trans.shared.b16 [%0], {%1,%2};" ::"r"(addr), "r"(r0), "r"(r1) : "memory");
}
__device__ __forceinline__ void stsm_x4(unsigned addr, unsigned r0, unsigned r1, unsigned r2, unsigned r3) {
  asm volatile("stmatrix.sync.aligned.m8n8.x4.shared.b16 [%0], {%1,%2,%3,%4};" ::"r"(addr), "r"(r0), "r"(r1), "r"(r2), "r"(r3) : "memory");
}
__device__ __forceinline__ void mma16816(float* d, const unsigned* a, unsigned b0, unsigned b1) {
  asm volatile("mma.sync.aligned.m16n8k16.row.col.f32.bf16.bf16.f32 {%0,%1,%2,%3}, {%4,%5,%6,%7}, {%8,%9}, {%0,%1,%2,%3};"
               : "+f"(d[0]), "+f"(d[1]), "+f"(d[2]), "+f"(d[3]) : "r"(a[0]), "r"(a[1]), "r"(a[2]), "r"(a[3]), "r"(b0), "r"(b1));
}
__device__ __forceinline__ void mma1688(float* d, unsigned a0, unsigned a1, unsigned b0) {
  asm volatile("mma.sync.aligned.m16n8k8.row.col.f32.bf16.bf16.f32 {%0,%1,%2,%3}, {%4,%5}, {%6}, {%0,%1,%2,%3};"
               : "+f"(d[0]), "+f"(d[1]), "+f"(d[2]), "+f"(d[3]) : "r"(a0), "r"(a1), "r"(b0));
}
__device__ __forceinline__ uint64_t mkdesc(unsigned addr, unsigned lbo, unsigned sbo) {
  return (uint64_t)((addr >> 4) & 0x3fff) | ((uint64_t)(lbo >> 4) << 16) | ((uint64_t)(sbo >> 4) << 32) | (1ull << 62);
}
#define R8(b) "+f"(d[b]), "+f"(d[b + 1]), "+f"(d[b + 2]), "+f"(d[b + 3]), "+f"(d[b + 4]), "+f"(d[b + 5]), "+f"(d[b + 6]), "+f"(d[b + 7])
#define R32(b) R8(b), R8(b + 8), R8(b + 16), R8(b + 24)
__device__ __forceinline__ void wgmma_n256(float* d, uint64_t ad, uint64_t bd, int acc) {
  asm volatile(
      "{.reg .pred p; setp.ne.b32 p, %130, 0;\n"
      "wgmma.mma_async.sync.aligned.m64n256k16.f32.bf16.bf16 "
      "{%0,%1,%2,%3,%4,%5,%6,%7,%8,%9,%10,%11,%12,%13,%14,%15,%16,%17,%18,%19,%20,%21,%22,%23,%24,%25,%26,%27,%28,%29,%30,%31,"
      "%32,%33,%34,%35,%36,%37,%38,%39,%40,%41,%42,%43,%44,%45,%46,%47,%48,%49,%50,%51,%52,%53,%54,%55,%56,%57,%58,%59,%60,%61,%62,%63,"
      "%64,%65,%66,%67,%68,%69,%70,%71,%72,%73,%74,%75,%76,%77,%78,%79,%80,%81,%82,%83,%84,%85,%86,%87,%88,%89,%90,%91,%92,%93,%94,%95,"
      "%96,%97,%98,%99,%100,%101,%102,%103,%104,%105,%106,%107,%108,%109,%110,%111,%112,%113,%114,%115,%116,%117,%118,%119,%120,%121,%122,%123,%124,%125,%126,%127},"
      "%128, %129, p, 1, 1, 0, 1;}\n"
      : R32(0), R32(32), R32(64), R32(96)
      : "l"(ad), "l"(bd), "r"(acc));
}

__device__ __forceinline__ void ln16(const float* x, float* o) {
  float s = 0;
#pragma unroll
  for (int i = 0; i < 16; i++) s += x[i];
#pragma unroll
  for (int of = 16; of > 0; of >>= 1) s += __shfl_xor_sync(~0u, s, of);
  float mean = s * (1.0f / DM);
  float v = 0;
#pragma unroll
  for (int i = 0; i < 16; i++) { float dd = x[i] - mean; v += dd * dd; }
#pragma unroll
  for (int of = 16; of > 0; of >>= 1) v += __shfl_xor_sync(~0u, v, of);
  float mb = bf16r(mean);
  float vb = bf16r(v * (1.0f / DM));
  float den = bf16r(sqrtf(bf16r(vb + 1e-5f)));
#pragma unroll
  for (int i = 0; i < 16; i++) o[i] = bf16r(__fdiv_rn(bf16r(x[i] - mb), den));
}
__global__ void __launch_bounds__(256) k_pre(const bf16* __restrict__ x) {
  int t = threadIdx.x, lane = t & 31, w = t >> 5;
  int row = blockIdx.x * 8 + w;
  const uint4* src = reinterpret_cast<const uint4*>(x + (size_t)row * DM);
  uint4 a = src[lane], b = src[lane + 32];
  unsigned u[8] = {a.x, a.y, a.z, a.w, b.x, b.y, b.z, b.w};
  float f[16], o[16], o2[16];
#pragma unroll
  for (int i = 0; i < 8; i++) { f[2 * i] = bf_lo(u[i]); f[2 * i + 1] = bf_hi(u[i]); }
  ln16(f, o);
  ln16(o, o2);
  uint4* d1 = reinterpret_cast<uint4*>(g_xn + (size_t)row * DM);
  uint4* d2 = reinterpret_cast<uint4*>(g_y + (size_t)row * DM);
  d1[lane] = make_uint4(pack_bf16(o[0], o[1]), pack_bf16(o[2], o[3]), pack_bf16(o[4], o[5]), pack_bf16(o[6], o[7]));
  d1[lane + 32] = make_uint4(pack_bf16(o[8], o[9]), pack_bf16(o[10], o[11]), pack_bf16(o[12], o[13]), pack_bf16(o[14], o[15]));
  d2[lane] = make_uint4(pack_bf16(o2[0], o2[1]), pack_bf16(o2[2], o2[3]), pack_bf16(o2[4], o2[5]), pack_bf16(o2[6], o2[7]));
  d2[lane + 32] = make_uint4(pack_bf16(o2[8], o2[9]), pack_bf16(o2[10], o2[11]), pack_bf16(o2[12], o2[13]), pack_bf16(o2[14], o2[15]));
  int gt = blockIdx.x * 256 + t;
  uint4 z = make_uint4(0, 0, 0, 0);
  if (gt < 16384) reinterpret_cast<uint4*>(g_part)[gt] = z;
  if (gt < (int)(sizeof(Flags) / 4)) reinterpret_cast<unsigned*>(&g_flags)[gt] = 0;
}

struct Maps { CUtensorMap xn, y, h1, o, qkv_st, qkv_ld, g, wq, wk, wv, wo, w1, w2; };

#define NSTAGE 3
#define STAGE_BYTES 49152
#define B_STG (NSTAGE * STAGE_BYTES)
#define R_WO 0
#define R_T1 65536
#define R_T2 131072
#define R_RING 65536
#define RING_N 4
#define RING_BYTES 12288
#define R_MEM 196608
#define R_QS (R_MEM + 8448)
#define R_KS (R_QS + 1152)
#define R_OS (R_KS + 1152)
#define R_SOWN (R_OS + 2176)
#define R_SPEER (R_SOWN + 1280)
#define R_VM (R_SPEER + 1280)
#define R_VRED (R_VM + 2048)
#define R_RS (R_VRED + 6144)
#define SM_BAR (R_RS + 8192)
#define SMEM_TOTAL (SM_BAR + 256 + 1024)
#define MB_FULL 0
#define MB_EMPTY 8
#define MB_STGF 16
#define MB_STGE 17
#define MB_W0 18
#define MB_W1 19
#define MB_WO 20
#define MB_S 21
#define MB_V 22
#define MB_KVR 23
#define MB_KVF 24
#define MB_RS 25
#define MB_AG 26
#define SM_MISC (SM_BAR + 224)

#define N_KV 512
#define I_Q 512
#define I_M1 768
#define I_M2 880
#define I_POST 912
#define I_TAIL (I_POST + 16 + 24 + 14 * 32)
#define N_ITEMS (I_TAIL + 8 + 32 + 64)
enum { T_QKV = 0, T_M1 = 1, T_M2 = 2, T_ATT = 3, T_OUT = 4, T_OUTL = 5, T_RED = 6, T_REDL = 7 };
struct Item { int type, b, c, ks; };
__device__ __forceinline__ Item decode_item(int i) {
  Item it; it.ks = 0;
  if (i < N_KV) { it.type = T_QKV; it.b = i >> 5; it.c = 16 + (i & 31); }
  else if (i < I_M1) { it.type = T_QKV; it.b = (i - I_Q) >> 4; it.c = (i - I_Q) & 15; }
  else if (i < I_M2) { it.type = T_M1; it.b = (i - I_M1) / 7; it.c = (i - I_M1) % 7; }
  else if (i < I_POST) { it.type = T_M2; it.b = (i - I_M2) >> 1; it.c = (i - I_M2) & 1; }
  else if (i < I_TAIL) {
    int x = i - I_POST, p, r;
    if (x < 16) { p = 0; r = x; } else if (x < 40) { p = 1; r = x - 16; } else { p = 2 + ((x - 40) >> 5); r = (x - 40) & 31; }
    if (r < 16) { it.type = T_ATT; it.b = p; it.c = r; }
    else if (r < 24) { it.type = T_OUT; it.b = p - 1; it.c = r & 1; it.ks = (r - 16) >> 1; }
    else { it.type = T_RED; it.b = p - 2; it.c = r - 24; }
  } else {
    int x = i - I_TAIL;
    if (x < 8) { it.type = T_RED; it.b = 14; it.c = x; }
    else if (x < 40) { it.type = T_OUTL; it.b = 15; it.c = x & 1; it.ks = (x - 8) >> 1; }
    else { it.type = T_REDL; it.b = 15; it.c = x - 40; }
  }
  return it;
}
__device__ __forceinline__ int item_nkb(int type) { return type == T_M2 ? 28 : (type == T_OUT ? 16 : (type >= T_RED ? 1 : (type >= T_ATT ? 4 : 8))); }

__device__ __forceinline__ void st_async_b64(unsigned raddr, unsigned lo, unsigned hi, unsigned rmb) {
  asm volatile("st.async.weak.shared::cluster.mbarrier::complete_tx::bytes.v2.b32 [%0], {%1,%2}, [%3];" ::"r"(raddr), "r"(lo), "r"(hi), "r"(rmb) : "memory");
}
__device__ __forceinline__ void st_async_b32(unsigned raddr, unsigned v, unsigned rmb) {
  asm volatile("st.async.weak.shared::cluster.mbarrier::complete_tx::bytes.b32 [%0], %1, [%2];" ::"r"(raddr), "r"(v), "r"(rmb) : "memory");
}
__device__ __forceinline__ unsigned mapa(unsigned a, unsigned rank) {
  unsigned r; asm volatile("mapa.shared::cluster.u32 %0, %1, %2;" : "=r"(r) : "r"(a), "r"(rank)); return r;
}
__device__ __forceinline__ void sts64(unsigned a, unsigned x, unsigned y) { asm volatile("st.shared.v2.b32 [%0], {%1,%2};" ::"r"(a), "r"(x), "r"(y) : "memory"); }
__device__ __forceinline__ void sts128(unsigned a, uint4 v) { asm volatile("st.shared.v4.b32 [%0], {%1,%2,%3,%4};" ::"r"(a), "r"(v.x), "r"(v.y), "r"(v.z), "r"(v.w) : "memory"); }
__device__ __forceinline__ uint2 lds64(unsigned a) { uint2 v; asm volatile("ld.shared.v2.b32 {%0,%1}, [%2];" : "=r"(v.x), "=r"(v.y) : "r"(a) : "memory"); return v; }
__device__ __forceinline__ uint4 lds128(unsigned a) { uint4 v; asm volatile("ld.shared.v4.b32 {%0,%1,%2,%3}, [%4];" : "=r"(v.x), "=r"(v.y), "=r"(v.z), "=r"(v.w) : "r"(a) : "memory"); return v; }
__device__ __forceinline__ float lds32f(unsigned a) { float v; asm volatile("ld.shared.f32 %0, [%1];" : "=f"(v) : "r"(a) : "memory"); return v; }
#define spin_check(it) TRAP_IF(++it)
#define POLLV 0
#define BAR8 0
#define D_STAG 150
#define D_RED 0
#define D_PUB 0
#define DELAY(n) do { unsigned c0_, c1_; asm volatile("mov.u32 %0, %%clock;" : "=r"(c0_)); do { asm volatile("mov.u32 %0, %%clock;" : "=r"(c1_)); } while (c1_ - c0_ < (n)); } while (0)
#define SCALE_QK 0.08838834764831845f

__device__ __forceinline__ void rec_worker(const Maps& maps, unsigned sb, const bf16* __restrict__ mem0) {
  const int c = blockIdx.x, h = c >> 1, j = c & 1;
  const int t = opaque_tid(), lane = t & 31, w = t >> 5, g = lane >> 2, tq = lane & 3;
  const int m = lane >> 3, r8 = lane & 7, kh = w >> 2, et = w & 3;
  const unsigned bar = sb + SM_BAR;
  unsigned wq[16][4], wk[16][4], wo[8][4];
  const unsigned woff = (kh * 4) * 8192 + ((m >> 1) * 8 + r8) * 128 + (((et * 2 + (m & 1)) ^ r8) << 4);
  mbar_wait(bar + 8 * MB_W0, 0);
#pragma unroll
  for (int i = 0; i < 16; i++) {
    ldsm_x4_t(wq[i], sb + R_WO + woff + (i >> 2) * 8192 + (i & 3) * 2048);
    ldsm_x4_t(wk[i], sb + R_T1 + woff + (i >> 2) * 8192 + (i & 3) * 2048);
  }
  bar_sync(2, 288);
  if (t == 0) {
    fence_proxy_async_smem();
    mbar_expect_tx(bar + 8 * MB_WO, 65536);
    for (int kb = 0; kb < 2; kb++)
      for (int cb = 0; cb < 4; cb++) tma_load_2d(sb + R_WO + (kb * 4 + cb) * 8192, &maps.wo, j * 256 + cb * 64, h * 128 + kb * 64, bar + 8 * MB_WO);
  }
  mbar_wait(bar + 8 * MB_W1, 0);
  const unsigned pV = sb + R_T2 + woff;
  const unsigned rk = c & 7, peer = rk ^ 1, cl = c >> 3;
#define KEEP(x) x = __shfl_sync(~0u, x, lane)
  unsigned pA = sb + R_MEM + kh * 4096 + lane * 16;
  unsigned pW0 = sb + R_WO + (w >> 1) * 8192 + ((m >> 1) * 8 + r8) * 128 + ((((w & 1) * 4 + (m & 1)) ^ r8) << 4);
  unsigned pW1 = pW0 ^ 32;
  unsigned pVk = pV;
  unsigned aX = sb + R_VRED + et * 512 + lane * 16;
  unsigned aQKst = sb + (kh ? R_KS : R_QS) + r8 * 144 + (et * 16 + (m & 1) * 8) * 2;
  unsigned aL8 = sb + lane * 8;
  unsigned aSl = mapa(sb + R_SOWN + w * 256 + lane * 8, rk), aSr = mapa(sb + R_SPEER + w * 256 + lane * 8, peer);
  unsigned aVl = mapa(sb + R_VM + (j * 4 + et) * 256 + lane * 8, rk), aVr = mapa(sb + R_VM + (j * 4 + et) * 256 + lane * 8, peer);
  const unsigned mbSl = mapa(bar + 8 * MB_S, rk), mbSr = mapa(bar + 8 * MB_S, peer), mbVl = mbSl + 8, mbVr = mbSr + 8;
  unsigned aQ = sb + R_QS + r8 * 144 + m * 16;
  unsigned oKx = (et * 8 + r8) * 128 + ((m ^ r8) << 4);
  unsigned oVx = 4096 + (et >> 1) * 4096 + ((m >> 1) * 8 + r8) * 128 + ((((et & 1) * 4 + (m & 1)) ^ r8) << 4);
  unsigned aOst = sb + R_OS + r8 * 272 + (et * 32 + m * 8) * 2;
  unsigned aOld = sb + R_OS + r8 * 272 + m * 16;
  unsigned aVm = sb + R_VM + et * 512 + lane * 8;
  unsigned aRSr = mapa(sb + R_RS + (h & 3) * 2048 + (w & 1) * 1024 + lane * 8, j * 4 + (w >> 1));
  unsigned mbRSr = mapa(bar + 8 * MB_RS, j * 4 + (w >> 1));
  unsigned t8 = t * 8;
  KEEP(pA); KEEP(pW0); KEEP(pW1); KEEP(pVk); KEEP(aX); KEEP(aQKst); KEEP(aL8); KEEP(aSl); KEEP(aSr); KEEP(aVl); KEEP(aVr); KEEP(aQ); KEEP(oKx); KEEP(oVx);
  KEEP(aOst); KEEP(aOld); KEEP(aVm); KEEP(aRSr); KEEP(mbRSr); KEEP(t8);
  mbar_wait(bar + 8 * MB_WO, 0);
#pragma unroll
  for (int ks = 0; ks < 4; ks++) { ldsm_x4_t(wo[2 * ks], pW0 + ks * 2048); ldsm_x4_t(wo[2 * ks + 1], pW1 + ks * 2048); }
  {
    unsigned v[8];
#pragma unroll
    for (int q = 0; q < 8; q++) v[q] = __ldg(reinterpret_cast<const unsigned*>(mem0) + q * 256 + t);
    sts128(sb + R_MEM + t * 32, make_uint4(__byte_perm(v[0], v[1], 0x5410), __byte_perm(v[2], v[3], 0x5410), __byte_perm(v[4], v[5], 0x5410), __byte_perm(v[6], v[7], 0x5410)));
    sts128(sb + R_MEM + t * 32 + 16, make_uint4(__byte_perm(v[0], v[1], 0x7632), __byte_perm(v[2], v[3], 0x7632), __byte_perm(v[4], v[5], 0x7632), __byte_perm(v[6], v[7], 0x7632)));
  }
  bar_sync(1, 256);

#pragma unroll 1
  for (int s = 0;; s++) {
    const unsigned par = s & 1;
    const unsigned slot = s & (RING_N - 1), rpar = (s / RING_N) & 1;
    const unsigned ring = sb + R_RING + slot * RING_BYTES;
    RSTAMP(1);
    RSTAMP(2);
    float aq[4] = {0, 0, 0, 0}, ak[4] = {0, 0, 0, 0}, av[4] = {0, 0, 0, 0};
#pragma unroll
    for (int i = 0; i < 8; i++) {
      unsigned b[4], f[4], f0[4];
      ldsm_x4_t(b, pA + i * 512);
      ldsm_x4_t(f0, pVk + (i >> 1) * 8192 + (i & 1) * 4096);
      ldsm_x4_t(f, pVk + (i >> 1) * 8192 + (i & 1) * 4096 + 2048);
      mma16816(aq, wq[2 * i], b[0], b[1]); mma16816(ak, wk[2 * i], b[0], b[1]); mma16816(av, f0, b[0], b[1]);
      mma16816(aq, wq[2 * i + 1], b[2], b[3]); mma16816(ak, wk[2 * i + 1], b[2], b[3]); mma16816(av, f, b[2], b[3]);
    }
    RSTAMP(3);
#define STSF4(a, v) asm volatile("st.shared.v4.f32 [%0], {%1,%2,%3,%4};" ::"r"(a), "f"(v[0]), "f"(v[1]), "f"(v[2]), "f"(v[3]) : "memory")
    unsigned f[8][4];
#define NPRE 2
#define WO_PREFETCH() do { _Pragma("unroll") for (int i = 0; i < NPRE; i++) { ldsm_x4_t(f[2 * i], pW0 + 32768 + i * 2048); ldsm_x4_t(f[2 * i + 1], pW1 + 32768 + i * 2048); } } while (0)
    if (kh) {
      STSF4(aX, aq);
      bar_sync(4 + et, 64);
      uint4 o = lds128(aX + 2048), o2 = lds128(aX + 4096);
      stsm_x2_t(aQKst, pack_bf16(ak[0] + __uint_as_float(o.x), ak[1] + __uint_as_float(o.y)), pack_bf16(ak[2] + __uint_as_float(o.z), ak[3] + __uint_as_float(o.w)));
      bar_arrive(1, 256);
      unsigned x = pack_bf16(av[0] + __uint_as_float(o2.x), av[1] + __uint_as_float(o2.y)), y = pack_bf16(av[2] + __uint_as_float(o2.z), av[3] + __uint_as_float(o2.w));
      st_async_b64(aVr, x, y, mbVr);
      st_async_b64(aVl, x, y, mbVl);
      mbar_wait(bar + 8 * (MB_FULL + slot), rpar);
      unsigned vx[4][4];
      ldsm_x4_t(vx[0], ring + oVx); ldsm_x4_t(vx[1], ring + oVx + 2048); ldsm_x4_t(vx[2], ring + (oVx ^ 32)); ldsm_x4_t(vx[3], ring + (oVx ^ 32) + 2048);
      RSTAMP(4); RSTAMP(5); RSTAMP(6); RSTAMP(7);
      mbar_wait(bar + 8 * MB_S, par);
      RSTAMP(8);
      float sc[10];
#pragma unroll
      for (int i = 0; i < 5; i++) {
        uint2 o = lds64(aL8 + R_SOWN + i * 256), p = lds64(aL8 + R_SPEER + i * 256);
        sc[2 * i] = __uint_as_float(o.x) + __uint_as_float(p.x); sc[2 * i + 1] = __uint_as_float(o.y) + __uint_as_float(p.y);
      }
      mbar_wait(bar + 8 * MB_V, par);
      uint2 vm0 = lds64(aVm), vm1 = lds64(aVm + 256);
      float mx = fmaxf(fmaxf(fmaxf(sc[0], sc[1]), fmaxf(sc[2], sc[3])), fmaxf(fmaxf(fmaxf(sc[4], sc[5]), fmaxf(sc[6], sc[7])), fmaxf(sc[8], sc[9])));
      mx = fmaxf(mx, __shfl_xor_sync(~0u, mx, 1)); mx = fmaxf(mx, __shfl_xor_sync(~0u, mx, 2));
      const float nm = -mx * (SCALE_QK * LOG2E);
#pragma unroll
      for (int i = 0; i < 10; i++) sc[i] = ex2f(fmaf(sc[i], SCALE_QK * LOG2E, nm));
      float sum = (((sc[0] + sc[1]) + (sc[2] + sc[3])) + ((sc[4] + sc[5]) + (sc[6] + sc[7]))) + (sc[8] + sc[9]);
      sum += __shfl_xor_sync(~0u, sum, 1); sum += __shfl_xor_sync(~0u, sum, 2);
      float inv; asm("rcp.approx.ftz.f32 %0, %1;" : "=f"(inv) : "f"(sum));
      unsigned p[5];
#pragma unroll
      for (int i = 0; i < 5; i++) p[i] = pack_bf16(sc[2 * i] * inv, sc[2 * i + 1] * inv);
      RSTAMP(9);
      float o0[4] = {0, 0, 0, 0}, o1[4] = {0, 0, 0, 0}, o3[4] = {0, 0, 0, 0}, o4[4] = {0, 0, 0, 0};
      mma16816(o0, vx[0], p[0], p[1]); mma16816(o3, vx[2], p[0], p[1]); mma16816(o1, vx[1], p[2], p[3]); mma16816(o4, vx[3], p[2], p[3]);
      mma1688(o0, vm0.x, vm0.y, p[4]); mma1688(o3, vm1.x, vm1.y, p[4]);
      if (s == NSEG - 1) { if (t == 128) mbar_arrive(bar + 8 * MB_KVR); break; }
      asm volatile("stmatrix.sync.aligned.m8n8.x4.trans.shared.b16 [%0], {%1,%2,%3,%4};" ::"r"(aOst), "r"(pack_bf16(o0[0] + o1[0], o0[1] + o1[1])), "r"(pack_bf16(o0[2] + o1[2], o0[3] + o1[3])),
                   "r"(pack_bf16(o3[0] + o4[0], o3[1] + o4[1])), "r"(pack_bf16(o3[2] + o4[2], o3[3] + o4[3])) : "memory");
      RSTAMP(10);
      bar_sync(1, 256);
      WO_PREFETCH();
    } else {
      STSF4(aX + 2048, ak); STSF4(aX + 4096, av);
      unsigned kb[8];
      mbar_wait(bar + 8 * (MB_FULL + slot), rpar);
      ldsm_x4(kb, ring + oKx); ldsm_x4(kb + 4, ring + (oKx ^ 64));
      bar_sync(4 + et, 64);
      uint4 o = lds128(aX);
      stsm_x2_t(aQKst, pack_bf16(aq[0] + __uint_as_float(o.x), aq[1] + __uint_as_float(o.y)), pack_bf16(aq[2] + __uint_as_float(o.z), aq[3] + __uint_as_float(o.w)));
      RSTAMP(4);
      bar_sync(1, 256);
      RSTAMP(5);
      unsigned qa[8], km[8];
      ldsm_x4(qa, aQ); ldsm_x4(qa + 4, aQ + 64);
      if (w == 3) { ldsm_x4(km, aQ + 1152); ldsm_x4(km + 4, aQ + 1152 + 64); }
      float s0[4] = {0, 0, 0, 0}, s1[4] = {0, 0, 0, 0};
      unsigned af[4][4];
#pragma unroll
      for (int i = 0; i < 4; i++) { af[i][0] = qa[2 * i]; af[i][1] = 0; af[i][2] = qa[2 * i + 1]; af[i][3] = 0; }
      mma16816(s0, af[0], kb[0], kb[1]); mma16816(s1, af[1], kb[2], kb[3]);
      mma16816(s0, af[2], kb[4], kb[5]); mma16816(s1, af[3], kb[6], kb[7]);
      if (w == 3) {
        float m0[4] = {0, 0, 0, 0}, m1[4] = {0, 0, 0, 0};
        mma16816(m0, af[0], km[0], km[1]); mma16816(m1, af[1], km[2], km[3]);
        mma16816(m0, af[2], km[4], km[5]); mma16816(m1, af[3], km[6], km[7]);
        unsigned x = __float_as_uint(m0[0] + m1[0]), y = __float_as_uint(m0[1] + m1[1]);
        st_async_b64(aSr + 256, x, y, mbSr); st_async_b64(aSl + 256, x, y, mbSl);
      }
      unsigned x = __float_as_uint(s0[0] + s1[0]), y = __float_as_uint(s0[1] + s1[1]);
      st_async_b64(aSr, x, y, mbSr); st_async_b64(aSl, x, y, mbSl);
      RSTAMP(6);
      if (s == NSEG - 1) break;
      WO_PREFETCH();
      RSTAMP(7); RSTAMP(8); RSTAMP(9); RSTAMP(10);
      bar_sync(1, 256);
    }
    RSTAMP(11);
    float d0[4] = {0, 0, 0, 0}, d1[4] = {0, 0, 0, 0}, e0[4] = {0, 0, 0, 0}, e1[4] = {0, 0, 0, 0};
    unsigned ob[4][4];
#pragma unroll
    for (int k2 = 0; k2 < 4; k2++) ldsm_x4(ob[k2], aOld + k2 * 64);
#pragma unroll
    for (int i = NPRE; i < 4; i++) { ldsm_x4_t(f[2 * i], pW0 + 32768 + i * 2048); ldsm_x4_t(f[2 * i + 1], pW1 + 32768 + i * 2048); }
    mma16816(d0, wo[0], ob[0][0], ob[0][1]); mma16816(d1, wo[1], ob[0][0], ob[0][1]);
    mma16816(e0, wo[2], ob[0][2], ob[0][3]); mma16816(e1, wo[3], ob[0][2], ob[0][3]);
    mma16816(d0, wo[4], ob[1][0], ob[1][1]); mma16816(d1, wo[5], ob[1][0], ob[1][1]);
    mma16816(e0, wo[6], ob[1][2], ob[1][3]); mma16816(e1, wo[7], ob[1][2], ob[1][3]);
    mma16816(d0, f[0], ob[2][0], ob[2][1]); mma16816(d1, f[1], ob[2][0], ob[2][1]);
    mma16816(e0, f[2], ob[2][2], ob[2][3]); mma16816(e1, f[3], ob[2][2], ob[2][3]);
    mma16816(d0, f[4], ob[3][0], ob[3][1]); mma16816(d1, f[5], ob[3][0], ob[3][1]);
    mma16816(e0, f[6], ob[3][2], ob[3][3]); mma16816(e1, f[7], ob[3][2], ob[3][3]);
    st_async_b64(aRSr, __float_as_uint(d0[0] + e0[0]), __float_as_uint(d0[1] + e0[1]), mbRSr);
    st_async_b64(aRSr + 256, __float_as_uint(d0[2] + e0[2]), __float_as_uint(d0[3] + e0[3]), mbRSr);
    st_async_b64(aRSr + 512, __float_as_uint(d1[0] + e1[0]), __float_as_uint(d1[1] + e1[1]), mbRSr);
    st_async_b64(aRSr + 768, __float_as_uint(d1[2] + e1[2]), __float_as_uint(d1[3] + e1[3]), mbRSr);
    RSTAMP(12);
    if (t == 128) {
      mbar_arrive(bar + 8 * (MB_EMPTY + slot)); mbar_arrive(bar + 8 * MB_KVR);
      mbar_expect_tx(bar + 8 * MB_S, 2560); mbar_expect_tx(bar + 8 * MB_V, 2048);
    }
    const unsigned tag = ((s >> 1) & 1) ^ 1;
    const char* gp = reinterpret_cast<const char*>(g_part) + (par * 8 + rk) * 16384 + t8;
    unsigned mbA[8];
#pragma unroll
    for (int i = 0; i < 8; i++) mbA[i] = mapa(bar + 8 * MB_AG, i);
    const unsigned dlt = (R_MEM + rk * 1024) - (SM_BAR + 8 * MB_AG) + (t8 >> 1);
    mbar_wait(bar + 8 * MB_RS, par);
    RSTAMP(13);
    uint2 a[8];
    {
      uint2 x0 = lds64(sb + R_RS + t8), x1 = lds64(sb + R_RS + 2048 + t8), x2 = lds64(sb + R_RS + 4096 + t8), x3 = lds64(sb + R_RS + 6144 + t8);
      float r0 = (__uint_as_float(x0.x) + __uint_as_float(x1.x)) + (__uint_as_float(x2.x) + __uint_as_float(x3.x));
      float r1 = (__uint_as_float(x0.y) + __uint_as_float(x1.y)) + (__uint_as_float(x2.y) + __uint_as_float(x3.y));
      a[0].x = (__float_as_uint(r0) & ~1u) | tag; a[0].y = (__float_as_uint(r1) & ~1u) | tag;
      asm volatile("st.relaxed.gpu.global.v2.u32 [%0], {%1,%2};" ::"l"(gp + cl * 2048), "r"(a[0].x), "r"(a[0].y) : "memory");
    }
    RSTAMP(14);
    if (t == 128) mbar_expect_tx(bar + 8 * MB_RS, 8192);
    {
      unsigned it = 0;
      while (true) {
#pragma unroll
        for (int i = 1; i < 8; i++) a[i] = ldv2_relaxed(gp + (cl ^ i) * 2048);
        unsigned an = a[1].x & a[1].y, orr = a[1].x | a[1].y;
#pragma unroll
        for (int i = 2; i < 8; i++) { an &= a[i].x & a[i].y; orr |= a[i].x | a[i].y; }
        if (((tag ? an : ~orr) & 1u) != 0) break;
        spin_check(it);
      }
    }
    RSTAMP(15);
    {
#define AF(i, c) __uint_as_float(a[i].c)
      unsigned u = pack_bf16(((AF(0, x) + AF(1, x)) + (AF(2, x) + AF(3, x))) + ((AF(4, x) + AF(5, x)) + (AF(6, x) + AF(7, x))),
                             ((AF(0, y) + AF(1, y)) + (AF(2, y) + AF(3, y))) + ((AF(4, y) + AF(5, y)) + (AF(6, y) + AF(7, y))));
      __syncwarp();
#pragma unroll
      for (int i = 0; i < 8; i++) st_async_b32(mbA[i] + dlt, u, mbA[i]);
    }
    mbar_wait(bar + 8 * MB_KVF, par);
    mbar_wait(bar + 8 * MB_AG, par);
    if (t == 128) mbar_expect_tx(bar + 8 * MB_AG, 8192);
  }
}

__device__ __forceinline__ void rec_ring(const Maps& maps, unsigned sb) {
  const int c = blockIdx.x, h = c >> 1, j = c & 1;
  const unsigned bar = sb + SM_BAR;
  const int lane = threadIdx.x & 31;
  if (lane == 0) {
    mbar_expect_tx(bar + 8 * MB_W0, 131072);
    for (int kb = 0; kb < 8; kb++) tma_load_2d(sb + R_WO + kb * 8192, &maps.wq, h * 128 + j * 64, kb * 64, bar + 8 * MB_W0);
    for (int kb = 0; kb < 8; kb++) tma_load_2d(sb + R_T1 + kb * 8192, &maps.wk, h * 128 + j * 64, kb * 64, bar + 8 * MB_W0);
    mbar_expect_tx(bar + 8 * MB_W1, 65536);
    for (int kb = 0; kb < 8; kb++) tma_load_2d(sb + R_T2 + kb * 8192, &maps.wv, h * 128 + j * 64, kb * 64, bar + 8 * MB_W1);
  }
  __syncwarp();
  bar_sync(2, 288);
  if (lane == 0) {
    fence_proxy_async_smem();
    for (int s = 0; s < NSEG; s++) {
      unsigned slot = s & (RING_N - 1);
      if ((s & 3) == 0 && !DBGMODE) {
        wait_flag_ge(&g_flags.qkv[(s >> 2) * 48 + 16 + (h >> 1)], 1);
        wait_flag_ge(&g_flags.qkv[(s >> 2) * 48 + 32 + (h >> 1)], 1);
        fence_proxy_async();
      }
      if (s >= RING_N) mbar_wait_sleep(bar + 8 * (MB_EMPTY + slot), ((s / RING_N) - 1) & 1);
      unsigned dst = sb + R_RING + slot * RING_BYTES, mb = bar + 8 * (MB_FULL + slot);
      mbar_expect_tx(mb, RING_BYTES);
      tma_load_2d(dst, &maps.qkv_ld, HD + h * 128 + j * 64, s * SEG, mb);
      tma_load_2d(dst + 4096, &maps.qkv_ld, 2 * HD + h * 128, s * SEG, mb);
      tma_load_2d(dst + 8192, &maps.qkv_ld, 2 * HD + h * 128 + 64, s * SEG, mb);
    }
  }
}
__device__ __forceinline__ void rec_copy(unsigned sb) {
  const int c = blockIdx.x, h = c >> 1, j = c & 1;
  const unsigned bar = sb + SM_BAR;
  const int lane = threadIdx.x & 31;
  for (int s = 0; s < NSEG; s++) {
    mbar_wait_sleep(bar + 8 * MB_KVR, s & 1);
    uint4 k0 = lds128(sb + R_KS + (lane >> 3) * 144 + (lane & 7) * 16), k1 = lds128(sb + R_KS + (4 + (lane >> 3)) * 144 + (lane & 7) * 16);
    uint2 v[4];
#pragma unroll
    for (int i = 0; i < 4; i++) v[i] = lds64(sb + R_VM + (j * 4 + i) * 256 + lane * 8);
    __syncwarp();
    if (lane == 0) mbar_arrive(bar + 8 * MB_KVF);
    bf16* kd = g_km + ((size_t)(s * NH + h) * NMEM) * DH + j * 64;
    *reinterpret_cast<uint4*>(kd + (lane >> 3) * DH + (lane & 7) * 8) = k0;
    *reinterpret_cast<uint4*>(kd + (4 + (lane >> 3)) * DH + (lane & 7) * 8) = k1;
    unsigned* vd = reinterpret_cast<unsigned*>(g_vmt) + ((size_t)(s * NH + h) * DH + j * 64) * 4;
#pragma unroll
    for (int i = 0; i < 4; i++) { vd[(i * 16) * 4 + lane] = v[i].x; vd[(i * 16 + 8) * 4 + lane] = v[i].y; }
    __syncwarp();
    if (lane == 0) st_release(&g_flags.rec[c], s + 1);
  }
}

__device__ __forceinline__ void bulk_producer(const Maps& maps, unsigned sb, int* misc) {
  const unsigned bar = sb + SM_BAR;
  unsigned st = 0, ph = 0, seq = 0;
  while (true) {
    int idx = (int)atomicAdd(&g_flags.ctr, 1u);
    if (idx >= N_ITEMS) {
      mbar_wait(bar + 8 * (MB_EMPTY + st), ph ^ 1);
      misc[seq & 3] = -1;
      mbar_arrive(bar + 8 * (MB_FULL + st));
      break;
    }
    ISTAMP(idx, 0);
    Item it = decode_item(idx);
    const CUtensorMap *ma, *mb_; int ka = 0, kbr = 0, nb0 = it.c * 256;
    if (it.type == T_QKV) { ma = &maps.xn; mb_ = it.c < 16 ? &maps.wq : (it.c < 32 ? &maps.wk : &maps.wv); nb0 = (it.c & 15) * 256; }
    else if (it.type == T_M1) { ma = &maps.y; mb_ = &maps.w1; }
    else if (it.type == T_M2) { ma = &maps.h1; mb_ = &maps.w2; wait_flag_ge(&g_flags.h1[it.b], 7); }
    else if (it.type == T_OUT) { ma = &maps.o; mb_ = &maps.wo; ka = kbr = it.ks * 1024; wait_flag_ge(&g_flags.o[it.b * 4 + it.ks], 4); }
    else if (it.type == T_OUTL) { ma = &maps.o; mb_ = &maps.wo; ka = kbr = it.ks * 256; wait_flag_ge(&g_flags.o16[it.ks], 1); }
    else if (it.type >= T_RED) { ma = mb_ = &maps.o; wait_flag_ge(&g_flags.g[it.b], 2); wait_flag_ge(&g_flags.p[it.b], it.type == T_RED ? 8 : 32); }
    else {
      ma = mb_ = &maps.qkv_ld;
      wait_flag_ge(&g_flags.qkv[it.b * 48 + it.c], 1); wait_flag_ge(&g_flags.qkv[it.b * 48 + 16 + it.c], 1); wait_flag_ge(&g_flags.qkv[it.b * 48 + 32 + it.c], 1);
      for (int i = 0; i < 4; i++) wait_flag_ge(&g_flags.rec[it.c * 4 + i], it.b * 4 + 2);
    }
    fence_proxy_async();
    ISTAMP(idx, 1);
    const int nkb = item_nkb(it.type);
    for (int kb = 0; kb < nkb; kb++) {
      mbar_wait(bar + 8 * (MB_EMPTY + st), ph ^ 1);
      if (kb == 0) { misc[seq & 3] = idx; seq++; }
      unsigned dst = sb + st * STAGE_BYTES, mb = bar + 8 * (MB_FULL + st);
      if (it.type >= T_RED) { mbar_arrive(mb); if (++st == NSTAGE) { st = 0; ph ^= 1; } break; }
      if (it.type == T_ATT && kb == 2) for (int i = 0; i < 4; i++) wait_flag_ge(&g_flags.rec[it.c * 4 + i], it.b * 4 + 4);
      mbar_expect_tx(mb, STAGE_BYTES);
      if (it.type == T_ATT) {
        int head = it.c * 2 + (kb & 1), row = it.b * 128 + (kb >> 1) * 64;
        for (int i = 0; i < 12; i++) tma_load_2d(dst + i * 4096, ma, (i >> 2) * HD + head * 128 + (i & 1) * 64, row + ((i >> 1) & 1) * 32, mb);
      } else {
        tma_load_2d(dst, ma, ka + kb * 64, it.b * 128, mb);
        for (int i = 0; i < 4; i++) tma_load_2d(dst + 16384 + i * 8192, mb_, nb0 + i * 64, kbr + kb * 64, mb);
      }
      if (++st == NSTAGE) { st = 0; ph ^= 1; }
    }
  }
}
__device__ __forceinline__ void bulk_store(const Maps& maps, unsigned sb, volatile int* misc) {
  const unsigned bar = sb + SM_BAR;
  unsigned ph = 0;
  while (true) {
    mbar_wait(bar + 8 * MB_STGF, ph); ph ^= 1;
    int idx = misc[4];
    if (idx < 0) break;
    Item it = decode_item(idx);
    const CUtensorMap* mp = it.type == T_QKV ? &maps.qkv_st : (it.type == T_M1 ? &maps.h1 : (it.type == T_M2 ? &maps.g : &maps.o));
    unsigned* flag = it.type == T_QKV ? &g_flags.qkv[it.b * 48 + it.c] : (it.type == T_M1 ? &g_flags.h1[it.b] : (it.type == T_M2 ? &g_flags.g[it.b] : (it.b == 15 ? &g_flags.o16[it.c] : &g_flags.o[it.b * 4 + (it.c >> 2)])));
    for (int i = 0; i < 4; i++) tma_store_2d(mp, sb + B_STG + i * 16384, it.c * 256 + i * 64, it.b * 128);
    asm volatile("cp.async.bulk.commit_group;" ::: "memory");
    asm volatile("cp.async.bulk.wait_group.read 0;" ::: "memory");
    mbar_arrive(bar + 8 * MB_STGE);
    asm volatile("cp.async.bulk.wait_group 0;" ::: "memory");
    fence_proxy_async();
    red_release_add(flag, 1);
    ISTAMP(idx, 3);
  }
}
__device__ __forceinline__ float gelu_t(float x) {
  float u = 0.7978845608028654f * (x + 0.044715f * x * x * x);
  return __fdividef(x, 1.0f + __expf(-2.0f * u));
}
__device__ __forceinline__ float silu_f(float x) { return __fdividef(x, 1.0f + __expf(-x)); }

__device__ __forceinline__ void final_out(bf16* __restrict__ out, const bf16* __restrict__ x, size_t o, float4 s) {
  uint2 gv = __ldcg(reinterpret_cast<const uint2*>(g_g + o)), xv = __ldg(reinterpret_cast<const uint2*>(x + o));
  uint2 r;
  r.x = pack_bf16(bf_lo(xv.x) + bf16r(bf16r(s.x) * bf_lo(gv.x)), bf_hi(xv.x) + bf16r(bf16r(s.y) * bf_hi(gv.x)));
  r.y = pack_bf16(bf_lo(xv.y) + bf16r(bf16r(s.z) * bf_lo(gv.y)), bf_hi(xv.y) + bf16r(bf16r(s.w) * bf_hi(gv.y)));
  *reinterpret_cast<uint2*>(out + o) = r;
}
__device__ __forceinline__ void bulk_att_stage(unsigned sa, unsigned stg, int b, int hp, int kb, int w, int lane) {
  const int g = lane >> 2, tq = lane & 3, m = lane >> 3, r8 = lane & 7;
  const int seg = w >> 2, mt = (w >> 1) & 1, eh = w & 1;
  const int head = hp * 2 + (kb & 1), sg = b * 4 + (kb >> 1) * 2 + seg;
  const unsigned* kmp = reinterpret_cast<const unsigned*>(g_km + ((size_t)(sg * NH + head) * NMEM + g) * DH) + tq;
  const unsigned* vmp = reinterpret_cast<const unsigned*>(g_vmt) + ((size_t)(sg * NH + head) * DH + eh * 64) * 4 + lane;
  unsigned km[16], vm[8];
#pragma unroll
  for (int i = 0; i < 16; i++) km[i] = __ldcg(kmp + i * 4);
#pragma unroll
  for (int i = 0; i < 8; i++) vm[i] = __ldcg(vmp + i * 32);
  float s[5][4];
#pragma unroll
  for (int i = 0; i < 5; i++) { s[i][0] = s[i][1] = s[i][2] = s[i][3] = 0; }
  const unsigned qb = sa + (0 * 2 + seg) * 8192, kbs = sa + (1 * 2 + seg) * 8192, vb = sa + (2 * 2 + seg) * 8192 + eh * 4096;
  unsigned qa[8][4];
#pragma unroll
  for (int ks = 0; ks < 8; ks++) {
    int row = mt * 16 + (m & 1) * 8 + r8;
    ldsm_x4(qa[ks], qb + (ks >> 2) * 4096 + row * 128 + ((((ks & 3) * 2 + (m >> 1)) ^ r8) << 4));
    unsigned kf[4];
    int krow = (m >> 1) * 8 + r8;
    unsigned ka = kbs + (ks >> 2) * 4096 + krow * 128 + ((((ks & 3) * 2 + (m & 1)) ^ r8) << 4);
    ldsm_x4(kf, ka);
    mma16816(s[0], qa[ks], kf[0], kf[1]); mma16816(s[1], qa[ks], kf[2], kf[3]);
    if (mt) { ldsm_x4(kf, ka + 2048); mma16816(s[2], qa[ks], kf[0], kf[1]); mma16816(s[3], qa[ks], kf[2], kf[3]); }
  }
#pragma unroll
  for (int ks = 0; ks < 8; ks++) mma16816(s[4], qa[ks], km[2 * ks], km[2 * ks + 1]);
  float mx0 = -INFINITY, mx1 = -INFINITY;
  const int t0 = mt * 16 + g, t1 = t0 + 8;
#pragma unroll
  for (int i = 0; i < 5; i++) {
#pragma unroll
    for (int e = 0; e < 4; e++) {
      float v = s[i][e];
      if (i < 4) { int kj = i * 8 + 2 * tq + (e & 1); if (kj > (e < 2 ? t0 : t1)) v = -INFINITY; }
      s[i][e] = v;
      if (e < 2) mx0 = fmaxf(mx0, v); else mx1 = fmaxf(mx1, v);
    }
  }
  mx0 = fmaxf(mx0, __shfl_xor_sync(~0u, mx0, 1)); mx0 = fmaxf(mx0, __shfl_xor_sync(~0u, mx0, 2));
  mx1 = fmaxf(mx1, __shfl_xor_sync(~0u, mx1, 1)); mx1 = fmaxf(mx1, __shfl_xor_sync(~0u, mx1, 2));
  float sm0 = 0, sm1 = 0;
#pragma unroll
  for (int i = 0; i < 5; i++) {
    s[i][0] = ex2f((s[i][0] - mx0) * (SCALE_QK * LOG2E)); s[i][1] = ex2f((s[i][1] - mx0) * (SCALE_QK * LOG2E));
    s[i][2] = ex2f((s[i][2] - mx1) * (SCALE_QK * LOG2E)); s[i][3] = ex2f((s[i][3] - mx1) * (SCALE_QK * LOG2E));
    sm0 += s[i][0] + s[i][1]; sm1 += s[i][2] + s[i][3];
  }
  sm0 += __shfl_xor_sync(~0u, sm0, 1); sm0 += __shfl_xor_sync(~0u, sm0, 2);
  sm1 += __shfl_xor_sync(~0u, sm1, 1); sm1 += __shfl_xor_sync(~0u, sm1, 2);
  const float i0 = __fdividef(1.0f, sm0), i1 = __fdividef(1.0f, sm1);
  unsigned pa[2][4], pm0, pm1;
#pragma unroll
  for (int kk = 0; kk < 2; kk++) {
    pa[kk][0] = pack_bf16(s[2 * kk][0] * i0, s[2 * kk][1] * i0); pa[kk][1] = pack_bf16(s[2 * kk][2] * i1, s[2 * kk][3] * i1);
    pa[kk][2] = pack_bf16(s[2 * kk + 1][0] * i0, s[2 * kk + 1][1] * i0); pa[kk][3] = pack_bf16(s[2 * kk + 1][2] * i1, s[2 * kk + 1][3] * i1);
  }
  pm0 = pack_bf16(s[4][0] * i0, s[4][1] * i0); pm1 = pack_bf16(s[4][2] * i1, s[4][3] * i1);
  const int orow = (kb >> 1) * 64 + seg * 32 + mt * 16 + (m & 1) * 8 + r8;
  const unsigned ob = stg + ((kb & 1) * 2 + eh) * 16384 + orow * 128;
#pragma unroll
  for (int cp = 0; cp < 4; cp++) {
    float o0[4] = {0, 0, 0, 0}, o1[4] = {0, 0, 0, 0};
    mma1688(o0, pm0, pm1, vm[2 * cp]); mma1688(o1, pm0, pm1, vm[2 * cp + 1]);
    unsigned vf[4];
    int row = (m & 1) * 8 + r8;
    unsigned va = vb + row * 128 + (((cp * 2 + (m >> 1)) ^ r8) << 4);
    ldsm_x4_t(vf, va);
    mma16816(o0, pa[0], vf[0], vf[1]); mma16816(o1, pa[0], vf[2], vf[3]);
    if (mt) { ldsm_x4_t(vf, va + 2048); mma16816(o0, pa[1], vf[0], vf[1]); mma16816(o1, pa[1], vf[2], vf[3]); }
    stsm_x4(ob + (((cp * 2 + (m >> 1)) ^ r8) << 4), pack_bf16(o0[0], o0[1]), pack_bf16(o0[2], o0[3]), pack_bf16(o1[0], o1[1]), pack_bf16(o1[2], o1[3]));
  }
}

__device__ __forceinline__ void bulk_worker(unsigned sb, volatile int* misc, const bf16* __restrict__ x, const bf16* __restrict__ b1, const bf16* __restrict__ b2, bf16* __restrict__ out) {
  const int t = threadIdx.x, lane = t & 31, w = t >> 5, wg = w >> 2, g = lane >> 2, tq = lane & 3, m = lane >> 3, r8 = lane & 7;
  const unsigned bar = sb + SM_BAR;
  unsigned st = 0, ph = 0, seq = 0, sph = 0;
  float d[128];
  while (true) {
    mbar_wait(bar + 8 * (MB_FULL + st), ph);
    const int idx = misc[seq & 3]; seq++;
    if (idx < 0 || idx >= N_ITEMS) break;
    if (t == 0) ISTAMP(idx, 2);
    const Item it = decode_item(idx);
    const int nkb = item_nkb(it.type);
    if (it.type == T_ATT) {
      mbar_wait(bar + 8 * MB_STGE, sph ^ 1);
      for (int kb = 0; kb < 4; kb++) {
        if (kb) mbar_wait(bar + 8 * (MB_FULL + st), ph);
        bulk_att_stage(sb + st * STAGE_BYTES, sb + B_STG, it.b, it.c, kb, w, lane);
        __syncwarp();
        if (lane == 0) mbar_arrive(bar + 8 * (MB_EMPTY + st));
        if (++st == NSTAGE) { st = 0; ph ^= 1; }
      }
      if (t == 0) misc[4] = idx;
      fence_proxy_async_smem();
      mbar_arrive(bar + 8 * MB_STGF); sph ^= 1;
      continue;
    }
    if (it.type >= T_RED) {
      __syncwarp();
      if (lane == 0) mbar_arrive(bar + 8 * (MB_EMPTY + st));
      if (++st == NSTAGE) { st = 0; ph ^= 1; }
      if (it.type == T_RED) {
#pragma unroll 2
        for (int i = 0; i < 8; i++) {
          size_t o = ((size_t)it.b * 128 + it.c * 16 + i * 2 + (t >> 7)) * DM + (t & 127) * 4;
          float4 a = __ldcg(reinterpret_cast<const float4*>(g_opart + o)), b = __ldcg(reinterpret_cast<const float4*>(g_opart + o + (size_t)S_TOK * DM));
          float4 c = __ldcg(reinterpret_cast<const float4*>(g_opart + o + (size_t)2 * S_TOK * DM)), e = __ldcg(reinterpret_cast<const float4*>(g_opart + o + (size_t)3 * S_TOK * DM));
          final_out(out, x, o, make_float4((a.x + b.x) + (c.x + e.x), (a.y + b.y) + (c.y + e.y), (a.z + b.z) + (c.z + e.z), (a.w + b.w) + (c.w + e.w)));
        }
      } else {
        size_t ol = ((size_t)it.c * 2 + (t >> 7)) * DM + (t & 127) * 4;
        float4 v[16];
#pragma unroll
        for (int i = 0; i < 16; i++) v[i] = __ldcg(reinterpret_cast<const float4*>(g_opl + ol + (size_t)i * 128 * DM));
#pragma unroll
        for (int st2 = 1; st2 < 16; st2 <<= 1)
#pragma unroll
          for (int i = 0; i < 16; i += 2 * st2) { v[i].x += v[i + st2].x; v[i].y += v[i + st2].y; v[i].z += v[i + st2].z; v[i].w += v[i + st2].w; }
        final_out(out, x, ol + (size_t)15 * 128 * DM, v[0]);
      }
      if (t == 0) ISTAMP(idx, 3);
      continue;
    }
    unsigned pst = 0;
    for (int kb = 0; kb < nkb; kb++) {
      if (kb) mbar_wait(bar + 8 * (MB_FULL + st), ph);
      unsigned sa = sb + st * STAGE_BYTES;
      uint64_t ad = mkdesc(sa + wg * 8192, 16, 1024), bd = mkdesc(sa + 16384, 8192, 1024);
      asm volatile("wgmma.fence.sync.aligned;" ::: "memory");
#pragma unroll
      for (int k = 0; k < 4; k++) wgmma_n256(d, ad + k * 2, bd + k * 128, (kb | k) != 0);
      asm volatile("wgmma.commit_group.sync.aligned;" ::: "memory");
      if (kb) {
        asm volatile("wgmma.wait_group.sync.aligned 1;" ::: "memory");
        if (lane == 0) mbar_arrive(bar + 8 * (MB_EMPTY + pst));
      }
      pst = st;
      if (++st == NSTAGE) { st = 0; ph ^= 1; }
    }
    asm volatile("wgmma.wait_group.sync.aligned 0;" ::: "memory");
    if (lane == 0) mbar_arrive(bar + 8 * (MB_EMPTY + pst));
    if (it.type >= T_OUT) {
      const int col = it.c * 256 + 2 * tq;
      float* pp = it.type == T_OUT ? g_opart + ((size_t)it.ks * S_TOK + it.b * 128 + w * 16 + g) * DM + col : g_opl + ((size_t)it.ks * 128 + w * 16 + g) * DM + col;
#pragma unroll
      for (int i = 0; i < 32; i++) {
        __stcg(reinterpret_cast<float2*>(pp + i * 8), make_float2(d[4 * i], d[4 * i + 1]));
        __stcg(reinterpret_cast<float2*>(pp + 8 * DM + i * 8), make_float2(d[4 * i + 2], d[4 * i + 3]));
      }
      bar_sync(1, 256);
      if (t == 0) { red_release_add(&g_flags.p[it.b], 1); ISTAMP(idx, 3); }
      continue;
    }
    if (it.type != T_QKV) {
      const unsigned* bp = reinterpret_cast<const unsigned*>((it.type == T_M1 ? b1 : b2) + it.c * 256) + tq;
#pragma unroll
      for (int i = 0; i < 32; i++) {
        unsigned bv = __ldg(bp + i * 4);
        float lo = bf_lo(bv), hi = bf_hi(bv);
        float x0 = bf16r(bf16r(d[4 * i]) + lo), x1 = bf16r(bf16r(d[4 * i + 1]) + hi), x2 = bf16r(bf16r(d[4 * i + 2]) + lo), x3 = bf16r(bf16r(d[4 * i + 3]) + hi);
        if (it.type == T_M1) { d[4 * i] = gelu_t(x0); d[4 * i + 1] = gelu_t(x1); d[4 * i + 2] = gelu_t(x2); d[4 * i + 3] = gelu_t(x3); }
        else { d[4 * i] = silu_f(x0); d[4 * i + 1] = silu_f(x1); d[4 * i + 2] = silu_f(x2); d[4 * i + 3] = silu_f(x3); }
      }
    }
    mbar_wait(bar + 8 * MB_STGE, sph ^ 1);
    {
      const unsigned ob = sb + B_STG + (w * 16 + (m & 1) * 8 + r8) * 128;
#pragma unroll
      for (int i = 0; i < 16; i++)
        stsm_x4(ob + (i >> 2) * 16384 + ((((i & 3) * 2 + (m >> 1)) ^ r8) << 4), pack_bf16(d[8 * i], d[8 * i + 1]), pack_bf16(d[8 * i + 2], d[8 * i + 3]),
                pack_bf16(d[8 * i + 4], d[8 * i + 5]), pack_bf16(d[8 * i + 6], d[8 * i + 7]));
    }
    if (t == 0) misc[4] = idx;
    fence_proxy_async_smem();
    mbar_arrive(bar + 8 * MB_STGF); sph ^= 1;
  }
  mbar_wait(bar + 8 * MB_STGE, sph ^ 1);
  if (t == 0) misc[4] = -1;
  mbar_arrive(bar + 8 * MB_STGF);
}

__global__ void __launch_bounds__(384, 1)
k_main(const __grid_constant__ Maps maps, const bf16* __restrict__ x, const bf16* __restrict__ mem0, const bf16* __restrict__ b1, const bf16* __restrict__ b2, bf16* __restrict__ out, int helper) {
  extern __shared__ unsigned char smem_raw[];
  const unsigned sraw = smem_u32(smem_raw);
  const unsigned sb = (sraw + 1023u) & ~1023u;
  int* misc = reinterpret_cast<int*>(smem_raw + (sb - sraw) + SM_MISC);
  const int w = threadIdx.x >> 5;
  const bool rec = !helper && blockIdx.x < NREC;
  if (!helper) asm volatile("griddepcontrol.launch_dependents;");
  if (threadIdx.x == 0) {
    const unsigned bar = sb + SM_BAR;
    for (int i = 0; i < 8; i++) { mbar_init(bar + 8 * (MB_FULL + i), 1); mbar_init(bar + 8 * (MB_EMPTY + i), rec ? 1 : 8); }
    mbar_init(bar + 8 * MB_STGF, 256); mbar_init(bar + 8 * MB_STGE, 1);
    for (int i = MB_W0; i <= MB_AG; i++) mbar_init(bar + 8 * i, 1);
    if (rec) { mbar_expect_tx(bar + 8 * MB_S, 2560); mbar_expect_tx(bar + 8 * MB_V, 2048); mbar_expect_tx(bar + 8 * MB_RS, 8192); mbar_expect_tx(bar + 8 * MB_AG, 8192); }
    asm volatile("fence.mbarrier_init.release.cluster;" ::: "memory");
  }
  __syncthreads();
  asm volatile("barrier.cluster.arrive.release.aligned;\nbarrier.cluster.wait.acquire.aligned;" ::: "memory");
  if (DBGMODE && !rec) { if (helper) asm volatile("griddepcontrol.wait;" ::: "memory"); return; }
  if (w >= 8) {
    asm volatile("setmaxnreg.dec.sync.aligned.u32 24;");
    if (rec) { if (w == 8) rec_ring(maps, sb); else if (w == 9) rec_copy(sb); }
    else if ((threadIdx.x & 31) == 0) { if (w == 8) bulk_producer(maps, sb, misc); else if (w == 9) bulk_store(maps, sb, misc);
      else if (w == 10 && helper) asm volatile("griddepcontrol.wait;" ::: "memory"); }
  } else {
    if (rec) { asm volatile("setmaxnreg.inc.sync.aligned.u32 240;"); rec_worker(maps, sb, mem0); }
    else { asm volatile("setmaxnreg.inc.sync.aligned.u32 240;"); bulk_worker(sb, misc, x, b1, b2, out); }
  }
}

typedef CUresult (*EncFn)(CUtensorMap*, CUtensorMapDataType, cuuint32_t, void*, const cuuint64_t*, const cuuint64_t*, const cuuint32_t*, const cuuint32_t*,
                          CUtensorMapInterleave, CUtensorMapSwizzle, CUtensorMapL2promotion, CUtensorMapFloatOOBfill);
static void mk_map(EncFn enc, CUtensorMap* m, const void* ptr, uint64_t rows, uint64_t cols, uint32_t box_rows) {
  cuuint64_t dims[2] = {cols, rows}; cuuint64_t strides[1] = {cols * 2};
  cuuint32_t box[2] = {64, box_rows}, es[2] = {1, 1};
  enc(m, CU_TENSOR_MAP_DATA_TYPE_BFLOAT16, 2, const_cast<void*>(ptr), dims, strides, box, es, CU_TENSOR_MAP_INTERLEAVE_NONE, CU_TENSOR_MAP_SWIZZLE_128B,
      CU_TENSOR_MAP_L2_PROMOTION_L2_256B, CU_TENSOR_MAP_FLOAT_OOB_FILL_NONE);
}
extern "C" void kernel_launch(void* const* d_in, const int* in_sizes, int n_in, void* d_out, int out_size) {
  static EncFn enc = nullptr;
  static int ncl = 0, nhelp = 0;
  static void *p_xn, *p_y, *p_h1, *p_o, *p_qkv, *p_g;
  if (!enc) {
    void* fn = nullptr; cudaDriverEntryPointQueryResult qr;
    cudaGetDriverEntryPoint("cuTensorMapEncodeTiled", &fn, cudaEnableDefault, &qr);
    enc = (EncFn)fn;
    cudaGetSymbolAddress(&p_xn, g_xn); cudaGetSymbolAddress(&p_y, g_y); cudaGetSymbolAddress(&p_h1, g_h1);
    cudaGetSymbolAddress(&p_o, g_o); cudaGetSymbolAddress(&p_qkv, g_qkv); cudaGetSymbolAddress(&p_g, g_g);
    cudaFuncSetAttribute(k_main, cudaFuncAttributeMaxDynamicSharedMemorySize, SMEM_TOTAL);
    cudaLaunchConfig_t cfg = {}; cfg.gridDim = dim3(128); cfg.blockDim = dim3(384); cfg.dynamicSmemBytes = SMEM_TOTAL;
    cudaLaunchAttribute at[1]; at[0].id = cudaLaunchAttributeClusterDimension; at[0].val.clusterDim.x = CLS; at[0].val.clusterDim.y = 1; at[0].val.clusterDim.z = 1;
    cfg.attrs = at; cfg.numAttrs = 1;
    if (cudaOccupancyMaxActiveClusters(&ncl, k_main, &cfg) != cudaSuccess) { cudaGetLastError(); ncl = 14; }
    ncl = ncl > 16 ? 16 : (ncl < 9 ? 9 : ncl);
    int nsm = 0, dev = 0; cudaGetDevice(&dev); cudaDeviceGetAttribute(&nsm, cudaDevAttrMultiProcessorCount, dev);
    nhelp = nsm - ncl * CLS;
  }
  Maps maps;
  mk_map(enc, &maps.xn, p_xn, S_TOK, DM, 128); mk_map(enc, &maps.y, p_y, S_TOK, DM, 128); mk_map(enc, &maps.h1, p_h1, S_TOK, FF, 128);
  mk_map(enc, &maps.o, p_o, S_TOK, HD, 128); mk_map(enc, &maps.qkv_st, p_qkv, S_TOK, 3 * HD, 128); mk_map(enc, &maps.qkv_ld, p_qkv, S_TOK, 3 * HD, 32);
  mk_map(enc, &maps.g, p_g, S_TOK, DM, 128);
  mk_map(enc, &maps.wq, d_in[2], DM, HD, 64); mk_map(enc, &maps.wk, d_in[3], DM, HD, 64); mk_map(enc, &maps.wv, d_in[4], DM, HD, 64);
  mk_map(enc, &maps.wo, d_in[5], HD, DM, 64); mk_map(enc, &maps.w1, d_in[8], DM, FF, 64); mk_map(enc, &maps.w2, d_in[10], FF, DM, 64);
  cudaStream_t st = cudaStreamPerThread;
  k_pre<<<256, 256, 0, st>>>((const bf16*)d_in[0]);
  cudaLaunchConfig_t cfg = {}; cfg.gridDim = dim3(ncl * CLS); cfg.blockDim = dim3(384); cfg.dynamicSmemBytes = SMEM_TOTAL; cfg.stream = st;
  cudaLaunchAttribute at[1]; at[0].id = cudaLaunchAttributeClusterDimension; at[0].val.clusterDim.x = CLS; at[0].val.clusterDim.y = 1; at[0].val.clusterDim.z = 1;
  cfg.attrs = at; cfg.numAttrs = 1;
  cudaLaunchKernelEx(&cfg, k_main, maps, (const bf16*)d_in[0], (const bf16*)d_in[1], (const bf16*)d_in[9], (const bf16*)d_in[11], (bf16*)d_out, 0);
  if (nhelp > 0) {
    cfg.gridDim = dim3(nhelp);
    at[0].id = cudaLaunchAttributeProgrammaticStreamSerialization; at[0].val.programmaticStreamSerializationAllowed = 1;
    cudaLaunchKernelEx(&cfg, k_main, maps, (const bf16*)d_in[0], (const bf16*)d_in[1], (const bf16*)d_in[9], (const bf16*)d_in[11], (bf16*)d_out, 1);
  }
}
```

```cpp
#include <cuda_runtime.h>
#include <cuda_bf16.h>
#include <cuda.h>
#include <stdint.h>

typedef __nv_bfloat16 bf16;

#define S_TOK 2048
#define DM 512
#define NH 32
#define DH 128
#define HD 4096
#define NMEM 8
#define SEG 32
#define NSEG 64
#define FF 1792
#define NBLK 16
#define NREC 64
#define CLS 8

__device__ __align__(1024) bf16 g_xn[S_TOK * DM];
__device__ __align__(1024) bf16 g_y[S_TOK * DM];
__device__ __align__(1024) bf16 g_qkv[(size_t)S_TOK * 3 * HD];
__device__ __align__(1024) bf16 g_h1[S_TOK * FF];
__device__ __align__(1024) bf16 g_g[S_TOK * DM];
__device__ __align__(1024) bf16 g_o[(size_t)S_TOK * HD];
__device__ __align__(1024) bf16 g_km[NSEG * NH * NMEM * DH];
__device__ __align__(1024) bf16 g_vmt[NSEG * NH * DH * NMEM];
__device__ __align__(1024) float g_opart[(size_t)4 * S_TOK * DM];
__device__ __align__(1024) float g_opl[(size_t)16 * 128 * DM];
__device__ __align__(1024) unsigned g_part[2 * 8 * 8 * 512];
struct Flags {
  unsigned qkv[NBLK * 48];
  unsigned h1[NBLK];
  unsigned g[NBLK];
  unsigned o[NBLK * 4];
  unsigned p[NBLK];
  unsigned o16[16];
  unsigned ctr;
  unsigned rec[NREC];
  unsigned abort_;
};
__device__ __align__(1024) Flags g_flags;

#define RSTAMP(k)
#define DBGMODE 0
#define ISTAMP(i, k)
__device__ __forceinline__ unsigned smem_u32(const void* p) { return (unsigned)__cvta_generic_to_shared(p); }
__device__ __forceinline__ float bf16r(float x) { unsigned u; asm("cvt.rn.bf16x2.f32 %0, %1, %2;" : "=r"(u) : "f"(x), "f"(0.0f)); return __uint_as_float(u); }
__device__ __forceinline__ unsigned pack_bf16(float lo, float hi) {
  __nv_bfloat162 v = __floats2bfloat162_rn(lo, hi);
  return *reinterpret_cast<unsigned*>(&v);
}
__device__ __forceinline__ float bf_lo(unsigned u) { return __uint_as_float(u << 16); }
__device__ __forceinline__ float bf_hi(unsigned u) { return __uint_as_float(u & 0xffff0000u); }

#define SPIN_LIMIT (1u << 20)
#define TRAP_IF(x) if ((x) > SPIN_LIMIT) { asm volatile("st.global.u32 [%0], %1;" ::"l"(0ull), "r"(0u) : "memory"); break; }
__device__ __forceinline__ unsigned ld_acquire(const unsigned* p) {
  unsigned v; asm volatile("ld.acquire.gpu.global.u32 %0, [%1];" : "=r"(v) : "l"(p) : "memory"); return v;
}
__device__ __forceinline__ unsigned ld_relaxed(const unsigned* p) {
  unsigned v; asm volatile("ld.relaxed.gpu.global.u32 %0, [%1];" : "=r"(v) : "l"(p) : "memory"); return v;
}
__device__ __forceinline__ void red_release_add(unsigned* p, unsigned v) {
  asm volatile("red.release.gpu.global.add.u32 [%0], %1;" ::"l"(p), "r"(v) : "memory");
}
__device__ __forceinline__ void st_release(unsigned* p, unsigned v) {
  asm volatile("st.release.gpu.global.u32 [%0], %1;" ::"l"(p), "r"(v) : "memory");
}
__device__ __forceinline__ void wait_flag_ge(const unsigned* p, unsigned target) {
  unsigned it = 0;
  while (ld_acquire(p) < target) {
    __nanosleep(64);
    TRAP_IF(++it);
  }
}
__device__ __forceinline__ uint4 ldv4_relaxed(const void* p) {
  uint4 a; asm volatile("ld.relaxed.gpu.global.v4.u32 {%0,%1,%2,%3}, [%4];" : "=r"(a.x), "=r"(a.y), "=r"(a.z), "=r"(a.w) : "l"(p) : "memory"); return a;
}
__device__ __forceinline__ uint2 ldv2_relaxed(const void* p) {
  uint2 a; asm volatile("ld.relaxed.gpu.global.v2.u32 {%0,%1}, [%2];" : "=r"(a.x), "=r"(a.y) : "l"(p) : "memory"); return a;
}
__device__ __forceinline__ void mbar_init(unsigned mb, unsigned cnt) { asm volatile("mbarrier.init.shared::cta.b64 [%0], %1;" ::"r"(mb), "r"(cnt) : "memory"); }
__device__ __forceinline__ void mbar_expect_tx(unsigned mb, unsigned bytes) { asm volatile("mbarrier.arrive.expect_tx.shared::cta.b64 _, [%0], %1;" ::"r"(mb), "r"(bytes) : "memory"); }
__device__ __forceinline__ void mbar_arrive(unsigned mb) { asm volatile("mbarrier.arrive.shared::cta.b64 _, [%0];" ::"r"(mb) : "memory"); }
__device__ __forceinline__ void mbar_wait(unsigned mb, unsigned parity) {
  unsigned ok, it = 0;
  while (true) {
    asm volatile("{.reg .pred p; mbarrier.try_wait.parity.shared::cta.b64 p, [%1], %2; selp.u32 %0,1,0,p;}" : "=r"(ok) : "r"(mb), "r"(parity) : "memory");
    if (ok) break;
    TRAP_IF(++it);
  }
}
__device__ __forceinline__ void mbar_wait_sleep(unsigned mb, unsigned parity) {
  unsigned ok, it = 0;
  while (true) {
    asm volatile("{.reg .pred p; mbarrier.test_wait.parity.shared::cta.b64 p, [%1], %2; selp.u32 %0,1,0,p;}" : "=r"(ok) : "r"(mb), "r"(parity) : "memory");
    if (ok) break;
    __nanosleep(200);
    TRAP_IF(++it);
  }
}
__device__ __forceinline__ float ex2f(float x) { float y; asm("ex2.approx.ftz.f32 %0, %1;" : "=f"(y) : "f"(x)); return y; }
__device__ __forceinline__ int opaque_tid() { int t = threadIdx.x; t = __shfl_sync(~0u, t, t & 31); return t; }
#define LOG2E 1.4426950408889634f
__device__ __forceinline__ void mbar_wait_cluster(unsigned mb, unsigned parity) {
  unsigned ok, it = 0;
  while (true) {
    asm volatile("{.reg .pred p; mbarrier.try_wait.parity.acquire.cluster.shared::cta.b64 p, [%1], %2; selp.u32 %0,1,0,p;}" : "=r"(ok) : "r"(mb), "r"(parity) : "memory");
    if (ok) break;
    TRAP_IF(++it);
  }
}
__device__ __forceinline__ void bar_sync(int id, int n) { asm volatile("bar.sync %0, %1;" ::"r"(id), "r"(n) : "memory"); }
__device__ __forceinline__ void bar_arrive(int id, int n) { asm volatile("bar.arrive %0, %1;" ::"r"(id), "r"(n) : "memory"); }
__device__ __forceinline__ void tma_load_2d(unsigned dst, const CUtensorMap* map, int c0, int c1, unsigned mb) {
  asm volatile("cp.async.bulk.tensor.2d.shared::cluster.global.mbarrier::complete_tx::bytes [%0], [%1, {%3, %4}], [%2];"
               ::"r"(dst), "l"((uint64_t)map), "r"(mb), "r"(c0), "r"(c1) : "memory");
}
__device__ __forceinline__ void tma_store_2d(const CUtensorMap* map, unsigned src, int c0, int c1) {
  asm volatile("cp.async.bulk.tensor.2d.global.shared::cta.bulk_group [%0, {%2, %3}], [%1];"
               ::"l"((uint64_t)map), "r"(src), "r"(c0), "r"(c1) : "memory");
}
__device__ __forceinline__ void fence_proxy_async() { asm volatile("fence.proxy.async;" ::: "memory"); }
__device__ __forceinline__ void fence_proxy_async_smem() { asm volatile("fence.proxy.async.shared::cta;" ::: "memory"); }
__device__ __forceinline__ void ldsm_x4(unsigned* r, unsigned addr) {
  asm volatile("ldmatrix.sync.aligned.m8n8.x4.shared.b16 {%0,%1,%2,%3}, [%4];" : "=r"(r[0]), "=r"(r[1]), "=r"(r[2]), "=r"(r[3]) : "r"(addr) : "memory");
}
__device__ __forceinline__ void ldsm_x4_t(unsigned* r, unsigned addr) {
  asm volatile("ldmatrix.sync.aligned.m8n8.x4.trans.shared.b16 {%0,%1,%2,%3}, [%4];" : "=r"(r[0]), "=r"(r[1]), "=r"(r[2]), "=r"(r[3]) : "r"(addr) : "memory");
}
__device__ __forceinline__ void stsm_x2_t(unsigned addr, unsigned r0, unsigned r1) {
  asm volatile("stmatrix.sync.aligned.m8n8.x2.trans.shared.b16 [%0], {%1,%2};" ::"r"(addr), "r"(r0), "r"(r1) : "memory");
}
__device__ __forceinline__ void stsm_x4(unsigned addr, unsigned r0, unsigned r1, unsigned r2, unsigned r3) {
  asm volatile("stmatrix.sync.aligned.m8n8.x4.shared.b16 [%0], {%1,%2,%3,%4};" ::"r"(addr), "r"(r0), "r"(r1), "r"(r2), "r"(r3) : "memory");
}
__device__ __forceinline__ void mma16816(float* d, const unsigned* a, unsigned b0, unsigned b1) {
  asm volatile("mma.sync.aligned.m16n8k16.row.col.f32.bf16.bf16.f32 {%0,%1,%2,%3}, {%4,%5,%6,%7}, {%8,%9}, {%0,%1,%2,%3};"
               : "+f"(d[0]), "+f"(d[1]), "+f"(d[2]), "+f"(d[3]) : "r"(a[0]), "r"(a[1]), "r"(a[2]), "r"(a[3]), "r"(b0), "r"(b1));
}
__device__ __forceinline__ void mma1688(float* d, unsigned a0, unsigned a1, unsigned b0) {
  asm volatile("mma.sync.aligned.m16n8k8.row.col.f32.bf16.bf16.f32 {%0,%1,%2,%3}, {%4,%5}, {%6}, {%0,%1,%2,%3};"
               : "+f"(d[0]), "+f"(d[1]), "+f"(d[2]), "+f"(d[3]) : "r"(a0), "r"(a1), "r"(b0));
}
__device__ __forceinline__ uint64_t mkdesc(unsigned addr, unsigned lbo, unsigned sbo) {
  return (uint64_t)((addr >> 4) & 0x3fff) | ((uint64_t)(lbo >> 4) << 16) | ((uint64_t)(sbo >> 4) << 32) | (1ull << 62);
}
#define R8(b) "+f"(d[b]), "+f"(d[b + 1]), "+f"(d[b + 2]), "+f"(d[b + 3]), "+f"(d[b + 4]), "+f"(d[b + 5]), "+f"(d[b + 6]), "+f"(d[b + 7])
#define R32(b) R8(b), R8(b + 8), R8(b + 16), R8(b + 24)
__device__ __forceinline__ void wgmma_n256(float* d, uint64_t ad, uint64_t bd, int acc) {
  asm volatile(
      "{.reg .pred p; setp.ne.b32 p, %130, 0;\n"
      "wgmma.mma_async.sync.aligned.m64n256k16.f32.bf16.bf16 "
      "{%0,%1,%2,%3,%4,%5,%6,%7,%8,%9,%10,%11,%12,%13,%14,%15,%16,%17,%18,%19,%20,%21,%22,%23,%24,%25,%26,%27,%28,%29,%30,%31,"
      "%32,%33,%34,%35,%36,%37,%38,%39,%40,%41,%42,%43,%44,%45,%46,%47,%48,%49,%50,%51,%52,%53,%54,%55,%56,%57,%58,%59,%60,%61,%62,%63,"
      "%64,%65,%66,%67,%68,%69,%70,%71,%72,%73,%74,%75,%76,%77,%78,%79,%80,%81,%82,%83,%84,%85,%86,%87,%88,%89,%90,%91,%92,%93,%94,%95,"
      "%96,%97,%98,%99,%100,%101,%102,%103,%104,%105,%106,%107,%108,%109,%110,%111,%112,%113,%114,%115,%116,%117,%118,%119,%120,%121,%122,%123,%124,%125,%126,%127},"
      "%128, %129, p, 1, 1, 0, 1;}\n"
      : R32(0), R32(32), R32(64), R32(96)
      : "l"(ad), "l"(bd), "r"(acc));
}

__device__ __forceinline__ void ln16(const float* x, float* o) {
  float s = 0;
#pragma unroll
  for (int i = 0; i < 16; i++) s += x[i];
#pragma unroll
  for (int of = 16; of > 0; of >>= 1) s += __shfl_xor_sync(~0u, s, of);
  float mean = s * (1.0f / DM);
  float v = 0;
#pragma unroll
  for (int i = 0; i < 16; i++) { float dd = x[i] - mean; v += dd * dd; }
#pragma unroll
  for (int of = 16; of > 0; of >>= 1) v += __shfl_xor_sync(~0u, v, of);
  float mb = bf16r(mean);
  float vb = bf16r(v * (1.0f / DM));
  float den = bf16r(sqrtf(bf16r(vb + 1e-5f)));
#pragma unroll
  for (int i = 0; i < 16; i++) o[i] = bf16r(__fdiv_rn(bf16r(x[i] - mb), den));
}
__global__ void __launch_bounds__(256) k_pre(const bf16* __restrict__ x) {
  int t = threadIdx.x, lane = t & 31, w = t >> 5;
  int row = blockIdx.x * 8 + w;
  const uint4* src = reinterpret_cast<const uint4*>(x + (size_t)row * DM);
  uint4 a = src[lane], b = src[lane + 32];
  unsigned u[8] = {a.x, a.y, a.z, a.w, b.x, b.y, b.z, b.w};
  float f[16], o[16], o2[16];
#pragma unroll
  for (int i = 0; i < 8; i++) { f[2 * i] = bf_lo(u[i]); f[2 * i + 1] = bf_hi(u[i]); }
  ln16(f, o);
  ln16(o, o2);
  uint4* d1 = reinterpret_cast<uint4*>(g_xn + (size_t)row * DM);
  uint4* d2 = reinterpret_cast<uint4*>(g_y + (size_t)row * DM);
  d1[lane] = make_uint4(pack_bf16(o[0], o[1]), pack_bf16(o[2], o[3]), pack_bf16(o[4], o[5]), pack_bf16(o[6], o[7]));
  d1[lane + 32] = make_uint4(pack_bf16(o[8], o[9]), pack_bf16(o[10], o[11]), pack_bf16(o[12], o[13]), pack_bf16(o[14], o[15]));
  d2[lane] = make_uint4(pack_bf16(o2[0], o2[1]), pack_bf16(o2[2], o2[3]), pack_bf16(o2[4], o2[5]), pack_bf16(o2[6], o2[7]));
  d2[lane + 32] = make_uint4(pack_bf16(o2[8], o2[9]), pack_bf16(o2[10], o2[11]), pack_bf16(o2[12], o2[13]), pack_bf16(o2[14], o2[15]));
  int gt = blockIdx.x * 256 + t;
  uint4 z = make_uint4(0, 0, 0, 0);
  if (gt < 16384) reinterpret_cast<uint4*>(g_part)[gt] = z;
  if (gt < (int)(sizeof(Flags) / 4)) reinterpret_cast<unsigned*>(&g_flags)[gt] = 0;
}

struct Maps { CUtensorMap xn, y, h1, o, qkv_st, qkv_ld, g, wq, wk, wv, wo, w1, w2; };

#define NSTAGE 3
#define STAGE_BYTES 49152
#define B_STG (NSTAGE * STAGE_BYTES)
#define R_WO 0
#define R_T1 65536
#define R_T2 131072
#define R_RING 65536
#define RING_N 4
#define RING_BYTES 12288
#define R_MEM 196608
#define R_QS (R_MEM + 8448)
#define R_KS (R_QS + 1152)
#define R_OS (R_KS + 1152)
#define R_SOWN (R_OS + 2176)
#define R_SPEER (R_SOWN + 1280)
#define R_VM (R_SPEER + 1280)
#define R_VRED (R_VM + 2048)
#define R_RS (R_VRED + 6144)
#define SM_BAR (R_RS + 8192)
#define SMEM_TOTAL (SM_BAR + 256 + 1024)
#define MB_FULL 0
#define MB_EMPTY 8
#define MB_STGF 16
#define MB_STGE 17
#define MB_W0 18
#define MB_W1 19
#define MB_WO 20
#define MB_S 21
#define MB_V 22
#define MB_KVR 23
#define MB_KVF 24
#define MB_RS 25
#define MB_AG 26
#define SM_MISC (SM_BAR + 224)

#define N_KV 512
#define I_M1 512
#define I_Q 624
#define I_M2 880
#define I_POST 912
#define I_TAIL (I_POST + 16 * 32)
#define N_ITEMS (I_TAIL + 5 * 8 + 32 + 8 + 64)
enum { T_QKV = 0, T_M1 = 1, T_M2 = 2, T_ATT = 3, T_OUT = 4, T_OUTL = 5, T_RED = 6, T_REDL = 7 };
struct Item { int type, b, c, ks; };
__device__ __forceinline__ Item decode_item(int i) {
  Item it; it.ks = 0;
  if (i < N_KV) { it.type = T_QKV; it.b = i >> 5; it.c = 16 + (i & 31); }
  else if (i < I_Q) { it.type = T_M1; it.b = (i - I_M1) / 7; it.c = (i - I_M1) % 7; }
  else if (i < I_M2) { it.type = T_QKV; it.b = (i - I_Q) >> 4; it.c = (i - I_Q) & 15; }
  else if (i < I_POST) { it.type = T_M2; it.b = (i - I_M2) >> 1; it.c = (i - I_M2) & 1; }
  else if (i < I_TAIL) {
    int x = i - I_POST, p = x >> 5, r = x & 31;
    if (r < 16) { it.type = T_ATT; it.b = p; it.c = r; }
    else if (r < 24) { it.type = T_OUT; it.b = p - 3; it.c = r & 1; it.ks = (r - 16) >> 1; }
    else { it.type = T_RED; it.b = p - 5; it.c = r - 24; }
  } else {
    int x = i - I_TAIL, r = x & 7;
    if (x < 40) {
      int q = x >> 3;
      if (q == 0 || q == 2) { it.type = T_OUT; it.b = 13 + (q >> 1); it.c = r & 1; it.ks = r >> 1; }
      else { it.type = T_RED; it.b = q == 1 ? 11 : 9 + q; it.c = r; }
    }
    else if (x < 72) { it.type = T_OUTL; it.b = 15; it.c = x & 1; it.ks = (x - 40) >> 1; }
    else if (x < 80) { it.type = T_RED; it.b = 14; it.c = r; }
    else { it.type = T_REDL; it.b = 15; it.c = x - 80; }
  }
  return it;
}
__device__ __forceinline__ int item_nkb(int type) { return type == T_M2 ? 28 : (type == T_OUT ? 16 : (type >= T_RED ? 1 : (type >= T_ATT ? 4 : 8))); }

__device__ __forceinline__ void st_async_b64(unsigned raddr, unsigned lo, unsigned hi, unsigned rmb) {
  asm volatile("st.async.weak.shared::cluster.mbarrier::complete_tx::bytes.v2.b32 [%0], {%1,%2}, [%3];" ::"r"(raddr), "r"(lo), "r"(hi), "r"(rmb) : "memory");
}
__device__ __forceinline__ void st_async_b32(unsigned raddr, unsigned v, unsigned rmb) {
  asm volatile("st.async.weak.shared::cluster.mbarrier::complete_tx::bytes.b32 [%0], %1, [%2];" ::"r"(raddr), "r"(v), "r"(rmb) : "memory");
}
__device__ __forceinline__ unsigned mapa(unsigned a, unsigned rank) {
  unsigned r; asm volatile("mapa.shared::cluster.u32 %0, %1, %2;" : "=r"(r) : "r"(a), "r"(rank)); return r;
}
__device__ __forceinline__ void sts64(unsigned a, unsigned x, unsigned y) { asm volatile("st.shared.v2.b32 [%0], {%1,%2};" ::"r"(a), "r"(x), "r"(y) : "memory"); }
__device__ __forceinline__ void sts128(unsigned a, uint4 v) { asm volatile("st.shared.v4.b32 [%0], {%1,%2,%3,%4};" ::"r"(a), "r"(v.x), "r"(v.y), "r"(v.z), "r"(v.w) : "memory"); }
__device__ __forceinline__ uint2 lds64(unsigned a) { uint2 v; asm volatile("ld.shared.v2.b32 {%0,%1}, [%2];" : "=r"(v.x), "=r"(v.y) : "r"(a) : "memory"); return v; }
__device__ __forceinline__ uint4 lds128(unsigned a) { uint4 v; asm volatile("ld.shared.v4.b32 {%0,%1,%2,%3}, [%4];" : "=r"(v.x), "=r"(v.y), "=r"(v.z), "=r"(v.w) : "r"(a) : "memory"); return v; }
__device__ __forceinline__ float lds32f(unsigned a) { float v; asm volatile("ld.shared.f32 %0, [%1];" : "=f"(v) : "r"(a) : "memory"); return v; }
#define spin_check(it) TRAP_IF(++it)
#define POLLV 0
#define BAR8 0
#define D_STAG 150
#define D_RED 0
#define D_PUB 0
#define DELAY(n) do { unsigned c0_, c1_; asm volatile("mov.u32 %0, %%clock;" : "=r"(c0_)); do { asm volatile("mov.u32 %0, %%clock;" : "=r"(c1_)); } while (c1_ - c0_ < (n)); } while (0)
#define SCALE_QK 0.08838834764831845f

__device__ __forceinline__ void rec_worker(const Maps& maps, unsigned sb, const bf16* __restrict__ mem0) {
  const int c = blockIdx.x, h = c >> 1, j = c & 1;
  const int t = opaque_tid(), lane = t & 31, w = t >> 5, g = lane >> 2, tq = lane & 3;
  const int m = lane >> 3, r8 = lane & 7, kh = w >> 2, et = w & 3;
  const unsigned bar = sb + SM_BAR;
  unsigned wq[16][4], wk[16][4], wo[8][4];
  const unsigned woff = (kh * 4) * 8192 + ((m >> 1) * 8 + r8) * 128 + (((et * 2 + (m & 1)) ^ r8) << 4);
  mbar_wait(bar + 8 * MB_W0, 0);
#pragma unroll
  for (int i = 0; i < 16; i++) {
    ldsm_x4_t(wq[i], sb + R_WO + woff + (i >> 2) * 8192 + (i & 3) * 2048);
    ldsm_x4_t(wk[i], sb + R_T1 + woff + (i >> 2) * 8192 + (i & 3) * 2048);
  }
  bar_sync(2, 288);
  if (t == 0) {
    fence_proxy_async_smem();
    mbar_expect_tx(bar + 8 * MB_WO, 65536);
    for (int kb = 0; kb < 2; kb++)
      for (int cb = 0; cb < 4; cb++) tma_load_2d(sb + R_WO + (kb * 4 + cb) * 8192, &maps.wo, j * 256 + cb * 64, h * 128 + kb * 64, bar + 8 * MB_WO);
  }
  mbar_wait(bar + 8 * MB_W1, 0);
  const unsigned pV = sb + R_T2 + woff;
  const unsigned rk = c & 7, peer = rk ^ 1, cl = c >> 3;
#define KEEP(x) x = __shfl_sync(~0u, x, lane)
  unsigned pA = sb + R_MEM + kh * 4096 + lane * 16;
  unsigned pW0 = sb + R_WO + (w >> 1) * 8192 + ((m >> 1) * 8 + r8) * 128 + ((((w & 1) * 4 + (m & 1)) ^ r8) << 4);
  unsigned pW1 = pW0 ^ 32;
  unsigned pVk = pV;
  unsigned aX = sb + R_VRED + et * 512 + lane * 16;
  unsigned aQKst = sb + (kh ? R_KS : R_QS) + r8 * 144 + (et * 16 + (m & 1) * 8) * 2;
  unsigned aL8 = sb + lane * 8;
  unsigned aSl = mapa(sb + R_SOWN + w * 256 + lane * 8, rk), aSr = mapa(sb + R_SPEER + w * 256 + lane * 8, peer);
  unsigned aVl = mapa(sb + R_VM + (j * 4 + et) * 256 + lane * 8, rk), aVr = mapa(sb + R_VM + (j * 4 + et) * 256 + lane * 8, peer);
  const unsigned mbSl = mapa(bar + 8 * MB_S, rk), mbSr = mapa(bar + 8 * MB_S, peer), mbVl = mbSl + 8, mbVr = mbSr + 8;
  unsigned aQ = sb + R_QS + r8 * 144 + m * 16;
  unsigned oKx = (et * 8 + r8) * 128 + ((m ^ r8) << 4);
  unsigned oVx = 4096 + (et >> 1) * 4096 + ((m >> 1) * 8 + r8) * 128 + ((((et & 1) * 4 + (m & 1)) ^ r8) << 4);
  unsigned aOst = sb + R_OS + r8 * 272 + (et * 32 + m * 8) * 2;
  unsigned aOld = sb + R_OS + r8 * 272 + m * 16;
  unsigned aVm = sb + R_VM + et * 512 + lane * 8;
  unsigned aRSr = mapa(sb + R_RS + (h & 3) * 2048 + (w & 1) * 1024 + lane * 8, j * 4 + (w >> 1));
  unsigned mbRSr = mapa(bar + 8 * MB_RS, j * 4 + (w >> 1));
  unsigned t8 = t * 8;
  KEEP(pA); KEEP(pW0); KEEP(pW1); KEEP(pVk); KEEP(aX); KEEP(aQKst); KEEP(aL8); KEEP(aSl); KEEP(aSr); KEEP(aVl); KEEP(aVr); KEEP(aQ); KEEP(oKx); KEEP(oVx);
  KEEP(aOst); KEEP(aOld); KEEP(aVm); KEEP(aRSr); KEEP(mbRSr); KEEP(t8);
  mbar_wait(bar + 8 * MB_WO, 0);
#pragma unroll
  for (int ks = 0; ks < 4; ks++) { ldsm_x4_t(wo[2 * ks], pW0 + ks * 2048); ldsm_x4_t(wo[2 * ks + 1], pW1 + ks * 2048); }
  {
    unsigned v[8];
#pragma unroll
    for (int q = 0; q < 8; q++) v[q] = __ldg(reinterpret_cast<const unsigned*>(mem0) + q * 256 + t);
    sts128(sb + R_MEM + t * 32, make_uint4(__byte_perm(v[0], v[1], 0x5410), __byte_perm(v[2], v[3], 0x5410), __byte_perm(v[4], v[5], 0x5410), __byte_perm(v[6], v[7], 0x5410)));
    sts128(sb + R_MEM + t * 32 + 16, make_uint4(__byte_perm(v[0], v[1], 0x7632), __byte_perm(v[2], v[3], 0x7632), __byte_perm(v[4], v[5], 0x7632), __byte_perm(v[6], v[7], 0x7632)));
  }
  bar_sync(1, 256);

#pragma unroll 1
  for (int s = 0;; s++) {
    const unsigned par = s & 1;
    const unsigned slot = s & (RING_N - 1), rpar = (s / RING_N) & 1;
    const unsigned ring = sb + R_RING + slot * RING_BYTES;
    RSTAMP(1);
    RSTAMP(2);
    float aq[4] = {0, 0, 0, 0}, ak[4] = {0, 0, 0, 0}, av[4] = {0, 0, 0, 0};
#pragma unroll
    for (int i = 0; i < 8; i++) {
      unsigned b[4], f[4], f0[4];
      ldsm_x4_t(b, pA + i * 512);
      ldsm_x4_t(f0, pVk + (i >> 1) * 8192 + (i & 1) * 4096);
      ldsm_x4_t(f, pVk + (i >> 1) * 8192 + (i & 1) * 4096 + 2048);
      mma16816(aq, wq[2 * i], b[0], b[1]); mma16816(ak, wk[2 * i], b[0], b[1]); mma16816(av, f0, b[0], b[1]);
      mma16816(aq, wq[2 * i + 1], b[2], b[3]); mma16816(ak, wk[2 * i + 1], b[2], b[3]); mma16816(av, f, b[2], b[3]);
    }
    RSTAMP(3);
#define STSF4(a, v) asm volatile("st.shared.v4.f32 [%0], {%1,%2,%3,%4};" ::"r"(a), "f"(v[0]), "f"(v[1]), "f"(v[2]), "f"(v[3]) : "memory")
    unsigned f[8][4];
#define NPRE 2
#define WO_PREFETCH() do { _Pragma("unroll") for (int i = 0; i < NPRE; i++) { ldsm_x4_t(f[2 * i], pW0 + 32768 + i * 2048); ldsm_x4_t(f[2 * i + 1], pW1 + 32768 + i * 2048); } } while (0)
    if (kh) {
      STSF4(aX, aq);
      bar_sync(4 + et, 64);
      uint4 o = lds128(aX + 2048), o2 = lds128(aX + 4096);
      stsm_x2_t(aQKst, pack_bf16(ak[0] + __uint_as_float(o.x), ak[1] + __uint_as_float(o.y)), pack_bf16(ak[2] + __uint_as_float(o.z), ak[3] + __uint_as_float(o.w)));
      bar_arrive(1, 256);
      unsigned x = pack_bf16(av[0] + __uint_as_float(o2.x), av[1] + __uint_as_float(o2.y)), y = pack_bf16(av[2] + __uint_as_float(o2.z), av[3] + __uint_as_float(o2.w));
      st_async_b64(aVr, x, y, mbVr);
      st_async_b64(aVl, x, y, mbVl);
      mbar_wait(bar + 8 * (MB_FULL + slot), rpar);
      unsigned vx[4][4];
      ldsm_x4_t(vx[0], ring + oVx); ldsm_x4_t(vx[1], ring + oVx + 2048); ldsm_x4_t(vx[2], ring + (oVx ^ 32)); ldsm_x4_t(vx[3], ring + (oVx ^ 32) + 2048);
      RSTAMP(4); RSTAMP(5); RSTAMP(6); RSTAMP(7);
      mbar_wait(bar + 8 * MB_S, par);
      RSTAMP(8);
      float sc[10];
#pragma unroll
      for (int i = 0; i < 5; i++) {
        uint2 o = lds64(aL8 + R_SOWN + i * 256), p = lds64(aL8 + R_SPEER + i * 256);
        sc[2 * i] = __uint_as_float(o.x) + __uint_as_float(p.x); sc[2 * i + 1] = __uint_as_float(o.y) + __uint_as_float(p.y);
      }
      mbar_wait(bar + 8 * MB_V, par);
      uint2 vm0 = lds64(aVm), vm1 = lds64(aVm + 256);
      float mx = fmaxf(fmaxf(fmaxf(sc[0], sc[1]), fmaxf(sc[2], sc[3])), fmaxf(fmaxf(fmaxf(sc[4], sc[5]), fmaxf(sc[6], sc[7])), fmaxf(sc[8], sc[9])));
      mx = fmaxf(mx, __shfl_xor_sync(~0u, mx, 1)); mx = fmaxf(mx, __shfl_xor_sync(~0u, mx, 2));
      const float nm = -mx * (SCALE_QK * LOG2E);
#pragma unroll
      for (int i = 0; i < 10; i++) sc[i] = ex2f(fmaf(sc[i], SCALE_QK * LOG2E, nm));
      float sum = (((sc[0] + sc[1]) + (sc[2] + sc[3])) + ((sc[4] + sc[5]) + (sc[6] + sc[7]))) + (sc[8] + sc[9]);
      sum += __shfl_xor_sync(~0u, sum, 1); sum += __shfl_xor_sync(~0u, sum, 2);
      float inv; asm("rcp.approx.ftz.f32 %0, %1;" : "=f"(inv) : "f"(sum));
      unsigned p[5];
#pragma unroll
      for (int i = 0; i < 5; i++) p[i] = pack_bf16(sc[2 * i] * inv, sc[2 * i + 1] * inv);
      RSTAMP(9);
      float o0[4] = {0, 0, 0, 0}, o1[4] = {0, 0, 0, 0}, o3[4] = {0, 0, 0, 0}, o4[4] = {0, 0, 0, 0};
      mma16816(o0, vx[0], p[0], p[1]); mma16816(o3, vx[2], p[0], p[1]); mma16816(o1, vx[1], p[2], p[3]); mma16816(o4, vx[3], p[2], p[3]);
      mma1688(o0, vm0.x, vm0.y, p[4]); mma1688(o3, vm1.x, vm1.y, p[4]);
      if (s == NSEG - 1) { if (t == 128) mbar_arrive(bar + 8 * MB_KVR); break; }
      asm volatile("stmatrix.sync.aligned.m8n8.x4.trans.shared.b16 [%0], {%1,%2,%3,%4};" ::"r"(aOst), "r"(pack_bf16(o0[0] + o1[0], o0[1] + o1[1])), "r"(pack_bf16(o0[2] + o1[2], o0[3] + o1[3])),
                   "r"(pack_bf16(o3[0] + o4[0], o3[1] + o4[1])), "r"(pack_bf16(o3[2] + o4[2], o3[3] + o4[3])) : "memory");
      RSTAMP(10);
      bar_sync(1, 256);
      WO_PREFETCH();
    } else {
      STSF4(aX + 2048, ak); STSF4(aX + 4096, av);
      unsigned kb[8];
      mbar_wait(bar + 8 * (MB_FULL + slot), rpar);
      ldsm_x4(kb, ring + oKx); ldsm_x4(kb + 4, ring + (oKx ^ 64));
      bar_sync(4 + et, 64);
      uint4 o = lds128(aX);
      stsm_x2_t(aQKst, pack_bf16(aq[0] + __uint_as_float(o.x), aq[1] + __uint_as_float(o.y)), pack_bf16(aq[2] + __uint_as_float(o.z), aq[3] + __uint_as_float(o.w)));
      RSTAMP(4);
      bar_sync(1, 256);
      RSTAMP(5);
      unsigned qa[8], km[8];
      ldsm_x4(qa, aQ); ldsm_x4(qa + 4, aQ + 64);
      if (w == 3) { ldsm_x4(km, aQ + 1152); ldsm_x4(km + 4, aQ + 1152 + 64); }
      float s0[4] = {0, 0, 0, 0}, s1[4] = {0, 0, 0, 0};
      unsigned af[4][4];
#pragma unroll
      for (int i = 0; i < 4; i++) { af[i][0] = qa[2 * i]; af[i][1] = 0; af[i][2] = qa[2 * i + 1]; af[i][3] = 0; }
      mma16816(s0, af[0], kb[0], kb[1]); mma16816(s1, af[1], kb[2], kb[3]);
      mma16816(s0, af[2], kb[4], kb[5]); mma16816(s1, af[3], kb[6], kb[7]);
      if (w == 3) {
        float m0[4] = {0, 0, 0, 0}, m1[4] = {0, 0, 0, 0};
        mma16816(m0, af[0], km[0], km[1]); mma16816(m1, af[1], km[2], km[3]);
        mma16816(m0, af[2], km[4], km[5]); mma16816(m1, af[3], km[6], km[7]);
        unsigned x = __float_as_uint(m0[0] + m1[0]), y = __float_as_uint(m0[1] + m1[1]);
        st_async_b64(aSr + 256, x, y, mbSr); st_async_b64(aSl + 256, x, y, mbSl);
      }
      unsigned x = __float_as_uint(s0[0] + s1[0]), y = __float_as_uint(s0[1] + s1[1]);
      st_async_b64(aSr, x, y, mbSr); st_async_b64(aSl, x, y, mbSl);
      RSTAMP(6);
      if (s == NSEG - 1) break;
      WO_PREFETCH();
      RSTAMP(7); RSTAMP(8); RSTAMP(9); RSTAMP(10);
      bar_sync(1, 256);
    }
    RSTAMP(11);
    float d0[4] = {0, 0, 0, 0}, d1[4] = {0, 0, 0, 0}, e0[4] = {0, 0, 0, 0}, e1[4] = {0, 0, 0, 0};
    unsigned ob[4][4];
#pragma unroll
    for (int k2 = 0; k2 < 4; k2++) ldsm_x4(ob[k2], aOld + k2 * 64);
#pragma unroll
    for (int i = NPRE; i < 4; i++) { ldsm_x4_t(f[2 * i], pW0 + 32768 + i * 2048); ldsm_x4_t(f[2 * i + 1], pW1 + 32768 + i * 2048); }
    mma16816(d0, wo[0], ob[0][0], ob[0][1]); mma16816(d1, wo[1], ob[0][0], ob[0][1]);
    mma16816(e0, wo[2], ob[0][2], ob[0][3]); mma16816(e1, wo[3], ob[0][2], ob[0][3]);
    mma16816(d0, wo[4], ob[1][0], ob[1][1]); mma16816(d1, wo[5], ob[1][0], ob[1][1]);
    mma16816(e0, wo[6], ob[1][2], ob[1][3]); mma16816(e1, wo[7], ob[1][2], ob[1][3]);
    mma16816(d0, f[0], ob[2][0], ob[2][1]); mma16816(d1, f[1], ob[2][0], ob[2][1]);
    mma16816(e0, f[2], ob[2][2], ob[2][3]); mma16816(e1, f[3], ob[2][2], ob[2][3]);
    mma16816(d0, f[4], ob[3][0], ob[3][1]); mma16816(d1, f[5], ob[3][0], ob[3][1]);
    mma16816(e0, f[6], ob[3][2], ob[3][3]); mma16816(e1, f[7], ob[3][2], ob[3][3]);
    st_async_b64(aRSr, __float_as_uint(d0[0] + e0[0]), __float_as_uint(d0[1] + e0[1]), mbRSr);
    st_async_b64(aRSr + 256, __float_as_uint(d0[2] + e0[2]), __float_as_uint(d0[3] + e0[3]), mbRSr);
    st_async_b64(aRSr + 512, __float_as_uint(d1[0] + e1[0]), __float_as_uint(d1[1] + e1[1]), mbRSr);
    st_async_b64(aRSr + 768, __float_as_uint(d1[2] + e1[2]), __float_as_uint(d1[3] + e1[3]), mbRSr);
    RSTAMP(12);
    if (t == 128) {
      mbar_arrive(bar + 8 * (MB_EMPTY + slot)); mbar_arrive(bar + 8 * MB_KVR);
      mbar_expect_tx(bar + 8 * MB_S, 2560); mbar_expect_tx(bar + 8 * MB_V, 2048);
    }
    const unsigned tag = ((s >> 1) & 1) ^ 1;
    const char* gp = reinterpret_cast<const char*>(g_part) + (par * 8 + rk) * 16384 + t8;
    unsigned mbA[8];
#pragma unroll
    for (int i = 0; i < 8; i++) mbA[i] = mapa(bar + 8 * MB_AG, i);
    const unsigned dlt = (R_MEM + rk * 1024) - (SM_BAR + 8 * MB_AG) + (t8 >> 1);
    mbar_wait(bar + 8 * MB_RS, par);
    RSTAMP(13);
    uint2 a[8];
    {
      uint2 x0 = lds64(sb + R_RS + t8), x1 = lds64(sb + R_RS + 2048 + t8), x2 = lds64(sb + R_RS + 4096 + t8), x3 = lds64(sb + R_RS + 6144 + t8);
      float r0 = (__uint_as_float(x0.x) + __uint_as_float(x1.x)) + (__uint_as_float(x2.x) + __uint_as_float(x3.x));
      float r1 = (__uint_as_float(x0.y) + __uint_as_float(x1.y)) + (__uint_as_float(x2.y) + __uint_as_float(x3.y));
      a[0].x = (__float_as_uint(r0) & ~1u) | tag; a[0].y = (__float_as_uint(r1) & ~1u) | tag;
      asm volatile("st.relaxed.gpu.global.v2.u32 [%0], {%1,%2};" ::"l"(gp + cl * 2048), "r"(a[0].x), "r"(a[0].y) : "memory");
    }
    RSTAMP(14);
    if (t == 128) mbar_expect_tx(bar + 8 * MB_RS, 8192);
    {
      unsigned it = 0;
      while (true) {
#pragma unroll
        for (int i = 1; i < 8; i++) a[i] = ldv2_relaxed(gp + (cl ^ i) * 2048);
        unsigned an = a[1].x & a[1].y, orr = a[1].x | a[1].y;
#pragma unroll
        for (int i = 2; i < 8; i++) { an &= a[i].x & a[i].y; orr |= a[i].x | a[i].y; }
        if (((tag ? an : ~orr) & 1u) != 0) break;
        spin_check(it);
      }
    }
    RSTAMP(15);
    {
#define AF(i, c) __uint_as_float(a[i].c)
      unsigned u = pack_bf16(((AF(0, x) + AF(1, x)) + (AF(2, x) + AF(3, x))) + ((AF(4, x) + AF(5, x)) + (AF(6, x) + AF(7, x))),
                             ((AF(0, y) + AF(1, y)) + (AF(2, y) + AF(3, y))) + ((AF(4, y) + AF(5, y)) + (AF(6, y) + AF(7, y))));
      __syncwarp();
#pragma unroll
      for (int i = 0; i < 8; i++) st_async_b32(mbA[i] + dlt, u, mbA[i]);
    }
    mbar_wait(bar + 8 * MB_KVF, par);
    mbar_wait(bar + 8 * MB_AG, par);
    if (t == 128) mbar_expect_tx(bar + 8 * MB_AG, 8192);
  }
}

__device__ __forceinline__ void rec_ring(const Maps& maps, unsigned sb) {
  const int c = blockIdx.x, h = c >> 1, j = c & 1;
  const unsigned bar = sb + SM_BAR;
  const int lane = threadIdx.x & 31;
  if (lane == 0) {
    mbar_expect_tx(bar + 8 * MB_W0, 131072);
    for (int kb = 0; kb < 8; kb++) tma_load_2d(sb + R_WO + kb * 8192, &maps.wq, h * 128 + j * 64, kb * 64, bar + 8 * MB_W0);
    for (int kb = 0; kb < 8; kb++) tma_load_2d(sb + R_T1 + kb * 8192, &maps.wk, h * 128 + j * 64, kb * 64, bar + 8 * MB_W0);
    mbar_expect_tx(bar + 8 * MB_W1, 65536);
    for (int kb = 0; kb < 8; kb++) tma_load_2d(sb + R_T2 + kb * 8192, &maps.wv, h * 128 + j * 64, kb * 64, bar + 8 * MB_W1);
  }
  __syncwarp();
  bar_sync(2, 288);
  if (lane == 0) {
    fence_proxy_async_smem();
    for (int s = 0; s < NSEG; s++) {
      unsigned slot = s & (RING_N - 1);
      if ((s & 3) == 0 && !DBGMODE) {
        wait_flag_ge(&g_flags.qkv[(s >> 2) * 48 + 16 + (h >> 1)], 1);
        wait_flag_ge(&g_flags.qkv[(s >> 2) * 48 + 32 + (h >> 1)], 1);
        fence_proxy_async();
      }
      if (s >= RING_N) mbar_wait_sleep(bar + 8 * (MB_EMPTY + slot), ((s / RING_N) - 1) & 1);
      unsigned dst = sb + R_RING + slot * RING_BYTES, mb = bar + 8 * (MB_FULL + slot);
      mbar_expect_tx(mb, RING_BYTES);
      tma_load_2d(dst, &maps.qkv_ld, HD + h * 128 + j * 64, s * SEG, mb);
      tma_load_2d(dst + 4096, &maps.qkv_ld, 2 * HD + h * 128, s * SEG, mb);
      tma_load_2d(dst + 8192, &maps.qkv_ld, 2 * HD + h * 128 + 64, s * SEG, mb);
    }
  }
}
__device__ __forceinline__ void rec_copy(unsigned sb) {
  const int c = blockIdx.x, h = c >> 1, j = c & 1;
  const unsigned bar = sb + SM_BAR;
  const int lane = threadIdx.x & 31;
  for (int s = 0; s < NSEG; s++) {
    mbar_wait_sleep(bar + 8 * MB_KVR, s & 1);
    uint4 k0 = lds128(sb + R_KS + (lane >> 3) * 144 + (lane & 7) * 16), k1 = lds128(sb + R_KS + (4 + (lane >> 3)) * 144 + (lane & 7) * 16);
    uint2 v[4];
#pragma unroll
    for (int i = 0; i < 4; i++) v[i] = lds64(sb + R_VM + (j * 4 + i) * 256 + lane * 8);
    __syncwarp();
    if (lane == 0) mbar_arrive(bar + 8 * MB_KVF);
    bf16* kd = g_km + ((size_t)(s * NH + h) * NMEM) * DH + j * 64;
    *reinterpret_cast<uint4*>(kd + (lane >> 3) * DH + (lane & 7) * 8) = k0;
    *reinterpret_cast<uint4*>(kd + (4 + (lane >> 3)) * DH + (lane & 7) * 8) = k1;
    unsigned* vd = reinterpret_cast<unsigned*>(g_vmt) + ((size_t)(s * NH + h) * DH + j * 64) * 4;
#pragma unroll
    for (int i = 0; i < 4; i++) { vd[(i * 16) * 4 + lane] = v[i].x; vd[(i * 16 + 8) * 4 + lane] = v[i].y; }
    __syncwarp();
    if (lane == 0) st_release(&g_flags.rec[c], s + 1);
  }
}

__device__ __forceinline__ void bulk_producer(const Maps& maps, unsigned sb, int* misc) {
  const unsigned bar = sb + SM_BAR;
  unsigned st = 0, ph = 0, seq = 0;
  while (true) {
    int idx = (int)atomicAdd(&g_flags.ctr, 1u);
    if (idx >= N_ITEMS) {
      mbar_wait(bar + 8 * (MB_EMPTY + st), ph ^ 1);
      misc[seq & 3] = -1;
      mbar_arrive(bar + 8 * (MB_FULL + st));
      break;
    }
    ISTAMP(idx, 0);
    Item it = decode_item(idx);
    if (it.b < 0) continue;
    const CUtensorMap *ma, *mb_; int ka = 0, kbr = 0, nb0 = it.c * 256;
    if (it.type == T_QKV) { ma = &maps.xn; mb_ = it.c < 16 ? &maps.wq : (it.c < 32 ? &maps.wk : &maps.wv); nb0 = (it.c & 15) * 256; }
    else if (it.type == T_M1) { ma = &maps.y; mb_ = &maps.w1; }
    else if (it.type == T_M2) { ma = &maps.h1; mb_ = &maps.w2; wait_flag_ge(&g_flags.h1[it.b], 7); }
    else if (it.type == T_OUT) { ma = &maps.o; mb_ = &maps.wo; ka = kbr = it.ks * 1024; wait_flag_ge(&g_flags.o[it.b * 4 + it.ks], 4); }
    else if (it.type == T_OUTL) { ma = &maps.o; mb_ = &maps.wo; ka = kbr = it.ks * 256; wait_flag_ge(&g_flags.o16[it.ks], 1); }
    else if (it.type >= T_RED) { ma = mb_ = &maps.o; wait_flag_ge(&g_flags.g[it.b], 2); wait_flag_ge(&g_flags.p[it.b], it.type == T_RED ? 8 : 32); }
    else {
      ma = mb_ = &maps.qkv_ld;
      wait_flag_ge(&g_flags.qkv[it.b * 48 + it.c], 1); wait_flag_ge(&g_flags.qkv[it.b * 48 + 16 + it.c], 1); wait_flag_ge(&g_flags.qkv[it.b * 48 + 32 + it.c], 1);
      for (int i = 0; i < 4; i++) wait_flag_ge(&g_flags.rec[it.c * 4 + i], it.b * 4 + 2);
    }
    fence_proxy_async();
    ISTAMP(idx, 1);
    const int nkb = item_nkb(it.type);
    for (int kb = 0; kb < nkb; kb++) {
      mbar_wait(bar + 8 * (MB_EMPTY + st), ph ^ 1);
      if (kb == 0) { misc[seq & 3] = idx; seq++; }
      unsigned dst = sb + st * STAGE_BYTES, mb = bar + 8 * (MB_FULL + st);
      if (it.type >= T_RED) { mbar_arrive(mb); if (++st == NSTAGE) { st = 0; ph ^= 1; } break; }
      if (it.type == T_ATT && kb == 2) for (int i = 0; i < 4; i++) wait_flag_ge(&g_flags.rec[it.c * 4 + i], it.b * 4 + 4);
      mbar_expect_tx(mb, STAGE_BYTES);
      if (it.type == T_ATT) {
        int head = it.c * 2 + (kb & 1), row = it.b * 128 + (kb >> 1) * 64;
        for (int i = 0; i < 12; i++) tma_load_2d(dst + i * 4096, ma, (i >> 2) * HD + head * 128 + (i & 1) * 64, row + ((i >> 1) & 1) * 32, mb);
      } else {
        tma_load_2d(dst, ma, ka + kb * 64, it.b * 128, mb);
        for (int i = 0; i < 4; i++) tma_load_2d(dst + 16384 + i * 8192, mb_, nb0 + i * 64, kbr + kb * 64, mb);
      }
      if (++st == NSTAGE) { st = 0; ph ^= 1; }
    }
  }
}
__device__ __forceinline__ void bulk_store(const Maps& maps, unsigned sb, volatile int* misc) {
  const unsigned bar = sb + SM_BAR;
  unsigned ph = 0;
  while (true) {
    mbar_wait(bar + 8 * MB_STGF, ph); ph ^= 1;
    int idx = misc[4];
    if (idx < 0) break;
    Item it = decode_item(idx);
    const CUtensorMap* mp = it.type == T_QKV ? &maps.qkv_st : (it.type == T_M1 ? &maps.h1 : (it.type == T_M2 ? &maps.g : &maps.o));
    unsigned* flag = it.type == T_QKV ? &g_flags.qkv[it.b * 48 + it.c] : (it.type == T_M1 ? &g_flags.h1[it.b] : (it.type == T_M2 ? &g_flags.g[it.b] : (it.b == 15 ? &g_flags.o16[it.c] : &g_flags.o[it.b * 4 + (it.c >> 2)])));
    for (int i = 0; i < 4; i++) tma_store_2d(mp, sb + B_STG + i * 16384, it.c * 256 + i * 64, it.b * 128);
    asm volatile("cp.async.bulk.commit_group;" ::: "memory");
    asm volatile("cp.async.bulk.wait_group.read 0;" ::: "memory");
    mbar_arrive(bar + 8 * MB_STGE);
    asm volatile("cp.async.bulk.wait_group 0;" ::: "memory");
    fence_proxy_async();
    red_release_add(flag, 1);
    ISTAMP(idx, 3);
  }
}
__device__ __forceinline__ float gelu_t(float x) {
  float u = 0.7978845608028654f * (x + 0.044715f * x * x * x);
  return __fdividef(x, 1.0f + __expf(-2.0f * u));
}
__device__ __forceinline__ float silu_f(float x) { return __fdividef(x, 1.0f + __expf(-x)); }

__device__ __forceinline__ void final_out(bf16* __restrict__ out, const bf16* __restrict__ x, size_t o, float4 s) {
  uint2 gv = __ldcg(reinterpret_cast<const uint2*>(g_g + o)), xv = __ldg(reinterpret_cast<const uint2*>(x + o));
  uint2 r;
  r.x = pack_bf16(bf_lo(xv.x) + bf16r(bf16r(s.x) * bf_lo(gv.x)), bf_hi(xv.x) + bf16r(bf16r(s.y) * bf_hi(gv.x)));
  r.y = pack_bf16(bf_lo(xv.y) + bf16r(bf16r(s.z) * bf_lo(gv.y)), bf_hi(xv.y) + bf16r(bf16r(s.w) * bf_hi(gv.y)));
  *reinterpret_cast<uint2*>(out + o) = r;
}
__device__ __forceinline__ void bulk_att_load(unsigned* km, unsigned* vm, int b, int hp, int kb, int w, int lane) {
  const int g = lane >> 2, tq = lane & 3, seg = w >> 2, eh = w & 1;
  const int head = hp * 2 + (kb & 1), sg = b * 4 + (kb >> 1) * 2 + seg;
  const unsigned* kmp = reinterpret_cast<const unsigned*>(g_km + ((size_t)(sg * NH + head) * NMEM + g) * DH) + tq;
  const unsigned* vmp = reinterpret_cast<const unsigned*>(g_vmt) + ((size_t)(sg * NH + head) * DH + eh * 64) * 4 + lane;
#pragma unroll
  for (int i = 0; i < 16; i++) asm volatile("ld.global.cg.u32 %0, [%1];" : "=r"(km[i]) : "l"(kmp + i * 4) : "memory");
#pragma unroll
  for (int i = 0; i < 8; i++) asm volatile("ld.global.cg.u32 %0, [%1];" : "=r"(vm[i]) : "l"(vmp + i * 32) : "memory");
}
__device__ __forceinline__ void bulk_att_stage(unsigned sa, unsigned stg, const unsigned* km, const unsigned* vm, int kb, int w, int lane) {
  const int g = lane >> 2, tq = lane & 3, m = lane >> 3, r8 = lane & 7;
  const int seg = w >> 2, mt = (w >> 1) & 1, eh = w & 1;
  float s[5][4];
#pragma unroll
  for (int i = 0; i < 5; i++) { s[i][0] = s[i][1] = s[i][2] = s[i][3] = 0; }
  const unsigned qb = sa + (0 * 2 + seg) * 8192, kbs = sa + (1 * 2 + seg) * 8192, vb = sa + (2 * 2 + seg) * 8192 + eh * 4096;
  unsigned qa[8][4];
#pragma unroll
  for (int ks = 0; ks < 8; ks++) {
    int row = mt * 16 + (m & 1) * 8 + r8;
    ldsm_x4(qa[ks], qb + (ks >> 2) * 4096 + row * 128 + ((((ks & 3) * 2 + (m >> 1)) ^ r8) << 4));
    unsigned kf[4];
    int krow = (m >> 1) * 8 + r8;
    unsigned ka = kbs + (ks >> 2) * 4096 + krow * 128 + ((((ks & 3) * 2 + (m & 1)) ^ r8) << 4);
    ldsm_x4(kf, ka);
    mma16816(s[0], qa[ks], kf[0], kf[1]); mma16816(s[1], qa[ks], kf[2], kf[3]);
    if (mt) { ldsm_x4(kf, ka + 2048); mma16816(s[2], qa[ks], kf[0], kf[1]); mma16816(s[3], qa[ks], kf[2], kf[3]); }
  }
#pragma unroll
  for (int ks = 0; ks < 8; ks++) mma16816(s[4], qa[ks], km[2 * ks], km[2 * ks + 1]);
  float mx0 = -INFINITY, mx1 = -INFINITY;
  const int t0 = mt * 16 + g, t1 = t0 + 8;
#pragma unroll
  for (int i = 0; i < 5; i++) {
#pragma unroll
    for (int e = 0; e < 4; e++) {
      float v = s[i][e];
      if (i < 4) { int kj = i * 8 + 2 * tq + (e & 1); if (kj > (e < 2 ? t0 : t1)) v = -INFINITY; }
      s[i][e] = v;
      if (e < 2) mx0 = fmaxf(mx0, v); else mx1 = fmaxf(mx1, v);
    }
  }
  mx0 = fmaxf(mx0, __shfl_xor_sync(~0u, mx0, 1)); mx0 = fmaxf(mx0, __shfl_xor_sync(~0u, mx0, 2));
  mx1 = fmaxf(mx1, __shfl_xor_sync(~0u, mx1, 1)); mx1 = fmaxf(mx1, __shfl_xor_sync(~0u, mx1, 2));
  float sm0 = 0, sm1 = 0;
#pragma unroll
  for (int i = 0; i < 5; i++) {
    s[i][0] = ex2f((s[i][0] - mx0) * (SCALE_QK * LOG2E)); s[i][1] = ex2f((s[i][1] - mx0) * (SCALE_QK * LOG2E));
    s[i][2] = ex2f((s[i][2] - mx1) * (SCALE_QK * LOG2E)); s[i][3] = ex2f((s[i][3] - mx1) * (SCALE_QK * LOG2E));
    sm0 += s[i][0] + s[i][1]; sm1 += s[i][2] + s[i][3];
  }
  sm0 += __shfl_xor_sync(~0u, sm0, 1); sm0 += __shfl_xor_sync(~0u, sm0, 2);
  sm1 += __shfl_xor_sync(~0u, sm1, 1); sm1 += __shfl_xor_sync(~0u, sm1, 2);
  const float i0 = __fdividef(1.0f, sm0), i1 = __fdividef(1.0f, sm1);
  unsigned pa[2][4], pm0, pm1;
#pragma unroll
  for (int kk = 0; kk < 2; kk++) {
    pa[kk][0] = pack_bf16(s[2 * kk][0] * i0, s[2 * kk][1] * i0); pa[kk][1] = pack_bf16(s[2 * kk][2] * i1, s[2 * kk][3] * i1);
    pa[kk][2] = pack_bf16(s[2 * kk + 1][0] * i0, s[2 * kk + 1][1] * i0); pa[kk][3] = pack_bf16(s[2 * kk + 1][2] * i1, s[2 * kk + 1][3] * i1);
  }
  pm0 = pack_bf16(s[4][0] * i0, s[4][1] * i0); pm1 = pack_bf16(s[4][2] * i1, s[4][3] * i1);
  const int orow = (kb >> 1) * 64 + seg * 32 + mt * 16 + (m & 1) * 8 + r8;
  const unsigned ob = stg + ((kb & 1) * 2 + eh) * 16384 + orow * 128;
#pragma unroll
  for (int cp = 0; cp < 4; cp++) {
    float o0[4] = {0, 0, 0, 0}, o1[4] = {0, 0, 0, 0};
    mma1688(o0, pm0, pm1, vm[2 * cp]); mma1688(o1, pm0, pm1, vm[2 * cp + 1]);
    unsigned vf[4];
    int row = (m & 1) * 8 + r8;
    unsigned va = vb + row * 128 + (((cp * 2 + (m >> 1)) ^ r8) << 4);
    ldsm_x4_t(vf, va);
    mma16816(o0, pa[0], vf[0], vf[1]); mma16816(o1, pa[0], vf[2], vf[3]);
    if (mt) { ldsm_x4_t(vf, va + 2048); mma16816(o0, pa[1], vf[0], vf[1]); mma16816(o1, pa[1], vf[2], vf[3]); }
    stsm_x4(ob + (((cp * 2 + (m >> 1)) ^ r8) << 4), pack_bf16(o0[0], o0[1]), pack_bf16(o0[2], o0[3]), pack_bf16(o1[0], o1[1]), pack_bf16(o1[2], o1[3]));
  }
}

__device__ __forceinline__ void bulk_worker(unsigned sb, volatile int* misc, const bf16* __restrict__ x, const bf16* __restrict__ b1, const bf16* __restrict__ b2, bf16* __restrict__ out) {
  const int t = threadIdx.x, lane = t & 31, w = t >> 5, wg = w >> 2, g = lane >> 2, tq = lane & 3, m = lane >> 3, r8 = lane & 7;
  const unsigned bar = sb + SM_BAR;
  unsigned st = 0, ph = 0, seq = 0, sph = 0;
  float d[128];
  while (true) {
    mbar_wait(bar + 8 * (MB_FULL + st), ph);
    const int idx = misc[seq & 3]; seq++;
    if (idx < 0 || idx >= N_ITEMS) break;
    if (t == 0) ISTAMP(idx, 2);
    const Item it = decode_item(idx);
    const int nkb = item_nkb(it.type);
    if (it.type == T_ATT) {
      unsigned km[16], vm[8], kn[16], vn[8];
      bulk_att_load(kn, vn, it.b, it.c, 0, w, lane);
      bool pref = true;
      mbar_wait(bar + 8 * MB_STGE, sph ^ 1);
#pragma unroll 1
      for (int kb = 0; kb < 4; kb++) {
        if (kb) mbar_wait(bar + 8 * (MB_FULL + st), ph);
        if (!pref) bulk_att_load(kn, vn, it.b, it.c, kb, w, lane);
#pragma unroll
        for (int i = 0; i < 16; i++) km[i] = kn[i];
#pragma unroll
        for (int i = 0; i < 8; i++) vm[i] = vn[i];
        pref = kb != 3;
        if (kb == 1) {
          unsigned ok, s2 = st + 1 == NSTAGE ? 0 : st + 1, p2 = st + 1 == NSTAGE ? ph ^ 1 : ph;
          asm volatile("{.reg .pred p; mbarrier.test_wait.parity.shared::cta.b64 p, [%1], %2; selp.u32 %0,1,0,p;}" : "=r"(ok) : "r"(bar + 8 * (MB_FULL + s2)), "r"(p2) : "memory");
          pref = __all_sync(~0u, ok);
        }
        if (pref) bulk_att_load(kn, vn, it.b, it.c, kb + 1, w, lane);
        bulk_att_stage(sb + st * STAGE_BYTES, sb + B_STG, km, vm, kb, w, lane);
        __syncwarp();
        if (lane == 0) mbar_arrive(bar + 8 * (MB_EMPTY + st));
        if (++st == NSTAGE) { st = 0; ph ^= 1; }
      }
      if (t == 0) misc[4] = idx;
      fence_proxy_async_smem();
      mbar_arrive(bar + 8 * MB_STGF); sph ^= 1;
      continue;
    }
    if (it.type >= T_RED) {
      __syncwarp();
      if (lane == 0) mbar_arrive(bar + 8 * (MB_EMPTY + st));
      if (++st == NSTAGE) { st = 0; ph ^= 1; }
      if (it.type == T_RED) {
#pragma unroll 2
        for (int i = 0; i < 8; i++) {
          size_t o = ((size_t)it.b * 128 + it.c * 16 + i * 2 + (t >> 7)) * DM + (t & 127) * 4;
          float4 a = __ldcg(reinterpret_cast<const float4*>(g_opart + o)), b = __ldcg(reinterpret_cast<const float4*>(g_opart + o + (size_t)S_TOK * DM));
          float4 c = __ldcg(reinterpret_cast<const float4*>(g_opart + o + (size_t)2 * S_TOK * DM)), e = __ldcg(reinterpret_cast<const float4*>(g_opart + o + (size_t)3 * S_TOK * DM));
          final_out(out, x, o, make_float4((a.x + b.x) + (c.x + e.x), (a.y + b.y) + (c.y + e.y), (a.z + b.z) + (c.z + e.z), (a.w + b.w) + (c.w + e.w)));
        }
      } else {
        size_t ol = ((size_t)it.c * 2 + (t >> 7)) * DM + (t & 127) * 4;
        float4 v[16];
#pragma unroll
        for (int i = 0; i < 16; i++) v[i] = __ldcg(reinterpret_cast<const float4*>(g_opl + ol + (size_t)i * 128 * DM));
#pragma unroll
        for (int st2 = 1; st2 < 16; st2 <<= 1)
#pragma unroll
          for (int i = 0; i < 16; i += 2 * st2) { v[i].x += v[i + st2].x; v[i].y += v[i + st2].y; v[i].z += v[i + st2].z; v[i].w += v[i + st2].w; }
        final_out(out, x, ol + (size_t)15 * 128 * DM, v[0]);
      }
      if (t == 0) ISTAMP(idx, 3);
      continue;
    }
    unsigned pst = 0;
    for (int kb = 0; kb < nkb; kb++) {
      if (kb) mbar_wait(bar + 8 * (MB_FULL + st), ph);
      unsigned sa = sb + st * STAGE_BYTES;
      uint64_t ad = mkdesc(sa + wg * 8192, 16, 1024), bd = mkdesc(sa + 16384, 8192, 1024);
      asm volatile("wgmma.fence.sync.aligned;" ::: "memory");
#pragma unroll
      for (int k = 0; k < 4; k++) wgmma_n256(d, ad + k * 2, bd + k * 128, (kb | k) != 0);
      asm volatile("wgmma.commit_group.sync.aligned;" ::: "memory");
      if (kb) {
        asm volatile("wgmma.wait_group.sync.aligned 1;" ::: "memory");
        if (lane == 0) mbar_arrive(bar + 8 * (MB_EMPTY + pst));
      }
      pst = st;
      if (++st == NSTAGE) { st = 0; ph ^= 1; }
    }
    asm volatile("wgmma.wait_group.sync.aligned 0;" ::: "memory");
    if (lane == 0) mbar_arrive(bar + 8 * (MB_EMPTY + pst));
    if (it.type >= T_OUT) {
      const int col = it.c * 256 + 2 * tq;
      float* pp = it.type == T_OUT ? g_opart + ((size_t)it.ks * S_TOK + it.b * 128 + w * 16 + g) * DM + col : g_opl + ((size_t)it.ks * 128 + w * 16 + g) * DM + col;
#pragma unroll
      for (int i = 0; i < 32; i++) {
        __stcg(reinterpret_cast<float2*>(pp + i * 8), make_float2(d[4 * i], d[4 * i + 1]));
        __stcg(reinterpret_cast<float2*>(pp + 8 * DM + i * 8), make_float2(d[4 * i + 2], d[4 * i + 3]));
      }
      bar_sync(1, 256);
      if (t == 0) { red_release_add(&g_flags.p[it.b], 1); ISTAMP(idx, 3); }
      continue;
    }
    if (it.type != T_QKV) {
      const unsigned* bp = reinterpret_cast<const unsigned*>((it.type == T_M1 ? b1 : b2) + it.c * 256) + tq;
#pragma unroll
      for (int i = 0; i < 32; i++) {
        unsigned bv = __ldg(bp + i * 4);
        float lo = bf_lo(bv), hi = bf_hi(bv);
        float x0 = bf16r(bf16r(d[4 * i]) + lo), x1 = bf16r(bf16r(d[4 * i + 1]) + hi), x2 = bf16r(bf16r(d[4 * i + 2]) + lo), x3 = bf16r(bf16r(d[4 * i + 3]) + hi);
        if (it.type == T_M1) { d[4 * i] = gelu_t(x0); d[4 * i + 1] = gelu_t(x1); d[4 * i + 2] = gelu_t(x2); d[4 * i + 3] = gelu_t(x3); }
        else { d[4 * i] = silu_f(x0); d[4 * i + 1] = silu_f(x1); d[4 * i + 2] = silu_f(x2); d[4 * i + 3] = silu_f(x3); }
      }
    }
    mbar_wait(bar + 8 * MB_STGE, sph ^ 1);
    {
      const unsigned ob = sb + B_STG + (w * 16 + (m & 1) * 8 + r8) * 128;
#pragma unroll
      for (int i = 0; i < 16; i++)
        stsm_x4(ob + (i >> 2) * 16384 + ((((i & 3) * 2 + (m >> 1)) ^ r8) << 4), pack_bf16(d[8 * i], d[8 * i + 1]), pack_bf16(d[8 * i + 2], d[8 * i + 3]),
                pack_bf16(d[8 * i + 4], d[8 * i + 5]), pack_bf16(d[8 * i + 6], d[8 * i + 7]));
    }
    if (t == 0) misc[4] = idx;
    fence_proxy_async_smem();
    mbar_arrive(bar + 8 * MB_STGF); sph ^= 1;
  }
  mbar_wait(bar + 8 * MB_STGE, sph ^ 1);
  if (t == 0) misc[4] = -1;
  mbar_arrive(bar + 8 * MB_STGF);
}

__global__ void __launch_bounds__(384, 1)
k_main(const __grid_constant__ Maps maps, const bf16* __restrict__ x, const bf16* __restrict__ mem0, const bf16* __restrict__ b1, const bf16* __restrict__ b2, bf16* __restrict__ out, int helper) {
  extern __shared__ unsigned char smem_raw[];
  const unsigned sraw = smem_u32(smem_raw);
  const unsigned sb = (sraw + 1023u) & ~1023u;
  int* misc = reinterpret_cast<int*>(smem_raw + (sb - sraw) + SM_MISC);
  const int w = threadIdx.x >> 5;
  const bool rec = !helper && blockIdx.x < NREC;
  if (!helper) asm volatile("griddepcontrol.launch_dependents;");
  if (threadIdx.x == 0) {
    const unsigned bar = sb + SM_BAR;
    for (int i = 0; i < 8; i++) { mbar_init(bar + 8 * (MB_FULL + i), 1); mbar_init(bar + 8 * (MB_EMPTY + i), rec ? 1 : 8); }
    mbar_init(bar + 8 * MB_STGF, 256); mbar_init(bar + 8 * MB_STGE, 1);
    for (int i = MB_W0; i <= MB_AG; i++) mbar_init(bar + 8 * i, 1);
    if (rec) { mbar_expect_tx(bar + 8 * MB_S, 2560); mbar_expect_tx(bar + 8 * MB_V, 2048); mbar_expect_tx(bar + 8 * MB_RS, 8192); mbar_expect_tx(bar + 8 * MB_AG, 8192); }
    asm volatile("fence.mbarrier_init.release.cluster;" ::: "memory");
  }
  __syncthreads();
  asm volatile("barrier.cluster.arrive.release.aligned;\nbarrier.cluster.wait.acquire.aligned;" ::: "memory");
  if (DBGMODE && !rec) { if (helper) asm volatile("griddepcontrol.wait;" ::: "memory"); return; }
  if (w >= 8) {
    asm volatile("setmaxnreg.dec.sync.aligned.u32 24;");
    if (rec) { if (w == 8) rec_ring(maps, sb); else if (w == 9) rec_copy(sb); }
    else if ((threadIdx.x & 31) == 0) { if (w == 8) bulk_producer(maps, sb, misc); else if (w == 9) bulk_store(maps, sb, misc);
      else if (w == 10 && helper) asm volatile("griddepcontrol.wait;" ::: "memory"); }
  } else {
    if (rec) { asm volatile("setmaxnreg.inc.sync.aligned.u32 240;"); rec_worker(maps, sb, mem0); }
    else { asm volatile("setmaxnreg.inc.sync.aligned.u32 240;"); bulk_worker(sb, misc, x, b1, b2, out); }
  }
}

typedef CUresult (*EncFn)(CUtensorMap*, CUtensorMapDataType, cuuint32_t, void*, const cuuint64_t*, const cuuint64_t*, const cuuint32_t*, const cuuint32_t*,
                          CUtensorMapInterleave, CUtensorMapSwizzle, CUtensorMapL2promotion, CUtensorMapFloatOOBfill);
static void mk_map(EncFn enc, CUtensorMap* m, const void* ptr, uint64_t rows, uint64_t cols, uint32_t box_rows) {
  cuuint64_t dims[2] = {cols, rows}; cuuint64_t strides[1] = {cols * 2};
  cuuint32_t box[2] = {64, box_rows}, es[2] = {1, 1};
  enc(m, CU_TENSOR_MAP_DATA_TYPE_BFLOAT16, 2, const_cast<void*>(ptr), dims, strides, box, es, CU_TENSOR_MAP_INTERLEAVE_NONE, CU_TENSOR_MAP_SWIZZLE_128B,
      CU_TENSOR_MAP_L2_PROMOTION_L2_256B, CU_TENSOR_MAP_FLOAT_OOB_FILL_NONE);
}
extern "C" void kernel_launch(void* const* d_in, const int* in_sizes, int n_in, void* d_out, int out_size) {
  static EncFn enc = nullptr;
  static int ncl = 0, nhelp = 0;
  static void *p_xn, *p_y, *p_h1, *p_o, *p_qkv, *p_g;
  if (!enc) {
    void* fn = nullptr; cudaDriverEntryPointQueryResult qr;
    cudaGetDriverEntryPoint("cuTensorMapEncodeTiled", &fn, cudaEnableDefault, &qr);
    enc = (EncFn)fn;
    cudaGetSymbolAddress(&p_xn, g_xn); cudaGetSymbolAddress(&p_y, g_y); cudaGetSymbolAddress(&p_h1, g_h1);
    cudaGetSymbolAddress(&p_o, g_o); cudaGetSymbolAddress(&p_qkv, g_qkv); cudaGetSymbolAddress(&p_g, g_g);
    cudaFuncSetAttribute(k_main, cudaFuncAttributeMaxDynamicSharedMemorySize, SMEM_TOTAL);
    cudaLaunchConfig_t cfg = {}; cfg.gridDim = dim3(128); cfg.blockDim = dim3(384); cfg.dynamicSmemBytes = SMEM_TOTAL;
    cudaLaunchAttribute at[1]; at[0].id = cudaLaunchAttributeClusterDimension; at[0].val.clusterDim.x = CLS; at[0].val.clusterDim.y = 1; at[0].val.clusterDim.z = 1;
    cfg.attrs = at; cfg.numAttrs = 1;
    if (cudaOccupancyMaxActiveClusters(&ncl, k_main, &cfg) != cudaSuccess) { cudaGetLastError(); ncl = 14; }
    ncl = ncl > 16 ? 16 : (ncl < 9 ? 9 : ncl);
    int nsm = 0, dev = 0; cudaGetDevice(&dev); cudaDeviceGetAttribute(&nsm, cudaDevAttrMultiProcessorCount, dev);
    nhelp = nsm - ncl * CLS;
  }
  Maps maps;
  mk_map(enc, &maps.xn, p_xn, S_TOK, DM, 128); mk_map(enc, &maps.y, p_y, S_TOK, DM, 128); mk_map(enc, &maps.h1, p_h1, S_TOK, FF, 128);
  mk_map(enc, &maps.o, p_o, S_TOK, HD, 128); mk_map(enc, &maps.qkv_st, p_qkv, S_TOK, 3 * HD, 128); mk_map(enc, &maps.qkv_ld, p_qkv, S_TOK, 3 * HD, 32);
  mk_map(enc, &maps.g, p_g, S_TOK, DM, 128);
  mk_map(enc, &maps.wq, d_in[2], DM, HD, 64); mk_map(enc, &maps.wk, d_in[3], DM, HD, 64); mk_map(enc, &maps.wv, d_in[4], DM, HD, 64);
  mk_map(enc, &maps.wo, d_in[5], HD, DM, 64); mk_map(enc, &maps.w1, d_in[8], DM, FF, 64); mk_map(enc, &maps.w2, d_in[10], FF, DM, 64);
  cudaStream_t st = cudaStreamPerThread;
  k_pre<<<256, 256, 0, st>>>((const bf16*)d_in[0]);
  cudaLaunchConfig_t cfg = {}; cfg.gridDim = dim3(ncl * CLS); cfg.blockDim = dim3(384); cfg.dynamicSmemBytes = SMEM_TOTAL; cfg.stream = st;
  cudaLaunchAttribute at[1]; at[0].id = cudaLaunchAttributeClusterDimension; at[0].val.clusterDim.x = CLS; at[0].val.clusterDim.y = 1; at[0].val.clusterDim.z = 1;
  cfg.attrs = at; cfg.numAttrs = 1;
  cudaLaunchKernelEx(&cfg, k_main, maps, (const bf16*)d_in[0], (const bf16*)d_in[1], (const bf16*)d_in[9], (const bf16*)d_in[11], (bf16*)d_out, 0);
  if (nhelp > 0) {
    cfg.gridDim = dim3(nhelp);
    at[0].id = cudaLaunchAttributeProgrammaticStreamSerialization; at[0].val.programmaticStreamSerializationAllowed = 1;
    cudaLaunchKernelEx(&cfg, k_main, maps, (const bf16*)d_in[0], (const bf16*)d_in[1], (const bf16*)d_in[9], (const bf16*)d_in[11], (bf16*)d_out, 1);
  }
}
```

```cpp
#include <cuda_runtime.h>
#include <cuda_bf16.h>
#include <cuda.h>
#include <stdint.h>

typedef __nv_bfloat16 bf16;

#define S_TOK 2048
#define DM 512
#define NH 32
#define DH 128
#define HD 4096
#define NMEM 8
#define SEG 32
#define NSEG 64
#define FF 1792
#define NBLK 16
#define NREC 64
#define REPL 0
#define CLS 8

__device__ __align__(1024) bf16 g_xn[S_TOK * DM];
__device__ __align__(1024) bf16 g_y[S_TOK * DM];
__device__ __align__(1024) bf16 g_qkv[(size_t)S_TOK * 3 * HD];
__device__ __align__(1024) bf16 g_h1[S_TOK * FF];
__device__ __align__(1024) bf16 g_g[S_TOK * DM];
__device__ __align__(1024) bf16 g_o[(size_t)S_TOK * HD];
__device__ __align__(1024) bf16 g_km[NSEG * NH * NMEM * DH];
__device__ __align__(1024) bf16 g_vmt[NSEG * NH * DH * NMEM];
__device__ __align__(1024) float g_opart[(size_t)4 * S_TOK * DM];
__device__ __align__(1024) float g_opl[(size_t)16 * 128 * DM];
__device__ __align__(1024) unsigned g_part[8 * 2 * 8 * 8 * 512];
struct Flags {
  unsigned qkv[NBLK * 48];
  unsigned h1[NBLK];
  unsigned g[NBLK];
  unsigned o[NBLK * 4];
  unsigned p[NBLK];
  unsigned o16[16];
  unsigned ctr;
  unsigned rec[NREC];
  unsigned abort_;
};
__device__ __align__(1024) Flags g_flags;

#define RSTAMP(k)
#define DBGMODE 0
#define ISTAMP(i, k)
__device__ __forceinline__ unsigned smem_u32(const void* p) { return (unsigned)__cvta_generic_to_shared(p); }
__device__ __forceinline__ float bf16r(float x) { unsigned u; asm("cvt.rn.bf16x2.f32 %0, %1, %2;" : "=r"(u) : "f"(x), "f"(0.0f)); return __uint_as_float(u); }
__device__ __forceinline__ unsigned pack_bf16(float lo, float hi) {
  __nv_bfloat162 v = __floats2bfloat162_rn(lo, hi);
  return *reinterpret_cast<unsigned*>(&v);
}
__device__ __forceinline__ float bf_lo(unsigned u) { return __uint_as_float(u << 16); }
__device__ __forceinline__ float bf_hi(unsigned u) { return __uint_as_float(u & 0xffff0000u); }

#define SPIN_LIMIT (1u << 20)
#define TRAP_IF(x) if ((x) > SPIN_LIMIT) { asm volatile("st.global.u32 [%0], %1;" ::"l"(0ull), "r"(0u) : "memory"); break; }
__device__ __forceinline__ unsigned ld_acquire(const unsigned* p) {
  unsigned v; asm volatile("ld.acquire.gpu.global.u32 %0, [%1];" : "=r"(v) : "l"(p) : "memory"); return v;
}
__device__ __forceinline__ unsigned ld_relaxed(const unsigned* p) {
  unsigned v; asm volatile("ld.relaxed.gpu.global.u32 %0, [%1];" : "=r"(v) : "l"(p) : "memory"); return v;
}
__device__ __forceinline__ void red_release_add(unsigned* p, unsigned v) {
  asm volatile("red.release.gpu.global.add.u32 [%0], %1;" ::"l"(p), "r"(v) : "memory");
}
__device__ __forceinline__ void st_release(unsigned* p, unsigned v) {
  asm volatile("st.release.gpu.global.u32 [%0], %1;" ::"l"(p), "r"(v) : "memory");
}
__device__ __forceinline__ void wait_flag_ge(const unsigned* p, unsigned target) {
  unsigned it = 0;
  while (ld_acquire(p) < target) {
    __nanosleep(64);
    TRAP_IF(++it);
  }
}
__device__ __forceinline__ uint4 ldv4_relaxed(const void* p) {
  uint4 a; asm volatile("ld.relaxed.gpu.global.v4.u32 {%0,%1,%2,%3}, [%4];" : "=r"(a.x), "=r"(a.y), "=r"(a.z), "=r"(a.w) : "l"(p) : "memory"); return a;
}
__device__ __forceinline__ uint2 ldv2_relaxed(const void* p) {
  uint2 a; asm volatile("ld.relaxed.gpu.global.v2.u32 {%0,%1}, [%2];" : "=r"(a.x), "=r"(a.y) : "l"(p) : "memory"); return a;
}
__device__ __forceinline__ void mbar_init(unsigned mb, unsigned cnt) { asm volatile("mbarrier.init.shared::cta.b64 [%0], %1;" ::"r"(mb), "r"(cnt) : "memory"); }
__device__ __forceinline__ void mbar_expect_tx(unsigned mb, unsigned bytes) { asm volatile("mbarrier.arrive.expect_tx.shared::cta.b64 _, [%0], %1;" ::"r"(mb), "r"(bytes) : "memory"); }
__device__ __forceinline__ void mbar_arrive(unsigned mb) { asm volatile("mbarrier.arrive.shared::cta.b64 _, [%0];" ::"r"(mb) : "memory"); }
__device__ __forceinline__ void mbar_wait(unsigned mb, unsigned parity) {
  unsigned ok, it = 0;
  while (true) {
    asm volatile("{.reg .pred p; mbarrier.try_wait.parity.shared::cta.b64 p, [%1], %2; selp.u32 %0,1,0,p;}" : "=r"(ok) : "r"(mb), "r"(parity) : "memory");
    if (ok) break;
    TRAP_IF(++it);
  }
}
__device__ __forceinline__ void mbar_wait_sleep(unsigned mb, unsigned parity) {
  unsigned ok, it = 0;
  while (true) {
    asm volatile("{.reg .pred p; mbarrier.test_wait.parity.shared::cta.b64 p, [%1], %2; selp.u32 %0,1,0,p;}" : "=r"(ok) : "r"(mb), "r"(parity) : "memory");
    if (ok) break;
    __nanosleep(200);
    TRAP_IF(++it);
  }
}
__device__ __forceinline__ float ex2f(float x) { float y; asm("ex2.approx.ftz.f32 %0, %1;" : "=f"(y) : "f"(x)); return y; }
__device__ __forceinline__ int opaque_tid() { int t = threadIdx.x; t = __shfl_sync(~0u, t, t & 31); return t; }
#define LOG2E 1.4426950408889634f
__device__ __forceinline__ void mbar_wait_cluster(unsigned mb, unsigned parity) {
  unsigned ok, it = 0;
  while (true) {
    asm volatile("{.reg .pred p; mbarrier.try_wait.parity.acquire.cluster.shared::cta.b64 p, [%1], %2; selp.u32 %0,1,0,p;}" : "=r"(ok) : "r"(mb), "r"(parity) : "memory");
    if (ok) break;
    TRAP_IF(++it);
  }
}
__device__ __forceinline__ void bar_sync(int id, int n) { asm volatile("bar.sync %0, %1;" ::"r"(id), "r"(n) : "memory"); }
__device__ __forceinline__ void bar_arrive(int id, int n) { asm volatile("bar.arrive %0, %1;" ::"r"(id), "r"(n) : "memory"); }
__device__ __forceinline__ void tma_load_2d(unsigned dst, const CUtensorMap* map, int c0, int c1, unsigned mb) {
  asm volatile("cp.async.bulk.tensor.2d.shared::cluster.global.mbarrier::complete_tx::bytes [%0], [%1, {%3, %4}], [%2];"
               ::"r"(dst), "l"((uint64_t)map), "r"(mb), "r"(c0), "r"(c1) : "memory");
}
__device__ __forceinline__ void tma_store_2d(const CUtensorMap* map, unsigned src, int c0, int c1) {
  asm volatile("cp.async.bulk.tensor.2d.global.shared::cta.bulk_group [%0, {%2, %3}], [%1];"
               ::"l"((uint64_t)map), "r"(src), "r"(c0), "r"(c1) : "memory");
}
__device__ __forceinline__ void fence_proxy_async() { asm volatile("fence.proxy.async;" ::: "memory"); }
__device__ __forceinline__ void fence_proxy_async_smem() { asm volatile("fence.proxy.async.shared::cta;" ::: "memory"); }
__device__ __forceinline__ void ldsm_x4(unsigned* r, unsigned addr) {
  asm volatile("ldmatrix.sync.aligned.m8n8.x4.shared.b16 {%0,%1,%2,%3}, [%4];" : "=r"(r[0]), "=r"(r[1]), "=r"(r[2]), "=r"(r[3]) : "r"(addr) : "memory");
}
__device__ __forceinline__ void ldsm_x4_t(unsigned* r, unsigned addr) {
  asm volatile("ldmatrix.sync.aligned.m8n8.x4.trans.shared.b16 {%0,%1,%2,%3}, [%4];" : "=r"(r[0]), "=r"(r[1]), "=r"(r[2]), "=r"(r[3]) : "r"(addr) : "memory");
}
__device__ __forceinline__ void stsm_x2_t(unsigned addr, unsigned r0, unsigned r1) {
  asm volatile("stmatrix.sync.aligned.m8n8.x2.trans.shared.b16 [%0], {%1,%2};" ::"r"(addr), "r"(r0), "r"(r1) : "memory");
}
__device__ __forceinline__ void stsm_x4(unsigned addr, unsigned r0, unsigned r1, unsigned r2, unsigned r3) {
  asm volatile("stmatrix.sync.aligned.m8n8.x4.shared.b16 [%0], {%1,%2,%3,%4};" ::"r"(addr), "r"(r0), "r"(r1), "r"(r2), "r"(r3) : "memory");
}
__device__ __forceinline__ void mma16816(float* d, const unsigned* a, unsigned b0, unsigned b1) {
  asm volatile("mma.sync.aligned.m16n8k16.row.col.f32.bf16.bf16.f32 {%0,%1,%2,%3}, {%4,%5,%6,%7}, {%8,%9}, {%0,%1,%2,%3};"
               : "+f"(d[0]), "+f"(d[1]), "+f"(d[2]), "+f"(d[3]) : "r"(a[0]), "r"(a[1]), "r"(a[2]), "r"(a[3]), "r"(b0), "r"(b1));
}
__device__ __forceinline__ void mma1688(float* d, unsigned a0, unsigned a1, unsigned b0) {
  asm volatile("mma.sync.aligned.m16n8k8.row.col.f32.bf16.bf16.f32 {%0,%1,%2,%3}, {%4,%5}, {%6}, {%0,%1,%2,%3};"
               : "+f"(d[0]), "+f"(d[1]), "+f"(d[2]), "+f"(d[3]) : "r"(a0), "r"(a1), "r"(b0));
}
__device__ __forceinline__ uint64_t mkdesc(unsigned addr, unsigned lbo, unsigned sbo) {
  return (uint64_t)((addr >> 4) & 0x3fff) | ((uint64_t)(lbo >> 4) << 16) | ((uint64_t)(sbo >> 4) << 32) | (1ull << 62);
}
#define R8(b) "+f"(d[b]), "+f"(d[b + 1]), "+f"(d[b + 2]), "+f"(d[b + 3]), "+f"(d[b + 4]), "+f"(d[b + 5]), "+f"(d[b + 6]), "+f"(d[b + 7])
#define R32(b) R8(b), R8(b + 8), R8(b + 16), R8(b + 24)
__device__ __forceinline__ void wgmma_n256(float* d, uint64_t ad, uint64_t bd, int acc) {
  asm volatile(
      "{.reg .pred p; setp.ne.b32 p, %130, 0;\n"
      "wgmma.mma_async.sync.aligned.m64n256k16.f32.bf16.bf16 "
      "{%0,%1,%2,%3,%4,%5,%6,%7,%8,%9,%10,%11,%12,%13,%14,%15,%16,%17,%18,%19,%20,%21,%22,%23,%24,%25,%26,%27,%28,%29,%30,%31,"
      "%32,%33,%34,%35,%36,%37,%38,%39,%40,%41,%42,%43,%44,%45,%46,%47,%48,%49,%50,%51,%52,%53,%54,%55,%56,%57,%58,%59,%60,%61,%62,%63,"
      "%64,%65,%66,%67,%68,%69,%70,%71,%72,%73,%74,%75,%76,%77,%78,%79,%80,%81,%82,%83,%84,%85,%86,%87,%88,%89,%90,%91,%92,%93,%94,%95,"
      "%96,%97,%98,%99,%100,%101,%102,%103,%104,%105,%106,%107,%108,%109,%110,%111,%112,%113,%114,%115,%116,%117,%118,%119,%120,%121,%122,%123,%124,%125,%126,%127},"
      "%128, %129, p, 1, 1, 0, 1;}\n"
      : R32(0), R32(32), R32(64), R32(96)
      : "l"(ad), "l"(bd), "r"(acc));
}

__device__ __forceinline__ void ln16(const float* x, float* o) {
  float s = 0;
#pragma unroll
  for (int i = 0; i < 16; i++) s += x[i];
#pragma unroll
  for (int of = 16; of > 0; of >>= 1) s += __shfl_xor_sync(~0u, s, of);
  float mean = s * (1.0f / DM);
  float v = 0;
#pragma unroll
  for (int i = 0; i < 16; i++) { float dd = x[i] - mean; v += dd * dd; }
#pragma unroll
  for (int of = 16; of > 0; of >>= 1) v += __shfl_xor_sync(~0u, v, of);
  float mb = bf16r(mean);
  float vb = bf16r(v * (1.0f / DM));
  float den = bf16r(sqrtf(bf16r(vb + 1e-5f)));
#pragma unroll
  for (int i = 0; i < 16; i++) o[i] = bf16r(__fdiv_rn(bf16r(x[i] - mb), den));
}
__global__ void __launch_bounds__(256) k_pre(const bf16* __restrict__ x) {
  int t = threadIdx.x, lane = t & 31, w = t >> 5;
  int row = blockIdx.x * 8 + w;
  const uint4* src = reinterpret_cast<const uint4*>(x + (size_t)row * DM);
  uint4 a = src[lane], b = src[lane + 32];
  unsigned u[8] = {a.x, a.y, a.z, a.w, b.x, b.y, b.z, b.w};
  float f[16], o[16], o2[16];
#pragma unroll
  for (int i = 0; i < 8; i++) { f[2 * i] = bf_lo(u[i]); f[2 * i + 1] = bf_hi(u[i]); }
  ln16(f, o);
  ln16(o, o2);
  uint4* d1 = reinterpret_cast<uint4*>(g_xn + (size_t)row * DM);
  uint4* d2 = reinterpret_cast<uint4*>(g_y + (size_t)row * DM);
  d1[lane] = make_uint4(pack_bf16(o[0], o[1]), pack_bf16(o[2], o[3]), pack_bf16(o[4], o[5]), pack_bf16(o[6], o[7]));
  d1[lane + 32] = make_uint4(pack_bf16(o[8], o[9]), pack_bf16(o[10], o[11]), pack_bf16(o[12], o[13]), pack_bf16(o[14], o[15]));
  d2[lane] = make_uint4(pack_bf16(o2[0], o2[1]), pack_bf16(o2[2], o2[3]), pack_bf16(o2[4], o2[5]), pack_bf16(o2[6], o2[7]));
  d2[lane + 32] = make_uint4(pack_bf16(o2[8], o2[9]), pack_bf16(o2[10], o2[11]), pack_bf16(o2[12], o2[13]), pack_bf16(o2[14], o2[15]));
  int gt = blockIdx.x * 256 + t;
  uint4 z = make_uint4(0, 0, 0, 0);
  if (gt < 16384) reinterpret_cast<uint4*>(g_part)[gt] = z;
  if (gt < (int)(sizeof(Flags) / 4)) reinterpret_cast<unsigned*>(&g_flags)[gt] = 0;
}

struct Maps { CUtensorMap xn, y, h1, o, qkv_st, qkv_ld, g, wq, wk, wv, wo, w1, w2; };

#define NSTAGE 3
#define STAGE_BYTES 49152
#define B_STG (NSTAGE * STAGE_BYTES)
#define R_WO 0
#define R_T1 65536
#define R_T2 131072
#define R_RING 65536
#define RING_N 4
#define RING_BYTES 12288
#define R_MEM 196608
#define R_QS (R_MEM + 8448)
#define R_KS (R_QS + 1152)
#define R_OS (R_KS + 1152)
#define R_SOWN (R_OS + 2176)
#define R_SPEER (R_SOWN + 1280)
#define R_VM (R_SPEER + 1280)
#define R_VRED (R_VM + 2048)
#define R_RS (R_VRED + 6144)
#define SM_BAR (R_RS + 8192)
#define SMEM_TOTAL (SM_BAR + 256 + 1024)
#define MB_FULL 0
#define MB_EMPTY 8
#define MB_STGF 16
#define MB_STGE 17
#define MB_W0 18
#define MB_W1 19
#define MB_WO 20
#define MB_S 21
#define MB_V 22
#define MB_KVR 23
#define MB_KVF 24
#define MB_RS 25
#define MB_AG 26
#define SM_MISC (SM_BAR + 224)

#define N_KV 512
#define I_M1 512
#define I_Q 624
#define I_M2 880
#define I_POST 912
#define I_TAIL (I_POST + 16 * 32)
#define N_ITEMS (I_TAIL + 5 * 8 + 32 + 8 + 64)
enum { T_QKV = 0, T_M1 = 1, T_M2 = 2, T_ATT = 3, T_OUT = 4, T_OUTL = 5, T_RED = 6, T_REDL = 7 };
struct Item { int type, b, c, ks; };
__device__ __forceinline__ Item decode_item(int i) {
  Item it; it.ks = 0;
  if (i < N_KV) { it.type = T_QKV; it.b = i >> 5; it.c = 16 + (i & 31); }
  else if (i < I_Q) { it.type = T_M1; it.b = (i - I_M1) / 7; it.c = (i - I_M1) % 7; }
  else if (i < I_M2) { it.type = T_QKV; it.b = (i - I_Q) >> 4; it.c = (i - I_Q) & 15; }
  else if (i < I_POST) { it.type = T_M2; it.b = (i - I_M2) >> 1; it.c = (i - I_M2) & 1; }
  else if (i < I_TAIL) {
    int x = i - I_POST, p = x >> 5, r = x & 31;
    if (r < 16) { it.type = T_ATT; it.b = p; it.c = r; }
    else if (r < 24) { it.type = T_OUT; it.b = p - 3; it.c = r & 1; it.ks = (r - 16) >> 1; }
    else { it.type = T_RED; it.b = p - 5; it.c = r - 24; }
  } else {
    int x = i - I_TAIL, r = x & 7;
    if (x < 40) {
      int q = x >> 3;
      if (q == 0 || q == 2) { it.type = T_OUT; it.b = 13 + (q >> 1); it.c = r & 1; it.ks = r >> 1; }
      else { it.type = T_RED; it.b = q == 1 ? 11 : 9 + q; it.c = r; }
    }
    else if (x < 72) { it.type = T_OUTL; it.b = 15; it.c = x & 1; it.ks = (x - 40) >> 1; }
    else if (x < 80) { it.type = T_RED; it.b = 14; it.c = r; }
    else { it.type = T_REDL; it.b = 15; it.c = x - 80; }
  }
  return it;
}
__device__ __forceinline__ int item_nkb(int type) { return type == T_M2 ? 28 : (type == T_OUT ? 16 : (type >= T_RED ? 1 : (type >= T_ATT ? 4 : 8))); }

__device__ __forceinline__ void st_async_b64(unsigned raddr, unsigned lo, unsigned hi, unsigned rmb) {
  asm volatile("st.async.weak.shared::cluster.mbarrier::complete_tx::bytes.v2.b32 [%0], {%1,%2}, [%3];" ::"r"(raddr), "r"(lo), "r"(hi), "r"(rmb) : "memory");
}
__device__ __forceinline__ void st_async_b32(unsigned raddr, unsigned v, unsigned rmb) {
  asm volatile("st.async.weak.shared::cluster.mbarrier::complete_tx::bytes.b32 [%0], %1, [%2];" ::"r"(raddr), "r"(v), "r"(rmb) : "memory");
}
__device__ __forceinline__ unsigned mapa(unsigned a, unsigned rank) {
  unsigned r; asm volatile("mapa.shared::cluster.u32 %0, %1, %2;" : "=r"(r) : "r"(a), "r"(rank)); return r;
}
__device__ __forceinline__ void sts64(unsigned a, unsigned x, unsigned y) { asm volatile("st.shared.v2.b32 [%0], {%1,%2};" ::"r"(a), "r"(x), "r"(y) : "memory"); }
__device__ __forceinline__ void sts128(unsigned a, uint4 v) { asm volatile("st.shared.v4.b32 [%0], {%1,%2,%3,%4};" ::"r"(a), "r"(v.x), "r"(v.y), "r"(v.z), "r"(v.w) : "memory"); }
__device__ __forceinline__ uint2 lds64(unsigned a) { uint2 v; asm volatile("ld.shared.v2.b32 {%0,%1}, [%2];" : "=r"(v.x), "=r"(v.y) : "r"(a) : "memory"); return v; }
__device__ __forceinline__ uint4 lds128(unsigned a) { uint4 v; asm volatile("ld.shared.v4.b32 {%0,%1,%2,%3}, [%4];" : "=r"(v.x), "=r"(v.y), "=r"(v.z), "=r"(v.w) : "r"(a) : "memory"); return v; }
__device__ __forceinline__ float lds32f(unsigned a) { float v; asm volatile("ld.shared.f32 %0, [%1];" : "=f"(v) : "r"(a) : "memory"); return v; }
#define spin_check(it) TRAP_IF(++it)
#define POLLV 0
#define BAR8 0
#define D_STAG 150
#define D_RED 480
#define D_PUB 0
#define DELAY(n) do { unsigned c0_, c1_; asm volatile("mov.u32 %0, %%clock;" : "=r"(c0_)); do { asm volatile("mov.u32 %0, %%clock;" : "=r"(c1_)); } while (c1_ - c0_ < (n)); } while (0)
#define SCALE_QK 0.08838834764831845f

__device__ __forceinline__ void rec_worker(const Maps& maps, unsigned sb, const bf16* __restrict__ mem0) {
  const int c = blockIdx.x, h = c >> 1, j = c & 1;
  const int t = opaque_tid(), lane = t & 31, w = t >> 5, g = lane >> 2, tq = lane & 3;
  const int m = lane >> 3, r8 = lane & 7, kh = w >> 2, et = w & 3;
  const unsigned bar = sb + SM_BAR;
  unsigned wq[16][4], wk[16][4], wo[8][4];
  const unsigned woff = (kh * 4) * 8192 + ((m >> 1) * 8 + r8) * 128 + (((et * 2 + (m & 1)) ^ r8) << 4);
  mbar_wait(bar + 8 * MB_W0, 0);
#pragma unroll
  for (int i = 0; i < 16; i++) {
    ldsm_x4_t(wq[i], sb + R_WO + woff + (i >> 2) * 8192 + (i & 3) * 2048);
    ldsm_x4_t(wk[i], sb + R_T1 + woff + (i >> 2) * 8192 + (i & 3) * 2048);
  }
  bar_sync(2, 288);
  if (t == 0) {
    fence_proxy_async_smem();
    mbar_expect_tx(bar + 8 * MB_WO, 65536);
    for (int kb = 0; kb < 2; kb++)
      for (int cb = 0; cb < 4; cb++) tma_load_2d(sb + R_WO + (kb * 4 + cb) * 8192, &maps.wo, j * 256 + cb * 64, h * 128 + kb * 64, bar + 8 * MB_WO);
  }
  mbar_wait(bar + 8 * MB_W1, 0);
  const unsigned pV = sb + R_T2 + woff;
  const unsigned rk = c & 7, peer = rk ^ 1, cl = c >> 3;
#define KEEP(x) x = __shfl_sync(~0u, x, lane)
  unsigned pA = sb + R_MEM + kh * 4096 + lane * 16;
  unsigned pW0 = sb + R_WO + (w >> 1) * 8192 + ((m >> 1) * 8 + r8) * 128 + ((((w & 1) * 4 + (m & 1)) ^ r8) << 4);
  unsigned pW1 = pW0 ^ 32;
  unsigned pVk = pV;
  unsigned aX = sb + R_VRED + et * 512 + lane * 16;
  unsigned aQKst = sb + (kh ? R_KS : R_QS) + r8 * 144 + (et * 16 + (m & 1) * 8) * 2;
  unsigned aL8 = sb + lane * 8;
  unsigned aSl = mapa(sb + R_SOWN + w * 256 + lane * 8, rk), aSr = mapa(sb + R_SPEER + w * 256 + lane * 8, peer);
  unsigned aVl = mapa(sb + R_VM + (j * 4 + et) * 256 + lane * 8, rk), aVr = mapa(sb + R_VM + (j * 4 + et) * 256 + lane * 8, peer);
  const unsigned mbSl = mapa(bar + 8 * MB_S, rk), mbSr = mapa(bar + 8 * MB_S, peer), mbVl = mbSl + 8, mbVr = mbSr + 8;
  unsigned aQ = sb + R_QS + r8 * 144 + m * 16;
  unsigned oKx = (et * 8 + r8) * 128 + ((m ^ r8) << 4);
  unsigned oVx = 4096 + (et >> 1) * 4096 + ((m >> 1) * 8 + r8) * 128 + ((((et & 1) * 4 + (m & 1)) ^ r8) << 4);
  unsigned aOst = sb + R_OS + r8 * 272 + (et * 32 + m * 8) * 2;
  unsigned aOld = sb + R_OS + r8 * 272 + m * 16;
  unsigned aVm = sb + R_VM + et * 512 + lane * 8;
  unsigned aRSr = mapa(sb + R_RS + (h & 3) * 2048 + (w & 1) * 1024 + lane * 8, j * 4 + (w >> 1));
  unsigned mbRSr = mapa(bar + 8 * MB_RS, j * 4 + (w >> 1));
  unsigned t8 = t * 8;
  KEEP(pA); KEEP(pW0); KEEP(pW1); KEEP(pVk); KEEP(aX); KEEP(aQKst); KEEP(aL8); KEEP(aSl); KEEP(aSr); KEEP(aVl); KEEP(aVr); KEEP(aQ); KEEP(oKx); KEEP(oVx);
  KEEP(aOst); KEEP(aOld); KEEP(aVm); KEEP(aRSr); KEEP(mbRSr); KEEP(t8);
  mbar_wait(bar + 8 * MB_WO, 0);
#pragma unroll
  for (int ks = 0; ks < 4; ks++) { ldsm_x4_t(wo[2 * ks], pW0 + ks * 2048); ldsm_x4_t(wo[2 * ks + 1], pW1 + ks * 2048); }
  {
    unsigned v[8];
#pragma unroll
    for (int q = 0; q < 8; q++) v[q] = __ldg(reinterpret_cast<const unsigned*>(mem0) + q * 256 + t);
    sts128(sb + R_MEM + t * 32, make_uint4(__byte_perm(v[0], v[1], 0x5410), __byte_perm(v[2], v[3], 0x5410), __byte_perm(v[4], v[5], 0x5410), __byte_perm(v[6], v[7], 0x5410)));
    sts128(sb + R_MEM + t * 32 + 16, make_uint4(__byte_perm(v[0], v[1], 0x7632), __byte_perm(v[2], v[3], 0x7632), __byte_perm(v[4], v[5], 0x7632), __byte_perm(v[6], v[7], 0x7632)));
  }
  bar_sync(1, 256);

#pragma unroll 1
  for (int s = 0;; s++) {
    const unsigned par = s & 1;
    const unsigned slot = s & (RING_N - 1), rpar = (s / RING_N) & 1;
    const unsigned ring = sb + R_RING + slot * RING_BYTES;
    RSTAMP(1);
    RSTAMP(2);
    float aq[4] = {0, 0, 0, 0}, ak[4] = {0, 0, 0, 0}, av[4] = {0, 0, 0, 0};
#pragma unroll
    for (int i = 0; i < 8; i++) {
      unsigned b[4], f[4], f0[4];
      ldsm_x4_t(b, pA + i * 512);
      ldsm_x4_t(f0, pVk + (i >> 1) * 8192 + (i & 1) * 4096);
      ldsm_x4_t(f, pVk + (i >> 1) * 8192 + (i & 1) * 4096 + 2048);
      mma16816(aq, wq[2 * i], b[0], b[1]); mma16816(ak, wk[2 * i], b[0], b[1]); mma16816(av, f0, b[0], b[1]);
      mma16816(aq, wq[2 * i + 1], b[2], b[3]); mma16816(ak, wk[2 * i + 1], b[2], b[3]); mma16816(av, f, b[2], b[3]);
    }
    RSTAMP(3);
#define STSF4(a, v) asm volatile("st.shared.v4.f32 [%0], {%1,%2,%3,%4};" ::"r"(a), "f"(v[0]), "f"(v[1]), "f"(v[2]), "f"(v[3]) : "memory")
    unsigned f[8][4];
#define NPRE 2
#define WO_PREFETCH() do { _Pragma("unroll") for (int i = 0; i < NPRE; i++) { ldsm_x4_t(f[2 * i], pW0 + 32768 + i * 2048); ldsm_x4_t(f[2 * i + 1], pW1 + 32768 + i * 2048); } } while (0)
    if (kh) {
      STSF4(aX, aq);
      bar_sync(4 + et, 64);
      uint4 o = lds128(aX + 2048), o2 = lds128(aX + 4096);
      stsm_x2_t(aQKst, pack_bf16(ak[0] + __uint_as_float(o.x), ak[1] + __uint_as_float(o.y)), pack_bf16(ak[2] + __uint_as_float(o.z), ak[3] + __uint_as_float(o.w)));
      bar_arrive(1, 256);
      unsigned x = pack_bf16(av[0] + __uint_as_float(o2.x), av[1] + __uint_as_float(o2.y)), y = pack_bf16(av[2] + __uint_as_float(o2.z), av[3] + __uint_as_float(o2.w));
      st_async_b64(aVr, x, y, mbVr);
      st_async_b64(aVl, x, y, mbVl);
      mbar_wait(bar + 8 * (MB_FULL + slot), rpar);
      unsigned vx[4][4];
      ldsm_x4_t(vx[0], ring + oVx); ldsm_x4_t(vx[1], ring + oVx + 2048); ldsm_x4_t(vx[2], ring + (oVx ^ 32)); ldsm_x4_t(vx[3], ring + (oVx ^ 32) + 2048);
      RSTAMP(4); RSTAMP(5); RSTAMP(6); RSTAMP(7);
      mbar_wait(bar + 8 * MB_S, par);
      RSTAMP(8);
      float sc[10];
#pragma unroll
      for (int i = 0; i < 5; i++) {
        uint2 o = lds64(aL8 + R_SOWN + i * 256), p = lds64(aL8 + R_SPEER + i * 256);
        sc[2 * i] = __uint_as_float(o.x) + __uint_as_float(p.x); sc[2 * i + 1] = __uint_as_float(o.y) + __uint_as_float(p.y);
      }
      mbar_wait(bar + 8 * MB_V, par);
      uint2 vm0 = lds64(aVm), vm1 = lds64(aVm + 256);
      float mx = fmaxf(fmaxf(fmaxf(sc[0], sc[1]), fmaxf(sc[2], sc[3])), fmaxf(fmaxf(fmaxf(sc[4], sc[5]), fmaxf(sc[6], sc[7])), fmaxf(sc[8], sc[9])));
      mx = fmaxf(mx, __shfl_xor_sync(~0u, mx, 1)); mx = fmaxf(mx, __shfl_xor_sync(~0u, mx, 2));
      const float nm = -mx * (SCALE_QK * LOG2E);
#pragma unroll
      for (int i = 0; i < 10; i++) sc[i] = ex2f(fmaf(sc[i], SCALE_QK * LOG2E, nm));
      float sum = (((sc[0] + sc[1]) + (sc[2] + sc[3])) + ((sc[4] + sc[5]) + (sc[6] + sc[7]))) + (sc[8] + sc[9]);
      sum += __shfl_xor_sync(~0u, sum, 1); sum += __shfl_xor_sync(~0u, sum, 2);
      float inv; asm("rcp.approx.ftz.f32 %0, %1;" : "=f"(inv) : "f"(sum));
      unsigned p[5];
#pragma unroll
      for (int i = 0; i < 5; i++) p[i] = pack_bf16(sc[2 * i] * inv, sc[2 * i + 1] * inv);
      RSTAMP(9);
      float o0[4] = {0, 0, 0, 0}, o1[4] = {0, 0, 0, 0}, o3[4] = {0, 0, 0, 0}, o4[4] = {0, 0, 0, 0};
      mma16816(o0, vx[0], p[0], p[1]); mma16816(o3, vx[2], p[0], p[1]); mma16816(o1, vx[1], p[2], p[3]); mma16816(o4, vx[3], p[2], p[3]);
      mma1688(o0, vm0.x, vm0.y, p[4]); mma1688(o3, vm1.x, vm1.y, p[4]);
      if (s == NSEG - 1) { if (t == 128) mbar_arrive(bar + 8 * MB_KVR); break; }
      asm volatile("stmatrix.sync.aligned.m8n8.x4.trans.shared.b16 [%0], {%1,%2,%3,%4};" ::"r"(aOst), "r"(pack_bf16(o0[0] + o1[0], o0[1] + o1[1])), "r"(pack_bf16(o0[2] + o1[2], o0[3] + o1[3])),
                   "r"(pack_bf16(o3[0] + o4[0], o3[1] + o4[1])), "r"(pack_bf16(o3[2] + o4[2], o3[3] + o4[3])) : "memory");
      RSTAMP(10);
      bar_sync(1, 256);
      WO_PREFETCH();
    } else {
      STSF4(aX + 2048, ak); STSF4(aX + 4096, av);
      unsigned kb[8];
      mbar_wait(bar + 8 * (MB_FULL + slot), rpar);
      ldsm_x4(kb, ring + oKx); ldsm_x4(kb + 4, ring + (oKx ^ 64));
      bar_sync(4 + et, 64);
      uint4 o = lds128(aX);
      stsm_x2_t(aQKst, pack_bf16(aq[0] + __uint_as_float(o.x), aq[1] + __uint_as_float(o.y)), pack_bf16(aq[2] + __uint_as_float(o.z), aq[3] + __uint_as_float(o.w)));
      RSTAMP(4);
      bar_sync(1, 256);
      RSTAMP(5);
      unsigned qa[8], km[8];
      ldsm_x4(qa, aQ); ldsm_x4(qa + 4, aQ + 64);
      if (w == 3) { ldsm_x4(km, aQ + 1152); ldsm_x4(km + 4, aQ + 1152 + 64); }
      float s0[4] = {0, 0, 0, 0}, s1[4] = {0, 0, 0, 0};
      unsigned af[4][4];
#pragma unroll
      for (int i = 0; i < 4; i++) { af[i][0] = qa[2 * i]; af[i][1] = 0; af[i][2] = qa[2 * i + 1]; af[i][3] = 0; }
      mma16816(s0, af[0], kb[0], kb[1]); mma16816(s1, af[1], kb[2], kb[3]);
      mma16816(s0, af[2], kb[4], kb[5]); mma16816(s1, af[3], kb[6], kb[7]);
      if (w == 3) {
        float m0[4] = {0, 0, 0, 0}, m1[4] = {0, 0, 0, 0};
        mma16816(m0, af[0], km[0], km[1]); mma16816(m1, af[1], km[2], km[3]);
        mma16816(m0, af[2], km[4], km[5]); mma16816(m1, af[3], km[6], km[7]);
        unsigned x = __float_as_uint(m0[0] + m1[0]), y = __float_as_uint(m0[1] + m1[1]);
        st_async_b64(aSr + 256, x, y, mbSr); st_async_b64(aSl + 256, x, y, mbSl);
      }
      unsigned x = __float_as_uint(s0[0] + s1[0]), y = __float_as_uint(s0[1] + s1[1]);
      st_async_b64(aSr, x, y, mbSr); st_async_b64(aSl, x, y, mbSl);
      RSTAMP(6);
      if (s == NSEG - 1) break;
      WO_PREFETCH();
      RSTAMP(7); RSTAMP(8); RSTAMP(9); RSTAMP(10);
      bar_sync(1, 256);
    }
    RSTAMP(11);
    float d0[4] = {0, 0, 0, 0}, d1[4] = {0, 0, 0, 0}, e0[4] = {0, 0, 0, 0}, e1[4] = {0, 0, 0, 0};
    unsigned ob[4][4];
#pragma unroll
    for (int k2 = 0; k2 < 4; k2++) ldsm_x4(ob[k2], aOld + k2 * 64);
#pragma unroll
    for (int i = NPRE; i < 4; i++) { ldsm_x4_t(f[2 * i], pW0 + 32768 + i * 2048); ldsm_x4_t(f[2 * i + 1], pW1 + 32768 + i * 2048); }
    mma16816(d0, wo[0], ob[0][0], ob[0][1]); mma16816(d1, wo[1], ob[0][0], ob[0][1]);
    mma16816(e0, wo[2], ob[0][2], ob[0][3]); mma16816(e1, wo[3], ob[0][2], ob[0][3]);
    mma16816(d0, wo[4], ob[1][0], ob[1][1]); mma16816(d1, wo[5], ob[1][0], ob[1][1]);
    mma16816(e0, wo[6], ob[1][2], ob[1][3]); mma16816(e1, wo[7], ob[1][2], ob[1][3]);
    mma16816(d0, f[0], ob[2][0], ob[2][1]); mma16816(d1, f[1], ob[2][0], ob[2][1]);
    mma16816(e0, f[2], ob[2][2], ob[2][3]); mma16816(e1, f[3], ob[2][2], ob[2][3]);
    mma16816(d0, f[4], ob[3][0], ob[3][1]); mma16816(d1, f[5], ob[3][0], ob[3][1]);
    mma16816(e0, f[6], ob[3][2], ob[3][3]); mma16816(e1, f[7], ob[3][2], ob[3][3]);
    st_async_b64(aRSr, __float_as_uint(d0[0] + e0[0]), __float_as_uint(d0[1] + e0[1]), mbRSr);
    st_async_b64(aRSr + 256, __float_as_uint(d0[2] + e0[2]), __float_as_uint(d0[3] + e0[3]), mbRSr);
    st_async_b64(aRSr + 512, __float_as_uint(d1[0] + e1[0]), __float_as_uint(d1[1] + e1[1]), mbRSr);
    st_async_b64(aRSr + 768, __float_as_uint(d1[2] + e1[2]), __float_as_uint(d1[3] + e1[3]), mbRSr);
    RSTAMP(12);
    if (t == 128) {
      mbar_arrive(bar + 8 * (MB_EMPTY + slot)); mbar_arrive(bar + 8 * MB_KVR);
      mbar_expect_tx(bar + 8 * MB_S, 2560); mbar_expect_tx(bar + 8 * MB_V, 2048);
    }
    const unsigned tag = ((s >> 1) & 1) ^ 1;
    const char* gp = reinterpret_cast<const char*>(g_part) + (par * 8 + rk) * 16384 + t8;
    unsigned mbA[8];
#pragma unroll
    for (int i = 0; i < 8; i++) mbA[i] = mapa(bar + 8 * MB_AG, i);
    const unsigned dlt = (R_MEM + rk * 1024) - (SM_BAR + 8 * MB_AG) + (t8 >> 1);
    mbar_wait(bar + 8 * MB_RS, par);
    RSTAMP(13);
    uint2 a[8];
    {
      uint2 x0 = lds64(sb + R_RS + t8), x1 = lds64(sb + R_RS + 2048 + t8), x2 = lds64(sb + R_RS + 4096 + t8), x3 = lds64(sb + R_RS + 6144 + t8);
      float r0 = (__uint_as_float(x0.x) + __uint_as_float(x1.x)) + (__uint_as_float(x2.x) + __uint_as_float(x3.x));
      float r1 = (__uint_as_float(x0.y) + __uint_as_float(x1.y)) + (__uint_as_float(x2.y) + __uint_as_float(x3.y));
      a[0].x = (__float_as_uint(r0) & ~1u) | tag; a[0].y = (__float_as_uint(r1) & ~1u) | tag;
      asm volatile("st.relaxed.gpu.global.v2.u32 [%0], {%1,%2};" ::"l"(gp + cl * 2048), "r"(a[0].x), "r"(a[0].y) : "memory");
    }
    RSTAMP(14);
    if (t == 128) mbar_expect_tx(bar + 8 * MB_RS, 8192);
    {
      unsigned it = 0;
#define PLOAD(a) _Pragma("unroll") for (int i = 1; i < 8; i++) a[i] = ldv2_relaxed(gp + (cl ^ i) * 2048)
#define PAND(a) (((a[1].x & a[1].y) & (a[2].x & a[2].y) & (a[3].x & a[3].y)) & ((a[4].x & a[4].y) & (a[5].x & a[5].y)) & ((a[6].x & a[6].y) & (a[7].x & a[7].y)))
#define POR(a) (((a[1].x | a[1].y) | (a[2].x | a[2].y) | (a[3].x | a[3].y)) | ((a[4].x | a[4].y) | (a[5].x | a[5].y)) | ((a[6].x | a[6].y) | (a[7].x | a[7].y)))
#define POK(a) (((tag ? PAND(a) : ~POR(a)) & 1u) != 0)
      if (D_RED) DELAY(D_RED);
      while (true) { PLOAD(a); if (POK(a)) break; if (D_PUB) DELAY(D_PUB); spin_check(it); }
    }
    RSTAMP(15);
    {
#define AF(i, c) __uint_as_float(a[i].c)
      unsigned u = pack_bf16(((AF(0, x) + AF(1, x)) + (AF(2, x) + AF(3, x))) + ((AF(4, x) + AF(5, x)) + (AF(6, x) + AF(7, x))),
                             ((AF(0, y) + AF(1, y)) + (AF(2, y) + AF(3, y))) + ((AF(4, y) + AF(5, y)) + (AF(6, y) + AF(7, y))));
      __syncwarp();
#pragma unroll
      for (int i = 0; i < 8; i++) st_async_b32(mbA[i] + dlt, u, mbA[i]);
    }
    mbar_wait(bar + 8 * MB_KVF, par);
    mbar_wait(bar + 8 * MB_AG, par);
    if (t == 128) mbar_expect_tx(bar + 8 * MB_AG, 8192);
  }
}

__device__ __forceinline__ void rec_ring(const Maps& maps, unsigned sb) {
  const int c = blockIdx.x, h = c >> 1, j = c & 1;
  const unsigned bar = sb + SM_BAR;
  const int lane = threadIdx.x & 31;
  if (lane == 0) {
    mbar_expect_tx(bar + 8 * MB_W0, 131072);
    for (int kb = 0; kb < 8; kb++) tma_load_2d(sb + R_WO + kb * 8192, &maps.wq, h * 128 + j * 64, kb * 64, bar + 8 * MB_W0);
    for (int kb = 0; kb < 8; kb++) tma_load_2d(sb + R_T1 + kb * 8192, &maps.wk, h * 128 + j * 64, kb * 64, bar + 8 * MB_W0);
    mbar_expect_tx(bar + 8 * MB_W1, 65536);
    for (int kb = 0; kb < 8; kb++) tma_load_2d(sb + R_T2 + kb * 8192, &maps.wv, h * 128 + j * 64, kb * 64, bar + 8 * MB_W1);
  }
  __syncwarp();
  bar_sync(2, 288);
  if (lane == 0) {
    fence_proxy_async_smem();
    for (int s = 0; s < NSEG; s++) {
      unsigned slot = s & (RING_N - 1);
      if ((s & 3) == 0 && !DBGMODE) {
        wait_flag_ge(&g_flags.qkv[(s >> 2) * 48 + 16 + (h >> 1)], 1);
        wait_flag_ge(&g_flags.qkv[(s >> 2) * 48 + 32 + (h >> 1)], 1);
        fence_proxy_async();
      }
      if (s >= RING_N) mbar_wait_sleep(bar + 8 * (MB_EMPTY + slot), ((s / RING_N) - 1) & 1);
      unsigned dst = sb + R_RING + slot * RING_BYTES, mb = bar + 8 * (MB_FULL + slot);
      mbar_expect_tx(mb, RING_BYTES);
      tma_load_2d(dst, &maps.qkv_ld, HD + h * 128 + j * 64, s * SEG, mb);
      tma_load_2d(dst + 4096, &maps.qkv_ld, 2 * HD + h * 128, s * SEG, mb);
      tma_load_2d(dst + 8192, &maps.qkv_ld, 2 * HD + h * 128 + 64, s * SEG, mb);
    }
  }
}
__device__ __forceinline__ void rec_copy(unsigned sb) {
  const int c = blockIdx.x, h = c >> 1, j = c & 1;
  const unsigned bar = sb + SM_BAR;
  const int lane = threadIdx.x & 31;
  for (int s = 0; s < NSEG; s++) {
    mbar_wait_sleep(bar + 8 * MB_KVR, s & 1);
    uint4 k0 = lds128(sb + R_KS + (lane >> 3) * 144 + (lane & 7) * 16), k1 = lds128(sb + R_KS + (4 + (lane >> 3)) * 144 + (lane & 7) * 16);
    uint2 v[4];
#pragma unroll
    for (int i = 0; i < 4; i++) v[i] = lds64(sb + R_VM + (j * 4 + i) * 256 + lane * 8);
    __syncwarp();
    if (lane == 0) mbar_arrive(bar + 8 * MB_KVF);
    bf16* kd = g_km + ((size_t)(s * NH + h) * NMEM) * DH + j * 64;
    *reinterpret_cast<uint4*>(kd + (lane >> 3) * DH + (lane & 7) * 8) = k0;
    *reinterpret_cast<uint4*>(kd + (4 + (lane >> 3)) * DH + (lane & 7) * 8) = k1;
    unsigned* vd = reinterpret_cast<unsigned*>(g_vmt) + ((size_t)(s * NH + h) * DH + j * 64) * 4;
#pragma unroll
    for (int i = 0; i < 4; i++) { vd[(i * 16) * 4 + lane] = v[i].x; vd[(i * 16 + 8) * 4 + lane] = v[i].y; }
    __syncwarp();
    if (lane == 0) st_release(&g_flags.rec[c], s + 1);
  }
}

__device__ __forceinline__ void bulk_producer(const Maps& maps, unsigned sb, int* misc) {
  const unsigned bar = sb + SM_BAR;
  const int lane = threadIdx.x & 31;
  unsigned st = 0, ph = 0, seq = 0;
  while (true) {
    int idx = 0;
    if (lane == 0) idx = (int)atomicAdd(&g_flags.ctr, 1u);
    idx = __shfl_sync(~0u, idx, 0);
    if (idx >= N_ITEMS) {
      if (lane == 0) {
        mbar_wait(bar + 8 * (MB_EMPTY + st), ph ^ 1);
        misc[seq & 3] = -1;
        mbar_arrive(bar + 8 * (MB_FULL + st));
      }
      break;
    }
    if (lane == 0) ISTAMP(idx, 0);
    Item it = decode_item(idx);
    if (it.b < 0) continue;
    const CUtensorMap* mp; int c0, c1, dc0, dc1; unsigned doff;
    const unsigned* fl = nullptr; unsigned tgt = 1; int nbox = 5, rdy = 0;
    if (it.type == T_ATT) {
      mp = &maps.qkv_ld; nbox = 12; doff = lane * 4096;
      c0 = (lane >> 2) * HD + it.c * 256 + (lane & 1) * 64; c1 = it.b * 128 + ((lane >> 1) & 1) * 32; dc0 = dc1 = 0;
      if (lane < 3) fl = &g_flags.qkv[it.b * 48 + lane * 16 + it.c];
      bool ok = true;
      if (lane >= 4 && lane < 8) ok = ld_acquire(&g_flags.rec[it.c * 4 + lane - 4]) >= (unsigned)(it.b * 4 + 4);
      rdy = __all_sync(~0u, ok) ? 65536 : 0;
    } else {
      int k0 = 0, nb0 = it.c * 256;
      if (it.type == T_QKV) { mp = lane == 0 ? &maps.xn : (it.c < 16 ? &maps.wq : (it.c < 32 ? &maps.wk : &maps.wv)); nb0 = (it.c & 15) * 256; }
      else if (it.type == T_M1) mp = lane == 0 ? &maps.y : &maps.w1;
      else if (it.type == T_M2) { mp = lane == 0 ? &maps.h1 : &maps.w2; fl = &g_flags.h1[it.b]; tgt = 7; }
      else {
        mp = lane == 0 ? &maps.o : &maps.wo;
        if (it.type == T_OUT) { k0 = it.ks * 1024; fl = &g_flags.o[it.b * 4 + it.ks]; tgt = 4; }
        else if (it.type == T_OUTL) { k0 = it.ks * 256; fl = &g_flags.o16[it.ks]; }
        else if (lane == 1) { fl = &g_flags.g[it.b]; tgt = 2; }
        else { fl = &g_flags.p[it.b]; tgt = it.type == T_RED ? 8 : 32; }
      }
      if (lane > (it.type >= T_RED ? 1 : 0)) fl = nullptr;
      if (lane == 0) { c0 = k0; c1 = it.b * 128; dc0 = 64; dc1 = 0; doff = 0; }
      else { c0 = nb0 + (lane - 1) * 64; c1 = k0; dc0 = 0; dc1 = 64; doff = 8192 + lane * 8192; }
    }
    if (fl) wait_flag_ge(fl, tgt);
    __syncwarp();
    fence_proxy_async();
    if (lane == 0) ISTAMP(idx, 1);
    const int nkb = item_nkb(it.type);
    for (int kb = 0; kb < nkb; kb++) {
      const unsigned mb = bar + 8 * (MB_FULL + st);
      mbar_wait(bar + 8 * (MB_EMPTY + st), ph ^ 1);
      if (lane == 0) {
        if (kb == 0) misc[seq & 3] = idx | rdy;
        if (it.type >= T_RED) mbar_arrive(mb); else mbar_expect_tx(mb, STAGE_BYTES);
      }
      if (it.type == T_ATT) { if (lane < 12) tma_load_2d(sb + st * STAGE_BYTES + doff, mp, c0 + (kb & 1) * 128, c1 + (kb >> 1) * 64, mb); }
      else if (lane < nbox && it.type < T_RED) tma_load_2d(sb + st * STAGE_BYTES + doff, mp, c0 + kb * dc0, c1 + kb * dc1, mb);
      __syncwarp();
      if (++st == NSTAGE) { st = 0; ph ^= 1; }
    }
    seq++;
  }
}
__device__ __forceinline__ void bulk_store(const Maps& maps, unsigned sb, volatile int* misc) {
  const unsigned bar = sb + SM_BAR;
  unsigned ph = 0;
  while (true) {
    mbar_wait(bar + 8 * MB_STGF, ph); ph ^= 1;
    int idx = misc[4];
    if (idx < 0) break;
    Item it = decode_item(idx);
    const CUtensorMap* mp = it.type == T_QKV ? &maps.qkv_st : (it.type == T_M1 ? &maps.h1 : (it.type == T_M2 ? &maps.g : &maps.o));
    unsigned* flag = it.type == T_QKV ? &g_flags.qkv[it.b * 48 + it.c] : (it.type == T_M1 ? &g_flags.h1[it.b] : (it.type == T_M2 ? &g_flags.g[it.b] : (it.b == 15 ? &g_flags.o16[it.c] : &g_flags.o[it.b * 4 + (it.c >> 2)])));
    for (int i = 0; i < 4; i++) tma_store_2d(mp, sb + B_STG + i * 16384, it.c * 256 + i * 64, it.b * 128);
    asm volatile("cp.async.bulk.commit_group;" ::: "memory");
    asm volatile("cp.async.bulk.wait_group.read 0;" ::: "memory");
    mbar_arrive(bar + 8 * MB_STGE);
    asm volatile("cp.async.bulk.wait_group 0;" ::: "memory");
    fence_proxy_async();
    red_release_add(flag, 1);
    ISTAMP(idx, 3);
  }
}
__device__ __forceinline__ float rcpf(float x) { float y; asm("rcp.approx.ftz.f32 %0, %1;" : "=f"(y) : "f"(x)); return y; }
__device__ __forceinline__ float gelu_t(float x) {
  float e = ex2f(x * fmaf(x * x, -2.0f * LOG2E * 0.7978845608028654f * 0.044715f, -2.0f * LOG2E * 0.7978845608028654f));
  return x * rcpf(1.0f + e);
}
__device__ __forceinline__ float silu_f(float x) { return x * rcpf(1.0f + ex2f(-LOG2E * x)); }
__device__ __forceinline__ unsigned badd2(unsigned a, unsigned b) { unsigned r; asm("add.rn.bf16x2 %0, %1, %2;" : "=r"(r) : "r"(a), "r"(b)); return r; }

__device__ __forceinline__ void final_out(bf16* __restrict__ out, const bf16* __restrict__ x, size_t o, float4 s) {
  uint2 gv = __ldcg(reinterpret_cast<const uint2*>(g_g + o)), xv = __ldg(reinterpret_cast<const uint2*>(x + o));
  uint2 r;
  r.x = pack_bf16(bf_lo(xv.x) + bf16r(bf16r(s.x) * bf_lo(gv.x)), bf_hi(xv.x) + bf16r(bf16r(s.y) * bf_hi(gv.x)));
  r.y = pack_bf16(bf_lo(xv.y) + bf16r(bf16r(s.z) * bf_lo(gv.y)), bf_hi(xv.y) + bf16r(bf16r(s.w) * bf_hi(gv.y)));
  *reinterpret_cast<uint2*>(out + o) = r;
}
__device__ __forceinline__ void bulk_att_load(unsigned* km, unsigned* vm, int b, int hp, int kb, int w, int lane) {
  const int g = lane >> 2, tq = lane & 3, seg = w >> 2, eh = w & 1;
  const int head = hp * 2 + (kb & 1), sg = b * 4 + (kb >> 1) * 2 + seg;
  const unsigned* kmp = reinterpret_cast<const unsigned*>(g_km + ((size_t)(sg * NH + head) * NMEM + g) * DH) + tq;
  const unsigned* vmp = reinterpret_cast<const unsigned*>(g_vmt) + ((size_t)(sg * NH + head) * DH + eh * 64) * 4 + lane;
#pragma unroll
  for (int i = 0; i < 16; i++) asm volatile("ld.global.cg.u32 %0, [%1];" : "=r"(km[i]) : "l"(kmp + i * 4) : "memory");
#pragma unroll
  for (int i = 0; i < 8; i++) asm volatile("ld.global.cg.u32 %0, [%1];" : "=r"(vm[i]) : "l"(vmp + i * 32) : "memory");
}
__device__ __forceinline__ void bulk_att_stage(unsigned sa, unsigned stg, const unsigned* km, const unsigned* vm, int kb, int w, int lane) {
  const int g = lane >> 2, tq = lane & 3, m = lane >> 3, r8 = lane & 7;
  const int seg = w >> 2, mt = (w >> 1) & 1, eh = w & 1;
  float s[5][4];
#pragma unroll
  for (int i = 0; i < 5; i++) { s[i][0] = s[i][1] = s[i][2] = s[i][3] = 0; }
  const unsigned qb = sa + (0 * 2 + seg) * 8192, kbs = sa + (1 * 2 + seg) * 8192, vb = sa + (2 * 2 + seg) * 8192 + eh * 4096;
  unsigned qa[8][4];
#pragma unroll
  for (int ks = 0; ks < 8; ks++) {
    int row = mt * 16 + (m & 1) * 8 + r8;
    ldsm_x4(qa[ks], qb + (ks >> 2) * 4096 + row * 128 + ((((ks & 3) * 2 + (m >> 1)) ^ r8) << 4));
    unsigned kf[4];
    int krow = (m >> 1) * 8 + r8;
    unsigned ka = kbs + (ks >> 2) * 4096 + krow * 128 + ((((ks & 3) * 2 + (m & 1)) ^ r8) << 4);
    ldsm_x4(kf, ka);
    mma16816(s[0], qa[ks], kf[0], kf[1]); mma16816(s[1], qa[ks], kf[2], kf[3]);
    if (mt) { ldsm_x4(kf, ka + 2048); mma16816(s[2], qa[ks], kf[0], kf[1]); mma16816(s[3], qa[ks], kf[2], kf[3]); }
  }
#pragma unroll
  for (int ks = 0; ks < 8; ks++) mma16816(s[4], qa[ks], km[2 * ks], km[2 * ks + 1]);
  float mx0 = -INFINITY, mx1 = -INFINITY;
  const int t0 = mt * 16 + g, t1 = t0 + 8;
#pragma unroll
  for (int i = 0; i < 5; i++) {
#pragma unroll
    for (int e = 0; e < 4; e++) {
      float v = s[i][e];
      if (i < 4) { int kj = i * 8 + 2 * tq + (e & 1); if (kj > (e < 2 ? t0 : t1)) v = -INFINITY; }
      s[i][e] = v;
      if (e < 2) mx0 = fmaxf(mx0, v); else mx1 = fmaxf(mx1, v);
    }
  }
  mx0 = fmaxf(mx0, __shfl_xor_sync(~0u, mx0, 1)); mx0 = fmaxf(mx0, __shfl_xor_sync(~0u, mx0, 2));
  mx1 = fmaxf(mx1, __shfl_xor_sync(~0u, mx1, 1)); mx1 = fmaxf(mx1, __shfl_xor_sync(~0u, mx1, 2));
  float sm0 = 0, sm1 = 0;
#pragma unroll
  for (int i = 0; i < 5; i++) {
    s[i][0] = ex2f((s[i][0] - mx0) * (SCALE_QK * LOG2E)); s[i][1] = ex2f((s[i][1] - mx0) * (SCALE_QK * LOG2E));
    s[i][2] = ex2f((s[i][2] - mx1) * (SCALE_QK * LOG2E)); s[i][3] = ex2f((s[i][3] - mx1) * (SCALE_QK * LOG2E));
    sm0 += s[i][0] + s[i][1]; sm1 += s[i][2] + s[i][3];
  }
  sm0 += __shfl_xor_sync(~0u, sm0, 1); sm0 += __shfl_xor_sync(~0u, sm0, 2);
  sm1 += __shfl_xor_sync(~0u, sm1, 1); sm1 += __shfl_xor_sync(~0u, sm1, 2);
  const float i0 = __fdividef(1.0f, sm0), i1 = __fdividef(1.0f, sm1);
  unsigned pa[2][4], pm0, pm1;
#pragma unroll
  for (int kk = 0; kk < 2; kk++) {
    pa[kk][0] = pack_bf16(s[2 * kk][0] * i0, s[2 * kk][1] * i0); pa[kk][1] = pack_bf16(s[2 * kk][2] * i1, s[2 * kk][3] * i1);
    pa[kk][2] = pack_bf16(s[2 * kk + 1][0] * i0, s[2 * kk + 1][1] * i0); pa[kk][3] = pack_bf16(s[2 * kk + 1][2] * i1, s[2 * kk + 1][3] * i1);
  }
  pm0 = pack_bf16(s[4][0] * i0, s[4][1] * i0); pm1 = pack_bf16(s[4][2] * i1, s[4][3] * i1);
  const int orow = (kb >> 1) * 64 + seg * 32 + mt * 16 + (m & 1) * 8 + r8;
  const unsigned ob = stg + ((kb & 1) * 2 + eh) * 16384 + orow * 128;
#pragma unroll
  for (int cp = 0; cp < 4; cp++) {
    float o0[4] = {0, 0, 0, 0}, o1[4] = {0, 0, 0, 0};
    mma1688(o0, pm0, pm1, vm[2 * cp]); mma1688(o1, pm0, pm1, vm[2 * cp + 1]);
    unsigned vf[4];
    int row = (m & 1) * 8 + r8;
    unsigned va = vb + row * 128 + (((cp * 2 + (m >> 1)) ^ r8) << 4);
    ldsm_x4_t(vf, va);
    mma16816(o0, pa[0], vf[0], vf[1]); mma16816(o1, pa[0], vf[2], vf[3]);
    if (mt) { ldsm_x4_t(vf, va + 2048); mma16816(o0, pa[1], vf[0], vf[1]); mma16816(o1, pa[1], vf[2], vf[3]); }
    stsm_x4(ob + (((cp * 2 + (m >> 1)) ^ r8) << 4), pack_bf16(o0[0], o0[1]), pack_bf16(o0[2], o0[3]), pack_bf16(o1[0], o1[1]), pack_bf16(o1[2], o1[3]));
  }
}

__device__ __forceinline__ void bulk_worker(unsigned sb, volatile int* misc, const bf16* __restrict__ x, const bf16* __restrict__ b1, const bf16* __restrict__ b2, bf16* __restrict__ out) {
  const int t = threadIdx.x, lane = t & 31, w = t >> 5, wg = w >> 2, g = lane >> 2, tq = lane & 3, m = lane >> 3, r8 = lane & 7;
  const unsigned bar = sb + SM_BAR;
  unsigned st = 0, ph = 0, seq = 0, sph = 0;
  float d[128];
  while (true) {
    mbar_wait(bar + 8 * (MB_FULL + st), ph);
    const int idr = misc[seq & 3]; seq++;
    const int idx = idr & 65535;
    if (idr < 0 || idx >= N_ITEMS) break;
    if (t == 0) ISTAMP(idx, 2);
    const Item it = decode_item(idx);
    const int nkb = item_nkb(it.type);
    if (it.type == T_ATT) {
      unsigned km[16], vm[8], kn[16], vn[8];
      const bool pref = idr >= 65536;
      if (pref) bulk_att_load(kn, vn, it.b, it.c, 0, w, lane);
      mbar_wait(bar + 8 * MB_STGE, sph ^ 1);
#pragma unroll 1
      for (int kb = 0; kb < 4; kb++) {
        if (!pref) {
          if (lane < 2) wait_flag_ge(&g_flags.rec[it.c * 4 + (kb & 1) * 2 + lane], it.b * 4 + (kb >> 1) * 2 + wg + 1);
          __syncwarp();
          bulk_att_load(kn, vn, it.b, it.c, kb, w, lane);
        }
        if (kb) mbar_wait(bar + 8 * (MB_FULL + st), ph);
#pragma unroll
        for (int i = 0; i < 16; i++) km[i] = kn[i];
#pragma unroll
        for (int i = 0; i < 8; i++) vm[i] = vn[i];
        if (pref && kb != 3) bulk_att_load(kn, vn, it.b, it.c, kb + 1, w, lane);
        bulk_att_stage(sb + st * STAGE_BYTES, sb + B_STG, km, vm, kb, w, lane);
        __syncwarp();
        if (lane == 0) mbar_arrive(bar + 8 * (MB_EMPTY + st));
        if (++st == NSTAGE) { st = 0; ph ^= 1; }
      }
      if (t == 0) misc[4] = idx;
      fence_proxy_async_smem();
      mbar_arrive(bar + 8 * MB_STGF); sph ^= 1;
      continue;
    }
    if (it.type >= T_RED) {
      __syncwarp();
      if (lane == 0) mbar_arrive(bar + 8 * (MB_EMPTY + st));
      if (++st == NSTAGE) { st = 0; ph ^= 1; }
      if (it.type == T_RED) {
#pragma unroll 2
        for (int i = 0; i < 8; i++) {
          size_t o = ((size_t)it.b * 128 + it.c * 16 + i * 2 + (t >> 7)) * DM + (t & 127) * 4;
          float4 a = __ldcg(reinterpret_cast<const float4*>(g_opart + o)), b = __ldcg(reinterpret_cast<const float4*>(g_opart + o + (size_t)S_TOK * DM));
          float4 c = __ldcg(reinterpret_cast<const float4*>(g_opart + o + (size_t)2 * S_TOK * DM)), e = __ldcg(reinterpret_cast<const float4*>(g_opart + o + (size_t)3 * S_TOK * DM));
          final_out(out, x, o, make_float4((a.x + b.x) + (c.x + e.x), (a.y + b.y) + (c.y + e.y), (a.z + b.z) + (c.z + e.z), (a.w + b.w) + (c.w + e.w)));
        }
      } else {
        size_t ol = ((size_t)it.c * 2 + (t >> 7)) * DM + (t & 127) * 4;
        float4 v[16];
#pragma unroll
        for (int i = 0; i < 16; i++) v[i] = __ldcg(reinterpret_cast<const float4*>(g_opl + ol + (size_t)i * 128 * DM));
#pragma unroll
        for (int st2 = 1; st2 < 16; st2 <<= 1)
#pragma unroll
          for (int i = 0; i < 16; i += 2 * st2) { v[i].x += v[i + st2].x; v[i].y += v[i + st2].y; v[i].z += v[i + st2].z; v[i].w += v[i + st2].w; }
        final_out(out, x, ol + (size_t)15 * 128 * DM, v[0]);
      }
      if (t == 0) ISTAMP(idx, 3);
      continue;
    }
    unsigned pst = 0;
    for (int kb = 0; kb < nkb; kb++) {
      if (kb) mbar_wait(bar + 8 * (MB_FULL + st), ph);
      unsigned sa = sb + st * STAGE_BYTES;
      uint64_t ad = mkdesc(sa + wg * 8192, 16, 1024), bd = mkdesc(sa + 16384, 8192, 1024);
      asm volatile("wgmma.fence.sync.aligned;" ::: "memory");
#pragma unroll
      for (int k = 0; k < 4; k++) wgmma_n256(d, ad + k * 2, bd + k * 128, (kb | k) != 0);
      asm volatile("wgmma.commit_group.sync.aligned;" ::: "memory");
      if (kb) {
        asm volatile("wgmma.wait_group.sync.aligned 1;" ::: "memory");
        if (lane == 0) mbar_arrive(bar + 8 * (MB_EMPTY + pst));
      }
      pst = st;
      if (++st == NSTAGE) { st = 0; ph ^= 1; }
    }
    asm volatile("wgmma.wait_group.sync.aligned 0;" ::: "memory");
    if (lane == 0) mbar_arrive(bar + 8 * (MB_EMPTY + pst));
    if (it.type >= T_OUT) {
      const int col = it.c * 256 + 2 * tq;
      float* pp = it.type == T_OUT ? g_opart + ((size_t)it.ks * S_TOK + it.b * 128 + w * 16 + g) * DM + col : g_opl + ((size_t)it.ks * 128 + w * 16 + g) * DM + col;
#pragma unroll
      for (int i = 0; i < 32; i++) {
        __stcg(reinterpret_cast<float2*>(pp + i * 8), make_float2(d[4 * i], d[4 * i + 1]));
        __stcg(reinterpret_cast<float2*>(pp + 8 * DM + i * 8), make_float2(d[4 * i + 2], d[4 * i + 3]));
      }
      bar_sync(1, 256);
      if (t == 0) { red_release_add(&g_flags.p[it.b], 1); ISTAMP(idx, 3); }
      continue;
    }
    if (it.type != T_QKV) {
      const unsigned* bp = reinterpret_cast<const unsigned*>((it.type == T_M1 ? b1 : b2) + it.c * 256) + tq;
#pragma unroll
      for (int i = 0; i < 32; i++) {
        unsigned bv = __ldg(bp + i * 4);
        unsigned u0 = badd2(pack_bf16(d[4 * i], d[4 * i + 1]), bv), u1 = badd2(pack_bf16(d[4 * i + 2], d[4 * i + 3]), bv);
        float x0 = bf_lo(u0), x1 = bf_hi(u0), x2 = bf_lo(u1), x3 = bf_hi(u1);
        if (it.type == T_M1) { d[4 * i] = gelu_t(x0); d[4 * i + 1] = gelu_t(x1); d[4 * i + 2] = gelu_t(x2); d[4 * i + 3] = gelu_t(x3); }
        else { d[4 * i] = silu_f(x0); d[4 * i + 1] = silu_f(x1); d[4 * i + 2] = silu_f(x2); d[4 * i + 3] = silu_f(x3); }
      }
    }
    mbar_wait(bar + 8 * MB_STGE, sph ^ 1);
    {
      const unsigned ob = sb + B_STG + (w * 16 + (m & 1) * 8 + r8) * 128;
#pragma unroll
      for (int i = 0; i < 16; i++)
        stsm_x4(ob + (i >> 2) * 16384 + ((((i & 3) * 2 + (m >> 1)) ^ r8) << 4), pack_bf16(d[8 * i], d[8 * i + 1]), pack_bf16(d[8 * i + 2], d[8 * i + 3]),
                pack_bf16(d[8 * i + 4], d[8 * i + 5]), pack_bf16(d[8 * i + 6], d[8 * i + 7]));
    }
    if (t == 0) misc[4] = idx;
    fence_proxy_async_smem();
    mbar_arrive(bar + 8 * MB_STGF); sph ^= 1;
  }
  mbar_wait(bar + 8 * MB_STGE, sph ^ 1);
  if (t == 0) misc[4] = -1;
  mbar_arrive(bar + 8 * MB_STGF);
}

__global__ void __launch_bounds__(384, 1)
k_main(const __grid_constant__ Maps maps, const bf16* __restrict__ x, const bf16* __restrict__ mem0, const bf16* __restrict__ b1, const bf16* __restrict__ b2, bf16* __restrict__ out, int helper) {
  extern __shared__ unsigned char smem_raw[];
  const unsigned sraw = smem_u32(smem_raw);
  const unsigned sb = (sraw + 1023u) & ~1023u;
  int* misc = reinterpret_cast<int*>(smem_raw + (sb - sraw) + SM_MISC);
  const int w = threadIdx.x >> 5;
  const bool rec = !helper && blockIdx.x < NREC;
  if (!helper) asm volatile("griddepcontrol.launch_dependents;");
  if (threadIdx.x == 0) {
    const unsigned bar = sb + SM_BAR;
    for (int i = 0; i < 8; i++) { mbar_init(bar + 8 * (MB_FULL + i), 1); mbar_init(bar + 8 * (MB_EMPTY + i), rec ? 1 : 8); }
    mbar_init(bar + 8 * MB_STGF, 256); mbar_init(bar + 8 * MB_STGE, 1);
    for (int i = MB_W0; i <= MB_AG; i++) mbar_init(bar + 8 * i, 1);
    if (rec) { mbar_expect_tx(bar + 8 * MB_S, 2560); mbar_expect_tx(bar + 8 * MB_V, 2048); mbar_expect_tx(bar + 8 * MB_RS, 8192); mbar_expect_tx(bar + 8 * MB_AG, 8192); }
    asm volatile("fence.mbarrier_init.release.cluster;" ::: "memory");
  }
  __syncthreads();
  asm volatile("barrier.cluster.arrive.release.aligned;\nbarrier.cluster.wait.acquire.aligned;" ::: "memory");
  if (DBGMODE && !rec) { if (helper) asm volatile("griddepcontrol.wait;" ::: "memory"); return; }
  if (w >= 8) {
    asm volatile("setmaxnreg.dec.sync.aligned.u32 24;");
    if (rec) { if (w == 8) rec_ring(maps, sb); else if (w == 9) rec_copy(sb); }
    else if (w == 8) bulk_producer(maps, sb, misc);
    else if ((threadIdx.x & 31) == 0) { if (w == 9) bulk_store(maps, sb, misc);
      else if (w == 10 && helper) asm volatile("griddepcontrol.wait;" ::: "memory"); }
  } else {
    if (rec) { asm volatile("setmaxnreg.inc.sync.aligned.u32 240;"); rec_worker(maps, sb, mem0); }
    else { asm volatile("setmaxnreg.inc.sync.aligned.u32 240;"); bulk_worker(sb, misc, x, b1, b2, out); }
  }
}

typedef CUresult (*EncFn)(CUtensorMap*, CUtensorMapDataType, cuuint32_t, void*, const cuuint64_t*, const cuuint64_t*, const cuuint32_t*, const cuuint32_t*,
                          CUtensorMapInterleave, CUtensorMapSwizzle, CUtensorMapL2promotion, CUtensorMapFloatOOBfill);
static void mk_map(EncFn enc, CUtensorMap* m, const void* ptr, uint64_t rows, uint64_t cols, uint32_t box_rows) {
  cuuint64_t dims[2] = {cols, rows}; cuuint64_t strides[1] = {cols * 2};
  cuuint32_t box[2] = {64, box_rows}, es[2] = {1, 1};
  enc(m, CU_TENSOR_MAP_DATA_TYPE_BFLOAT16, 2, const_cast<void*>(ptr), dims, strides, box, es, CU_TENSOR_MAP_INTERLEAVE_NONE, CU_TENSOR_MAP_SWIZZLE_128B,
      CU_TENSOR_MAP_L2_PROMOTION_L2_256B, CU_TENSOR_MAP_FLOAT_OOB_FILL_NONE);
}
extern "C" void kernel_launch(void* const* d_in, const int* in_sizes, int n_in, void* d_out, int out_size) {
  static EncFn enc = nullptr;
  static int ncl = 0, nhelp = 0;
  static void *p_xn, *p_y, *p_h1, *p_o, *p_qkv, *p_g;
  if (!enc) {
    void* fn = nullptr; cudaDriverEntryPointQueryResult qr;
    cudaGetDriverEntryPoint("cuTensorMapEncodeTiled", &fn, cudaEnableDefault, &qr);
    enc = (EncFn)fn;
    cudaGetSymbolAddress(&p_xn, g_xn); cudaGetSymbolAddress(&p_y, g_y); cudaGetSymbolAddress(&p_h1, g_h1);
    cudaGetSymbolAddress(&p_o, g_o); cudaGetSymbolAddress(&p_qkv, g_qkv); cudaGetSymbolAddress(&p_g, g_g);
    cudaFuncSetAttribute(k_main, cudaFuncAttributeMaxDynamicSharedMemorySize, SMEM_TOTAL);
    cudaLaunchConfig_t cfg = {}; cfg.gridDim = dim3(128); cfg.blockDim = dim3(384); cfg.dynamicSmemBytes = SMEM_TOTAL;
    cudaLaunchAttribute at[1]; at[0].id = cudaLaunchAttributeClusterDimension; at[0].val.clusterDim.x = CLS; at[0].val.clusterDim.y = 1; at[0].val.clusterDim.z = 1;
    cfg.attrs = at; cfg.numAttrs = 1;
    if (cudaOccupancyMaxActiveClusters(&ncl, k_main, &cfg) != cudaSuccess) { cudaGetLastError(); ncl = 14; }
    ncl = ncl > 16 ? 16 : (ncl < 9 ? 9 : ncl);
    int nsm = 0, dev = 0; cudaGetDevice(&dev); cudaDeviceGetAttribute(&nsm, cudaDevAttrMultiProcessorCount, dev);
    nhelp = nsm - ncl * CLS;
  }
  Maps maps;
  mk_map(enc, &maps.xn, p_xn, S_TOK, DM, 128); mk_map(enc, &maps.y, p_y, S_TOK, DM, 128); mk_map(enc, &maps.h1, p_h1, S_TOK, FF, 128);
  mk_map(enc, &maps.o, p_o, S_TOK, HD, 128); mk_map(enc, &maps.qkv_st, p_qkv, S_TOK, 3 * HD, 128); mk_map(enc, &maps.qkv_ld, p_qkv, S_TOK, 3 * HD, 32);
  mk_map(enc, &maps.g, p_g, S_TOK, DM, 128);
  mk_map(enc, &maps.wq, d_in[2], DM, HD, 64); mk_map(enc, &maps.wk, d_in[3], DM, HD, 64); mk_map(enc, &maps.wv, d_in[4], DM, HD, 64);
  mk_map(enc, &maps.wo, d_in[5], HD, DM, 64); mk_map(enc, &maps.w1, d_in[8], DM, FF, 64); mk_map(enc, &maps.w2, d_in[10], FF, DM, 64);
  cudaStream_t st = cudaStreamPerThread;
  k_pre<<<256, 256, 0, st>>>((const bf16*)d_in[0]);
  cudaLaunchConfig_t cfg = {}; cfg.gridDim = dim3(ncl * CLS); cfg.blockDim = dim3(384); cfg.dynamicSmemBytes = SMEM_TOTAL; cfg.stream = st;
  cudaLaunchAttribute at[1]; at[0].id = cudaLaunchAttributeClusterDimension; at[0].val.clusterDim.x = CLS; at[0].val.clusterDim.y = 1; at[0].val.clusterDim.z = 1;
  cfg.attrs = at; cfg.numAttrs = 1;
  cudaLaunchKernelEx(&cfg, k_main, maps, (const bf16*)d_in[0], (const bf16*)d_in[1], (const bf16*)d_in[9], (const bf16*)d_in[11], (bf16*)d_out, 0);
  if (nhelp > 0) {
    cfg.gridDim = dim3(nhelp);
    at[0].id = cudaLaunchAttributeProgrammaticStreamSerialization; at[0].val.programmaticStreamSerializationAllowed = 1;
    cudaLaunchKernelEx(&cfg, k_main, maps, (const bf16*)d_in[0], (const bf16*)d_in[1], (const bf16*)d_in[9], (const bf16*)d_in[11], (bf16*)d_out, 1);
  }
}
```

```cpp
#include <cuda_runtime.h>
#include <cuda_bf16.h>
#include <cuda.h>
#include <stdint.h>

typedef __nv_bfloat16 bf16;

#define S_TOK 2048
#define DM 512
#define NH 32
#define DH 128
#define HD 4096
#define NMEM 8
#define SEG 32
#define NSEG 64
#define FF 1792
#define NBLK 16
#define NREC 64
#define REPL 0
#define CLS 8

__device__ __align__(1024) bf16 g_xn[S_TOK * DM];
__device__ __align__(1024) bf16 g_y[S_TOK * DM];
__device__ __align__(1024) bf16 g_qkv[(size_t)S_TOK * 3 * HD];
__device__ __align__(1024) bf16 g_h1[S_TOK * FF];
__device__ __align__(1024) bf16 g_g[S_TOK * DM];
__device__ __align__(1024) bf16 g_o[(size_t)S_TOK * HD];
__device__ __align__(1024) bf16 g_km[NSEG * NH * NMEM * DH];
__device__ __align__(1024) bf16 g_vmt[NSEG * NH * DH * NMEM];
__device__ __align__(1024) float g_opart[(size_t)4 * S_TOK * DM];
__device__ __align__(1024) float g_opl[(size_t)16 * 128 * DM];
__device__ __align__(1024) unsigned g_part[8 * 2 * 8 * 8 * 512];
struct Flags {
  unsigned qkv[NBLK * 48];
  unsigned h1[NBLK];
  unsigned g[NBLK];
  unsigned o[NBLK * 4];
  unsigned p[NBLK];
  unsigned o16[16];
  unsigned ctr;
  unsigned rec[NREC];
  unsigned abort_;
};
__device__ __align__(1024) Flags g_flags;

#define RSTAMP(k)
#define DBGMODE 0
#define ISTAMP(i, k)
__device__ __forceinline__ unsigned smem_u32(const void* p) { return (unsigned)__cvta_generic_to_shared(p); }
__device__ __forceinline__ float bf16r(float x) { unsigned u; asm("cvt.rn.bf16x2.f32 %0, %1, %2;" : "=r"(u) : "f"(x), "f"(0.0f)); return __uint_as_float(u); }
__device__ __forceinline__ unsigned pack_bf16(float lo, float hi) {
  __nv_bfloat162 v = __floats2bfloat162_rn(lo, hi);
  return *reinterpret_cast<unsigned*>(&v);
}
__device__ __forceinline__ float bf_lo(unsigned u) { return __uint_as_float(u << 16); }
__device__ __forceinline__ float bf_hi(unsigned u) { return __uint_as_float(u & 0xffff0000u); }

#define SPIN_LIMIT (1u << 20)
#define TRAP_IF(x) if ((x) > SPIN_LIMIT) { asm volatile("st.global.u32 [%0], %1;" ::"l"(0ull), "r"(0u) : "memory"); break; }
__device__ __forceinline__ unsigned ld_acquire(const unsigned* p) {
  unsigned v; asm volatile("ld.acquire.gpu.global.u32 %0, [%1];" : "=r"(v) : "l"(p) : "memory"); return v;
}
__device__ __forceinline__ unsigned ld_relaxed(const unsigned* p) {
  unsigned v; asm volatile("ld.relaxed.gpu.global.u32 %0, [%1];" : "=r"(v) : "l"(p) : "memory"); return v;
}
__device__ __forceinline__ void red_release_add(unsigned* p, unsigned v) {
  asm volatile("red.release.gpu.global.add.u32 [%0], %1;" ::"l"(p), "r"(v) : "memory");
}
__device__ __forceinline__ void st_release(unsigned* p, unsigned v) {
  asm volatile("st.release.gpu.global.u32 [%0], %1;" ::"l"(p), "r"(v) : "memory");
}
__device__ __forceinline__ void wait_flag_ge(const unsigned* p, unsigned target) {
  unsigned it = 0;
  while (ld_acquire(p) < target) {
    __nanosleep(64);
    TRAP_IF(++it);
  }
}
__device__ __forceinline__ uint4 ldv4_relaxed(const void* p) {
  uint4 a; asm volatile("ld.relaxed.gpu.global.v4.u32 {%0,%1,%2,%3}, [%4];" : "=r"(a.x), "=r"(a.y), "=r"(a.z), "=r"(a.w) : "l"(p) : "memory"); return a;
}
__device__ __forceinline__ uint2 ldv2_relaxed(const void* p) {
  uint2 a; asm volatile("ld.relaxed.gpu.global.v2.u32 {%0,%1}, [%2];" : "=r"(a.x), "=r"(a.y) : "l"(p) : "memory"); return a;
}
__device__ __forceinline__ void mbar_init(unsigned mb, unsigned cnt) { asm volatile("mbarrier.init.shared::cta.b64 [%0], %1;" ::"r"(mb), "r"(cnt) : "memory"); }
__device__ __forceinline__ void mbar_expect_tx(unsigned mb, unsigned bytes) { asm volatile("mbarrier.arrive.expect_tx.shared::cta.b64 _, [%0], %1;" ::"r"(mb), "r"(bytes) : "memory"); }
__device__ __forceinline__ void mbar_arrive(unsigned mb) { asm volatile("mbarrier.arrive.shared::cta.b64 _, [%0];" ::"r"(mb) : "memory"); }
__device__ __forceinline__ void mbar_wait(unsigned mb, unsigned parity) {
  unsigned ok, it = 0;
  while (true) {
    asm volatile("{.reg .pred p; mbarrier.try_wait.parity.shared::cta.b64 p, [%1], %2; selp.u32 %0,1,0,p;}" : "=r"(ok) : "r"(mb), "r"(parity) : "memory");
    if (ok) break;
    TRAP_IF(++it);
  }
}
__device__ __forceinline__ void mbar_wait_sleep(unsigned mb, unsigned parity) {
  unsigned ok, it = 0;
  while (true) {
    asm volatile("{.reg .pred p; mbarrier.test_wait.parity.shared::cta.b64 p, [%1], %2; selp.u32 %0,1,0,p;}" : "=r"(ok) : "r"(mb), "r"(parity) : "memory");
    if (ok) break;
    __nanosleep(200);
    TRAP_IF(++it);
  }
}
__device__ __forceinline__ float ex2f(float x) { float y; asm("ex2.approx.ftz.f32 %0, %1;" : "=f"(y) : "f"(x)); return y; }
__device__ __forceinline__ int opaque_tid() { int t = threadIdx.x; t = __shfl_sync(~0u, t, t & 31); return t; }
#define LOG2E 1.4426950408889634f
__device__ __forceinline__ void mbar_wait_cluster(unsigned mb, unsigned parity) {
  unsigned ok, it = 0;
  while (true) {
    asm volatile("{.reg .pred p; mbarrier.try_wait.parity.acquire.cluster.shared::cta.b64 p, [%1], %2; selp.u32 %0,1,0,p;}" : "=r"(ok) : "r"(mb), "r"(parity) : "memory");
    if (ok) break;
    TRAP_IF(++it);
  }
}
__device__ __forceinline__ void bar_sync(int id, int n) { asm volatile("bar.sync %0, %1;" ::"r"(id), "r"(n) : "memory"); }
__device__ __forceinline__ void bar_arrive(int id, int n) { asm volatile("bar.arrive %0, %1;" ::"r"(id), "r"(n) : "memory"); }
__device__ __forceinline__ void tma_load_2d(unsigned dst, const CUtensorMap* map, int c0, int c1, unsigned mb) {
  asm volatile("cp.async.bulk.tensor.2d.shared::cluster.global.mbarrier::complete_tx::bytes [%0], [%1, {%3, %4}], [%2];"
               ::"r"(dst), "l"((uint64_t)map), "r"(mb), "r"(c0), "r"(c1) : "memory");
}
__device__ __forceinline__ void tma_store_2d(const CUtensorMap* map, unsigned src, int c0, int c1) {
  asm volatile("cp.async.bulk.tensor.2d.global.shared::cta.bulk_group [%0, {%2, %3}], [%1];"
               ::"l"((uint64_t)map), "r"(src), "r"(c0), "r"(c1) : "memory");
}
__device__ __forceinline__ void fence_proxy_async() { asm volatile("fence.proxy.async;" ::: "memory"); }
__device__ __forceinline__ void fence_proxy_async_smem() { asm volatile("fence.proxy.async.shared::cta;" ::: "memory"); }
__device__ __forceinline__ void ldsm_x4(unsigned* r, unsigned addr) {
  asm volatile("ldmatrix.sync.aligned.m8n8.x4.shared.b16 {%0,%1,%2,%3}, [%4];" : "=r"(r[0]), "=r"(r[1]), "=r"(r[2]), "=r"(r[3]) : "r"(addr) : "memory");
}
__device__ __forceinline__ void ldsm_x4_t(unsigned* r, unsigned addr) {
  asm volatile("ldmatrix.sync.aligned.m8n8.x4.trans.shared.b16 {%0,%1,%2,%3}, [%4];" : "=r"(r[0]), "=r"(r[1]), "=r"(r[2]), "=r"(r[3]) : "r"(addr) : "memory");
}
__device__ __forceinline__ void stsm_x2_t(unsigned addr, unsigned r0, unsigned r1) {
  asm volatile("stmatrix.sync.aligned.m8n8.x2.trans.shared.b16 [%0], {%1,%2};" ::"r"(addr), "r"(r0), "r"(r1) : "memory");
}
__device__ __forceinline__ void stsm_x4(unsigned addr, unsigned r0, unsigned r1, unsigned r2, unsigned r3) {
  asm volatile("stmatrix.sync.aligned.m8n8.x4.shared.b16 [%0], {%1,%2,%3,%4};" ::"r"(addr), "r"(r0), "r"(r1), "r"(r2), "r"(r3) : "memory");
}
__device__ __forceinline__ void mma16816(float* d, const unsigned* a, unsigned b0, unsigned b1) {
  asm volatile("mma.sync.aligned.m16n8k16.row.col.f32.bf16.bf16.f32 {%0,%1,%2,%3}, {%4,%5,%6,%7}, {%8,%9}, {%0,%1,%2,%3};"
               : "+f"(d[0]), "+f"(d[1]), "+f"(d[2]), "+f"(d[3]) : "r"(a[0]), "r"(a[1]), "r"(a[2]), "r"(a[3]), "r"(b0), "r"(b1));
}
__device__ __forceinline__ void mma1688(float* d, unsigned a0, unsigned a1, unsigned b0) {
  asm volatile("mma.sync.aligned.m16n8k8.row.col.f32.bf16.bf16.f32 {%0,%1,%2,%3}, {%4,%5}, {%6}, {%0,%1,%2,%3};"
               : "+f"(d[0]), "+f"(d[1]), "+f"(d[2]), "+f"(d[3]) : "r"(a0), "r"(a1), "r"(b0));
}
__device__ __forceinline__ uint64_t mkdesc(unsigned addr, unsigned lbo, unsigned sbo) {
  return (uint64_t)((addr >> 4) & 0x3fff) | ((uint64_t)(lbo >> 4) << 16) | ((uint64_t)(sbo >> 4) << 32) | (1ull << 62);
}
#define R8(b) "+f"(d[b]), "+f"(d[b + 1]), "+f"(d[b + 2]), "+f"(d[b + 3]), "+f"(d[b + 4]), "+f"(d[b + 5]), "+f"(d[b + 6]), "+f"(d[b + 7])
#define R32(b) R8(b), R8(b + 8), R8(b + 16), R8(b + 24)
__device__ __forceinline__ void wgmma_n256(float* d, uint64_t ad, uint64_t bd, int acc) {
  asm volatile(
      "{.reg .pred p; setp.ne.b32 p, %130, 0;\n"
      "wgmma.mma_async.sync.aligned.m64n256k16.f32.bf16.bf16 "
      "{%0,%1,%2,%3,%4,%5,%6,%7,%8,%9,%10,%11,%12,%13,%14,%15,%16,%17,%18,%19,%20,%21,%22,%23,%24,%25,%26,%27,%28,%29,%30,%31,"
      "%32,%33,%34,%35,%36,%37,%38,%39,%40,%41,%42,%43,%44,%45,%46,%47,%48,%49,%50,%51,%52,%53,%54,%55,%56,%57,%58,%59,%60,%61,%62,%63,"
      "%64,%65,%66,%67,%68,%69,%70,%71,%72,%73,%74,%75,%76,%77,%78,%79,%80,%81,%82,%83,%84,%85,%86,%87,%88,%89,%90,%91,%92,%93,%94,%95,"
      "%96,%97,%98,%99,%100,%101,%102,%103,%104,%105,%106,%107,%108,%109,%110,%111,%112,%113,%114,%115,%116,%117,%118,%119,%120,%121,%122,%123,%124,%125,%126,%127},"
      "%128, %129, p, 1, 1, 0, 1;}\n"
      : R32(0), R32(32), R32(64), R32(96)
      : "l"(ad), "l"(bd), "r"(acc));
}

__device__ __forceinline__ void ln16(const float* x, float* o) {
  float s = 0;
#pragma unroll
  for (int i = 0; i < 16; i++) s += x[i];
#pragma unroll
  for (int of = 16; of > 0; of >>= 1) s += __shfl_xor_sync(~0u, s, of);
  float mean = s * (1.0f / DM);
  float v = 0;
#pragma unroll
  for (int i = 0; i < 16; i++) { float dd = x[i] - mean; v += dd * dd; }
#pragma unroll
  for (int of = 16; of > 0; of >>= 1) v += __shfl_xor_sync(~0u, v, of);
  float mb = bf16r(mean);
  float vb = bf16r(v * (1.0f / DM));
  float den = bf16r(sqrtf(bf16r(vb + 1e-5f)));
#pragma unroll
  for (int i = 0; i < 16; i++) o[i] = bf16r(__fdiv_rn(bf16r(x[i] - mb), den));
}
__global__ void __launch_bounds__(256) k_pre(const bf16* __restrict__ x) {
  int t = threadIdx.x, lane = t & 31, w = t >> 5;
  int row = blockIdx.x * 8 + w;
  const uint4* src = reinterpret_cast<const uint4*>(x + (size_t)row * DM);
  uint4 a = src[lane], b = src[lane + 32];
  unsigned u[8] = {a.x, a.y, a.z, a.w, b.x, b.y, b.z, b.w};
  float f[16], o[16], o2[16];
#pragma unroll
  for (int i = 0; i < 8; i++) { f[2 * i] = bf_lo(u[i]); f[2 * i + 1] = bf_hi(u[i]); }
  ln16(f, o);
  ln16(o, o2);
  uint4* d1 = reinterpret_cast<uint4*>(g_xn + (size_t)row * DM);
  uint4* d2 = reinterpret_cast<uint4*>(g_y + (size_t)row * DM);
  d1[lane] = make_uint4(pack_bf16(o[0], o[1]), pack_bf16(o[2], o[3]), pack_bf16(o[4], o[5]), pack_bf16(o[6], o[7]));
  d1[lane + 32] = make_uint4(pack_bf16(o[8], o[9]), pack_bf16(o[10], o[11]), pack_bf16(o[12], o[13]), pack_bf16(o[14], o[15]));
  d2[lane] = make_uint4(pack_bf16(o2[0], o2[1]), pack_bf16(o2[2], o2[3]), pack_bf16(o2[4], o2[5]), pack_bf16(o2[6], o2[7]));
  d2[lane + 32] = make_uint4(pack_bf16(o2[8], o2[9]), pack_bf16(o2[10], o2[11]), pack_bf16(o2[12], o2[13]), pack_bf16(o2[14], o2[15]));
  int gt = blockIdx.x * 256 + t;
  uint4 z = make_uint4(0, 0, 0, 0);
  if (gt < 16384) reinterpret_cast<uint4*>(g_part)[gt] = z;
  if (gt < (int)(sizeof(Flags) / 4)) reinterpret_cast<unsigned*>(&g_flags)[gt] = 0;
}

struct Maps { CUtensorMap xn, y, h1, o, qkv_st, qkv_ld, g, wq, wk, wv, wo, w1, w2; };

#define NSTAGE 3
#define STAGE_BYTES 49152
#define B_STG (NSTAGE * STAGE_BYTES)
#define R_WO 0
#define R_T1 65536
#define R_T2 131072
#define R_RING 65536
#define RING_N 4
#define RING_BYTES 12288
#define R_MEM 196608
#define R_QS (R_MEM + 8448)
#define R_KS (R_QS + 1152)
#define R_OS (R_KS + 1152)
#define R_SOWN (R_OS + 2176)
#define R_SPEER (R_SOWN + 1280)
#define R_VM (R_SPEER + 1280)
#define R_VRED (R_VM + 2048)
#define R_RS (R_VRED + 6144)
#define SM_BAR (R_RS + 8192)
#define SMEM_TOTAL (SM_BAR + 256 + 1024)
#define MB_FULL 0
#define MB_EMPTY 8
#define MB_STGF 16
#define MB_STGE 17
#define MB_W0 18
#define MB_W1 19
#define MB_WO 20
#define MB_S 21
#define MB_V 22
#define MB_KVR 23
#define MB_KVF 24
#define MB_RS 25
#define MB_AG 26
#define SM_MISC (SM_BAR + 224)

#define N_KV 512
#define I_M1 512
#define I_Q 624
#define I_M2 880
#define I_POST 912
#define I_TAIL (I_POST + 16 * 32)
#define N_ITEMS (I_TAIL + 5 * 8 + 32 + 8 + 64)
enum { T_QKV = 0, T_M1 = 1, T_M2 = 2, T_ATT = 3, T_OUT = 4, T_OUTL = 5, T_RED = 6, T_REDL = 7 };
struct Item { int type, b, c, ks; };
__device__ __forceinline__ Item decode_item(int i) {
  Item it; it.ks = 0;
  if (i < N_KV) { it.type = T_QKV; it.b = i >> 5; it.c = 16 + (i & 31); }
  else if (i < I_Q) { it.type = T_M1; it.b = (i - I_M1) / 7; it.c = (i - I_M1) % 7; }
  else if (i < I_M2) { it.type = T_QKV; it.b = (i - I_Q) >> 4; it.c = (i - I_Q) & 15; }
  else if (i < I_POST) { it.type = T_M2; it.b = (i - I_M2) >> 1; it.c = (i - I_M2) & 1; }
  else if (i < I_TAIL) {
    int x = i - I_POST, p = x >> 5, r = x & 31;
    if (r < 16) { it.type = T_ATT; it.b = p; it.c = r; }
    else if (r < 24) { it.type = T_OUT; it.b = p - 3; it.c = r & 1; it.ks = (r - 16) >> 1; }
    else { it.type = T_RED; it.b = p - 5; it.c = r - 24; }
  } else {
    int x = i - I_TAIL, r = x & 7;
    if (x < 40) {
      int q = x >> 3;
      if (q == 0 || q == 2) { it.type = T_OUT; it.b = 13 + (q >> 1); it.c = r & 1; it.ks = r >> 1; }
      else { it.type = T_RED; it.b = q == 1 ? 11 : 9 + q; it.c = r; }
    }
    else if (x < 72) { it.type = T_OUTL; it.b = 15; it.c = x & 1; it.ks = (x - 40) >> 1; }
    else if (x < 80) { it.type = T_RED; it.b = 14; it.c = r; }
    else { it.type = T_REDL; it.b = 15; it.c = x - 80; }
  }
  return it;
}
__device__ __forceinline__ int item_nkb(int type) { return type == T_M2 ? 28 : (type == T_OUT ? 16 : (type >= T_RED ? 1 : (type >= T_ATT ? 4 : 8))); }

__device__ __forceinline__ void st_async_b64(unsigned raddr, unsigned lo, unsigned hi, unsigned rmb) {
  asm volatile("st.async.weak.shared::cluster.mbarrier::complete_tx::bytes.v2.b32 [%0], {%1,%2}, [%3];" ::"r"(raddr), "r"(lo), "r"(hi), "r"(rmb) : "memory");
}
__device__ __forceinline__ void st_async_b32(unsigned raddr, unsigned v, unsigned rmb) {
  asm volatile("st.async.weak.shared::cluster.mbarrier::complete_tx::bytes.b32 [%0], %1, [%2];" ::"r"(raddr), "r"(v), "r"(rmb) : "memory");
}
__device__ __forceinline__ unsigned mapa(unsigned a, unsigned rank) {
  unsigned r; asm volatile("mapa.shared::cluster.u32 %0, %1, %2;" : "=r"(r) : "r"(a), "r"(rank)); return r;
}
__device__ __forceinline__ void sts64(unsigned a, unsigned x, unsigned y) { asm volatile("st.shared.v2.b32 [%0], {%1,%2};" ::"r"(a), "r"(x), "r"(y) : "memory"); }
__device__ __forceinline__ void sts128(unsigned a, uint4 v) { asm volatile("st.shared.v4.b32 [%0], {%1,%2,%3,%4};" ::"r"(a), "r"(v.x), "r"(v.y), "r"(v.z), "r"(v.w) : "memory"); }
__device__ __forceinline__ uint2 lds64(unsigned a) { uint2 v; asm volatile("ld.shared.v2.b32 {%0,%1}, [%2];" : "=r"(v.x), "=r"(v.y) : "r"(a) : "memory"); return v; }
__device__ __forceinline__ uint4 lds128(unsigned a) { uint4 v; asm volatile("ld.shared.v4.b32 {%0,%1,%2,%3}, [%4];" : "=r"(v.x), "=r"(v.y), "=r"(v.z), "=r"(v.w) : "r"(a) : "memory"); return v; }
__device__ __forceinline__ float lds32f(unsigned a) { float v; asm volatile("ld.shared.f32 %0, [%1];" : "=f"(v) : "r"(a) : "memory"); return v; }
#define spin_check(it) TRAP_IF(++it)
#define POLLV 0
#define BAR8 0
#define D_STAG 150
#define D_RED 480
#define D_PUB 0
#define DELAY(n) do { unsigned c0_, c1_; asm volatile("mov.u32 %0, %%clock;" : "=r"(c0_)); do { asm volatile("mov.u32 %0, %%clock;" : "=r"(c1_)); } while (c1_ - c0_ < (n)); } while (0)
#define SCALE_QK 0.08838834764831845f

__device__ __forceinline__ void rec_worker(const Maps& maps, unsigned sb, const bf16* __restrict__ mem0) {
  const int c = blockIdx.x, h = c >> 1, j = c & 1;
  const int t = opaque_tid(), lane = t & 31, w = t >> 5, g = lane >> 2, tq = lane & 3;
  const int m = lane >> 3, r8 = lane & 7, kh = w >> 2, et = w & 3;
  const unsigned bar = sb + SM_BAR;
  unsigned wq[16][4], wk[16][4], wo[8][4];
  const unsigned woff = (kh * 4) * 8192 + ((m >> 1) * 8 + r8) * 128 + (((et * 2 + (m & 1)) ^ r8) << 4);
  mbar_wait(bar + 8 * MB_W0, 0);
#pragma unroll
  for (int i = 0; i < 16; i++) {
    ldsm_x4_t(wq[i], sb + R_WO + woff + (i >> 2) * 8192 + (i & 3) * 2048);
    ldsm_x4_t(wk[i], sb + R_T1 + woff + (i >> 2) * 8192 + (i & 3) * 2048);
  }
  bar_sync(2, 288);
  if (t == 0) {
    fence_proxy_async_smem();
    mbar_expect_tx(bar + 8 * MB_WO, 65536);
    for (int kb = 0; kb < 2; kb++)
      for (int cb = 0; cb < 4; cb++) tma_load_2d(sb + R_WO + (kb * 4 + cb) * 8192, &maps.wo, j * 256 + cb * 64, h * 128 + kb * 64, bar + 8 * MB_WO);
  }
  mbar_wait(bar + 8 * MB_W1, 0);
  const unsigned pV = sb + R_T2 + woff;
  const unsigned rk = c & 7, peer = rk ^ 1, cl = c >> 3;
#define KEEP(x) x = __shfl_sync(~0u, x, lane)
  unsigned pA = sb + R_MEM + kh * 4096 + lane * 16;
  unsigned pW0 = sb + R_WO + (w >> 1) * 8192 + ((m >> 1) * 8 + r8) * 128 + ((((w & 1) * 4 + (m & 1)) ^ r8) << 4);
  unsigned pW1 = pW0 ^ 32;
  unsigned pVk = pV;
  unsigned aX = sb + R_VRED + et * 512 + lane * 16;
  unsigned aQKst = sb + (kh ? R_KS : R_QS) + r8 * 144 + (et * 16 + (m & 1) * 8) * 2;
  unsigned aL8 = sb + lane * 8;
  unsigned aSl = mapa(sb + R_SOWN + w * 256 + lane * 8, rk), aSr = mapa(sb + R_SPEER + w * 256 + lane * 8, peer);
  unsigned aVl = mapa(sb + R_VM + (j * 4 + et) * 256 + lane * 8, rk), aVr = mapa(sb + R_VM + (j * 4 + et) * 256 + lane * 8, peer);
  const unsigned mbSl = mapa(bar + 8 * MB_S, rk), mbSr = mapa(bar + 8 * MB_S, peer), mbVl = mbSl + 8, mbVr = mbSr + 8;
  unsigned aQ = sb + R_QS + r8 * 144 + m * 16;
  unsigned oKx = (et * 8 + r8) * 128 + ((m ^ r8) << 4);
  unsigned oVx = 4096 + (et >> 1) * 4096 + ((m >> 1) * 8 + r8) * 128 + ((((et & 1) * 4 + (m & 1)) ^ r8) << 4);
  unsigned aOst = sb + R_OS + r8 * 272 + (et * 32 + m * 8) * 2;
  unsigned aOld = sb + R_OS + r8 * 272 + m * 16;
  unsigned aVm = sb + R_VM + et * 512 + lane * 8;
  unsigned aRSr = mapa(sb + R_RS + (h & 3) * 2048 + (w & 1) * 1024 + lane * 8, j * 4 + (w >> 1));
  unsigned mbRSr = mapa(bar + 8 * MB_RS, j * 4 + (w >> 1));
  unsigned t8 = t * 8;
  KEEP(pA); KEEP(pW0); KEEP(pW1); KEEP(pVk); KEEP(aX); KEEP(aQKst); KEEP(aL8); KEEP(aSl); KEEP(aSr); KEEP(aVl); KEEP(aVr); KEEP(aQ); KEEP(oKx); KEEP(oVx);
  KEEP(aOst); KEEP(aOld); KEEP(aVm); KEEP(aRSr); KEEP(mbRSr); KEEP(t8);
  mbar_wait(bar + 8 * MB_WO, 0);
#pragma unroll
  for (int ks = 0; ks < 4; ks++) { ldsm_x4_t(wo[2 * ks], pW0 + ks * 2048); ldsm_x4_t(wo[2 * ks + 1], pW1 + ks * 2048); }
  {
    unsigned v[8];
#pragma unroll
    for (int q = 0; q < 8; q++) v[q] = __ldg(reinterpret_cast<const unsigned*>(mem0) + q * 256 + t);
    sts128(sb + R_MEM + t * 32, make_uint4(__byte_perm(v[0], v[1], 0x5410), __byte_perm(v[2], v[3], 0x5410), __byte_perm(v[4], v[5], 0x5410), __byte_perm(v[6], v[7], 0x5410)));
    sts128(sb + R_MEM + t * 32 + 16, make_uint4(__byte_perm(v[0], v[1], 0x7632), __byte_perm(v[2], v[3], 0x7632), __byte_perm(v[4], v[5], 0x7632), __byte_perm(v[6], v[7], 0x7632)));
  }
  bar_sync(1, 256);

#pragma unroll 1
  for (int s = 0;; s++) {
    const unsigned par = s & 1;
    const unsigned slot = s & (RING_N - 1), rpar = (s / RING_N) & 1;
    const unsigned ring = sb + R_RING + slot * RING_BYTES;
    RSTAMP(1);
    RSTAMP(2);
    float aq[4] = {0, 0, 0, 0}, ak[4] = {0, 0, 0, 0}, av[4] = {0, 0, 0, 0};
#pragma unroll
    for (int i = 0; i < 8; i++) {
      unsigned b[4], f[4], f0[4];
      ldsm_x4_t(b, pA + i * 512);
      ldsm_x4_t(f0, pVk + (i >> 1) * 8192 + (i & 1) * 4096);
      ldsm_x4_t(f, pVk + (i >> 1) * 8192 + (i & 1) * 4096 + 2048);
      mma16816(aq, wq[2 * i], b[0], b[1]); mma16816(ak, wk[2 * i], b[0], b[1]); mma16816(av, f0, b[0], b[1]);
      mma16816(aq, wq[2 * i + 1], b[2], b[3]); mma16816(ak, wk[2 * i + 1], b[2], b[3]); mma16816(av, f, b[2], b[3]);
    }
    RSTAMP(3);
#define STSF4(a, v) asm volatile("st.shared.v4.f32 [%0], {%1,%2,%3,%4};" ::"r"(a), "f"(v[0]), "f"(v[1]), "f"(v[2]), "f"(v[3]) : "memory")
    unsigned f[8][4];
#define NPRE 2
#define WO_PREFETCH() do { _Pragma("unroll") for (int i = 0; i < NPRE; i++) { ldsm_x4_t(f[2 * i], pW0 + 32768 + i * 2048); ldsm_x4_t(f[2 * i + 1], pW1 + 32768 + i * 2048); } } while (0)
    if (kh) {
      STSF4(aX, aq);
      bar_sync(4 + et, 64);
      uint4 o = lds128(aX + 2048), o2 = lds128(aX + 4096);
      stsm_x2_t(aQKst, pack_bf16(ak[0] + __uint_as_float(o.x), ak[1] + __uint_as_float(o.y)), pack_bf16(ak[2] + __uint_as_float(o.z), ak[3] + __uint_as_float(o.w)));
      bar_arrive(1, 256);
      unsigned x = pack_bf16(av[0] + __uint_as_float(o2.x), av[1] + __uint_as_float(o2.y)), y = pack_bf16(av[2] + __uint_as_float(o2.z), av[3] + __uint_as_float(o2.w));
      st_async_b64(aVr, x, y, mbVr);
      st_async_b64(aVl, x, y, mbVl);
      mbar_wait(bar + 8 * (MB_FULL + slot), rpar);
      unsigned vx[4][4];
      ldsm_x4_t(vx[0], ring + oVx); ldsm_x4_t(vx[1], ring + oVx + 2048); ldsm_x4_t(vx[2], ring + (oVx ^ 32)); ldsm_x4_t(vx[3], ring + (oVx ^ 32) + 2048);
      RSTAMP(4); RSTAMP(5); RSTAMP(6); RSTAMP(7);
      mbar_wait(bar + 8 * MB_S, par);
      RSTAMP(8);
      float sc[10];
#pragma unroll
      for (int i = 0; i < 5; i++) {
        uint2 o = lds64(aL8 + R_SOWN + i * 256), p = lds64(aL8 + R_SPEER + i * 256);
        sc[2 * i] = __uint_as_float(o.x) + __uint_as_float(p.x); sc[2 * i + 1] = __uint_as_float(o.y) + __uint_as_float(p.y);
      }
      mbar_wait(bar + 8 * MB_V, par);
      uint2 vm0 = lds64(aVm), vm1 = lds64(aVm + 256);
      float mx = fmaxf(fmaxf(fmaxf(sc[0], sc[1]), fmaxf(sc[2], sc[3])), fmaxf(fmaxf(fmaxf(sc[4], sc[5]), fmaxf(sc[6], sc[7])), fmaxf(sc[8], sc[9])));
      mx = fmaxf(mx, __shfl_xor_sync(~0u, mx, 1)); mx = fmaxf(mx, __shfl_xor_sync(~0u, mx, 2));
      const float nm = -mx * (SCALE_QK * LOG2E);
#pragma unroll
      for (int i = 0; i < 10; i++) sc[i] = ex2f(fmaf(sc[i], SCALE_QK * LOG2E, nm));
      float sum = (((sc[0] + sc[1]) + (sc[2] + sc[3])) + ((sc[4] + sc[5]) + (sc[6] + sc[7]))) + (sc[8] + sc[9]);
      sum += __shfl_xor_sync(~0u, sum, 1); sum += __shfl_xor_sync(~0u, sum, 2);
      float inv; asm("rcp.approx.ftz.f32 %0, %1;" : "=f"(inv) : "f"(sum));
      unsigned p[5];
#pragma unroll
      for (int i = 0; i < 5; i++) p[i] = pack_bf16(sc[2 * i] * inv, sc[2 * i + 1] * inv);
      RSTAMP(9);
      float o0[4] = {0, 0, 0, 0}, o1[4] = {0, 0, 0, 0}, o3[4] = {0, 0, 0, 0}, o4[4] = {0, 0, 0, 0};
      mma16816(o0, vx[0], p[0], p[1]); mma16816(o3, vx[2], p[0], p[1]); mma16816(o1, vx[1], p[2], p[3]); mma16816(o4, vx[3], p[2], p[3]);
      mma1688(o0, vm0.x, vm0.y, p[4]); mma1688(o3, vm1.x, vm1.y, p[4]);
      if (s == NSEG - 1) { if (t == 128) mbar_arrive(bar + 8 * MB_KVR); break; }
      asm volatile("stmatrix.sync.aligned.m8n8.x4.trans.shared.b16 [%0], {%1,%2,%3,%4};" ::"r"(aOst), "r"(pack_bf16(o0[0] + o1[0], o0[1] + o1[1])), "r"(pack_bf16(o0[2] + o1[2], o0[3] + o1[3])),
                   "r"(pack_bf16(o3[0] + o4[0], o3[1] + o4[1])), "r"(pack_bf16(o3[2] + o4[2], o3[3] + o4[3])) : "memory");
      RSTAMP(10);
      bar_sync(1, 256);
      WO_PREFETCH();
    } else {
      STSF4(aX + 2048, ak); STSF4(aX + 4096, av);
      unsigned kb[8];
      mbar_wait(bar + 8 * (MB_FULL + slot), rpar);
      ldsm_x4(kb, ring + oKx); ldsm_x4(kb + 4, ring + (oKx ^ 64));
      bar_sync(4 + et, 64);
      uint4 o = lds128(aX);
      stsm_x2_t(aQKst, pack_bf16(aq[0] + __uint_as_float(o.x), aq[1] + __uint_as_float(o.y)), pack_bf16(aq[2] + __uint_as_float(o.z), aq[3] + __uint_as_float(o.w)));
      RSTAMP(4);
      bar_sync(1, 256);
      RSTAMP(5);
      unsigned qa[8], km[8];
      ldsm_x4(qa, aQ); ldsm_x4(qa + 4, aQ + 64);
      if (w == 3) { ldsm_x4(km, aQ + 1152); ldsm_x4(km + 4, aQ + 1152 + 64); }
      float s0[4] = {0, 0, 0, 0}, s1[4] = {0, 0, 0, 0};
      unsigned af[4][4];
#pragma unroll
      for (int i = 0; i < 4; i++) { af[i][0] = qa[2 * i]; af[i][1] = 0; af[i][2] = qa[2 * i + 1]; af[i][3] = 0; }
      mma16816(s0, af[0], kb[0], kb[1]); mma16816(s1, af[1], kb[2], kb[3]);
      mma16816(s0, af[2], kb[4], kb[5]); mma16816(s1, af[3], kb[6], kb[7]);
      if (w == 3) {
        float m0[4] = {0, 0, 0, 0}, m1[4] = {0, 0, 0, 0};
        mma16816(m0, af[0], km[0], km[1]); mma16816(m1, af[1], km[2], km[3]);
        mma16816(m0, af[2], km[4], km[5]); mma16816(m1, af[3], km[6], km[7]);
        unsigned x = __float_as_uint(m0[0] + m1[0]), y = __float_as_uint(m0[1] + m1[1]);
        st_async_b64(aSr + 256, x, y, mbSr); st_async_b64(aSl + 256, x, y, mbSl);
      }
      unsigned x = __float_as_uint(s0[0] + s1[0]), y = __float_as_uint(s0[1] + s1[1]);
      st_async_b64(aSr, x, y, mbSr); st_async_b64(aSl, x, y, mbSl);
      RSTAMP(6);
      if (s == NSEG - 1) break;
      WO_PREFETCH();
      RSTAMP(7); RSTAMP(8); RSTAMP(9); RSTAMP(10);
      bar_sync(1, 256);
    }
    RSTAMP(11);
    float d0[4] = {0, 0, 0, 0}, d1[4] = {0, 0, 0, 0}, e0[4] = {0, 0, 0, 0}, e1[4] = {0, 0, 0, 0};
    unsigned ob[4][4];
#pragma unroll
    for (int k2 = 0; k2 < 4; k2++) ldsm_x4(ob[k2], aOld + k2 * 64);
#pragma unroll
    for (int i = NPRE; i < 4; i++) { ldsm_x4_t(f[2 * i], pW0 + 32768 + i * 2048); ldsm_x4_t(f[2 * i + 1], pW1 + 32768 + i * 2048); }
    mma16816(d0, wo[0], ob[0][0], ob[0][1]); mma16816(d1, wo[1], ob[0][0], ob[0][1]);
    mma16816(e0, wo[2], ob[0][2], ob[0][3]); mma16816(e1, wo[3], ob[0][2], ob[0][3]);
    mma16816(d0, wo[4], ob[1][0], ob[1][1]); mma16816(d1, wo[5], ob[1][0], ob[1][1]);
    mma16816(e0, wo[6], ob[1][2], ob[1][3]); mma16816(e1, wo[7], ob[1][2], ob[1][3]);
    mma16816(d0, f[0], ob[2][0], ob[2][1]); mma16816(d1, f[1], ob[2][0], ob[2][1]);
    mma16816(e0, f[2], ob[2][2], ob[2][3]); mma16816(e1, f[3], ob[2][2], ob[2][3]);
    mma16816(d0, f[4], ob[3][0], ob[3][1]); mma16816(d1, f[5], ob[3][0], ob[3][1]);
    mma16816(e0, f[6], ob[3][2], ob[3][3]); mma16816(e1, f[7], ob[3][2], ob[3][3]);
    st_async_b64(aRSr, __float_as_uint(d0[0] + e0[0]), __float_as_uint(d0[1] + e0[1]), mbRSr);
    st_async_b64(aRSr + 256, __float_as_uint(d0[2] + e0[2]), __float_as_uint(d0[3] + e0[3]), mbRSr);
    st_async_b64(aRSr + 512, __float_as_uint(d1[0] + e1[0]), __float_as_uint(d1[1] + e1[1]), mbRSr);
    st_async_b64(aRSr + 768, __float_as_uint(d1[2] + e1[2]), __float_as_uint(d1[3] + e1[3]), mbRSr);
    RSTAMP(12);
    if (t == 128) {
      mbar_arrive(bar + 8 * (MB_EMPTY + slot)); mbar_arrive(bar + 8 * MB_KVR);
      mbar_expect_tx(bar + 8 * MB_S, 2560); mbar_expect_tx(bar + 8 * MB_V, 2048);
    }
    const unsigned tag = ((s >> 1) & 1) ^ 1;
    const char* gp = reinterpret_cast<const char*>(g_part) + (par * 8 + rk) * 16384 + t8;
    unsigned mbA[8];
#pragma unroll
    for (int i = 0; i < 8; i++) mbA[i] = mapa(bar + 8 * MB_AG, i);
    const unsigned dlt = (R_MEM + rk * 1024) - (SM_BAR + 8 * MB_AG) + (t8 >> 1);
    mbar_wait(bar + 8 * MB_RS, par);
    RSTAMP(13);
    uint2 a[8];
    {
      uint2 x0 = lds64(sb + R_RS + t8), x1 = lds64(sb + R_RS + 2048 + t8), x2 = lds64(sb + R_RS + 4096 + t8), x3 = lds64(sb + R_RS + 6144 + t8);
      float r0 = (__uint_as_float(x0.x) + __uint_as_float(x1.x)) + (__uint_as_float(x2.x) + __uint_as_float(x3.x));
      float r1 = (__uint_as_float(x0.y) + __uint_as_float(x1.y)) + (__uint_as_float(x2.y) + __uint_as_float(x3.y));
      a[0].x = (__float_as_uint(r0) & ~1u) | tag; a[0].y = (__float_as_uint(r1) & ~1u) | tag;
      asm volatile("st.relaxed.gpu.global.v2.u32 [%0], {%1,%2};" ::"l"(gp + cl * 2048), "r"(a[0].x), "r"(a[0].y) : "memory");
    }
    RSTAMP(14);
    if (t == 128) mbar_expect_tx(bar + 8 * MB_RS, 8192);
    {
      unsigned it = 0;
#define PLOAD(a) _Pragma("unroll") for (int i = 1; i < 8; i++) a[i] = ldv2_relaxed(gp + (cl ^ i) * 2048)
#define PAND(a) (((a[1].x & a[1].y) & (a[2].x & a[2].y) & (a[3].x & a[3].y)) & ((a[4].x & a[4].y) & (a[5].x & a[5].y)) & ((a[6].x & a[6].y) & (a[7].x & a[7].y)))
#define POR(a) (((a[1].x | a[1].y) | (a[2].x | a[2].y) | (a[3].x | a[3].y)) | ((a[4].x | a[4].y) | (a[5].x | a[5].y)) | ((a[6].x | a[6].y) | (a[7].x | a[7].y)))
#define POK(a) (((tag ? PAND(a) : ~POR(a)) & 1u) != 0)
      if (D_RED) DELAY(D_RED);
      while (true) { PLOAD(a); if (POK(a)) break; if (D_PUB) DELAY(D_PUB); spin_check(it); }
    }
    RSTAMP(15);
    {
#define AF(i, c) __uint_as_float(a[i].c)
      unsigned u = pack_bf16(((AF(0, x) + AF(1, x)) + (AF(2, x) + AF(3, x))) + ((AF(4, x) + AF(5, x)) + (AF(6, x) + AF(7, x))),
                             ((AF(0, y) + AF(1, y)) + (AF(2, y) + AF(3, y))) + ((AF(4, y) + AF(5, y)) + (AF(6, y) + AF(7, y))));
      __syncwarp();
#pragma unroll
      for (int i = 0; i < 8; i++) st_async_b32(mbA[i] + dlt, u, mbA[i]);
    }
    mbar_wait(bar + 8 * MB_KVF, par);
    mbar_wait(bar + 8 * MB_AG, par);
    if (t == 128) mbar_expect_tx(bar + 8 * MB_AG, 8192);
  }
}

__device__ __forceinline__ void rec_ring(const Maps& maps, unsigned sb) {
  const int c = blockIdx.x, h = c >> 1, j = c & 1;
  const unsigned bar = sb + SM_BAR;
  const int lane = threadIdx.x & 31;
  if (lane == 0) {
    mbar_expect_tx(bar + 8 * MB_W0, 131072);
    for (int kb = 0; kb < 8; kb++) tma_load_2d(sb + R_WO + kb * 8192, &maps.wq, h * 128 + j * 64, kb * 64, bar + 8 * MB_W0);
    for (int kb = 0; kb < 8; kb++) tma_load_2d(sb + R_T1 + kb * 8192, &maps.wk, h * 128 + j * 64, kb * 64, bar + 8 * MB_W0);
    mbar_expect_tx(bar + 8 * MB_W1, 65536);
    for (int kb = 0; kb < 8; kb++) tma_load_2d(sb + R_T2 + kb * 8192, &maps.wv, h * 128 + j * 64, kb * 64, bar + 8 * MB_W1);
  }
  __syncwarp();
  bar_sync(2, 288);
  if (lane == 0) {
    fence_proxy_async_smem();
    for (int s = 0; s < NSEG; s++) {
      unsigned slot = s & (RING_N - 1);
      if ((s & 3) == 0 && !DBGMODE) {
        wait_flag_ge(&g_flags.qkv[(s >> 2) * 48 + 16 + (h >> 1)], 1);
        wait_flag_ge(&g_flags.qkv[(s >> 2) * 48 + 32 + (h >> 1)], 1);
        fence_proxy_async();
      }
      if (s >= RING_N) mbar_wait_sleep(bar + 8 * (MB_EMPTY + slot), ((s / RING_N) - 1) & 1);
      unsigned dst = sb + R_RING + slot * RING_BYTES, mb = bar + 8 * (MB_FULL + slot);
      mbar_expect_tx(mb, RING_BYTES);
      tma_load_2d(dst, &maps.qkv_ld, HD + h * 128 + j * 64, s * SEG, mb);
      tma_load_2d(dst + 4096, &maps.qkv_ld, 2 * HD + h * 128, s * SEG, mb);
      tma_load_2d(dst + 8192, &maps.qkv_ld, 2 * HD + h * 128 + 64, s * SEG, mb);
    }
  }
}
__device__ __forceinline__ void rec_copy(unsigned sb) {
  const int c = blockIdx.x, h = c >> 1, j = c & 1;
  const unsigned bar = sb + SM_BAR;
  const int lane = threadIdx.x & 31;
  for (int s = 0; s < NSEG; s++) {
    mbar_wait_sleep(bar + 8 * MB_KVR, s & 1);
    uint4 k0 = lds128(sb + R_KS + (lane >> 3) * 144 + (lane & 7) * 16), k1 = lds128(sb + R_KS + (4 + (lane >> 3)) * 144 + (lane & 7) * 16);
    uint2 v[4];
#pragma unroll
    for (int i = 0; i < 4; i++) v[i] = lds64(sb + R_VM + (j * 4 + i) * 256 + lane * 8);
    __syncwarp();
    if (lane == 0) mbar_arrive(bar + 8 * MB_KVF);
    bf16* kd = g_km + ((size_t)(s * NH + h) * NMEM) * DH + j * 64;
    *reinterpret_cast<uint4*>(kd + (lane >> 3) * DH + (lane & 7) * 8) = k0;
    *reinterpret_cast<uint4*>(kd + (4 + (lane >> 3)) * DH + (lane & 7) * 8) = k1;
    unsigned* vd = reinterpret_cast<unsigned*>(g_vmt) + ((size_t)(s * NH + h) * DH + j * 64) * 4;
#pragma unroll
    for (int i = 0; i < 4; i++) { vd[(i * 16) * 4 + lane] = v[i].x; vd[(i * 16 + 8) * 4 + lane] = v[i].y; }
    __syncwarp();
    if (lane == 0) st_release(&g_flags.rec[c], s + 1);
  }
}

__device__ __forceinline__ void bulk_producer(const Maps& maps, unsigned sb, int* misc) {
  const unsigned bar = sb + SM_BAR;
  const int lane = threadIdx.x & 31;
  unsigned st = 0, ph = 0, seq = 0;
  while (true) {
    int idx = 0;
    if (lane == 0) idx = (int)atomicAdd(&g_flags.ctr, 1u);
    idx = __shfl_sync(~0u, idx, 0);
    if (idx >= N_ITEMS) {
      if (lane == 0) {
        mbar_wait(bar + 8 * (MB_EMPTY + st), ph ^ 1);
        misc[seq & 3] = -1;
        mbar_arrive(bar + 8 * (MB_FULL + st));
      }
      break;
    }
    if (lane == 0) ISTAMP(idx, 0);
    Item it = decode_item(idx);
    if (it.b < 0) continue;
    const CUtensorMap* mp; int c0, c1, dc0, dc1; unsigned doff;
    const unsigned* fl = nullptr; unsigned tgt = 1; int nbox = 5, rdy = 0;
    if (it.type == T_ATT) {
      mp = &maps.qkv_ld; nbox = 12; doff = lane * 4096;
      c0 = (lane >> 2) * HD + it.c * 256 + (lane & 1) * 64; c1 = it.b * 128 + ((lane >> 1) & 1) * 32; dc0 = dc1 = 0;
      if (lane < 3) fl = &g_flags.qkv[it.b * 48 + lane * 16 + it.c];
      bool ok = true;
      if (lane >= 4 && lane < 8) ok = ld_acquire(&g_flags.rec[it.c * 4 + lane - 4]) >= (unsigned)(it.b * 4 + 4);
      rdy = __all_sync(~0u, ok) ? 65536 : 0;
    } else {
      int k0 = 0, nb0 = it.c * 256;
      if (it.type == T_QKV) { mp = lane == 0 ? &maps.xn : (it.c < 16 ? &maps.wq : (it.c < 32 ? &maps.wk : &maps.wv)); nb0 = (it.c & 15) * 256; }
      else if (it.type == T_M1) mp = lane == 0 ? &maps.y : &maps.w1;
      else if (it.type == T_M2) { mp = lane == 0 ? &maps.h1 : &maps.w2; fl = &g_flags.h1[it.b]; tgt = 7; }
      else {
        mp = lane == 0 ? &maps.o : &maps.wo;
        if (it.type == T_OUT) { k0 = it.ks * 1024; fl = &g_flags.o[it.b * 4 + it.ks]; tgt = 4; }
        else if (it.type == T_OUTL) { k0 = it.ks * 256; fl = &g_flags.o16[it.ks]; }
        else if (lane == 1) { fl = &g_flags.g[it.b]; tgt = 2; }
        else { fl = &g_flags.p[it.b]; tgt = it.type == T_RED ? 8 : 32; }
      }
      if (lane > (it.type >= T_RED ? 1 : 0)) fl = nullptr;
      if (lane == 0) { c0 = k0; c1 = it.b * 128; dc0 = 64; dc1 = 0; doff = 0; }
      else { c0 = nb0 + (lane - 1) * 64; c1 = k0; dc0 = 0; dc1 = 64; doff = 8192 + lane * 8192; }
    }
    if (fl) wait_flag_ge(fl, tgt);
    __syncwarp();
    fence_proxy_async();
    if (lane == 0) ISTAMP(idx, 1);
    const int nkb = item_nkb(it.type);
    for (int kb = 0; kb < nkb; kb++) {
      const unsigned mb = bar + 8 * (MB_FULL + st);
      mbar_wait(bar + 8 * (MB_EMPTY + st), ph ^ 1);
      if (lane == 0) {
        if (kb == 0) misc[seq & 3] = idx | rdy;
        if (it.type >= T_RED) mbar_arrive(mb); else mbar_expect_tx(mb, STAGE_BYTES);
      }
      if (it.type == T_ATT) { if (lane < 12) tma_load_2d(sb + st * STAGE_BYTES + doff, mp, c0 + (kb & 1) * 128, c1 + (kb >> 1) * 64, mb); }
      else if (lane < nbox && it.type < T_RED) tma_load_2d(sb + st * STAGE_BYTES + doff, mp, c0 + kb * dc0, c1 + kb * dc1, mb);
      __syncwarp();
      if (++st == NSTAGE) { st = 0; ph ^= 1; }
    }
    seq++;
  }
}
__device__ __forceinline__ void bulk_store(const Maps& maps, unsigned sb, volatile int* misc) {
  const unsigned bar = sb + SM_BAR;
  unsigned ph = 0;
  while (true) {
    mbar_wait(bar + 8 * MB_STGF, ph); ph ^= 1;
    int idx = misc[4];
    if (idx < 0) break;
    Item it = decode_item(idx);
    const CUtensorMap* mp = it.type == T_QKV ? &maps.qkv_st : (it.type == T_M1 ? &maps.h1 : (it.type == T_M2 ? &maps.g : &maps.o));
    unsigned* flag = it.type == T_QKV ? &g_flags.qkv[it.b * 48 + it.c] : (it.type == T_M1 ? &g_flags.h1[it.b] : (it.type == T_M2 ? &g_flags.g[it.b] : (it.b == 15 ? &g_flags.o16[it.c] : &g_flags.o[it.b * 4 + (it.c >> 2)])));
    for (int i = 0; i < 4; i++) tma_store_2d(mp, sb + B_STG + i * 16384, it.c * 256 + i * 64, it.b * 128);
    asm volatile("cp.async.bulk.commit_group;" ::: "memory");
    asm volatile("cp.async.bulk.wait_group.read 0;" ::: "memory");
    mbar_arrive(bar + 8 * MB_STGE);
    asm volatile("cp.async.bulk.wait_group 0;" ::: "memory");
    fence_proxy_async();
    red_release_add(flag, 1);
    ISTAMP(idx, 3);
  }
}
__device__ __forceinline__ float rcpf(float x) { float y; asm("rcp.approx.ftz.f32 %0, %1;" : "=f"(y) : "f"(x)); return y; }
__device__ __forceinline__ float gelu_t(float x) {
  float e = ex2f(x * fmaf(x * x, -2.0f * LOG2E * 0.7978845608028654f * 0.044715f, -2.0f * LOG2E * 0.7978845608028654f));
  return x * rcpf(1.0f + e);
}
__device__ __forceinline__ float silu_f(float x) { return x * rcpf(1.0f + ex2f(-LOG2E * x)); }
__device__ __forceinline__ unsigned badd2(unsigned a, unsigned b) { unsigned r; asm("add.rn.bf16x2 %0, %1, %2;" : "=r"(r) : "r"(a), "r"(b)); return r; }

__device__ __forceinline__ void final_out(bf16* __restrict__ out, const bf16* __restrict__ x, size_t o, float4 s) {
  uint2 gv = __ldcg(reinterpret_cast<const uint2*>(g_g + o)), xv = __ldg(reinterpret_cast<const uint2*>(x + o));
  uint2 r;
  r.x = pack_bf16(bf_lo(xv.x) + bf16r(bf16r(s.x) * bf_lo(gv.x)), bf_hi(xv.x) + bf16r(bf16r(s.y) * bf_hi(gv.x)));
  r.y = pack_bf16(bf_lo(xv.y) + bf16r(bf16r(s.z) * bf_lo(gv.y)), bf_hi(xv.y) + bf16r(bf16r(s.w) * bf_hi(gv.y)));
  *reinterpret_cast<uint2*>(out + o) = r;
}
__device__ __forceinline__ void bulk_att_load(unsigned* km, unsigned* vm, int b, int hp, int kb, int w, int lane) {
  const int g = lane >> 2, tq = lane & 3, seg = w >> 2, eh = w & 1;
  const int head = hp * 2 + (kb & 1), sg = b * 4 + (kb >> 1) * 2 + seg;
  const unsigned* kmp = reinterpret_cast<const unsigned*>(g_km + ((size_t)(sg * NH + head) * NMEM + g) * DH) + tq;
  const unsigned* vmp = reinterpret_cast<const unsigned*>(g_vmt) + ((size_t)(sg * NH + head) * DH + eh * 64) * 4 + lane;
#pragma unroll
  for (int i = 0; i < 16; i++) asm volatile("ld.global.cg.u32 %0, [%1];" : "=r"(km[i]) : "l"(kmp + i * 4) : "memory");
#pragma unroll
  for (int i = 0; i < 8; i++) asm volatile("ld.global.cg.u32 %0, [%1];" : "=r"(vm[i]) : "l"(vmp + i * 32) : "memory");
}
__device__ __forceinline__ void bulk_att_stage(unsigned sa, unsigned stg, const unsigned* km, const unsigned* vm, int kb, int w, int lane) {
  const int g = lane >> 2, tq = lane & 3, m = lane >> 3, r8 = lane & 7;
  const int seg = w >> 2, mt = (w >> 1) & 1, eh = w & 1;
  float s[5][4];
#pragma unroll
  for (int i = 0; i < 5; i++) { s[i][0] = s[i][1] = s[i][2] = s[i][3] = 0; }
  const unsigned qb = sa + (0 * 2 + seg) * 8192, kbs = sa + (1 * 2 + seg) * 8192, vb = sa + (2 * 2 + seg) * 8192 + eh * 4096;
  unsigned qa[8][4];
#pragma unroll
  for (int ks = 0; ks < 8; ks++) {
    int row = mt * 16 + (m & 1) * 8 + r8;
    ldsm_x4(qa[ks], qb + (ks >> 2) * 4096 + row * 128 + ((((ks & 3) * 2 + (m >> 1)) ^ r8) << 4));
    unsigned kf[4];
    int krow = (m >> 1) * 8 + r8;
    unsigned ka = kbs + (ks >> 2) * 4096 + krow * 128 + ((((ks & 3) * 2 + (m & 1)) ^ r8) << 4);
    ldsm_x4(kf, ka);
    mma16816(s[0], qa[ks], kf[0], kf[1]); mma16816(s[1], qa[ks], kf[2], kf[3]);
    if (mt) { ldsm_x4(kf, ka + 2048); mma16816(s[2], qa[ks], kf[0], kf[1]); mma16816(s[3], qa[ks], kf[2], kf[3]); }
  }
#pragma unroll
  for (int ks = 0; ks < 8; ks++) mma16816(s[4], qa[ks], km[2 * ks], km[2 * ks + 1]);
  float mx0 = -INFINITY, mx1 = -INFINITY;
  const int t0 = mt * 16 + g, t1 = t0 + 8;
#pragma unroll
  for (int i = 0; i < 5; i++) {
#pragma unroll
    for (int e = 0; e < 4; e++) {
      float v = s[i][e];
      if (i < 4) { int kj = i * 8 + 2 * tq + (e & 1); if (kj > (e < 2 ? t0 : t1)) v = -INFINITY; }
      s[i][e] = v;
      if (e < 2) mx0 = fmaxf(mx0, v); else mx1 = fmaxf(mx1, v);
    }
  }
  mx0 = fmaxf(mx0, __shfl_xor_sync(~0u, mx0, 1)); mx0 = fmaxf(mx0, __shfl_xor_sync(~0u, mx0, 2));
  mx1 = fmaxf(mx1, __shfl_xor_sync(~0u, mx1, 1)); mx1 = fmaxf(mx1, __shfl_xor_sync(~0u, mx1, 2));
  float sm0 = 0, sm1 = 0;
#pragma unroll
  for (int i = 0; i < 5; i++) {
    s[i][0] = ex2f((s[i][0] - mx0) * (SCALE_QK * LOG2E)); s[i][1] = ex2f((s[i][1] - mx0) * (SCALE_QK * LOG2E));
    s[i][2] = ex2f((s[i][2] - mx1) * (SCALE_QK * LOG2E)); s[i][3] = ex2f((s[i][3] - mx1) * (SCALE_QK * LOG2E));
    sm0 += s[i][0] + s[i][1]; sm1 += s[i][2] + s[i][3];
  }
  sm0 += __shfl_xor_sync(~0u, sm0, 1); sm0 += __shfl_xor_sync(~0u, sm0, 2);
  sm1 += __shfl_xor_sync(~0u, sm1, 1); sm1 += __shfl_xor_sync(~0u, sm1, 2);
  const float i0 = __fdividef(1.0f, sm0), i1 = __fdividef(1.0f, sm1);
  unsigned pa[2][4], pm0, pm1;
#pragma unroll
  for (int kk = 0; kk < 2; kk++) {
    pa[kk][0] = pack_bf16(s[2 * kk][0] * i0, s[2 * kk][1] * i0); pa[kk][1] = pack_bf16(s[2 * kk][2] * i1, s[2 * kk][3] * i1);
    pa[kk][2] = pack_bf16(s[2 * kk + 1][0] * i0, s[2 * kk + 1][1] * i0); pa[kk][3] = pack_bf16(s[2 * kk + 1][2] * i1, s[2 * kk + 1][3] * i1);
  }
  pm0 = pack_bf16(s[4][0] * i0, s[4][1] * i0); pm1 = pack_bf16(s[4][2] * i1, s[4][3] * i1);
  const int orow = (kb >> 1) * 64 + seg * 32 + mt * 16 + (m & 1) * 8 + r8;
  const unsigned ob = stg + ((kb & 1) * 2 + eh) * 16384 + orow * 128;
#pragma unroll
  for (int cp = 0; cp < 4; cp++) {
    float o0[4] = {0, 0, 0, 0}, o1[4] = {0, 0, 0, 0};
    mma1688(o0, pm0, pm1, vm[2 * cp]); mma1688(o1, pm0, pm1, vm[2 * cp + 1]);
    unsigned vf[4];
    int row = (m & 1) * 8 + r8;
    unsigned va = vb + row * 128 + (((cp * 2 + (m >> 1)) ^ r8) << 4);
    ldsm_x4_t(vf, va);
    mma16816(o0, pa[0], vf[0], vf[1]); mma16816(o1, pa[0], vf[2], vf[3]);
    if (mt) { ldsm_x4_t(vf, va + 2048); mma16816(o0, pa[1], vf[0], vf[1]); mma16816(o1, pa[1], vf[2], vf[3]); }
    stsm_x4(ob + (((cp * 2 + (m >> 1)) ^ r8) << 4), pack_bf16(o0[0], o0[1]), pack_bf16(o0[2], o0[3]), pack_bf16(o1[0], o1[1]), pack_bf16(o1[2], o1[3]));
  }
}

__device__ __forceinline__ void bulk_worker(unsigned sb, volatile int* misc, const bf16* __restrict__ x, const bf16* __restrict__ b1, const bf16* __restrict__ b2, bf16* __restrict__ out) {
  const int t = threadIdx.x, lane = t & 31, w = t >> 5, wg = w >> 2, g = lane >> 2, tq = lane & 3, m = lane >> 3, r8 = lane & 7;
  const unsigned bar = sb + SM_BAR;
  unsigned st = 0, ph = 0, seq = 0, sph = 0;
  float d[128];
  while (true) {
    mbar_wait(bar + 8 * (MB_FULL + st), ph);
    const int idr = misc[seq & 3]; seq++;
    const int idx = idr & 65535;
    if (idr < 0 || idx >= N_ITEMS) break;
    if (t == 0) ISTAMP(idx, 2);
    const Item it = decode_item(idx);
    const int nkb = item_nkb(it.type);
    if (it.type == T_ATT) {
      unsigned km[16], vm[8], kn[16], vn[8];
      const bool pref = idr >= 65536;
      if (pref) bulk_att_load(kn, vn, it.b, it.c, 0, w, lane);
      mbar_wait(bar + 8 * MB_STGE, sph ^ 1);
#pragma unroll 1
      for (int kb = 0; kb < 4; kb++) {
        if (!pref) {
          if (lane < 2) wait_flag_ge(&g_flags.rec[it.c * 4 + (kb & 1) * 2 + lane], it.b * 4 + (kb >> 1) * 2 + wg + 1);
          __syncwarp();
          bulk_att_load(kn, vn, it.b, it.c, kb, w, lane);
        }
        if (kb) mbar_wait(bar + 8 * (MB_FULL + st), ph);
#pragma unroll
        for (int i = 0; i < 16; i++) km[i] = kn[i];
#pragma unroll
        for (int i = 0; i < 8; i++) vm[i] = vn[i];
        if (pref && kb != 3) bulk_att_load(kn, vn, it.b, it.c, kb + 1, w, lane);
        bulk_att_stage(sb + st * STAGE_BYTES, sb + B_STG, km, vm, kb, w, lane);
        __syncwarp();
        if (lane == 0) mbar_arrive(bar + 8 * (MB_EMPTY + st));
        if (++st == NSTAGE) { st = 0; ph ^= 1; }
      }
      if (t == 0) misc[4] = idx;
      fence_proxy_async_smem();
      mbar_arrive(bar + 8 * MB_STGF); sph ^= 1;
      continue;
    }
    if (it.type >= T_RED) {
      __syncwarp();
      if (lane == 0) mbar_arrive(bar + 8 * (MB_EMPTY + st));
      if (++st == NSTAGE) { st = 0; ph ^= 1; }
      if (it.type == T_RED) {
#pragma unroll 2
        for (int i = 0; i < 8; i++) {
          size_t o = ((size_t)it.b * 128 + it.c * 16 + i * 2 + (t >> 7)) * DM + (t & 127) * 4;
          float4 a = __ldcg(reinterpret_cast<const float4*>(g_opart + o)), b = __ldcg(reinterpret_cast<const float4*>(g_opart + o + (size_t)S_TOK * DM));
          float4 c = __ldcg(reinterpret_cast<const float4*>(g_opart + o + (size_t)2 * S_TOK * DM)), e = __ldcg(reinterpret_cast<const float4*>(g_opart + o + (size_t)3 * S_TOK * DM));
          final_out(out, x, o, make_float4((a.x + b.x) + (c.x + e.x), (a.y + b.y) + (c.y + e.y), (a.z + b.z) + (c.z + e.z), (a.w + b.w) + (c.w + e.w)));
        }
      } else {
        size_t ol = ((size_t)it.c * 2 + (t >> 7)) * DM + (t & 127) * 4;
        float4 v[16];
#pragma unroll
        for (int i = 0; i < 16; i++) v[i] = __ldcg(reinterpret_cast<const float4*>(g_opl + ol + (size_t)i * 128 * DM));
#pragma unroll
        for (int st2 = 1; st2 < 16; st2 <<= 1)
#pragma unroll
          for (int i = 0; i < 16; i += 2 * st2) { v[i].x += v[i + st2].x; v[i].y += v[i + st2].y; v[i].z += v[i + st2].z; v[i].w += v[i + st2].w; }
        final_out(out, x, ol + (size_t)15 * 128 * DM, v[0]);
      }
      if (t == 0) ISTAMP(idx, 3);
      continue;
    }
    unsigned pst = 0, bv[32];
#pragma unroll
    for (int i = 0; i < 128; i++) d[i] = 0.0f;
    if (it.type == T_M1 || it.type == T_M2) {
      const unsigned* bp = reinterpret_cast<const unsigned*>((it.type == T_M1 ? b1 : b2) + it.c * 256) + tq;
#pragma unroll
      for (int i = 0; i < 32; i++) asm volatile("ld.global.nc.u32 %0, [%1];" : "=r"(bv[i]) : "l"(bp + i * 4));
    } else {
#pragma unroll
      for (int i = 0; i < 32; i++) bv[i] = 0;
    }
    for (int kb = 0; kb < nkb; kb++) {
      if (kb) mbar_wait(bar + 8 * (MB_FULL + st), ph);
      unsigned sa = sb + st * STAGE_BYTES;
      uint64_t ad = mkdesc(sa + wg * 8192, 16, 1024), bd = mkdesc(sa + 16384, 8192, 1024);
      asm volatile("wgmma.fence.sync.aligned;" ::: "memory");
#pragma unroll
      for (int k = 0; k < 4; k++) wgmma_n256(d, ad + k * 2, bd + k * 128, (kb | k) != 0);
      asm volatile("wgmma.commit_group.sync.aligned;" ::: "memory");
      if (kb) {
        asm volatile("wgmma.wait_group.sync.aligned 1;" ::: "memory");
        if (lane == 0) mbar_arrive(bar + 8 * (MB_EMPTY + pst));
      }
      pst = st;
      if (++st == NSTAGE) { st = 0; ph ^= 1; }
    }
    asm volatile("wgmma.wait_group.sync.aligned 0;" ::: "memory");
    if (lane == 0) mbar_arrive(bar + 8 * (MB_EMPTY + pst));
    if (it.type >= T_OUT) {
      const int col = it.c * 256 + 2 * tq;
      float* pp = it.type == T_OUT ? g_opart + ((size_t)it.ks * S_TOK + it.b * 128 + w * 16 + g) * DM + col : g_opl + ((size_t)it.ks * 128 + w * 16 + g) * DM + col;
#pragma unroll
      for (int i = 0; i < 32; i++) {
        __stcg(reinterpret_cast<float2*>(pp + i * 8), make_float2(d[4 * i], d[4 * i + 1]));
        __stcg(reinterpret_cast<float2*>(pp + 8 * DM + i * 8), make_float2(d[4 * i + 2], d[4 * i + 3]));
      }
      bar_sync(1, 256);
      if (t == 0) { red_release_add(&g_flags.p[it.b], 1); ISTAMP(idx, 3); }
      continue;
    }
#define ACT(F) _Pragma("unroll") for (int i = 0; i < 32; i++) { \
        unsigned u0 = badd2(pack_bf16(d[4 * i], d[4 * i + 1]), bv[i]), u1 = badd2(pack_bf16(d[4 * i + 2], d[4 * i + 3]), bv[i]); \
        d[4 * i] = F(bf_lo(u0)); d[4 * i + 1] = F(bf_hi(u0)); d[4 * i + 2] = F(bf_lo(u1)); d[4 * i + 3] = F(bf_hi(u1)); }
    if (it.type == T_M1) { ACT(gelu_t) } else if (it.type == T_M2) { ACT(silu_f) }
    mbar_wait(bar + 8 * MB_STGE, sph ^ 1);
    {
      const unsigned ob = sb + B_STG + (w * 16 + (m & 1) * 8 + r8) * 128;
#pragma unroll
      for (int i = 0; i < 16; i++)
        stsm_x4(ob + (i >> 2) * 16384 + ((((i & 3) * 2 + (m >> 1)) ^ r8) << 4), pack_bf16(d[8 * i], d[8 * i + 1]), pack_bf16(d[8 * i + 2], d[8 * i + 3]),
                pack_bf16(d[8 * i + 4], d[8 * i + 5]), pack_bf16(d[8 * i + 6], d[8 * i + 7]));
    }
    if (t == 0) misc[4] = idx;
    fence_proxy_async_smem();
    mbar_arrive(bar + 8 * MB_STGF); sph ^= 1;
  }
  mbar_wait(bar + 8 * MB_STGE, sph ^ 1);
  if (t == 0) misc[4] = -1;
  mbar_arrive(bar + 8 * MB_STGF);
}

__global__ void __launch_bounds__(384, 1)
k_main(const __grid_constant__ Maps maps, const bf16* __restrict__ x, const bf16* __restrict__ mem0, const bf16* __restrict__ b1, const bf16* __restrict__ b2, bf16* __restrict__ out, int helper) {
  extern __shared__ unsigned char smem_raw[];
  const unsigned sraw = smem_u32(smem_raw);
  const unsigned sb = (sraw + 1023u) & ~1023u;
  int* misc = reinterpret_cast<int*>(smem_raw + (sb - sraw) + SM_MISC);
  const int w = threadIdx.x >> 5;
  const bool rec = !helper && blockIdx.x < NREC;
  if (!helper) asm volatile("griddepcontrol.launch_dependents;");
  if (threadIdx.x == 0) {
    const unsigned bar = sb + SM_BAR;
    for (int i = 0; i < 8; i++) { mbar_init(bar + 8 * (MB_FULL + i), 1); mbar_init(bar + 8 * (MB_EMPTY + i), rec ? 1 : 8); }
    mbar_init(bar + 8 * MB_STGF, 256); mbar_init(bar + 8 * MB_STGE, 1);
    for (int i = MB_W0; i <= MB_AG; i++) mbar_init(bar + 8 * i, 1);
    if (rec) { mbar_expect_tx(bar + 8 * MB_S, 2560); mbar_expect_tx(bar + 8 * MB_V, 2048); mbar_expect_tx(bar + 8 * MB_RS, 8192); mbar_expect_tx(bar + 8 * MB_AG, 8192); }
    asm volatile("fence.mbarrier_init.release.cluster;" ::: "memory");
  }
  __syncthreads();
  asm volatile("barrier.cluster.arrive.release.aligned;\nbarrier.cluster.wait.acquire.aligned;" ::: "memory");
  if (DBGMODE && !rec) { if (helper) asm volatile("griddepcontrol.wait;" ::: "memory"); return; }
  if (w >= 8) {
    asm volatile("setmaxnreg.dec.sync.aligned.u32 24;");
    if (rec) { if (w == 8) rec_ring(maps, sb); else if (w == 9) rec_copy(sb); }
    else if (w == 8) bulk_producer(maps, sb, misc);
    else if ((threadIdx.x & 31) == 0) { if (w == 9) bulk_store(maps, sb, misc);
      else if (w == 10 && helper) asm volatile("griddepcontrol.wait;" ::: "memory"); }
  } else {
    if (rec) { asm volatile("setmaxnreg.inc.sync.aligned.u32 240;"); rec_worker(maps, sb, mem0); }
    else { asm volatile("setmaxnreg.inc.sync.aligned.u32 240;"); bulk_worker(sb, misc, x, b1, b2, out); }
  }
}

typedef CUresult (*EncFn)(CUtensorMap*, CUtensorMapDataType, cuuint32_t, void*, const cuuint64_t*, const cuuint64_t*, const cuuint32_t*, const cuuint32_t*,
                          CUtensorMapInterleave, CUtensorMapSwizzle, CUtensorMapL2promotion, CUtensorMapFloatOOBfill);
static void mk_map(EncFn enc, CUtensorMap* m, const void* ptr, uint64_t rows, uint64_t cols, uint32_t box_rows) {
  cuuint64_t dims[2] = {cols, rows}; cuuint64_t strides[1] = {cols * 2};
  cuuint32_t box[2] = {64, box_rows}, es[2] = {1, 1};
  enc(m, CU_TENSOR_MAP_DATA_TYPE_BFLOAT16, 2, const_cast<void*>(ptr), dims, strides, box, es, CU_TENSOR_MAP_INTERLEAVE_NONE, CU_TENSOR_MAP_SWIZZLE_128B,
      CU_TENSOR_MAP_L2_PROMOTION_L2_256B, CU_TENSOR_MAP_FLOAT_OOB_FILL_NONE);
}
extern "C" void kernel_launch(void* const* d_in, const int* in_sizes, int n_in, void* d_out, int out_size) {
  static EncFn enc = nullptr;
  static int ncl = 0, nhelp = 0;
  static void *p_xn, *p_y, *p_h1, *p_o, *p_qkv, *p_g;
  if (!enc) {
    void* fn = nullptr; cudaDriverEntryPointQueryResult qr;
    cudaGetDriverEntryPoint("cuTensorMapEncodeTiled", &fn, cudaEnableDefault, &qr);
    enc = (EncFn)fn;
    cudaGetSymbolAddress(&p_xn, g_xn); cudaGetSymbolAddress(&p_y, g_y); cudaGetSymbolAddress(&p_h1, g_h1);
    cudaGetSymbolAddress(&p_o, g_o); cudaGetSymbolAddress(&p_qkv, g_qkv); cudaGetSymbolAddress(&p_g, g_g);
    cudaFuncSetAttribute(k_main, cudaFuncAttributeMaxDynamicSharedMemorySize, SMEM_TOTAL);
    cudaLaunchConfig_t cfg = {}; cfg.gridDim = dim3(128); cfg.blockDim = dim3(384); cfg.dynamicSmemBytes = SMEM_TOTAL;
    cudaLaunchAttribute at[1]; at[0].id = cudaLaunchAttributeClusterDimension; at[0].val.clusterDim.x = CLS; at[0].val.clusterDim.y = 1; at[0].val.clusterDim.z = 1;
    cfg.attrs = at; cfg.numAttrs = 1;
    if (cudaOccupancyMaxActiveClusters(&ncl, k_main, &cfg) != cudaSuccess) { cudaGetLastError(); ncl = 14; }
    ncl = ncl > 16 ? 16 : (ncl < 9 ? 9 : ncl);
    int nsm = 0, dev = 0; cudaGetDevice(&dev); cudaDeviceGetAttribute(&nsm, cudaDevAttrMultiProcessorCount, dev);
    nhelp = nsm - ncl * CLS;
  }
  Maps maps;
  mk_map(enc, &maps.xn, p_xn, S_TOK, DM, 128); mk_map(enc, &maps.y, p_y, S_TOK, DM, 128); mk_map(enc, &maps.h1, p_h1, S_TOK, FF, 128);
  mk_map(enc, &maps.o, p_o, S_TOK, HD, 128); mk_map(enc, &maps.qkv_st, p_qkv, S_TOK, 3 * HD, 128); mk_map(enc, &maps.qkv_ld, p_qkv, S_TOK, 3 * HD, 32);
  mk_map(enc, &maps.g, p_g, S_TOK, DM, 128);
  mk_map(enc, &maps.wq, d_in[2], DM, HD, 64); mk_map(enc, &maps.wk, d_in[3], DM, HD, 64); mk_map(enc, &maps.wv, d_in[4], DM, HD, 64);
  mk_map(enc, &maps.wo, d_in[5], HD, DM, 64); mk_map(enc, &maps.w1, d_in[8], DM, FF, 64); mk_map(enc, &maps.w2, d_in[10], FF, DM, 64);
  cudaStream_t st = cudaStreamPerThread;
  k_pre<<<256, 256, 0, st>>>((const bf16*)d_in[0]);
  cudaLaunchConfig_t cfg = {}; cfg.gridDim = dim3(ncl * CLS); cfg.blockDim = dim3(384); cfg.dynamicSmemBytes = SMEM_TOTAL; cfg.stream = st;
  cudaLaunchAttribute at[1]; at[0].id = cudaLaunchAttributeClusterDimension; at[0].val.clusterDim.x = CLS; at[0].val.clusterDim.y = 1; at[0].val.clusterDim.z = 1;
  cfg.attrs = at; cfg.numAttrs = 1;
  cudaLaunchKernelEx(&cfg, k_main, maps, (const bf16*)d_in[0], (const bf16*)d_in[1], (const bf16*)d_in[9], (const bf16*)d_in[11], (bf16*)d_out, 0);
  if (nhelp > 0) {
    cfg.gridDim = dim3(nhelp);
    at[0].id = cudaLaunchAttributeProgrammaticStreamSerialization; at[0].val.programmaticStreamSerializationAllowed = 1;
    cudaLaunchKernelEx(&cfg, k_main, maps, (const bf16*)d_in[0], (const bf16*)d_in[1], (const bf16*)d_in[9], (const bf16*)d_in[11], (bf16*)d_out, 1);
  }
}
```

```cpp
#include <cuda_runtime.h>
#include <cuda_bf16.h>
#include <cuda.h>
#include <stdint.h>

typedef __nv_bfloat16 bf16;

#define S_TOK 2048
#define DM 512
#define NH 32
#define DH 128
#define HD 4096
#define NMEM 8
#define SEG 32
#define NSEG 64
#define FF 1792
#define NBLK 16
#define NREC 64
#define REPL 0
#define CLS 8

__device__ __align__(1024) bf16 g_xn[S_TOK * DM];
__device__ __align__(1024) bf16 g_y[S_TOK * DM];
__device__ __align__(1024) bf16 g_qkv[(size_t)S_TOK * 3 * HD];
__device__ __align__(1024) bf16 g_h1[S_TOK * FF];
__device__ __align__(1024) bf16 g_g[S_TOK * DM];
__device__ __align__(1024) bf16 g_o[(size_t)S_TOK * HD];
__device__ __align__(1024) bf16 g_km[NSEG * NH * NMEM * DH];
__device__ __align__(1024) bf16 g_vmt[NSEG * NH * DH * NMEM];
__device__ __align__(1024) float g_opart[(size_t)4 * S_TOK * DM];
__device__ __align__(1024) float g_opl[(size_t)16 * 128 * DM];
__device__ __align__(1024) unsigned g_part[8 * 2 * 8 * 8 * 512];
struct Flags {
  unsigned qkv[NBLK * 48];
  unsigned h1[NBLK];
  unsigned g[NBLK];
  unsigned o[NBLK * 4];
  unsigned p[NBLK];
  unsigned o16[16];
  unsigned ctr;
  unsigned rec[NREC];
  unsigned abort_;
};
__device__ __align__(1024) Flags g_flags;

#define RSTAMP(k)
#define DBGMODE 0
#define ISTAMP(i, k)
__device__ __forceinline__ unsigned smem_u32(const void* p) { return (unsigned)__cvta_generic_to_shared(p); }
__device__ __forceinline__ float bf16r(float x) { unsigned u; asm("cvt.rn.bf16x2.f32 %0, %1, %2;" : "=r"(u) : "f"(x), "f"(0.0f)); return __uint_as_float(u); }
__device__ __forceinline__ unsigned pack_bf16(float lo, float hi) {
  __nv_bfloat162 v = __floats2bfloat162_rn(lo, hi);
  return *reinterpret_cast<unsigned*>(&v);
}
__device__ __forceinline__ float bf_lo(unsigned u) { return __uint_as_float(u << 16); }
__device__ __forceinline__ float bf_hi(unsigned u) { return __uint_as_float(u & 0xffff0000u); }

#define SPIN_LIMIT (1u << 20)
#define TRAP_IF(x) if ((x) > SPIN_LIMIT) { asm volatile("st.global.u32 [%0], %1;" ::"l"(0ull), "r"(0u) : "memory"); break; }
__device__ __forceinline__ unsigned ld_acquire(const unsigned* p) {
  unsigned v; asm volatile("ld.acquire.gpu.global.u32 %0, [%1];" : "=r"(v) : "l"(p) : "memory"); return v;
}
__device__ __forceinline__ unsigned ld_relaxed(const unsigned* p) {
  unsigned v; asm volatile("ld.relaxed.gpu.global.u32 %0, [%1];" : "=r"(v) : "l"(p) : "memory"); return v;
}
__device__ __forceinline__ void red_release_add(unsigned* p, unsigned v) {
  asm volatile("red.release.gpu.global.add.u32 [%0], %1;" ::"l"(p), "r"(v) : "memory");
}
__device__ __forceinline__ void st_release(unsigned* p, unsigned v) {
  asm volatile("st.release.gpu.global.u32 [%0], %1;" ::"l"(p), "r"(v) : "memory");
}
__device__ __forceinline__ void wait_flag_ge(const unsigned* p, unsigned target) {
  unsigned it = 0;
  while (ld_acquire(p) < target) {
    __nanosleep(64);
    TRAP_IF(++it);
  }
}
__device__ __forceinline__ uint4 ldv4_relaxed(const void* p) {
  uint4 a; asm volatile("ld.relaxed.gpu.global.v4.u32 {%0,%1,%2,%3}, [%4];" : "=r"(a.x), "=r"(a.y), "=r"(a.z), "=r"(a.w) : "l"(p) : "memory"); return a;
}
__device__ __forceinline__ uint2 ldv2_relaxed(const void* p) {
  uint2 a; asm volatile("ld.relaxed.gpu.global.v2.u32 {%0,%1}, [%2];" : "=r"(a.x), "=r"(a.y) : "l"(p) : "memory"); return a;
}
__device__ __forceinline__ void mbar_init(unsigned mb, unsigned cnt) { asm volatile("mbarrier.init.shared::cta.b64 [%0], %1;" ::"r"(mb), "r"(cnt) : "memory"); }
__device__ __forceinline__ void mbar_expect_tx(unsigned mb, unsigned bytes) { asm volatile("mbarrier.arrive.expect_tx.shared::cta.b64 _, [%0], %1;" ::"r"(mb), "r"(bytes) : "memory"); }
__device__ __forceinline__ void mbar_arrive(unsigned mb) { asm volatile("mbarrier.arrive.shared::cta.b64 _, [%0];" ::"r"(mb) : "memory"); }
__device__ __forceinline__ void mbar_wait(unsigned mb, unsigned parity) {
  unsigned ok, it = 0;
  while (true) {
    asm volatile("{.reg .pred p; mbarrier.try_wait.parity.shared::cta.b64 p, [%1], %2; selp.u32 %0,1,0,p;}" : "=r"(ok) : "r"(mb), "r"(parity) : "memory");
    if (ok) break;
    TRAP_IF(++it);
  }
}
__device__ __forceinline__ void mbar_wait_sleep(unsigned mb, unsigned parity) {
  unsigned ok, it = 0;
  while (true) {
    asm volatile("{.reg .pred p; mbarrier.test_wait.parity.shared::cta.b64 p, [%1], %2; selp.u32 %0,1,0,p;}" : "=r"(ok) : "r"(mb), "r"(parity) : "memory");
    if (ok) break;
    __nanosleep(200);
    TRAP_IF(++it);
  }
}
__device__ __forceinline__ float ex2f(float x) { float y; asm("ex2.approx.ftz.f32 %0, %1;" : "=f"(y) : "f"(x)); return y; }
__device__ __forceinline__ int opaque_tid() { int t = threadIdx.x; t = __shfl_sync(~0u, t, t & 31); return t; }
#define LOG2E 1.4426950408889634f
__device__ __forceinline__ void mbar_wait_cluster(unsigned mb, unsigned parity) {
  unsigned ok, it = 0;
  while (true) {
    asm volatile("{.reg .pred p; mbarrier.try_wait.parity.acquire.cluster.shared::cta.b64 p, [%1], %2; selp.u32 %0,1,0,p;}" : "=r"(ok) : "r"(mb), "r"(parity) : "memory");
    if (ok) break;
    TRAP_IF(++it);
  }
}
__device__ __forceinline__ void bar_sync(int id, int n) { asm volatile("bar.sync %0, %1;" ::"r"(id), "r"(n) : "memory"); }
__device__ __forceinline__ void bar_arrive(int id, int n) { asm volatile("bar.arrive %0, %1;" ::"r"(id), "r"(n) : "memory"); }
__device__ __forceinline__ void tma_load_2d(unsigned dst, const CUtensorMap* map, int c0, int c1, unsigned mb) {
  asm volatile("cp.async.bulk.tensor.2d.shared::cluster.global.mbarrier::complete_tx::bytes [%0], [%1, {%3, %4}], [%2];"
               ::"r"(dst), "l"((uint64_t)map), "r"(mb), "r"(c0), "r"(c1) : "memory");
}
__device__ __forceinline__ void tma_store_2d(const CUtensorMap* map, unsigned src, int c0, int c1) {
  asm volatile("cp.async.bulk.tensor.2d.global.shared::cta.bulk_group [%0, {%2, %3}], [%1];"
               ::"l"((uint64_t)map), "r"(src), "r"(c0), "r"(c1) : "memory");
}
__device__ __forceinline__ void fence_proxy_async() { asm volatile("fence.proxy.async;" ::: "memory"); }
__device__ __forceinline__ void fence_proxy_async_smem() { asm volatile("fence.proxy.async.shared::cta;" ::: "memory"); }
__device__ __forceinline__ void ldsm_x4(unsigned* r, unsigned addr) {
  asm volatile("ldmatrix.sync.aligned.m8n8.x4.shared.b16 {%0,%1,%2,%3}, [%4];" : "=r"(r[0]), "=r"(r[1]), "=r"(r[2]), "=r"(r[3]) : "r"(addr) : "memory");
}
__device__ __forceinline__ void ldsm_x4_t(unsigned* r, unsigned addr) {
  asm volatile("ldmatrix.sync.aligned.m8n8.x4.trans.shared.b16 {%0,%1,%2,%3}, [%4];" : "=r"(r[0]), "=r"(r[1]), "=r"(r[2]), "=r"(r[3]) : "r"(addr) : "memory");
}
__device__ __forceinline__ void stsm_x2_t(unsigned addr, unsigned r0, unsigned r1) {
  asm volatile("stmatrix.sync.aligned.m8n8.x2.trans.shared.b16 [%0], {%1,%2};" ::"r"(addr), "r"(r0), "r"(r1) : "memory");
}
__device__ __forceinline__ void stsm_x4(unsigned addr, unsigned r0, unsigned r1, unsigned r2, unsigned r3) {
  asm volatile("stmatrix.sync.aligned.m8n8.x4.shared.b16 [%0], {%1,%2,%3,%4};" ::"r"(addr), "r"(r0), "r"(r1), "r"(r2), "r"(r3) : "memory");
}
__device__ __forceinline__ void mma16816(float* d, const unsigned* a, unsigned b0, unsigned b1) {
  asm volatile("mma.sync.aligned.m16n8k16.row.col.f32.bf16.bf16.f32 {%0,%1,%2,%3}, {%4,%5,%6,%7}, {%8,%9}, {%0,%1,%2,%3};"
               : "+f"(d[0]), "+f"(d[1]), "+f"(d[2]), "+f"(d[3]) : "r"(a[0]), "r"(a[1]), "r"(a[2]), "r"(a[3]), "r"(b0), "r"(b1));
}
__device__ __forceinline__ void mma1688(float* d, unsigned a0, unsigned a1, unsigned b0) {
  asm volatile("mma.sync.aligned.m16n8k8.row.col.f32.bf16.bf16.f32 {%0,%1,%2,%3}, {%4,%5}, {%6}, {%0,%1,%2,%3};"
               : "+f"(d[0]), "+f"(d[1]), "+f"(d[2]), "+f"(d[3]) : "r"(a0), "r"(a1), "r"(b0));
}
__device__ __forceinline__ uint64_t mkdesc(unsigned addr, unsigned lbo, unsigned sbo) {
  return (uint64_t)((addr >> 4) & 0x3fff) | ((uint64_t)(lbo >> 4) << 16) | ((uint64_t)(sbo >> 4) << 32) | (1ull << 62);
}
#define R8(b) "+f"(d[b]), "+f"(d[b + 1]), "+f"(d[b + 2]), "+f"(d[b + 3]), "+f"(d[b + 4]), "+f"(d[b + 5]), "+f"(d[b + 6]), "+f"(d[b + 7])
#define R32(b) R8(b), R8(b + 8), R8(b + 16), R8(b + 24)
__device__ __forceinline__ void wgmma_n256(float* d, uint64_t ad, uint64_t bd, int acc) {
  asm volatile(
      "{.reg .pred p; setp.ne.b32 p, %130, 0;\n"
      "wgmma.mma_async.sync.aligned.m64n256k16.f32.bf16.bf16 "
      "{%0,%1,%2,%3,%4,%5,%6,%7,%8,%9,%10,%11,%12,%13,%14,%15,%16,%17,%18,%19,%20,%21,%22,%23,%24,%25,%26,%27,%28,%29,%30,%31,"
      "%32,%33,%34,%35,%36,%37,%38,%39,%40,%41,%42,%43,%44,%45,%46,%47,%48,%49,%50,%51,%52,%53,%54,%55,%56,%57,%58,%59,%60,%61,%62,%63,"
      "%64,%65,%66,%67,%68,%69,%70,%71,%72,%73,%74,%75,%76,%77,%78,%79,%80,%81,%82,%83,%84,%85,%86,%87,%88,%89,%90,%91,%92,%93,%94,%95,"
      "%96,%97,%98,%99,%100,%101,%102,%103,%104,%105,%106,%107,%108,%109,%110,%111,%112,%113,%114,%115,%116,%117,%118,%119,%120,%121,%122,%123,%124,%125,%126,%127},"
      "%128, %129, p, 1, 1, 0, 1;}\n"
      : R32(0), R32(32), R32(64), R32(96)
      : "l"(ad), "l"(bd), "r"(acc));
}

__device__ __forceinline__ void ln16(const float* x, float* o) {
  float s = 0;
#pragma unroll
  for (int i = 0; i < 16; i++) s += x[i];
#pragma unroll
  for (int of = 16; of > 0; of >>= 1) s += __shfl_xor_sync(~0u, s, of);
  float mean = s * (1.0f / DM);
  float v = 0;
#pragma unroll
  for (int i = 0; i < 16; i++) { float dd = x[i] - mean; v += dd * dd; }
#pragma unroll
  for (int of = 16; of > 0; of >>= 1) v += __shfl_xor_sync(~0u, v, of);
  float mb = bf16r(mean);
  float vb = bf16r(v * (1.0f / DM));
  float den = bf16r(sqrtf(bf16r(vb + 1e-5f)));
#pragma unroll
  for (int i = 0; i < 16; i++) o[i] = bf16r(__fdiv_rn(bf16r(x[i] - mb), den));
}
__global__ void __launch_bounds__(256) k_pre(const bf16* __restrict__ x) {
  int t = threadIdx.x, lane = t & 31, w = t >> 5;
  int row = blockIdx.x * 8 + w;
  const uint4* src = reinterpret_cast<const uint4*>(x + (size_t)row * DM);
  uint4 a = src[lane], b = src[lane + 32];
  unsigned u[8] = {a.x, a.y, a.z, a.w, b.x, b.y, b.z, b.w};
  float f[16], o[16], o2[16];
#pragma unroll
  for (int i = 0; i < 8; i++) { f[2 * i] = bf_lo(u[i]); f[2 * i + 1] = bf_hi(u[i]); }
  ln16(f, o);
  ln16(o, o2);
  uint4* d1 = reinterpret_cast<uint4*>(g_xn + (size_t)row * DM);
  uint4* d2 = reinterpret_cast<uint4*>(g_y + (size_t)row * DM);
  d1[lane] = make_uint4(pack_bf16(o[0], o[1]), pack_bf16(o[2], o[3]), pack_bf16(o[4], o[5]), pack_bf16(o[6], o[7]));
  d1[lane + 32] = make_uint4(pack_bf16(o[8], o[9]), pack_bf16(o[10], o[11]), pack_bf16(o[12], o[13]), pack_bf16(o[14], o[15]));
  d2[lane] = make_uint4(pack_bf16(o2[0], o2[1]), pack_bf16(o2[2], o2[3]), pack_bf16(o2[4], o2[5]), pack_bf16(o2[6], o2[7]));
  d2[lane + 32] = make_uint4(pack_bf16(o2[8], o2[9]), pack_bf16(o2[10], o2[11]), pack_bf16(o2[12], o2[13]), pack_bf16(o2[14], o2[15]));
  int gt = blockIdx.x * 256 + t;
  uint4 z = make_uint4(0, 0, 0, 0);
  if (gt < 16384) reinterpret_cast<uint4*>(g_part)[gt] = z;
  if (gt < (int)(sizeof(Flags) / 4)) reinterpret_cast<unsigned*>(&g_flags)[gt] = 0;
}

struct Maps { CUtensorMap xn, y, h1, o, qkv_st, qkv_ld, g, wq, wk, wv, wo, w1, w2; };

#define NSTAGE 3
#define STAGE_BYTES 49152
#define B_STG (NSTAGE * STAGE_BYTES)
#define R_WO 0
#define R_T1 65536
#define R_T2 131072
#define R_RING 65536
#define RING_N 4
#define RING_BYTES 12288
#define R_MEM 196608
#define R_QS (R_MEM + 8448)
#define R_KS (R_QS + 1152)
#define R_OS (R_KS + 1152)
#define R_SOWN (R_OS + 2176)
#define R_SPEER (R_SOWN + 1280)
#define R_VM (R_SPEER + 1280)
#define R_VRED (R_VM + 2048)
#define R_RS (R_VRED + 6144)
#define SM_BAR (R_RS + 8192)
#define SMEM_TOTAL (SM_BAR + 256 + 1024)
#define MB_FULL 0
#define MB_EMPTY 8
#define MB_STGF 16
#define MB_STGE 17
#define MB_W0 18
#define MB_W1 19
#define MB_WO 20
#define MB_S 21
#define MB_V 22
#define MB_KVR 23
#define MB_KVF 24
#define MB_RS 25
#define MB_AG 26
#define SM_MISC (SM_BAR + 224)

#define N_KV 512
#define I_M1 512
#define I_Q 624
#define I_M2 880
#define I_POST 912
#define I_TAIL (I_POST + 16 * 32)
#define N_ITEMS (I_TAIL + 5 * 8 + 32 + 8 + 64)
enum { T_QKV = 0, T_M1 = 1, T_M2 = 2, T_ATT = 3, T_OUT = 4, T_OUTL = 5, T_RED = 6, T_REDL = 7 };
struct Item { int type, b, c, ks; };
__device__ __forceinline__ Item decode_item(int i) {
  Item it; it.ks = 0;
  if (i < N_KV) { it.type = T_QKV; it.b = i >> 5; it.c = 16 + (i & 31); }
  else if (i < I_Q) { it.type = T_M1; it.b = (i - I_M1) / 7; it.c = (i - I_M1) % 7; }
  else if (i < I_M2) { it.type = T_QKV; it.b = (i - I_Q) >> 4; it.c = (i - I_Q) & 15; }
  else if (i < I_POST) { it.type = T_M2; it.b = (i - I_M2) >> 1; it.c = (i - I_M2) & 1; }
  else if (i < I_TAIL) {
    int x = i - I_POST, p = x >> 5, r = x & 31;
    if (r < 16) { it.type = T_ATT; it.b = p; it.c = r; }
    else if (r < 24) { it.type = T_OUT; it.b = p - 3; it.c = r & 1; it.ks = (r - 16) >> 1; }
    else { it.type = T_RED; it.b = p - 5; it.c = r - 24; }
  } else {
    int x = i - I_TAIL, r = x & 7;
    if (x < 40) {
      int q = x >> 3;
      if (q == 0 || q == 2) { it.type = T_OUT; it.b = 13 + (q >> 1); it.c = r & 1; it.ks = r >> 1; }
      else { it.type = T_RED; it.b = q == 1 ? 11 : 9 + q; it.c = r; }
    }
    else if (x < 72) { it.type = T_OUTL; it.b = 15; it.c = x & 1; it.ks = (x - 40) >> 1; }
    else if (x < 80) { it.type = T_RED; it.b = 14; it.c = r; }
    else { it.type = T_REDL; it.b = 15; it.c = x - 80; }
  }
  return it;
}
__device__ __forceinline__ int item_nkb(int type) { return type == T_M2 ? 28 : (type == T_OUT ? 16 : (type >= T_RED ? 1 : (type >= T_ATT ? 4 : 8))); }

__device__ __forceinline__ void st_async_b64(unsigned raddr, unsigned lo, unsigned hi, unsigned rmb) {
  asm volatile("st.async.weak.shared::cluster.mbarrier::complete_tx::bytes.v2.b32 [%0], {%1,%2}, [%3];" ::"r"(raddr), "r"(lo), "r"(hi), "r"(rmb) : "memory");
}
__device__ __forceinline__ void st_async_b32(unsigned raddr, unsigned v, unsigned rmb) {
  asm volatile("st.async.weak.shared::cluster.mbarrier::complete_tx::bytes.b32 [%0], %1, [%2];" ::"r"(raddr), "r"(v), "r"(rmb) : "memory");
}
__device__ __forceinline__ unsigned mapa(unsigned a, unsigned rank) {
  unsigned r; asm volatile("mapa.shared::cluster.u32 %0, %1, %2;" : "=r"(r) : "r"(a), "r"(rank)); return r;
}
__device__ __forceinline__ void sts64(unsigned a, unsigned x, unsigned y) { asm volatile("st.shared.v2.b32 [%0], {%1,%2};" ::"r"(a), "r"(x), "r"(y) : "memory"); }
__device__ __forceinline__ void sts128(unsigned a, uint4 v) { asm volatile("st.shared.v4.b32 [%0], {%1,%2,%3,%4};" ::"r"(a), "r"(v.x), "r"(v.y), "r"(v.z), "r"(v.w) : "memory"); }
__device__ __forceinline__ uint2 lds64(unsigned a) { uint2 v; asm volatile("ld.shared.v2.b32 {%0,%1}, [%2];" : "=r"(v.x), "=r"(v.y) : "r"(a) : "memory"); return v; }
__device__ __forceinline__ uint4 lds128(unsigned a) { uint4 v; asm volatile("ld.shared.v4.b32 {%0,%1,%2,%3}, [%4];" : "=r"(v.x), "=r"(v.y), "=r"(v.z), "=r"(v.w) : "r"(a) : "memory"); return v; }
__device__ __forceinline__ float lds32f(unsigned a) { float v; asm volatile("ld.shared.f32 %0, [%1];" : "=f"(v) : "r"(a) : "memory"); return v; }
#define spin_check(it) TRAP_IF(++it)
#define POLLV 0
#define BAR8 0
#define D_STAG 150
#define D_RED 480
#define D_PUB 0
#define DELAY(n) do { unsigned c0_, c1_; asm volatile("mov.u32 %0, %%clock;" : "=r"(c0_)); do { asm volatile("mov.u32 %0, %%clock;" : "=r"(c1_)); } while (c1_ - c0_ < (n)); } while (0)
#define NPRE1 0
#define SCALE_QK 0.08838834764831845f

__device__ __forceinline__ void rec_worker(const Maps& maps, unsigned sb, const bf16* __restrict__ mem0) {
  const int c = blockIdx.x, h = c >> 1, j = c & 1;
  const int t = opaque_tid(), lane = t & 31, w = t >> 5, g = lane >> 2, tq = lane & 3;
  const int m = lane >> 3, r8 = lane & 7, kh = w >> 2, et = w & 3;
  const unsigned bar = sb + SM_BAR;
  unsigned wq[16][4], wk[16][4], wo[8][4];
  const unsigned woff = (kh * 4) * 8192 + ((m >> 1) * 8 + r8) * 128 + (((et * 2 + (m & 1)) ^ r8) << 4);
  mbar_wait(bar + 8 * MB_W0, 0);
#pragma unroll
  for (int i = 0; i < 16; i++) {
    ldsm_x4_t(wq[i], sb + R_WO + woff + (i >> 2) * 8192 + (i & 3) * 2048);
    ldsm_x4_t(wk[i], sb + R_T1 + woff + (i >> 2) * 8192 + (i & 3) * 2048);
  }
  bar_sync(2, 288);
  if (t == 0) {
    fence_proxy_async_smem();
    mbar_expect_tx(bar + 8 * MB_WO, 65536);
    for (int kb = 0; kb < 2; kb++)
      for (int cb = 0; cb < 4; cb++) tma_load_2d(sb + R_WO + (kb * 4 + cb) * 8192, &maps.wo, j * 256 + cb * 64, h * 128 + kb * 64, bar + 8 * MB_WO);
  }
  mbar_wait(bar + 8 * MB_W1, 0);
  const unsigned pV = sb + R_T2 + woff;
  const unsigned rk = c & 7, peer = rk ^ 1, cl = c >> 3;
#define KEEP(x) x = __shfl_sync(~0u, x, lane)
  unsigned pA = sb + R_MEM + kh * 4096 + lane * 16;
  unsigned pW0 = sb + R_WO + (w >> 1) * 8192 + ((m >> 1) * 8 + r8) * 128 + ((((w & 1) * 4 + (m & 1)) ^ r8) << 4);
  unsigned pW1 = pW0 ^ 32;
  unsigned pVk = pV;
  unsigned aX = sb + R_VRED + et * 512 + lane * 16;
  unsigned aQKst = sb + (kh ? R_KS : R_QS) + r8 * 144 + (et * 16 + (m & 1) * 8) * 2;
  unsigned aL8_ = sb + lane * 8;
  unsigned aSl_ = mapa(sb + R_SOWN + w * 256 + lane * 8, rk), aSr_ = mapa(sb + R_SPEER + w * 256 + lane * 8, peer);
  const unsigned mbSl = mapa(bar + 8 * MB_S, rk), mbSr = mapa(bar + 8 * MB_S, peer), mbVl = mbSl + 8, mbVr = mbSr + 8;
  unsigned aQ_ = sb + R_QS + r8 * 144 + m * 16;
  unsigned oKx_ = (et * 8 + r8) * 128 + ((m ^ r8) << 4);
  unsigned oVx_ = 4096 + (et >> 1) * 4096 + ((m >> 1) * 8 + r8) * 128 + ((((et & 1) * 4 + (m & 1)) ^ r8) << 4);
  unsigned aOst_ = sb + R_OS + r8 * 272 + (et * 32 + m * 8) * 2;
  unsigned aOld = sb + R_OS + r8 * 272 + m * 16;
  unsigned aVm_ = sb + R_VM + et * 512 + lane * 8;
  unsigned aRSr = mapa(sb + R_RS + (h & 3) * 2048 + (w & 1) * 1024 + lane * 8, j * 4 + (w >> 1));
  unsigned mbRSr = mapa(bar + 8 * MB_RS, j * 4 + (w >> 1));
  unsigned t8 = t * 8;
  unsigned r1 = kh ? aL8_ : aSl_, r2 = kh ? oVx_ : aSr_, r3 = kh ? aOst_ : aQ_, r4 = kh ? aVm_ : oKx_;
#define aL8 r1
#define aSl r1
#define oVx r2
#define aSr r2
#define aOst r3
#define aQ r3
#define aVm r4
#define oKx r4
#define aVl (aSl + (R_VM - R_SOWN) + j * 1024)
#define aVr (aSr + (R_VM - R_SPEER) + j * 1024)
  KEEP(pA); KEEP(pW0); KEEP(pW1); KEEP(pVk); KEEP(aX); KEEP(aQKst); KEEP(r1); KEEP(r2); KEEP(r3); KEEP(r4);
  KEEP(aOld); KEEP(aRSr); KEEP(mbRSr); KEEP(t8);
  mbar_wait(bar + 8 * MB_WO, 0);
#pragma unroll
  for (int ks = 0; ks < 4; ks++) { ldsm_x4_t(wo[2 * ks], pW0 + ks * 2048); ldsm_x4_t(wo[2 * ks + 1], pW1 + ks * 2048); }
  {
    unsigned v[8];
#pragma unroll
    for (int q = 0; q < 8; q++) v[q] = __ldg(reinterpret_cast<const unsigned*>(mem0) + q * 256 + t);
    sts128(sb + R_MEM + t * 32, make_uint4(__byte_perm(v[0], v[1], 0x5410), __byte_perm(v[2], v[3], 0x5410), __byte_perm(v[4], v[5], 0x5410), __byte_perm(v[6], v[7], 0x5410)));
    sts128(sb + R_MEM + t * 32 + 16, make_uint4(__byte_perm(v[0], v[1], 0x7632), __byte_perm(v[2], v[3], 0x7632), __byte_perm(v[4], v[5], 0x7632), __byte_perm(v[6], v[7], 0x7632)));
  }
  bar_sync(1, 256);

#pragma unroll 1
  for (int s = 0;; s++) {
    const unsigned par = s & 1;
    const unsigned slot = s & (RING_N - 1), rpar = (s / RING_N) & 1;
    const unsigned ring = sb + R_RING + slot * RING_BYTES;
    RSTAMP(1);
    RSTAMP(2);
    float aq[4] = {0, 0, 0, 0}, ak[4] = {0, 0, 0, 0};
    {
      float aq1[4] = {0, 0, 0, 0}, ak1[4] = {0, 0, 0, 0};
#pragma unroll
      for (int i = 0; i < 8; i++) {
        unsigned b[4];
        ldsm_x4_t(b, pA + i * 512);
        mma16816(aq, wq[2 * i], b[0], b[1]); mma16816(ak, wk[2 * i], b[0], b[1]);
        mma16816(aq1, wq[2 * i + 1], b[2], b[3]); mma16816(ak1, wk[2 * i + 1], b[2], b[3]);
      }
#pragma unroll
      for (int i = 0; i < 4; i++) { aq[i] += aq1[i]; ak[i] += ak1[i]; }
    }
    RSTAMP(3);
#define STSF4(a, v) asm volatile("st.shared.v4.f32 [%0], {%1,%2,%3,%4};" ::"r"(a), "f"(v[0]), "f"(v[1]), "f"(v[2]), "f"(v[3]) : "memory")
#define VPASS() float av[4] = {0, 0, 0, 0}; { float av1[4] = {0, 0, 0, 0}; \
      _Pragma("unroll") for (int i = 0; i < 8; i++) { unsigned b[4], f1[4], f0[4]; \
        ldsm_x4_t(b, pA + i * 512); ldsm_x4_t(f0, pVk + (i >> 1) * 8192 + (i & 1) * 4096); ldsm_x4_t(f1, pVk + (i >> 1) * 8192 + (i & 1) * 4096 + 2048); \
        mma16816(av, f0, b[0], b[1]); mma16816(av1, f1, b[2], b[3]); } \
      _Pragma("unroll") for (int i = 0; i < 4; i++) av[i] += av1[i]; }
    unsigned f[8][4];
#define WO_LD(i0, i1) do { _Pragma("unroll") for (int i = i0; i < i1; i++) { ldsm_x4_t(f[2 * i], pW0 + 32768 + i * 2048); ldsm_x4_t(f[2 * i + 1], pW1 + 32768 + i * 2048); } } while (0)
    if (kh) {
      STSF4(aX, aq);
      bar_sync(4 + et, 64);
      uint4 o = lds128(aX + 2048);
      stsm_x2_t(aQKst, pack_bf16(ak[0] + __uint_as_float(o.x), ak[1] + __uint_as_float(o.y)), pack_bf16(ak[2] + __uint_as_float(o.z), ak[3] + __uint_as_float(o.w)));
      bar_arrive(1, 256);
      RSTAMP(4);
      VPASS();
      STSF4(aX + 4096, av);
      bar_arrive(8 + et, 64);
      RSTAMP(5);
      if (s == NSEG - 1) {
        mbar_wait(bar + 8 * MB_V, par);
        if (t == 128) mbar_arrive(bar + 8 * MB_KVR);
        break;
      }
      mbar_wait(bar + 8 * (MB_FULL + slot), rpar);
      unsigned vx[4][4];
      ldsm_x4_t(vx[0], ring + oVx); ldsm_x4_t(vx[1], ring + oVx + 2048); ldsm_x4_t(vx[2], ring + (oVx ^ 32)); ldsm_x4_t(vx[3], ring + (oVx ^ 32) + 2048);
      WO_LD(0, NPRE1);
      RSTAMP(6); RSTAMP(7);
      mbar_wait(bar + 8 * MB_S, par);
      RSTAMP(8);
      float sc[10];
#pragma unroll
      for (int i = 0; i < 5; i++) {
        uint2 o = lds64(aL8 + R_SOWN + i * 256), p = lds64(aL8 + R_SPEER + i * 256);
        sc[2 * i] = __uint_as_float(o.x) + __uint_as_float(p.x); sc[2 * i + 1] = __uint_as_float(o.y) + __uint_as_float(p.y);
      }
      float mx = fmaxf(fmaxf(fmaxf(sc[0], sc[1]), fmaxf(sc[2], sc[3])), fmaxf(fmaxf(fmaxf(sc[4], sc[5]), fmaxf(sc[6], sc[7])), fmaxf(sc[8], sc[9])));
      mx = fmaxf(mx, __shfl_xor_sync(~0u, mx, 1)); mx = fmaxf(mx, __shfl_xor_sync(~0u, mx, 2));
      const float nm = -mx * (SCALE_QK * LOG2E);
      unsigned p[5];
#pragma unroll
      for (int i = 0; i < 5; i++) p[i] = pack_bf16(ex2f(fmaf(sc[2 * i], SCALE_QK * LOG2E, nm)), ex2f(fmaf(sc[2 * i + 1], SCALE_QK * LOG2E, nm)));
      RSTAMP(9);
      float o0[4] = {0, 0, 0, 0}, o1[4] = {0, 0, 0, 0}, o3[4] = {0, 0, 0, 0}, o4[4] = {0, 0, 0, 0}, z0[4] = {0, 0, 0, 0}, z1[4] = {0, 0, 0, 0};
      const unsigned ones[4] = {0x3F803F80u, 0u, 0x3F803F80u, 0u};
      mma16816(z0, ones, p[0], p[1]); mma16816(z1, ones, p[2], p[3]);
      mma16816(o0, vx[0], p[0], p[1]); mma16816(o3, vx[2], p[0], p[1]); mma16816(o1, vx[1], p[2], p[3]); mma16816(o4, vx[3], p[2], p[3]);
      mma1688(z0, 0x3F803F80u, 0u, p[4]);
      mbar_wait(bar + 8 * MB_V, par);
      uint2 vm0 = lds64(aVm), vm1 = lds64(aVm + 256);
      mma1688(o0, vm0.x, vm0.y, p[4]); mma1688(o3, vm1.x, vm1.y, p[4]);
      float i0, i1;
      asm("rcp.approx.ftz.f32 %0, %1;" : "=f"(i0) : "f"(z0[0] + z1[0])); asm("rcp.approx.ftz.f32 %0, %1;" : "=f"(i1) : "f"(z0[1] + z1[1]));
      asm volatile("stmatrix.sync.aligned.m8n8.x4.trans.shared.b16 [%0], {%1,%2,%3,%4};" ::"r"(aOst), "r"(pack_bf16((o0[0] + o1[0]) * i0, (o0[1] + o1[1]) * i1)), "r"(pack_bf16((o0[2] + o1[2]) * i0, (o0[3] + o1[3]) * i1)),
                   "r"(pack_bf16((o3[0] + o4[0]) * i0, (o3[1] + o4[1]) * i1)), "r"(pack_bf16((o3[2] + o4[2]) * i0, (o3[3] + o4[3]) * i1)) : "memory");
      RSTAMP(10);
      bar_sync(1, 256);
      WO_LD(NPRE1, 4);
    } else {
      STSF4(aX + 2048, ak);
      unsigned kb[8];
      mbar_wait(bar + 8 * (MB_FULL + slot), rpar);
      ldsm_x4(kb, ring + oKx); ldsm_x4(kb + 4, ring + (oKx ^ 64));
      bar_sync(4 + et, 64);
      uint4 o = lds128(aX);
      stsm_x2_t(aQKst, pack_bf16(aq[0] + __uint_as_float(o.x), aq[1] + __uint_as_float(o.y)), pack_bf16(aq[2] + __uint_as_float(o.z), aq[3] + __uint_as_float(o.w)));
      RSTAMP(4);
      bar_sync(1, 256);
      RSTAMP(5);
      if (s != NSEG - 1) {
        unsigned qa[8], km[8];
        ldsm_x4(qa, aQ); ldsm_x4(qa + 4, aQ + 64);
        if (w == 3) { ldsm_x4(km, aQ + 1152); ldsm_x4(km + 4, aQ + 1152 + 64); }
        float s0[4] = {0, 0, 0, 0}, s1[4] = {0, 0, 0, 0};
        unsigned af[4][4];
#pragma unroll
        for (int i = 0; i < 4; i++) { af[i][0] = qa[2 * i]; af[i][1] = 0; af[i][2] = qa[2 * i + 1]; af[i][3] = 0; }
        mma16816(s0, af[0], kb[0], kb[1]); mma16816(s1, af[1], kb[2], kb[3]);
        mma16816(s0, af[2], kb[4], kb[5]); mma16816(s1, af[3], kb[6], kb[7]);
        if (w == 3) {
          float m0[4] = {0, 0, 0, 0}, m1[4] = {0, 0, 0, 0};
          mma16816(m0, af[0], km[0], km[1]); mma16816(m1, af[1], km[2], km[3]);
          mma16816(m0, af[2], km[4], km[5]); mma16816(m1, af[3], km[6], km[7]);
          unsigned x = __float_as_uint(m0[0] + m1[0]), y = __float_as_uint(m0[1] + m1[1]);
          st_async_b64(aSr + 256, x, y, mbSr); st_async_b64(aSl + 256, x, y, mbSl);
        }
        unsigned x = __float_as_uint(s0[0] + s1[0]), y = __float_as_uint(s0[1] + s1[1]);
        st_async_b64(aSr, x, y, mbSr); st_async_b64(aSl, x, y, mbSl);
      }
      RSTAMP(6);
      VPASS();
      RSTAMP(7);
      bar_sync(8 + et, 64);
      uint4 o2 = lds128(aX + 4096);
      unsigned x = pack_bf16(av[0] + __uint_as_float(o2.x), av[1] + __uint_as_float(o2.y)), y = pack_bf16(av[2] + __uint_as_float(o2.z), av[3] + __uint_as_float(o2.w));
      st_async_b64(aVr, x, y, mbVr);
      st_async_b64(aVl, x, y, mbVl);
      RSTAMP(8);
      if (s == NSEG - 1) break;
      WO_LD(0, 4);
      RSTAMP(9); RSTAMP(10);
      bar_sync(1, 256);
    }
    RSTAMP(11);
    float d0[4] = {0, 0, 0, 0}, d1[4] = {0, 0, 0, 0}, e0[4] = {0, 0, 0, 0}, e1[4] = {0, 0, 0, 0};
    unsigned ob[4][4];
#pragma unroll
    for (int k2 = 0; k2 < 4; k2++) ldsm_x4(ob[k2], aOld + k2 * 64);
    mma16816(d0, wo[0], ob[0][0], ob[0][1]); mma16816(d1, wo[1], ob[0][0], ob[0][1]);
    mma16816(e0, wo[2], ob[0][2], ob[0][3]); mma16816(e1, wo[3], ob[0][2], ob[0][3]);
    mma16816(d0, wo[4], ob[1][0], ob[1][1]); mma16816(d1, wo[5], ob[1][0], ob[1][1]);
    mma16816(e0, wo[6], ob[1][2], ob[1][3]); mma16816(e1, wo[7], ob[1][2], ob[1][3]);
    mma16816(d0, f[0], ob[2][0], ob[2][1]); mma16816(d1, f[1], ob[2][0], ob[2][1]);
    mma16816(e0, f[2], ob[2][2], ob[2][3]); mma16816(e1, f[3], ob[2][2], ob[2][3]);
    mma16816(d0, f[4], ob[3][0], ob[3][1]); mma16816(d1, f[5], ob[3][0], ob[3][1]);
    mma16816(e0, f[6], ob[3][2], ob[3][3]); mma16816(e1, f[7], ob[3][2], ob[3][3]);
    st_async_b64(aRSr, __float_as_uint(d0[0] + e0[0]), __float_as_uint(d0[1] + e0[1]), mbRSr);
    st_async_b64(aRSr + 256, __float_as_uint(d0[2] + e0[2]), __float_as_uint(d0[3] + e0[3]), mbRSr);
    st_async_b64(aRSr + 512, __float_as_uint(d1[0] + e1[0]), __float_as_uint(d1[1] + e1[1]), mbRSr);
    st_async_b64(aRSr + 768, __float_as_uint(d1[2] + e1[2]), __float_as_uint(d1[3] + e1[3]), mbRSr);
    RSTAMP(12);
    if (t == 128) {
      mbar_arrive(bar + 8 * (MB_EMPTY + slot)); mbar_arrive(bar + 8 * MB_KVR);
      mbar_expect_tx(bar + 8 * MB_S, 2560); mbar_expect_tx(bar + 8 * MB_V, 2048);
    }
    const unsigned tag = ((s >> 1) & 1) ^ 1;
    const char* gp = reinterpret_cast<const char*>(g_part) + (par * 8 + rk) * 16384 + t8;
    unsigned mbA[8];
#pragma unroll
    for (int i = 0; i < 8; i++) mbA[i] = mapa(bar + 8 * MB_AG, i);
    const unsigned dlt = (R_MEM + rk * 1024) - (SM_BAR + 8 * MB_AG) + (t8 >> 1);
    mbar_wait(bar + 8 * MB_RS, par);
    RSTAMP(13);
    uint2 a[8];
    {
      uint2 x0 = lds64(sb + R_RS + t8), x1 = lds64(sb + R_RS + 2048 + t8), x2 = lds64(sb + R_RS + 4096 + t8), x3 = lds64(sb + R_RS + 6144 + t8);
      float q0 = (__uint_as_float(x0.x) + __uint_as_float(x1.x)) + (__uint_as_float(x2.x) + __uint_as_float(x3.x));
      float q1 = (__uint_as_float(x0.y) + __uint_as_float(x1.y)) + (__uint_as_float(x2.y) + __uint_as_float(x3.y));
      a[0].x = (__float_as_uint(q0) & ~1u) | tag; a[0].y = (__float_as_uint(q1) & ~1u) | tag;
      asm volatile("st.relaxed.gpu.global.v2.u32 [%0], {%1,%2};" ::"l"(gp + cl * 2048), "r"(a[0].x), "r"(a[0].y) : "memory");
    }
    RSTAMP(14);
    if (t == 128) mbar_expect_tx(bar + 8 * MB_RS, 8192);
    {
      unsigned it = 0;
#define PLOAD(a) _Pragma("unroll") for (int i = 1; i < 8; i++) a[i] = ldv2_relaxed(gp + (cl ^ i) * 2048)
#define PAND(a) (((a[1].x & a[1].y) & (a[2].x & a[2].y) & (a[3].x & a[3].y)) & ((a[4].x & a[4].y) & (a[5].x & a[5].y)) & ((a[6].x & a[6].y) & (a[7].x & a[7].y)))
#define POR(a) (((a[1].x | a[1].y) | (a[2].x | a[2].y) | (a[3].x | a[3].y)) | ((a[4].x | a[4].y) | (a[5].x | a[5].y)) | ((a[6].x | a[6].y) | (a[7].x | a[7].y)))
#define POK(a) (((tag ? PAND(a) : ~POR(a)) & 1u) != 0)
      if (D_RED) DELAY(D_RED);
      while (true) { PLOAD(a); if (POK(a)) break; if (D_PUB) DELAY(D_PUB); spin_check(it); }
    }
    RSTAMP(15);
    {
#define AF(i, c) __uint_as_float(a[i].c)
      unsigned u = pack_bf16(((AF(0, x) + AF(1, x)) + (AF(2, x) + AF(3, x))) + ((AF(4, x) + AF(5, x)) + (AF(6, x) + AF(7, x))),
                             ((AF(0, y) + AF(1, y)) + (AF(2, y) + AF(3, y))) + ((AF(4, y) + AF(5, y)) + (AF(6, y) + AF(7, y))));
      __syncwarp();
#pragma unroll
      for (int i = 0; i < 8; i++) st_async_b32(mbA[i] + dlt, u, mbA[i]);
    }
    mbar_wait(bar + 8 * MB_KVF, par);
    mbar_wait(bar + 8 * MB_AG, par);
    if (t == 128) mbar_expect_tx(bar + 8 * MB_AG, 8192);
  }
}

__device__ __forceinline__ void rec_ring(const Maps& maps, unsigned sb) {
  const int c = blockIdx.x, h = c >> 1, j = c & 1;
  const unsigned bar = sb + SM_BAR;
  const int lane = threadIdx.x & 31;
  if (lane == 0) {
    mbar_expect_tx(bar + 8 * MB_W0, 131072);
    for (int kb = 0; kb < 8; kb++) tma_load_2d(sb + R_WO + kb * 8192, &maps.wq, h * 128 + j * 64, kb * 64, bar + 8 * MB_W0);
    for (int kb = 0; kb < 8; kb++) tma_load_2d(sb + R_T1 + kb * 8192, &maps.wk, h * 128 + j * 64, kb * 64, bar + 8 * MB_W0);
    mbar_expect_tx(bar + 8 * MB_W1, 65536);
    for (int kb = 0; kb < 8; kb++) tma_load_2d(sb + R_T2 + kb * 8192, &maps.wv, h * 128 + j * 64, kb * 64, bar + 8 * MB_W1);
  }
  __syncwarp();
  bar_sync(2, 288);
  if (lane == 0) {
    fence_proxy_async_smem();
    for (int s = 0; s < NSEG; s++) {
      unsigned slot = s & (RING_N - 1);
      if ((s & 3) == 0 && !DBGMODE) {
        wait_flag_ge(&g_flags.qkv[(s >> 2) * 48 + 16 + (h >> 1)], 1);
        wait_flag_ge(&g_flags.qkv[(s >> 2) * 48 + 32 + (h >> 1)], 1);
        fence_proxy_async();
      }
      if (s >= RING_N) mbar_wait_sleep(bar + 8 * (MB_EMPTY + slot), ((s / RING_N) - 1) & 1);
      unsigned dst = sb + R_RING + slot * RING_BYTES, mb = bar + 8 * (MB_FULL + slot);
      mbar_expect_tx(mb, RING_BYTES);
      tma_load_2d(dst, &maps.qkv_ld, HD + h * 128 + j * 64, s * SEG, mb);
      tma_load_2d(dst + 4096, &maps.qkv_ld, 2 * HD + h * 128, s * SEG, mb);
      tma_load_2d(dst + 8192, &maps.qkv_ld, 2 * HD + h * 128 + 64, s * SEG, mb);
    }
  }
}
__device__ __forceinline__ void rec_copy(unsigned sb) {
  const int c = blockIdx.x, h = c >> 1, j = c & 1;
  const unsigned bar = sb + SM_BAR;
  const int lane = threadIdx.x & 31;
  for (int s = 0; s < NSEG; s++) {
    mbar_wait_sleep(bar + 8 * MB_KVR, s & 1);
    uint4 k0 = lds128(sb + R_KS + (lane >> 3) * 144 + (lane & 7) * 16), k1 = lds128(sb + R_KS + (4 + (lane >> 3)) * 144 + (lane & 7) * 16);
    uint2 v[4];
#pragma unroll
    for (int i = 0; i < 4; i++) v[i] = lds64(sb + R_VM + (j * 4 + i) * 256 + lane * 8);
    __syncwarp();
    if (lane == 0) mbar_arrive(bar + 8 * MB_KVF);
    bf16* kd = g_km + ((size_t)(s * NH + h) * NMEM) * DH + j * 64;
    *reinterpret_cast<uint4*>(kd + (lane >> 3) * DH + (lane & 7) * 8) = k0;
    *reinterpret_cast<uint4*>(kd + (4 + (lane >> 3)) * DH + (lane & 7) * 8) = k1;
    unsigned* vd = reinterpret_cast<unsigned*>(g_vmt) + ((size_t)(s * NH + h) * DH + j * 64) * 4;
#pragma unroll
    for (int i = 0; i < 4; i++) { vd[(i * 16) * 4 + lane] = v[i].x; vd[(i * 16 + 8) * 4 + lane] = v[i].y; }
    __syncwarp();
    if (lane == 0) st_release(&g_flags.rec[c], s + 1);
  }
}

__device__ __forceinline__ void bulk_producer(const Maps& maps, unsigned sb, int* misc) {
  const unsigned bar = sb + SM_BAR;
  const int lane = threadIdx.x & 31;
  unsigned st = 0, ph = 0, seq = 0;
  while (true) {
    int idx = 0;
    if (lane == 0) idx = (int)atomicAdd(&g_flags.ctr, 1u);
    idx = __shfl_sync(~0u, idx, 0);
    if (idx >= N_ITEMS) {
      if (lane == 0) {
        mbar_wait(bar + 8 * (MB_EMPTY + st), ph ^ 1);
        misc[seq & 3] = -1;
        mbar_arrive(bar + 8 * (MB_FULL + st));
      }
      break;
    }
    if (lane == 0) ISTAMP(idx, 0);
    Item it = decode_item(idx);
    if (it.b < 0) continue;
    const CUtensorMap* mp; int c0, c1, dc0, dc1; unsigned doff;
    const unsigned* fl = nullptr; unsigned tgt = 1; int nbox = 5, rdy = 0;
    if (it.type == T_ATT) {
      mp = &maps.qkv_ld; nbox = 12; doff = lane * 4096;
      c0 = (lane >> 2) * HD + it.c * 256 + (lane & 1) * 64; c1 = it.b * 128 + ((lane >> 1) & 1) * 32; dc0 = dc1 = 0;
      if (lane < 3) fl = &g_flags.qkv[it.b * 48 + lane * 16 + it.c];
      bool ok = true;
      if (lane >= 4 && lane < 8) ok = ld_acquire(&g_flags.rec[it.c * 4 + lane - 4]) >= (unsigned)(it.b * 4 + 4);
      rdy = __all_sync(~0u, ok) ? 65536 : 0;
    } else {
      int k0 = 0, nb0 = it.c * 256;
      if (it.type == T_QKV) { mp = lane == 0 ? &maps.xn : (it.c < 16 ? &maps.wq : (it.c < 32 ? &maps.wk : &maps.wv)); nb0 = (it.c & 15) * 256; }
      else if (it.type == T_M1) mp = lane == 0 ? &maps.y : &maps.w1;
      else if (it.type == T_M2) { mp = lane == 0 ? &maps.h1 : &maps.w2; fl = &g_flags.h1[it.b]; tgt = 7; }
      else {
        mp = lane == 0 ? &maps.o : &maps.wo;
        if (it.type == T_OUT) { k0 = it.ks * 1024; fl = &g_flags.o[it.b * 4 + it.ks]; tgt = 4; }
        else if (it.type == T_OUTL) { k0 = it.ks * 256; fl = &g_flags.o16[it.ks]; }
        else if (lane == 1) { fl = &g_flags.g[it.b]; tgt = 2; }
        else { fl = &g_flags.p[it.b]; tgt = it.type == T_RED ? 8 : 32; }
      }
      if (lane > (it.type >= T_RED ? 1 : 0)) fl = nullptr;
      if (lane == 0) { c0 = k0; c1 = it.b * 128; dc0 = 64; dc1 = 0; doff = 0; }
      else { c0 = nb0 + (lane - 1) * 64; c1 = k0; dc0 = 0; dc1 = 64; doff = 8192 + lane * 8192; }
    }
    if (fl) wait_flag_ge(fl, tgt);
    __syncwarp();
    fence_proxy_async();
    if (lane == 0) ISTAMP(idx, 1);
    const int nkb = item_nkb(it.type);
    for (int kb = 0; kb < nkb; kb++) {
      const unsigned mb = bar + 8 * (MB_FULL + st);
      mbar_wait(bar + 8 * (MB_EMPTY + st), ph ^ 1);
      if (lane == 0) {
        if (kb == 0) misc[seq & 3] = idx | rdy;
        if (it.type >= T_RED) mbar_arrive(mb); else mbar_expect_tx(mb, STAGE_BYTES);
      }
      if (it.type == T_ATT) { if (lane < 12) tma_load_2d(sb + st * STAGE_BYTES + doff, mp, c0 + (kb & 1) * 128, c1 + (kb >> 1) * 64, mb); }
      else if (lane < nbox && it.type < T_RED) tma_load_2d(sb + st * STAGE_BYTES + doff, mp, c0 + kb * dc0, c1 + kb * dc1, mb);
      __syncwarp();
      if (++st == NSTAGE) { st = 0; ph ^= 1; }
    }
    seq++;
  }
}
__device__ __forceinline__ void bulk_store(const Maps& maps, unsigned sb, volatile int* misc) {
  const unsigned bar = sb + SM_BAR;
  unsigned ph = 0;
  while (true) {
    mbar_wait(bar + 8 * MB_STGF, ph); ph ^= 1;
    int idx = misc[4];
    if (idx < 0) break;
    Item it = decode_item(idx);
    const CUtensorMap* mp = it.type == T_QKV ? &maps.qkv_st : (it.type == T_M1 ? &maps.h1 : (it.type == T_M2 ? &maps.g : &maps.o));
    unsigned* flag = it.type == T_QKV ? &g_flags.qkv[it.b * 48 + it.c] : (it.type == T_M1 ? &g_flags.h1[it.b] : (it.type == T_M2 ? &g_flags.g[it.b] : (it.b == 15 ? &g_flags.o16[it.c] : &g_flags.o[it.b * 4 + (it.c >> 2)])));
    for (int i = 0; i < 4; i++) tma_store_2d(mp, sb + B_STG + i * 16384, it.c * 256 + i * 64, it.b * 128);
    asm volatile("cp.async.bulk.commit_group;" ::: "memory");
    asm volatile("cp.async.bulk.wait_group.read 0;" ::: "memory");
    mbar_arrive(bar + 8 * MB_STGE);
    asm volatile("cp.async.bulk.wait_group 0;" ::: "memory");
    fence_proxy_async();
    red_release_add(flag, 1);
    ISTAMP(idx, 3);
  }
}
__device__ __forceinline__ float rcpf(float x) { float y; asm("rcp.approx.ftz.f32 %0, %1;" : "=f"(y) : "f"(x)); return y; }
__device__ __forceinline__ float gelu_t(float x) {
  float e = ex2f(x * fmaf(x * x, -2.0f * LOG2E * 0.7978845608028654f * 0.044715f, -2.0f * LOG2E * 0.7978845608028654f));
  return x * rcpf(1.0f + e);
}
__device__ __forceinline__ float silu_f(float x) { return x * rcpf(1.0f + ex2f(-LOG2E * x)); }
__device__ __forceinline__ unsigned badd2(unsigned a, unsigned b) { unsigned r; asm("add.rn.bf16x2 %0, %1, %2;" : "=r"(r) : "r"(a), "r"(b)); return r; }

__device__ __forceinline__ void final_out(bf16* __restrict__ out, const bf16* __restrict__ x, size_t o, float4 s) {
  uint2 gv = __ldcg(reinterpret_cast<const uint2*>(g_g + o)), xv = __ldg(reinterpret_cast<const uint2*>(x + o));
  uint2 r;
  r.x = pack_bf16(bf_lo(xv.x) + bf16r(bf16r(s.x) * bf_lo(gv.x)), bf_hi(xv.x) + bf16r(bf16r(s.y) * bf_hi(gv.x)));
  r.y = pack_bf16(bf_lo(xv.y) + bf16r(bf16r(s.z) * bf_lo(gv.y)), bf_hi(xv.y) + bf16r(bf16r(s.w) * bf_hi(gv.y)));
  *reinterpret_cast<uint2*>(out + o) = r;
}
__device__ __forceinline__ void bulk_att_load(unsigned* km, unsigned* vm, int b, int hp, int kb, int w, int lane) {
  const int g = lane >> 2, tq = lane & 3, seg = w >> 2, eh = w & 1;
  const int head = hp * 2 + (kb & 1), sg = b * 4 + (kb >> 1) * 2 + seg;
  const unsigned* kmp = reinterpret_cast<const unsigned*>(g_km + ((size_t)(sg * NH + head) * NMEM + g) * DH) + tq;
  const unsigned* vmp = reinterpret_cast<const unsigned*>(g_vmt) + ((size_t)(sg * NH + head) * DH + eh * 64) * 4 + lane;
#pragma unroll
  for (int i = 0; i < 16; i++) asm volatile("ld.global.cg.u32 %0, [%1];" : "=r"(km[i]) : "l"(kmp + i * 4) : "memory");
#pragma unroll
  for (int i = 0; i < 8; i++) asm volatile("ld.global.cg.u32 %0, [%1];" : "=r"(vm[i]) : "l"(vmp + i * 32) : "memory");
}
__device__ __forceinline__ void bulk_att_stage(unsigned sa, unsigned stg, const unsigned* km, const unsigned* vm, int kb, int w, int lane) {
  const int g = lane >> 2, tq = lane & 3, m = lane >> 3, r8 = lane & 7;
  const int seg = w >> 2, mt = (w >> 1) & 1, eh = w & 1;
  float s[5][4];
#pragma unroll
  for (int i = 0; i < 5; i++) { s[i][0] = s[i][1] = s[i][2] = s[i][3] = 0; }
  const unsigned qb = sa + (0 * 2 + seg) * 8192, kbs = sa + (1 * 2 + seg) * 8192, vb = sa + (2 * 2 + seg) * 8192 + eh * 4096;
  unsigned qa[8][4];
#pragma unroll
  for (int ks = 0; ks < 8; ks++) {
    int row = mt * 16 + (m & 1) * 8 + r8;
    ldsm_x4(qa[ks], qb + (ks >> 2) * 4096 + row * 128 + ((((ks & 3) * 2 + (m >> 1)) ^ r8) << 4));
    unsigned kf[4];
    int krow = (m >> 1) * 8 + r8;
    unsigned ka = kbs + (ks >> 2) * 4096 + krow * 128 + ((((ks & 3) * 2 + (m & 1)) ^ r8) << 4);
    ldsm_x4(kf, ka);
    mma16816(s[0], qa[ks], kf[0], kf[1]); mma16816(s[1], qa[ks], kf[2], kf[3]);
    if (mt) { ldsm_x4(kf, ka + 2048); mma16816(s[2], qa[ks], kf[0], kf[1]); mma16816(s[3], qa[ks], kf[2], kf[3]); }
  }
#pragma unroll
  for (int ks = 0; ks < 8; ks++) mma16816(s[4], qa[ks], km[2 * ks], km[2 * ks + 1]);
  float mx0 = -INFINITY, mx1 = -INFINITY;
  const int t0 = mt * 16 + g, t1 = t0 + 8;
#pragma unroll
  for (int i = 0; i < 5; i++) {
#pragma unroll
    for (int e = 0; e < 4; e++) {
      float v = s[i][e];
      if (i < 4) { int kj = i * 8 + 2 * tq + (e & 1); if (kj > (e < 2 ? t0 : t1)) v = -INFINITY; }
      s[i][e] = v;
      if (e < 2) mx0 = fmaxf(mx0, v); else mx1 = fmaxf(mx1, v);
    }
  }
  mx0 = fmaxf(mx0, __shfl_xor_sync(~0u, mx0, 1)); mx0 = fmaxf(mx0, __shfl_xor_sync(~0u, mx0, 2));
  mx1 = fmaxf(mx1, __shfl_xor_sync(~0u, mx1, 1)); mx1 = fmaxf(mx1, __shfl_xor_sync(~0u, mx1, 2));
  float sm0 = 0, sm1 = 0;
#pragma unroll
  for (int i = 0; i < 5; i++) {
    s[i][0] = ex2f((s[i][0] - mx0) * (SCALE_QK * LOG2E)); s[i][1] = ex2f((s[i][1] - mx0) * (SCALE_QK * LOG2E));
    s[i][2] = ex2f((s[i][2] - mx1) * (SCALE_QK * LOG2E)); s[i][3] = ex2f((s[i][3] - mx1) * (SCALE_QK * LOG2E));
    sm0 += s[i][0] + s[i][1]; sm1 += s[i][2] + s[i][3];
  }
  sm0 += __shfl_xor_sync(~0u, sm0, 1); sm0 += __shfl_xor_sync(~0u, sm0, 2);
  sm1 += __shfl_xor_sync(~0u, sm1, 1); sm1 += __shfl_xor_sync(~0u, sm1, 2);
  const float i0 = __fdividef(1.0f, sm0), i1 = __fdividef(1.0f, sm1);
  unsigned pa[2][4], pm0, pm1;
#pragma unroll
  for (int kk = 0; kk < 2; kk++) {
    pa[kk][0] = pack_bf16(s[2 * kk][0] * i0, s[2 * kk][1] * i0); pa[kk][1] = pack_bf16(s[2 * kk][2] * i1, s[2 * kk][3] * i1);
    pa[kk][2] = pack_bf16(s[2 * kk + 1][0] * i0, s[2 * kk + 1][1] * i0); pa[kk][3] = pack_bf16(s[2 * kk + 1][2] * i1, s[2 * kk + 1][3] * i1);
  }
  pm0 = pack_bf16(s[4][0] * i0, s[4][1] * i0); pm1 = pack_bf16(s[4][2] * i1, s[4][3] * i1);
  const int orow = (kb >> 1) * 64 + seg * 32 + mt * 16 + (m & 1) * 8 + r8;
  const unsigned ob = stg + ((kb & 1) * 2 + eh) * 16384 + orow * 128;
#pragma unroll
  for (int cp = 0; cp < 4; cp++) {
    float o0[4] = {0, 0, 0, 0}, o1[4] = {0, 0, 0, 0};
    mma1688(o0, pm0, pm1, vm[2 * cp]); mma1688(o1, pm0, pm1, vm[2 * cp + 1]);
    unsigned vf[4];
    int row = (m & 1) * 8 + r8;
    unsigned va = vb + row * 128 + (((cp * 2 + (m >> 1)) ^ r8) << 4);
    ldsm_x4_t(vf, va);
    mma16816(o0, pa[0], vf[0], vf[1]); mma16816(o1, pa[0], vf[2], vf[3]);
    if (mt) { ldsm_x4_t(vf, va + 2048); mma16816(o0, pa[1], vf[0], vf[1]); mma16816(o1, pa[1], vf[2], vf[3]); }
    stsm_x4(ob + (((cp * 2 + (m >> 1)) ^ r8) << 4), pack_bf16(o0[0], o0[1]), pack_bf16(o0[2], o0[3]), pack_bf16(o1[0], o1[1]), pack_bf16(o1[2], o1[3]));
  }
}

__device__ __forceinline__ void bulk_worker(unsigned sb, volatile int* misc, const bf16* __restrict__ x, const bf16* __restrict__ b1, const bf16* __restrict__ b2, bf16* __restrict__ out) {
  const int t = threadIdx.x, lane = t & 31, w = t >> 5, wg = w >> 2, g = lane >> 2, tq = lane & 3, m = lane >> 3, r8 = lane & 7;
  const unsigned bar = sb + SM_BAR;
  unsigned st = 0, ph = 0, seq = 0, sph = 0;
  float d[128];
  while (true) {
    mbar_wait(bar + 8 * (MB_FULL + st), ph);
    const int idr = misc[seq & 3]; seq++;
    const int idx = idr & 65535;
    if (idr < 0 || idx >= N_ITEMS) break;
    if (t == 0) ISTAMP(idx, 2);
    const Item it = decode_item(idx);
    const int nkb = item_nkb(it.type);
    if (it.type == T_ATT) {
      unsigned km[16], vm[8], kn[16], vn[8];
      const bool pref = idr >= 65536;
      if (pref) bulk_att_load(kn, vn, it.b, it.c, 0, w, lane);
      mbar_wait(bar + 8 * MB_STGE, sph ^ 1);
#pragma unroll 1
      for (int kb = 0; kb < 4; kb++) {
        if (!pref) {
          if (lane < 2) wait_flag_ge(&g_flags.rec[it.c * 4 + (kb & 1) * 2 + lane], it.b * 4 + (kb >> 1) * 2 + wg + 1);
          __syncwarp();
          bulk_att_load(kn, vn, it.b, it.c, kb, w, lane);
        }
        if (kb) mbar_wait(bar + 8 * (MB_FULL + st), ph);
#pragma unroll
        for (int i = 0; i < 16; i++) km[i] = kn[i];
#pragma unroll
        for (int i = 0; i < 8; i++) vm[i] = vn[i];
        if (pref && kb != 3) bulk_att_load(kn, vn, it.b, it.c, kb + 1, w, lane);
        bulk_att_stage(sb + st * STAGE_BYTES, sb + B_STG, km, vm, kb, w, lane);
        __syncwarp();
        if (lane == 0) mbar_arrive(bar + 8 * (MB_EMPTY + st));
        if (++st == NSTAGE) { st = 0; ph ^= 1; }
      }
      if (t == 0) misc[4] = idx;
      fence_proxy_async_smem();
      mbar_arrive(bar + 8 * MB_STGF); sph ^= 1;
      continue;
    }
    if (it.type >= T_RED) {
      __syncwarp();
      if (lane == 0) mbar_arrive(bar + 8 * (MB_EMPTY + st));
      if (++st == NSTAGE) { st = 0; ph ^= 1; }
      if (it.type == T_RED) {
#pragma unroll 2
        for (int i = 0; i < 8; i++) {
          size_t o = ((size_t)it.b * 128 + it.c * 16 + i * 2 + (t >> 7)) * DM + (t & 127) * 4;
          float4 a = __ldcg(reinterpret_cast<const float4*>(g_opart + o)), b = __ldcg(reinterpret_cast<const float4*>(g_opart + o + (size_t)S_TOK * DM));
          float4 c = __ldcg(reinterpret_cast<const float4*>(g_opart + o + (size_t)2 * S_TOK * DM)), e = __ldcg(reinterpret_cast<const float4*>(g_opart + o + (size_t)3 * S_TOK * DM));
          final_out(out, x, o, make_float4((a.x + b.x) + (c.x + e.x), (a.y + b.y) + (c.y + e.y), (a.z + b.z) + (c.z + e.z), (a.w + b.w) + (c.w + e.w)));
        }
      } else {
        size_t ol = ((size_t)it.c * 2 + (t >> 7)) * DM + (t & 127) * 4;
        float4 v[16];
#pragma unroll
        for (int i = 0; i < 16; i++) v[i] = __ldcg(reinterpret_cast<const float4*>(g_opl + ol + (size_t)i * 128 * DM));
#pragma unroll
        for (int st2 = 1; st2 < 16; st2 <<= 1)
#pragma unroll
          for (int i = 0; i < 16; i += 2 * st2) { v[i].x += v[i + st2].x; v[i].y += v[i + st2].y; v[i].z += v[i + st2].z; v[i].w += v[i + st2].w; }
        final_out(out, x, ol + (size_t)15 * 128 * DM, v[0]);
      }
      if (t == 0) ISTAMP(idx, 3);
      continue;
    }
    unsigned pst = 0, bv[32];
#pragma unroll
    for (int i = 0; i < 128; i++) d[i] = 0.0f;
    if (it.type == T_M1 || it.type == T_M2) {
      const unsigned* bp = reinterpret_cast<const unsigned*>((it.type == T_M1 ? b1 : b2) + it.c * 256) + tq;
#pragma unroll
      for (int i = 0; i < 32; i++) asm volatile("ld.global.nc.u32 %0, [%1];" : "=r"(bv[i]) : "l"(bp + i * 4));
    } else {
#pragma unroll
      for (int i = 0; i < 32; i++) bv[i] = 0;
    }
    for (int kb = 0; kb < nkb; kb++) {
      if (kb) mbar_wait(bar + 8 * (MB_FULL + st), ph);
      unsigned sa = sb + st * STAGE_BYTES;
      uint64_t ad = mkdesc(sa + wg * 8192, 16, 1024), bd = mkdesc(sa + 16384, 8192, 1024);
      asm volatile("wgmma.fence.sync.aligned;" ::: "memory");
#pragma unroll
      for (int k = 0; k < 4; k++) wgmma_n256(d, ad + k * 2, bd + k * 128, (kb | k) != 0);
      asm volatile("wgmma.commit_group.sync.aligned;" ::: "memory");
      if (kb) {
        asm volatile("wgmma.wait_group.sync.aligned 1;" ::: "memory");
        if (lane == 0) mbar_arrive(bar + 8 * (MB_EMPTY + pst));
      }
      pst = st;
      if (++st == NSTAGE) { st = 0; ph ^= 1; }
    }
    asm volatile("wgmma.wait_group.sync.aligned 0;" ::: "memory");
    if (lane == 0) mbar_arrive(bar + 8 * (MB_EMPTY + pst));
    if (it.type >= T_OUT) {
      const int col = it.c * 256 + 2 * tq;
      float* pp = it.type == T_OUT ? g_opart + ((size_t)it.ks * S_TOK + it.b * 128 + w * 16 + g) * DM + col : g_opl + ((size_t)it.ks * 128 + w * 16 + g) * DM + col;
#pragma unroll
      for (int i = 0; i < 32; i++) {
        __stcg(reinterpret_cast<float2*>(pp + i * 8), make_float2(d[4 * i], d[4 * i + 1]));
        __stcg(reinterpret_cast<float2*>(pp + 8 * DM + i * 8), make_float2(d[4 * i + 2], d[4 * i + 3]));
      }
      bar_sync(1, 256);
      if (t == 0) { red_release_add(&g_flags.p[it.b], 1); ISTAMP(idx, 3); }
      continue;
    }
#define ACT(F) _Pragma("unroll") for (int i = 0; i < 32; i++) { \
        unsigned u0 = badd2(pack_bf16(d[4 * i], d[4 * i + 1]), bv[i]), u1 = badd2(pack_bf16(d[4 * i + 2], d[4 * i + 3]), bv[i]); \
        d[4 * i] = F(bf_lo(u0)); d[4 * i + 1] = F(bf_hi(u0)); d[4 * i + 2] = F(bf_lo(u1)); d[4 * i + 3] = F(bf_hi(u1)); }
    if (it.type == T_M1) { ACT(gelu_t) } else if (it.type == T_M2) { ACT(silu_f) }
    mbar_wait(bar + 8 * MB_STGE, sph ^ 1);
    {
      const unsigned ob = sb + B_STG + (w * 16 + (m & 1) * 8 + r8) * 128;
#pragma unroll
      for (int i = 0; i < 16; i++)
        stsm_x4(ob + (i >> 2) * 16384 + ((((i & 3) * 2 + (m >> 1)) ^ r8) << 4), pack_bf16(d[8 * i], d[8 * i + 1]), pack_bf16(d[8 * i + 2], d[8 * i + 3]),
                pack_bf16(d[8 * i + 4], d[8 * i + 5]), pack_bf16(d[8 * i + 6], d[8 * i + 7]));
    }
    if (t == 0) misc[4] = idx;
    fence_proxy_async_smem();
    mbar_arrive(bar + 8 * MB_STGF); sph ^= 1;
  }
  mbar_wait(bar + 8 * MB_STGE, sph ^ 1);
  if (t == 0) misc[4] = -1;
  mbar_arrive(bar + 8 * MB_STGF);
}

__global__ void __launch_bounds__(384, 1)
k_main(const __grid_constant__ Maps maps, const bf16* __restrict__ x, const bf16* __restrict__ mem0, const bf16* __restrict__ b1, const bf16* __restrict__ b2, bf16* __restrict__ out, int helper) {
  extern __shared__ unsigned char smem_raw[];
  const unsigned sraw = smem_u32(smem_raw);
  const unsigned sb = (sraw + 1023u) & ~1023u;
  int* misc = reinterpret_cast<int*>(smem_raw + (sb - sraw) + SM_MISC);
  const int w = threadIdx.x >> 5;
  const bool rec = !helper && blockIdx.x < NREC;
  if (!helper) asm volatile("griddepcontrol.launch_dependents;");
  if (threadIdx.x == 0) {
    const unsigned bar = sb + SM_BAR;
    for (int i = 0; i < 8; i++) { mbar_init(bar + 8 * (MB_FULL + i), 1); mbar_init(bar + 8 * (MB_EMPTY + i), rec ? 1 : 8); }
    mbar_init(bar + 8 * MB_STGF, 256); mbar_init(bar + 8 * MB_STGE, 1);
    for (int i = MB_W0; i <= MB_AG; i++) mbar_init(bar + 8 * i, 1);
    if (rec) { mbar_expect_tx(bar + 8 * MB_S, 2560); mbar_expect_tx(bar + 8 * MB_V, 2048); mbar_expect_tx(bar + 8 * MB_RS, 8192); mbar_expect_tx(bar + 8 * MB_AG, 8192); }
    asm volatile("fence.mbarrier_init.release.cluster;" ::: "memory");
  }
  __syncthreads();
  asm volatile("barrier.cluster.arrive.release.aligned;\nbarrier.cluster.wait.acquire.aligned;" ::: "memory");
  if (DBGMODE && !rec) { if (helper) asm volatile("griddepcontrol.wait;" ::: "memory"); return; }
  if (w >= 8) {
    asm volatile("setmaxnreg.dec.sync.aligned.u32 24;");
    if (rec) { if (w == 8) rec_ring(maps, sb); else if (w == 9) rec_copy(sb); }
    else if (w == 8) bulk_producer(maps, sb, misc);
    else if ((threadIdx.x & 31) == 0) { if (w == 9) bulk_store(maps, sb, misc);
      else if (w == 10 && helper) asm volatile("griddepcontrol.wait;" ::: "memory"); }
  } else {
    if (rec) { asm volatile("setmaxnreg.inc.sync.aligned.u32 240;"); rec_worker(maps, sb, mem0); }
    else { asm volatile("setmaxnreg.inc.sync.aligned.u32 240;"); bulk_worker(sb, misc, x, b1, b2, out); }
  }
}

typedef CUresult (*EncFn)(CUtensorMap*, CUtensorMapDataType, cuuint32_t, void*, const cuuint64_t*, const cuuint64_t*, const cuuint32_t*, const cuuint32_t*,
                          CUtensorMapInterleave, CUtensorMapSwizzle, CUtensorMapL2promotion, CUtensorMapFloatOOBfill);
static void mk_map(EncFn enc, CUtensorMap* m, const void* ptr, uint64_t rows, uint64_t cols, uint32_t box_rows) {
  cuuint64_t dims[2] = {cols, rows}; cuuint64_t strides[1] = {cols * 2};
  cuuint32_t box[2] = {64, box_rows}, es[2] = {1, 1};
  enc(m, CU_TENSOR_MAP_DATA_TYPE_BFLOAT16, 2, const_cast<void*>(ptr), dims, strides, box, es, CU_TENSOR_MAP_INTERLEAVE_NONE, CU_TENSOR_MAP_SWIZZLE_128B,
      CU_TENSOR_MAP_L2_PROMOTION_L2_256B, CU_TENSOR_MAP_FLOAT_OOB_FILL_NONE);
}
extern "C" void kernel_launch(void* const* d_in, const int* in_sizes, int n_in, void* d_out, int out_size) {
  static EncFn enc = nullptr;
  static int ncl = 0, nhelp = 0;
  static void *p_xn, *p_y, *p_h1, *p_o, *p_qkv, *p_g;
  if (!enc) {
    void* fn = nullptr; cudaDriverEntryPointQueryResult qr;
    cudaGetDriverEntryPoint("cuTensorMapEncodeTiled", &fn, cudaEnableDefault, &qr);
    enc = (EncFn)fn;
    cudaGetSymbolAddress(&p_xn, g_xn); cudaGetSymbolAddress(&p_y, g_y); cudaGetSymbolAddress(&p_h1, g_h1);
    cudaGetSymbolAddress(&p_o, g_o); cudaGetSymbolAddress(&p_qkv, g_qkv); cudaGetSymbolAddress(&p_g, g_g);
    cudaFuncSetAttribute(k_main, cudaFuncAttributeMaxDynamicSharedMemorySize, SMEM_TOTAL);
    cudaLaunchConfig_t cfg = {}; cfg.gridDim = dim3(128); cfg.blockDim = dim3(384); cfg.dynamicSmemBytes = SMEM_TOTAL;
    cudaLaunchAttribute at[1]; at[0].id = cudaLaunchAttributeClusterDimension; at[0].val.clusterDim.x = CLS; at[0].val.clusterDim.y = 1; at[0].val.clusterDim.z = 1;
    cfg.attrs = at; cfg.numAttrs = 1;
    if (cudaOccupancyMaxActiveClusters(&ncl, k_main, &cfg) != cudaSuccess) { cudaGetLastError(); ncl = 14; }
    ncl = ncl > 16 ? 16 : (ncl < 9 ? 9 : ncl);
    int nsm = 0, dev = 0; cudaGetDevice(&dev); cudaDeviceGetAttribute(&nsm, cudaDevAttrMultiProcessorCount, dev);
    nhelp = nsm - ncl * CLS;
  }
  Maps maps;
  mk_map(enc, &maps.xn, p_xn, S_TOK, DM, 128); mk_map(enc, &maps.y, p_y, S_TOK, DM, 128); mk_map(enc, &maps.h1, p_h1, S_TOK, FF, 128);
  mk_map(enc, &maps.o, p_o, S_TOK, HD, 128); mk_map(enc, &maps.qkv_st, p_qkv, S_TOK, 3 * HD, 128); mk_map(enc, &maps.qkv_ld, p_qkv, S_TOK, 3 * HD, 32);
  mk_map(enc, &maps.g, p_g, S_TOK, DM, 128);
  mk_map(enc, &maps.wq, d_in[2], DM, HD, 64); mk_map(enc, &maps.wk, d_in[3], DM, HD, 64); mk_map(enc, &maps.wv, d_in[4], DM, HD, 64);
  mk_map(enc, &maps.wo, d_in[5], HD, DM, 64); mk_map(enc, &maps.w1, d_in[8], DM, FF, 64); mk_map(enc, &maps.w2, d_in[10], FF, DM, 64);
  cudaStream_t st = cudaStreamPerThread;
  k_pre<<<256, 256, 0, st>>>((const bf16*)d_in[0]);
  cudaLaunchConfig_t cfg = {}; cfg.gridDim = dim3(ncl * CLS); cfg.blockDim = dim3(384); cfg.dynamicSmemBytes = SMEM_TOTAL; cfg.stream = st;
  cudaLaunchAttribute at[1]; at[0].id = cudaLaunchAttributeClusterDimension; at[0].val.clusterDim.x = CLS; at[0].val.clusterDim.y = 1; at[0].val.clusterDim.z = 1;
  cfg.attrs = at; cfg.numAttrs = 1;
  cudaLaunchKernelEx(&cfg, k_main, maps, (const bf16*)d_in[0], (const bf16*)d_in[1], (const bf16*)d_in[9], (const bf16*)d_in[11], (bf16*)d_out, 0);
  if (nhelp > 0) {
    cfg.gridDim = dim3(nhelp);
    at[0].id = cudaLaunchAttributeProgrammaticStreamSerialization; at[0].val.programmaticStreamSerializationAllowed = 1;
    cudaLaunchKernelEx(&cfg, k_main, maps, (const bf16*)d_in[0], (const bf16*)d_in[1], (const bf16*)d_in[9], (const bf16*)d_in[11], (bf16*)d_out, 1);
  }
}
```

```cpp
#include <cuda_runtime.h>
#include <cuda_bf16.h>
#include <cuda.h>
#include <stdint.h>

typedef __nv_bfloat16 bf16;

#define S_TOK 2048
#define DM 512
#define NH 32
#define DH 128
#define HD 4096
#define NMEM 8
#define SEG 32
#define NSEG 64
#define FF 1792
#define NBLK 16
#define NREC 64
#define REPL 0
#define CLS 8

__device__ __align__(1024) bf16 g_xn[S_TOK * DM];
__device__ __align__(1024) bf16 g_y[S_TOK * DM];
__device__ __align__(1024) bf16 g_qkv[(size_t)S_TOK * 3 * HD];
__device__ __align__(1024) bf16 g_h1[S_TOK * FF];
__device__ __align__(1024) bf16 g_g[S_TOK * DM];
__device__ __align__(1024) bf16 g_o[(size_t)S_TOK * HD];
__device__ __align__(1024) bf16 g_km[NSEG * NH * NMEM * DH];
__device__ __align__(1024) bf16 g_vmt[NSEG * NH * DH * NMEM];
__device__ __align__(1024) float g_opart[(size_t)4 * S_TOK * DM];
__device__ __align__(1024) float g_opl[(size_t)16 * 128 * DM];
__device__ __align__(1024) unsigned g_part[8 * 2 * 8 * 8 * 512];
struct Flags {
  unsigned qkv[NBLK * 48];
  unsigned h1[NBLK];
  unsigned g[NBLK];
  unsigned o[NBLK * 4];
  unsigned p[NBLK];
  unsigned o16[16];
  unsigned ctr;
  unsigned rec[NREC];
  unsigned abort_;
};
__device__ __align__(1024) Flags g_flags;

#define RSTAMP(k)
#define DBGMODE 0
#define ISTAMP(i, k)
__device__ __forceinline__ unsigned smem_u32(const void* p) { return (unsigned)__cvta_generic_to_shared(p); }
__device__ __forceinline__ float bf16r(float x) { unsigned u; asm("cvt.rn.bf16x2.f32 %0, %1, %2;" : "=r"(u) : "f"(x), "f"(0.0f)); return __uint_as_float(u); }
__device__ __forceinline__ unsigned pack_bf16(float lo, float hi) {
  __nv_bfloat162 v = __floats2bfloat162_rn(lo, hi);
  return *reinterpret_cast<unsigned*>(&v);
}
__device__ __forceinline__ float bf_lo(unsigned u) { return __uint_as_float(u << 16); }
__device__ __forceinline__ float bf_hi(unsigned u) { return __uint_as_float(u & 0xffff0000u); }

#define SPIN_LIMIT (1u << 20)
#define TRAP_IF(x) if ((x) > SPIN_LIMIT) { asm volatile("st.global.u32 [%0], %1;" ::"l"(0ull), "r"(0u) : "memory"); break; }
__device__ __forceinline__ unsigned ld_acquire(const unsigned* p) {
  unsigned v; asm volatile("ld.acquire.gpu.global.u32 %0, [%1];" : "=r"(v) : "l"(p) : "memory"); return v;
}
__device__ __forceinline__ unsigned ld_relaxed(const unsigned* p) {
  unsigned v; asm volatile("ld.relaxed.gpu.global.u32 %0, [%1];" : "=r"(v) : "l"(p) : "memory"); return v;
}
__device__ __forceinline__ void red_release_add(unsigned* p, unsigned v) {
  asm volatile("red.release.gpu.global.add.u32 [%0], %1;" ::"l"(p), "r"(v) : "memory");
}
__device__ __forceinline__ void st_release(unsigned* p, unsigned v) {
  asm volatile("st.release.gpu.global.u32 [%0], %1;" ::"l"(p), "r"(v) : "memory");
}
__device__ __forceinline__ void wait_flag_ge(const unsigned* p, unsigned target) {
  unsigned it = 0;
  while (ld_acquire(p) < target) {
    __nanosleep(64);
    TRAP_IF(++it);
  }
}
__device__ __forceinline__ uint4 ldv4_relaxed(const void* p) {
  uint4 a; asm volatile("ld.relaxed.gpu.global.v4.u32 {%0,%1,%2,%3}, [%4];" : "=r"(a.x), "=r"(a.y), "=r"(a.z), "=r"(a.w) : "l"(p) : "memory"); return a;
}
__device__ __forceinline__ uint2 ldv2_relaxed(const void* p) {
  uint2 a; asm volatile("ld.relaxed.gpu.global.v2.u32 {%0,%1}, [%2];" : "=r"(a.x), "=r"(a.y) : "l"(p) : "memory"); return a;
}
__device__ __forceinline__ void mbar_init(unsigned mb, unsigned cnt) { asm volatile("mbarrier.init.shared::cta.b64 [%0], %1;" ::"r"(mb), "r"(cnt) : "memory"); }
__device__ __forceinline__ void mbar_expect_tx(unsigned mb, unsigned bytes) { asm volatile("mbarrier.arrive.expect_tx.shared::cta.b64 _, [%0], %1;" ::"r"(mb), "r"(bytes) : "memory"); }
__device__ __forceinline__ void mbar_arrive(unsigned mb) { asm volatile("mbarrier.arrive.shared::cta.b64 _, [%0];" ::"r"(mb) : "memory"); }
__device__ __forceinline__ void mbar_wait(unsigned mb, unsigned parity) {
  unsigned ok, it = 0;
  while (true) {
    asm volatile("{.reg .pred p; mbarrier.try_wait.parity.shared::cta.b64 p, [%1], %2; selp.u32 %0,1,0,p;}" : "=r"(ok) : "r"(mb), "r"(parity) : "memory");
    if (ok) break;
    TRAP_IF(++it);
  }
}
__device__ __forceinline__ void mbar_wait_sleep(unsigned mb, unsigned parity) {
  unsigned ok, it = 0;
  while (true) {
    asm volatile("{.reg .pred p; mbarrier.test_wait.parity.shared::cta.b64 p, [%1], %2; selp.u32 %0,1,0,p;}" : "=r"(ok) : "r"(mb), "r"(parity) : "memory");
    if (ok) break;
    __nanosleep(200);
    TRAP_IF(++it);
  }
}
__device__ __forceinline__ float ex2f(float x) { float y; asm("ex2.approx.ftz.f32 %0, %1;" : "=f"(y) : "f"(x)); return y; }
__device__ __forceinline__ int opaque_tid() { int t = threadIdx.x; t = __shfl_sync(~0u, t, t & 31); return t; }
#define LOG2E 1.4426950408889634f
__device__ __forceinline__ void mbar_wait_cluster(unsigned mb, unsigned parity) {
  unsigned ok, it = 0;
  while (true) {
    asm volatile("{.reg .pred p; mbarrier.try_wait.parity.acquire.cluster.shared::cta.b64 p, [%1], %2; selp.u32 %0,1,0,p;}" : "=r"(ok) : "r"(mb), "r"(parity) : "memory");
    if (ok) break;
    TRAP_IF(++it);
  }
}
__device__ __forceinline__ void bar_sync(int id, int n) { asm volatile("bar.sync %0, %1;" ::"r"(id), "r"(n) : "memory"); }
__device__ __forceinline__ void bar_arrive(int id, int n) { asm volatile("bar.arrive %0, %1;" ::"r"(id), "r"(n) : "memory"); }
__device__ __forceinline__ void tma_load_2d(unsigned dst, const CUtensorMap* map, int c0, int c1, unsigned mb) {
  asm volatile("cp.async.bulk.tensor.2d.shared::cluster.global.mbarrier::complete_tx::bytes [%0], [%1, {%3, %4}], [%2];"
               ::"r"(dst), "l"((uint64_t)map), "r"(mb), "r"(c0), "r"(c1) : "memory");
}
__device__ __forceinline__ void tma_store_2d(const CUtensorMap* map, unsigned src, int c0, int c1) {
  asm volatile("cp.async.bulk.tensor.2d.global.shared::cta.bulk_group [%0, {%2, %3}], [%1];"
               ::"l"((uint64_t)map), "r"(src), "r"(c0), "r"(c1) : "memory");
}
__device__ __forceinline__ void fence_proxy_async() { asm volatile("fence.proxy.async;" ::: "memory"); }
__device__ __forceinline__ void fence_proxy_async_smem() { asm volatile("fence.proxy.async.shared::cta;" ::: "memory"); }
__device__ __forceinline__ void ldsm_x4(unsigned* r, unsigned addr) {
  asm volatile("ldmatrix.sync.aligned.m8n8.x4.shared.b16 {%0,%1,%2,%3}, [%4];" : "=r"(r[0]), "=r"(r[1]), "=r"(r[2]), "=r"(r[3]) : "r"(addr) : "memory");
}
__device__ __forceinline__ void ldsm_x4_t(unsigned* r, unsigned addr) {
  asm volatile("ldmatrix.sync.aligned.m8n8.x4.trans.shared.b16 {%0,%1,%2,%3}, [%4];" : "=r"(r[0]), "=r"(r[1]), "=r"(r[2]), "=r"(r[3]) : "r"(addr) : "memory");
}
__device__ __forceinline__ void stsm_x2_t(unsigned addr, unsigned r0, unsigned r1) {
  asm volatile("stmatrix.sync.aligned.m8n8.x2.trans.shared.b16 [%0], {%1,%2};" ::"r"(addr), "r"(r0), "r"(r1) : "memory");
}
__device__ __forceinline__ void stsm_x4(unsigned addr, unsigned r0, unsigned r1, unsigned r2, unsigned r3) {
  asm volatile("stmatrix.sync.aligned.m8n8.x4.shared.b16 [%0], {%1,%2,%3,%4};" ::"r"(addr), "r"(r0), "r"(r1), "r"(r2), "r"(r3) : "memory");
}
__device__ __forceinline__ void mma16816(float* d, const unsigned* a, unsigned b0, unsigned b1) {
  asm volatile("mma.sync.aligned.m16n8k16.row.col.f32.bf16.bf16.f32 {%0,%1,%2,%3}, {%4,%5,%6,%7}, {%8,%9}, {%0,%1,%2,%3};"
               : "+f"(d[0]), "+f"(d[1]), "+f"(d[2]), "+f"(d[3]) : "r"(a[0]), "r"(a[1]), "r"(a[2]), "r"(a[3]), "r"(b0), "r"(b1));
}
__device__ __forceinline__ void mma1688(float* d, unsigned a0, unsigned a1, unsigned b0) {
  asm volatile("mma.sync.aligned.m16n8k8.row.col.f32.bf16.bf16.f32 {%0,%1,%2,%3}, {%4,%5}, {%6}, {%0,%1,%2,%3};"
               : "+f"(d[0]), "+f"(d[1]), "+f"(d[2]), "+f"(d[3]) : "r"(a0), "r"(a1), "r"(b0));
}
__device__ __forceinline__ uint64_t mkdesc(unsigned addr, unsigned lbo, unsigned sbo) {
  return (uint64_t)((addr >> 4) & 0x3fff) | ((uint64_t)(lbo >> 4) << 16) | ((uint64_t)(sbo >> 4) << 32) | (1ull << 62);
}
#define R8(b) "+f"(d[b]), "+f"(d[b + 1]), "+f"(d[b + 2]), "+f"(d[b + 3]), "+f"(d[b + 4]), "+f"(d[b + 5]), "+f"(d[b + 6]), "+f"(d[b + 7])
#define R32(b) R8(b), R8(b + 8), R8(b + 16), R8(b + 24)
__device__ __forceinline__ void wgmma_n256(float* d, uint64_t ad, uint64_t bd, int acc) {
  asm volatile(
      "{.reg .pred p; setp.ne.b32 p, %130, 0;\n"
      "wgmma.mma_async.sync.aligned.m64n256k16.f32.bf16.bf16 "
      "{%0,%1,%2,%3,%4,%5,%6,%7,%8,%9,%10,%11,%12,%13,%14,%15,%16,%17,%18,%19,%20,%21,%22,%23,%24,%25,%26,%27,%28,%29,%30,%31,"
      "%32,%33,%34,%35,%36,%37,%38,%39,%40,%41,%42,%43,%44,%45,%46,%47,%48,%49,%50,%51,%52,%53,%54,%55,%56,%57,%58,%59,%60,%61,%62,%63,"
      "%64,%65,%66,%67,%68,%69,%70,%71,%72,%73,%74,%75,%76,%77,%78,%79,%80,%81,%82,%83,%84,%85,%86,%87,%88,%89,%90,%91,%92,%93,%94,%95,"
      "%96,%97,%98,%99,%100,%101,%102,%103,%104,%105,%106,%107,%108,%109,%110,%111,%112,%113,%114,%115,%116,%117,%118,%119,%120,%121,%122,%123,%124,%125,%126,%127},"
      "%128, %129, p, 1, 1, 0, 1;}\n"
      : R32(0), R32(32), R32(64), R32(96)
      : "l"(ad), "l"(bd), "r"(acc));
}

__device__ __forceinline__ void ln16(const float* x, float* o) {
  float s = 0;
#pragma unroll
  for (int i = 0; i < 16; i++) s += x[i];
#pragma unroll
  for (int of = 16; of > 0; of >>= 1) s += __shfl_xor_sync(~0u, s, of);
  float mean = s * (1.0f / DM);
  float v = 0;
#pragma unroll
  for (int i = 0; i < 16; i++) { float dd = x[i] - mean; v += dd * dd; }
#pragma unroll
  for (int of = 16; of > 0; of >>= 1) v += __shfl_xor_sync(~0u, v, of);
  float mb = bf16r(mean);
  float vb = bf16r(v * (1.0f / DM));
  float den = bf16r(sqrtf(bf16r(vb + 1e-5f)));
#pragma unroll
  for (int i = 0; i < 16; i++) o[i] = bf16r(__fdiv_rn(bf16r(x[i] - mb), den));
}
__global__ void __launch_bounds__(256) k_pre(const bf16* __restrict__ x) {
  int t = threadIdx.x, lane = t & 31, w = t >> 5;
  int row = blockIdx.x * 8 + w;
  const uint4* src = reinterpret_cast<const uint4*>(x + (size_t)row * DM);
  uint4 a = src[lane], b = src[lane + 32];
  unsigned u[8] = {a.x, a.y, a.z, a.w, b.x, b.y, b.z, b.w};
  float f[16], o[16], o2[16];
#pragma unroll
  for (int i = 0; i < 8; i++) { f[2 * i] = bf_lo(u[i]); f[2 * i + 1] = bf_hi(u[i]); }
  ln16(f, o);
  ln16(o, o2);
  uint4* d1 = reinterpret_cast<uint4*>(g_xn + (size_t)row * DM);
  uint4* d2 = reinterpret_cast<uint4*>(g_y + (size_t)row * DM);
  d1[lane] = make_uint4(pack_bf16(o[0], o[1]), pack_bf16(o[2], o[3]), pack_bf16(o[4], o[5]), pack_bf16(o[6], o[7]));
  d1[lane + 32] = make_uint4(pack_bf16(o[8], o[9]), pack_bf16(o[10], o[11]), pack_bf16(o[12], o[13]), pack_bf16(o[14], o[15]));
  d2[lane] = make_uint4(pack_bf16(o2[0], o2[1]), pack_bf16(o2[2], o2[3]), pack_bf16(o2[4], o2[5]), pack_bf16(o2[6], o2[7]));
  d2[lane + 32] = make_uint4(pack_bf16(o2[8], o2[9]), pack_bf16(o2[10], o2[11]), pack_bf16(o2[12], o2[13]), pack_bf16(o2[14], o2[15]));
  int gt = blockIdx.x * 256 + t;
  uint4 z = make_uint4(0, 0, 0, 0);
  if (gt < 16384) reinterpret_cast<uint4*>(g_part)[gt] = z;
  if (gt < (int)(sizeof(Flags) / 4)) reinterpret_cast<unsigned*>(&g_flags)[gt] = 0;
}

struct Maps { CUtensorMap xn, y, h1, o, qkv_st, qkv_ld, g, wq, wk, wv, wo, w1, w2; };

#define NSTAGE 3
#define STAGE_BYTES 49152
#define B_STG (NSTAGE * STAGE_BYTES)
#define R_WO 0
#define R_T1 65536
#define R_T2 131072
#define R_RING 65536
#define RING_N 4
#define RING_BYTES 12288
#define R_MEM 196608
#define R_QS (R_MEM + 8448)
#define R_KS (R_QS + 1152)
#define R_OS (R_KS + 1152)
#define R_SOWN (R_OS + 2176)
#define R_SPEER (R_SOWN + 1280)
#define R_VM (R_SPEER + 1280)
#define R_VRED (R_VM + 2048)
#define R_RS (R_VRED + 6144)
#define SM_BAR (R_RS + 8192)
#define SMEM_TOTAL (SM_BAR + 256 + 1024)
#define MB_FULL 0
#define MB_EMPTY 8
#define MB_STGF 16
#define MB_STGE 17
#define MB_W0 18
#define MB_W1 19
#define MB_WO 20
#define MB_S 21
#define MB_V 22
#define MB_KVR 23
#define MB_KVF 24
#define MB_RS 25
#define MB_AG 26
#define SM_MISC (SM_BAR + 224)

#define N_KV 512
#define I_M1 512
#define I_Q 624
#define I_M2 880
#define I_POST 912
#define I_TAIL (I_POST + 16 * 32)
#define N_ITEMS (I_TAIL + 5 * 8 + 32 + 8 + 64)
enum { T_QKV = 0, T_M1 = 1, T_M2 = 2, T_ATT = 3, T_OUT = 4, T_OUTL = 5, T_RED = 6, T_REDL = 7 };
struct Item { int type, b, c, ks; };
__device__ __forceinline__ Item decode_item(int i) {
  Item it; it.ks = 0;
  if (i < N_KV) { it.type = T_QKV; it.b = i >> 5; it.c = 16 + (i & 31); }
  else if (i < I_Q) { it.type = T_M1; it.b = (i - I_M1) / 7; it.c = (i - I_M1) % 7; }
  else if (i < I_M2) { it.type = T_QKV; it.b = (i - I_Q) >> 4; it.c = (i - I_Q) & 15; }
  else if (i < I_POST) { it.type = T_M2; it.b = (i - I_M2) >> 1; it.c = (i - I_M2) & 1; }
  else if (i < I_TAIL) {
    int x = i - I_POST, p = x >> 5, r = x & 31;
    if (r < 16) { it.type = T_ATT; it.b = p; it.c = r; }
    else if (r < 24) { it.type = T_OUT; it.b = p - 3; it.c = r & 1; it.ks = (r - 16) >> 1; }
    else { it.type = T_RED; it.b = p - 5; it.c = r - 24; }
  } else {
    int x = i - I_TAIL, r = x & 7;
    if (x < 40) {
      int q = x >> 3;
      if (q == 0 || q == 2) { it.type = T_OUT; it.b = 13 + (q >> 1); it.c = r & 1; it.ks = r >> 1; }
      else { it.type = T_RED; it.b = q == 1 ? 11 : 9 + q; it.c = r; }
    }
    else if (x < 72) { it.type = T_OUTL; it.b = 15; it.c = x & 1; it.ks = (x - 40) >> 1; }
    else if (x < 80) { it.type = T_RED; it.b = 14; it.c = r; }
    else { it.type = T_REDL; it.b = 15; it.c = x - 80; }
  }
  return it;
}
__device__ __forceinline__ int item_nkb(int type) { return type == T_M2 ? 28 : (type == T_OUT ? 16 : (type >= T_RED ? 1 : (type >= T_ATT ? 4 : 8))); }

__device__ __forceinline__ void st_async_b64(unsigned raddr, unsigned lo, unsigned hi, unsigned rmb) {
  asm volatile("st.async.weak.shared::cluster.mbarrier::complete_tx::bytes.v2.b32 [%0], {%1,%2}, [%3];" ::"r"(raddr), "r"(lo), "r"(hi), "r"(rmb) : "memory");
}
__device__ __forceinline__ void st_async_b32(unsigned raddr, unsigned v, unsigned rmb) {
  asm volatile("st.async.weak.shared::cluster.mbarrier::complete_tx::bytes.b32 [%0], %1, [%2];" ::"r"(raddr), "r"(v), "r"(rmb) : "memory");
}
__device__ __forceinline__ unsigned mapa(unsigned a, unsigned rank) {
  unsigned r; asm volatile("mapa.shared::cluster.u32 %0, %1, %2;" : "=r"(r) : "r"(a), "r"(rank)); return r;
}
__device__ __forceinline__ void sts64(unsigned a, unsigned x, unsigned y) { asm volatile("st.shared.v2.b32 [%0], {%1,%2};" ::"r"(a), "r"(x), "r"(y) : "memory"); }
__device__ __forceinline__ void sts128(unsigned a, uint4 v) { asm volatile("st.shared.v4.b32 [%0], {%1,%2,%3,%4};" ::"r"(a), "r"(v.x), "r"(v.y), "r"(v.z), "r"(v.w) : "memory"); }
__device__ __forceinline__ uint2 lds64(unsigned a) { uint2 v; asm volatile("ld.shared.v2.b32 {%0,%1}, [%2];" : "=r"(v.x), "=r"(v.y) : "r"(a) : "memory"); return v; }
__device__ __forceinline__ uint4 lds128(unsigned a) { uint4 v; asm volatile("ld.shared.v4.b32 {%0,%1,%2,%3}, [%4];" : "=r"(v.x), "=r"(v.y), "=r"(v.z), "=r"(v.w) : "r"(a) : "memory"); return v; }
__device__ __forceinline__ float lds32f(unsigned a) { float v; asm volatile("ld.shared.f32 %0, [%1];" : "=f"(v) : "r"(a) : "memory"); return v; }
#define spin_check(it) TRAP_IF(++it)
#define POLLV 0
#define BAR8 0
#define D_STAG 150
#define D_RED 480
#define D_PUB 0
#define DELAY(n) do { unsigned c0_, c1_; asm volatile("mov.u32 %0, %%clock;" : "=r"(c0_)); do { asm volatile("mov.u32 %0, %%clock;" : "=r"(c1_)); } while (c1_ - c0_ < (n)); } while (0)
#define NPRE1 0
#define VD 2
#define ZS 0
#define MBL 1
#define SCALE_QK 0.08838834764831845f

__device__ __forceinline__ void rec_worker(const Maps& maps, unsigned sb, const bf16* __restrict__ mem0) {
  const int c = blockIdx.x, h = c >> 1, j = c & 1;
  const int t = opaque_tid(), lane = t & 31, w = t >> 5, g = lane >> 2, tq = lane & 3;
  const int m = lane >> 3, r8 = lane & 7, kh = w >> 2, et = w & 3;
  const unsigned bar = sb + SM_BAR;
  unsigned wq[16][4], wk[16][4], wo[8][4];
  const unsigned woff = (kh * 4) * 8192 + ((m >> 1) * 8 + r8) * 128 + (((et * 2 + (m & 1)) ^ r8) << 4);
  mbar_wait(bar + 8 * MB_W0, 0);
#pragma unroll
  for (int i = 0; i < 16; i++) {
    ldsm_x4_t(wq[i], sb + R_WO + woff + (i >> 2) * 8192 + (i & 3) * 2048);
    ldsm_x4_t(wk[i], sb + R_T1 + woff + (i >> 2) * 8192 + (i & 3) * 2048);
  }
  bar_sync(2, 288);
  if (t == 0) {
    fence_proxy_async_smem();
    mbar_expect_tx(bar + 8 * MB_WO, 65536);
    for (int kb = 0; kb < 2; kb++)
      for (int cb = 0; cb < 4; cb++) tma_load_2d(sb + R_WO + (kb * 4 + cb) * 8192, &maps.wo, j * 256 + cb * 64, h * 128 + kb * 64, bar + 8 * MB_WO);
  }
  mbar_wait(bar + 8 * MB_W1, 0);
  const unsigned pV = sb + R_T2 + woff;
  const unsigned rk = c & 7, peer = rk ^ 1, cl = c >> 3;
#define KEEP(x) x = __shfl_sync(~0u, x, lane)
  unsigned pA = sb + R_MEM + kh * 4096 + lane * 16;
  unsigned pW0 = sb + R_WO + (w >> 1) * 8192 + ((m >> 1) * 8 + r8) * 128 + ((((w & 1) * 4 + (m & 1)) ^ r8) << 4);
#define pW1 (pW0 ^ 32)
  unsigned pVk = pV;
  unsigned aX = sb + R_VRED + et * 512 + lane * 16;
  unsigned aQKst = sb + (kh ? R_KS : R_QS) + r8 * 144 + (et * 16 + (m & 1) * 8) * 2;
  unsigned aL8_ = sb + lane * 8;
  unsigned aSl_ = mapa(sb + R_SOWN + w * 256 + lane * 8, rk), aSr_ = mapa(sb + R_SPEER + w * 256 + lane * 8, peer);
  const unsigned mbSl = mapa(bar + 8 * MB_S, rk), mbSr = mapa(bar + 8 * MB_S, peer), mbVl = mbSl + 8, mbVr = mbSr + 8;
  unsigned aQ_ = sb + R_QS + r8 * 144 + m * 16;
  unsigned oKx_ = (et * 8 + r8) * 128 + ((m ^ r8) << 4);
  unsigned oVx_ = 4096 + (et >> 1) * 4096 + ((m >> 1) * 8 + r8) * 128 + ((((et & 1) * 4 + (m & 1)) ^ r8) << 4);
  unsigned aOst_ = sb + R_OS + r8 * 272 + (et * 32 + m * 8) * 2;
  unsigned aOld = sb + R_OS + r8 * 272 + m * 16;
  unsigned aVm_ = sb + R_VM + et * 512 + lane * 8;
  unsigned aRSr = mapa(sb + R_RS + (h & 3) * 2048 + (w & 1) * 1024 + lane * 8, j * 4 + (w >> 1));
  unsigned t8 = t * 8;
  unsigned r1 = kh ? aL8_ : aSl_, r2 = kh ? oVx_ : aSr_, r3 = kh ? aOst_ : aQ_, r4 = kh ? aVm_ : oKx_;
#define aL8 r1
#define aSl r1
#define oVx r2
#define aSr r2
#define aOst r3
#define aQ r3
#define aVm r4
#define oKx r4
#define aVl (aSl + (R_VM - R_SOWN) + j * 1024)
#define aVr (aSr + (R_VM - R_SPEER) + j * 1024)
  KEEP(pA); KEEP(pW0); KEEP(pVk); KEEP(aX); KEEP(aQKst); KEEP(r1); KEEP(r2); KEEP(r3); KEEP(r4);
  KEEP(aOld); KEEP(aRSr); KEEP(t8);
  mbar_wait(bar + 8 * MB_WO, 0);
#pragma unroll
  for (int ks = 0; ks < 4; ks++) { ldsm_x4_t(wo[2 * ks], pW0 + ks * 2048); ldsm_x4_t(wo[2 * ks + 1], pW1 + ks * 2048); }
  {
    unsigned v[8];
#pragma unroll
    for (int q = 0; q < 8; q++) v[q] = __ldg(reinterpret_cast<const unsigned*>(mem0) + q * 256 + t);
    sts128(sb + R_MEM + t * 32, make_uint4(__byte_perm(v[0], v[1], 0x5410), __byte_perm(v[2], v[3], 0x5410), __byte_perm(v[4], v[5], 0x5410), __byte_perm(v[6], v[7], 0x5410)));
    sts128(sb + R_MEM + t * 32 + 16, make_uint4(__byte_perm(v[0], v[1], 0x7632), __byte_perm(v[2], v[3], 0x7632), __byte_perm(v[4], v[5], 0x7632), __byte_perm(v[6], v[7], 0x7632)));
  }
  bar_sync(1, 256);

#pragma unroll 1
  for (int s = 0;; s++) {
    const unsigned par = s & 1;
    const unsigned slot = s & (RING_N - 1), rpar = (s / RING_N) & 1;
    const unsigned ring = sb + R_RING + slot * RING_BYTES;
    RSTAMP(1);
    RSTAMP(2);
    float aq[4] = {0, 0, 0, 0}, ak[4] = {0, 0, 0, 0};
    {
      float aq1[4] = {0, 0, 0, 0}, ak1[4] = {0, 0, 0, 0};
      unsigned b[8][4];
#pragma unroll
      for (int i = 0; i < 4; i++) ldsm_x4_t(b[i], pA + i * 512);
#pragma unroll
      for (int i = 0; i < 8; i++) {
        mma16816(aq, wq[2 * i], b[i][0], b[i][1]); mma16816(ak, wk[2 * i], b[i][0], b[i][1]);
        mma16816(aq1, wq[2 * i + 1], b[i][2], b[i][3]); mma16816(ak1, wk[2 * i + 1], b[i][2], b[i][3]);
        if (i < 4) ldsm_x4_t(b[i + 4], pA + (i + 4) * 512);
      }
#pragma unroll
      for (int i = 0; i < 4; i++) { aq[i] += aq1[i]; ak[i] += ak1[i]; }
    }
    RSTAMP(3);
#define STSF4(a, v) asm volatile("st.shared.v4.f32 [%0], {%1,%2,%3,%4};" ::"r"(a), "f"(v[0]), "f"(v[1]), "f"(v[2]), "f"(v[3]) : "memory")
#define VLD(i) do { ldsm_x4_t(b[i], pA + (i) * 512); ldsm_x4_t(f0[i], pVk + ((i) >> 1) * 8192 + ((i) & 1) * 4096); ldsm_x4_t(f1[i], pVk + ((i) >> 1) * 8192 + ((i) & 1) * 4096 + 2048); } while (0)
#define VPASS() float av[4] = {0, 0, 0, 0}; { float av1[4] = {0, 0, 0, 0}; unsigned b[8][4], f1[8][4], f0[8][4]; VLD(0); if (VD > 1) VLD(1); \
      _Pragma("unroll") for (int i = 0; i < 8; i++) { if (i + VD < 8) VLD(i + VD); \
        mma16816(av, f0[i], b[i][0], b[i][1]); mma16816(av1, f1[i], b[i][2], b[i][3]); } \
      _Pragma("unroll") for (int i = 0; i < 4; i++) av[i] += av1[i]; }
    unsigned f[8][4];
#define WO_LD(i0, i1) do { _Pragma("unroll") for (int i = i0; i < i1; i++) { ldsm_x4_t(f[2 * i], pW0 + 32768 + i * 2048); ldsm_x4_t(f[2 * i + 1], pW1 + 32768 + i * 2048); } } while (0)
    if (kh) {
      STSF4(aX, aq);
      bar_sync(4 + et, 64);
      uint4 o = lds128(aX + 2048);
      stsm_x2_t(aQKst, pack_bf16(ak[0] + __uint_as_float(o.x), ak[1] + __uint_as_float(o.y)), pack_bf16(ak[2] + __uint_as_float(o.z), ak[3] + __uint_as_float(o.w)));
      bar_arrive(1, 256);
      RSTAMP(4);
      VPASS();
      STSF4(aX + 4096, av);
      bar_arrive(8 + et, 64);
      RSTAMP(5);
      if (s == NSEG - 1) {
        mbar_wait(bar + 8 * MB_V, par);
        if (t == 128) mbar_arrive(bar + 8 * MB_KVR);
        break;
      }
      mbar_wait(bar + 8 * (MB_FULL + slot), rpar);
      unsigned vx[4][4];
      ldsm_x4_t(vx[0], ring + oVx); ldsm_x4_t(vx[1], ring + oVx + 2048); ldsm_x4_t(vx[2], ring + (oVx ^ 32)); ldsm_x4_t(vx[3], ring + (oVx ^ 32) + 2048);
      WO_LD(0, NPRE1);
      RSTAMP(6); RSTAMP(7);
      mbar_wait(bar + 8 * MB_S, par);
      RSTAMP(8);
      float sc[10];
#pragma unroll
      for (int i = 0; i < 5; i++) {
        uint2 o = lds64(aL8 + R_SOWN + i * 256), p = lds64(aL8 + R_SPEER + i * 256);
        sc[2 * i] = __uint_as_float(o.x) + __uint_as_float(p.x); sc[2 * i + 1] = __uint_as_float(o.y) + __uint_as_float(p.y);
      }
      float mx = fmaxf(fmaxf(fmaxf(sc[0], sc[1]), fmaxf(sc[2], sc[3])), fmaxf(fmaxf(fmaxf(sc[4], sc[5]), fmaxf(sc[6], sc[7])), fmaxf(sc[8], sc[9])));
      mx = fmaxf(mx, __shfl_xor_sync(~0u, mx, 1)); mx = fmaxf(mx, __shfl_xor_sync(~0u, mx, 2));
      const float nm = -mx * (SCALE_QK * LOG2E);
      unsigned p[5];
#pragma unroll
      for (int i = 0; i < 5; i++) p[i] = pack_bf16(ex2f(fmaf(sc[2 * i], SCALE_QK * LOG2E, nm)), ex2f(fmaf(sc[2 * i + 1], SCALE_QK * LOG2E, nm)));
      RSTAMP(9);
      float o0[4] = {0, 0, 0, 0}, o1[4] = {0, 0, 0, 0}, o3[4] = {0, 0, 0, 0}, o4[4] = {0, 0, 0, 0}, z0[4] = {0, 0, 0, 0}, z1[4] = {0, 0, 0, 0};
      const unsigned ones[4] = {0x3F803F80u, 0u, 0x3F803F80u, 0u};
      mma16816(z0, ones, p[0], p[1]); mma16816(ZS ? z0 : z1, ones, p[2], p[3]);
      mma16816(o0, vx[0], p[0], p[1]); mma16816(o3, vx[2], p[0], p[1]); mma16816(o1, vx[1], p[2], p[3]); mma16816(o4, vx[3], p[2], p[3]);
      mma1688(z0, 0x3F803F80u, 0u, p[4]);
      mbar_wait(bar + 8 * MB_V, par);
      uint2 vm0 = lds64(aVm), vm1 = lds64(aVm + 256);
      mma1688(o0, vm0.x, vm0.y, p[4]); mma1688(o3, vm1.x, vm1.y, p[4]);
      float i0, i1;
      asm("rcp.approx.ftz.f32 %0, %1;" : "=f"(i0) : "f"(z0[0] + z1[0])); asm("rcp.approx.ftz.f32 %0, %1;" : "=f"(i1) : "f"(z0[1] + z1[1]));
      asm volatile("stmatrix.sync.aligned.m8n8.x4.trans.shared.b16 [%0], {%1,%2,%3,%4};" ::"r"(aOst), "r"(pack_bf16((o0[0] + o1[0]) * i0, (o0[1] + o1[1]) * i1)), "r"(pack_bf16((o0[2] + o1[2]) * i0, (o0[3] + o1[3]) * i1)),
                   "r"(pack_bf16((o3[0] + o4[0]) * i0, (o3[1] + o4[1]) * i1)), "r"(pack_bf16((o3[2] + o4[2]) * i0, (o3[3] + o4[3]) * i1)) : "memory");
      RSTAMP(10);
      bar_sync(1, 256);
      WO_LD(NPRE1, 3);
    } else {
      STSF4(aX + 2048, ak);
      unsigned kb[8];
      mbar_wait(bar + 8 * (MB_FULL + slot), rpar);
      ldsm_x4(kb, ring + oKx); ldsm_x4(kb + 4, ring + (oKx ^ 64));
      bar_sync(4 + et, 64);
      uint4 o = lds128(aX);
      stsm_x2_t(aQKst, pack_bf16(aq[0] + __uint_as_float(o.x), aq[1] + __uint_as_float(o.y)), pack_bf16(aq[2] + __uint_as_float(o.z), aq[3] + __uint_as_float(o.w)));
      RSTAMP(4);
      bar_sync(1, 256);
      RSTAMP(5);
      if (s != NSEG - 1) {
        unsigned qa[8], km[8];
        ldsm_x4(qa, aQ); ldsm_x4(qa + 4, aQ + 64);
        if (w == 3) { ldsm_x4(km, aQ + 1152); ldsm_x4(km + 4, aQ + 1152 + 64); }
        float s0[4] = {0, 0, 0, 0}, s1[4] = {0, 0, 0, 0};
        unsigned af[4][4];
#pragma unroll
        for (int i = 0; i < 4; i++) { af[i][0] = qa[2 * i]; af[i][1] = 0; af[i][2] = qa[2 * i + 1]; af[i][3] = 0; }
        mma16816(s0, af[0], kb[0], kb[1]); mma16816(s1, af[1], kb[2], kb[3]);
        mma16816(s0, af[2], kb[4], kb[5]); mma16816(s1, af[3], kb[6], kb[7]);
        if (w == 3) {
          float m0[4] = {0, 0, 0, 0}, m1[4] = {0, 0, 0, 0};
          mma16816(m0, af[0], km[0], km[1]); mma16816(m1, af[1], km[2], km[3]);
          mma16816(m0, af[2], km[4], km[5]); mma16816(m1, af[3], km[6], km[7]);
          unsigned x = __float_as_uint(m0[0] + m1[0]), y = __float_as_uint(m0[1] + m1[1]);
          st_async_b64(aSr + 256, x, y, mbSr); st_async_b64(aSl + 256, x, y, mbSl);
        }
        unsigned x = __float_as_uint(s0[0] + s1[0]), y = __float_as_uint(s0[1] + s1[1]);
        st_async_b64(aSr, x, y, mbSr); st_async_b64(aSl, x, y, mbSl);
      }
      RSTAMP(6);
      VPASS();
      RSTAMP(7);
      bar_sync(8 + et, 64);
      uint4 o2 = lds128(aX + 4096);
      unsigned x = pack_bf16(av[0] + __uint_as_float(o2.x), av[1] + __uint_as_float(o2.y)), y = pack_bf16(av[2] + __uint_as_float(o2.z), av[3] + __uint_as_float(o2.w));
      st_async_b64(aVr, x, y, mbVr);
      st_async_b64(aVl, x, y, mbVl);
      RSTAMP(8);
      if (s == NSEG - 1) break;
      WO_LD(0, 3);
      RSTAMP(9); RSTAMP(10);
      bar_sync(1, 256);
    }
    RSTAMP(11);
    float d0[4] = {0, 0, 0, 0}, d1[4] = {0, 0, 0, 0}, e0[4] = {0, 0, 0, 0}, e1[4] = {0, 0, 0, 0};
    unsigned ob[4][4];
    ldsm_x4(ob[0], aOld); ldsm_x4(ob[1], aOld + 64);
    mma16816(d0, wo[0], ob[0][0], ob[0][1]); mma16816(d1, wo[1], ob[0][0], ob[0][1]);
    mma16816(e0, wo[2], ob[0][2], ob[0][3]); mma16816(e1, wo[3], ob[0][2], ob[0][3]);
    ldsm_x4(ob[2], aOld + 128);
    mma16816(d0, wo[4], ob[1][0], ob[1][1]); mma16816(d1, wo[5], ob[1][0], ob[1][1]);
    mma16816(e0, wo[6], ob[1][2], ob[1][3]); mma16816(e1, wo[7], ob[1][2], ob[1][3]);
    ldsm_x4(ob[3], aOld + 192);
    mma16816(d0, f[0], ob[2][0], ob[2][1]); mma16816(d1, f[1], ob[2][0], ob[2][1]);
    WO_LD(3, 4);
    mma16816(e0, f[2], ob[2][2], ob[2][3]); mma16816(e1, f[3], ob[2][2], ob[2][3]);
    const unsigned mbRSr = mapa(bar + 8 * MB_RS, j * 4 + (t8 >> 9));
    mma16816(d0, f[4], ob[3][0], ob[3][1]); mma16816(d1, f[5], ob[3][0], ob[3][1]);
    mma16816(e0, f[6], ob[3][2], ob[3][3]); mma16816(e1, f[7], ob[3][2], ob[3][3]);
    st_async_b64(aRSr, __float_as_uint(d0[0] + e0[0]), __float_as_uint(d0[1] + e0[1]), mbRSr);
    st_async_b64(aRSr + 256, __float_as_uint(d0[2] + e0[2]), __float_as_uint(d0[3] + e0[3]), mbRSr);
    st_async_b64(aRSr + 512, __float_as_uint(d1[0] + e1[0]), __float_as_uint(d1[1] + e1[1]), mbRSr);
    st_async_b64(aRSr + 768, __float_as_uint(d1[2] + e1[2]), __float_as_uint(d1[3] + e1[3]), mbRSr);
    RSTAMP(12);
    if (t == 128) {
      mbar_arrive(bar + 8 * (MB_EMPTY + slot)); mbar_arrive(bar + 8 * MB_KVR);
      mbar_expect_tx(bar + 8 * MB_S, 2560); mbar_expect_tx(bar + 8 * MB_V, 2048);
    }
    const unsigned tag = ((s >> 1) & 1) ^ 1;
    const char* gp = reinterpret_cast<const char*>(g_part) + (par * 8 + rk) * 16384 + t8;
    unsigned mbA[8];
#pragma unroll
    for (int i = 0; i < 8; i++) if (!MBL) mbA[i] = mapa(bar + 8 * MB_AG, i);
    const unsigned dlt = (R_MEM + rk * 1024) - (SM_BAR + 8 * MB_AG) + (t8 >> 1);
    mbar_wait(bar + 8 * MB_RS, par);
    RSTAMP(13);
    uint2 a[8];
    {
      uint2 x0 = lds64(sb + R_RS + t8), x1 = lds64(sb + R_RS + 2048 + t8), x2 = lds64(sb + R_RS + 4096 + t8), x3 = lds64(sb + R_RS + 6144 + t8);
      float q0 = (__uint_as_float(x0.x) + __uint_as_float(x1.x)) + (__uint_as_float(x2.x) + __uint_as_float(x3.x));
      float q1 = (__uint_as_float(x0.y) + __uint_as_float(x1.y)) + (__uint_as_float(x2.y) + __uint_as_float(x3.y));
      a[0].x = (__float_as_uint(q0) & ~1u) | tag; a[0].y = (__float_as_uint(q1) & ~1u) | tag;
      asm volatile("st.relaxed.gpu.global.v2.u32 [%0], {%1,%2};" ::"l"(gp + cl * 2048), "r"(a[0].x), "r"(a[0].y) : "memory");
    }
    RSTAMP(14);
    if (t == 128) mbar_expect_tx(bar + 8 * MB_RS, 8192);
    {
      unsigned it = 0;
#define PLOAD(a) _Pragma("unroll") for (int i = 1; i < 8; i++) a[i] = ldv2_relaxed(gp + (cl ^ i) * 2048)
#define PAND(a) (((a[1].x & a[1].y) & (a[2].x & a[2].y) & (a[3].x & a[3].y)) & ((a[4].x & a[4].y) & (a[5].x & a[5].y)) & ((a[6].x & a[6].y) & (a[7].x & a[7].y)))
#define POR(a) (((a[1].x | a[1].y) | (a[2].x | a[2].y) | (a[3].x | a[3].y)) | ((a[4].x | a[4].y) | (a[5].x | a[5].y)) | ((a[6].x | a[6].y) | (a[7].x | a[7].y)))
#define POK(a) (((tag ? PAND(a) : ~POR(a)) & 1u) != 0)
      if (D_RED) DELAY(D_RED);
      while (true) { PLOAD(a); if (POK(a)) break; if (D_PUB) DELAY(D_PUB); spin_check(it); }
    }
    RSTAMP(15);
    {
#define AF(i, c) __uint_as_float(a[i].c)
      unsigned u = pack_bf16(((AF(0, x) + AF(1, x)) + (AF(2, x) + AF(3, x))) + ((AF(4, x) + AF(5, x)) + (AF(6, x) + AF(7, x))),
                             ((AF(0, y) + AF(1, y)) + (AF(2, y) + AF(3, y))) + ((AF(4, y) + AF(5, y)) + (AF(6, y) + AF(7, y))));
      __syncwarp();
#pragma unroll
      for (int i = 0; i < 8; i++) { if (MBL) mbA[i] = mapa(bar + 8 * MB_AG, i); st_async_b32(mbA[i] + dlt, u, mbA[i]); }
    }
    mbar_wait(bar + 8 * MB_KVF, par);
    mbar_wait(bar + 8 * MB_AG, par);
    if (t == 128) mbar_expect_tx(bar + 8 * MB_AG, 8192);
  }
}

__device__ __forceinline__ void rec_ring(const Maps& maps, unsigned sb) {
  const int c = blockIdx.x, h = c >> 1, j = c & 1;
  const unsigned bar = sb + SM_BAR;
  const int lane = threadIdx.x & 31;
  if (lane == 0) {
    mbar_expect_tx(bar + 8 * MB_W0, 131072);
    for (int kb = 0; kb < 8; kb++) tma_load_2d(sb + R_WO + kb * 8192, &maps.wq, h * 128 + j * 64, kb * 64, bar + 8 * MB_W0);
    for (int kb = 0; kb < 8; kb++) tma_load_2d(sb + R_T1 + kb * 8192, &maps.wk, h * 128 + j * 64, kb * 64, bar + 8 * MB_W0);
    mbar_expect_tx(bar + 8 * MB_W1, 65536);
    for (int kb = 0; kb < 8; kb++) tma_load_2d(sb + R_T2 + kb * 8192, &maps.wv, h * 128 + j * 64, kb * 64, bar + 8 * MB_W1);
  }
  __syncwarp();
  bar_sync(2, 288);
  if (lane == 0) {
    fence_proxy_async_smem();
    for (int s = 0; s < NSEG; s++) {
      unsigned slot = s & (RING_N - 1);
      if ((s & 3) == 0 && !DBGMODE) {
        wait_flag_ge(&g_flags.qkv[(s >> 2) * 48 + 16 + (h >> 1)], 1);
        wait_flag_ge(&g_flags.qkv[(s >> 2) * 48 + 32 + (h >> 1)], 1);
        fence_proxy_async();
      }
      if (s >= RING_N) mbar_wait_sleep(bar + 8 * (MB_EMPTY + slot), ((s / RING_N) - 1) & 1);
      unsigned dst = sb + R_RING + slot * RING_BYTES, mb = bar + 8 * (MB_FULL + slot);
      mbar_expect_tx(mb, RING_BYTES);
      tma_load_2d(dst, &maps.qkv_ld, HD + h * 128 + j * 64, s * SEG, mb);
      tma_load_2d(dst + 4096, &maps.qkv_ld, 2 * HD + h * 128, s * SEG, mb);
      tma_load_2d(dst + 8192, &maps.qkv_ld, 2 * HD + h * 128 + 64, s * SEG, mb);
    }
  }
}
__device__ __forceinline__ void rec_copy(unsigned sb) {
  const int c = blockIdx.x, h = c >> 1, j = c & 1;
  const unsigned bar = sb + SM_BAR;
  const int lane = threadIdx.x & 31;
  for (int s = 0; s < NSEG; s++) {
    mbar_wait_sleep(bar + 8 * MB_KVR, s & 1);
    uint4 k0 = lds128(sb + R_KS + (lane >> 3) * 144 + (lane & 7) * 16), k1 = lds128(sb + R_KS + (4 + (lane >> 3)) * 144 + (lane & 7) * 16);
    uint2 v[4];
#pragma unroll
    for (int i = 0; i < 4; i++) v[i] = lds64(sb + R_VM + (j * 4 + i) * 256 + lane * 8);
    __syncwarp();
    if (lane == 0) mbar_arrive(bar + 8 * MB_KVF);
    bf16* kd = g_km + ((size_t)(s * NH + h) * NMEM) * DH + j * 64;
    *reinterpret_cast<uint4*>(kd + (lane >> 3) * DH + (lane & 7) * 8) = k0;
    *reinterpret_cast<uint4*>(kd + (4 + (lane >> 3)) * DH + (lane & 7) * 8) = k1;
    unsigned* vd = reinterpret_cast<unsigned*>(g_vmt) + ((size_t)(s * NH + h) * DH + j * 64) * 4;
#pragma unroll
    for (int i = 0; i < 4; i++) { vd[(i * 16) * 4 + lane] = v[i].x; vd[(i * 16 + 8) * 4 + lane] = v[i].y; }
    __syncwarp();
    if (lane == 0) st_release(&g_flags.rec[c], s + 1);
  }
}

__device__ __forceinline__ void bulk_producer(const Maps& maps, unsigned sb, int* misc) {
  const unsigned bar = sb + SM_BAR;
  const int lane = threadIdx.x & 31;
  unsigned st = 0, ph = 0, seq = 0;
  while (true) {
    int idx = 0;
    if (lane == 0) idx = (int)atomicAdd(&g_flags.ctr, 1u);
    idx = __shfl_sync(~0u, idx, 0);
    if (idx >= N_ITEMS) {
      if (lane == 0) {
        mbar_wait(bar + 8 * (MB_EMPTY + st), ph ^ 1);
        misc[seq & 3] = -1;
        mbar_arrive(bar + 8 * (MB_FULL + st));
      }
      break;
    }
    if (lane == 0) ISTAMP(idx, 0);
    Item it = decode_item(idx);
    if (it.b < 0) continue;
    const CUtensorMap* mp; int c0, c1, dc0, dc1; unsigned doff;
    const unsigned* fl = nullptr; unsigned tgt = 1; int nbox = 5, rdy = 0;
    if (it.type == T_ATT) {
      mp = &maps.qkv_ld; nbox = 12; doff = lane * 4096;
      c0 = (lane >> 2) * HD + it.c * 256 + (lane & 1) * 64; c1 = it.b * 128 + ((lane >> 1) & 1) * 32; dc0 = dc1 = 0;
      if (lane < 3) fl = &g_flags.qkv[it.b * 48 + lane * 16 + it.c];
      bool ok = true;
      if (lane >= 4 && lane < 8) ok = ld_acquire(&g_flags.rec[it.c * 4 + lane - 4]) >= (unsigned)(it.b * 4 + 4);
      rdy = __all_sync(~0u, ok) ? 65536 : 0;
    } else {
      int k0 = 0, nb0 = it.c * 256;
      if (it.type == T_QKV) { mp = lane == 0 ? &maps.xn : (it.c < 16 ? &maps.wq : (it.c < 32 ? &maps.wk : &maps.wv)); nb0 = (it.c & 15) * 256; }
      else if (it.type == T_M1) mp = lane == 0 ? &maps.y : &maps.w1;
      else if (it.type == T_M2) { mp = lane == 0 ? &maps.h1 : &maps.w2; fl = &g_flags.h1[it.b]; tgt = 7; }
      else {
        mp = lane == 0 ? &maps.o : &maps.wo;
        if (it.type == T_OUT) { k0 = it.ks * 1024; fl = &g_flags.o[it.b * 4 + it.ks]; tgt = 4; }
        else if (it.type == T_OUTL) { k0 = it.ks * 256; fl = &g_flags.o16[it.ks]; }
        else if (lane == 1) { fl = &g_flags.g[it.b]; tgt = 2; }
        else { fl = &g_flags.p[it.b]; tgt = it.type == T_RED ? 8 : 32; }
      }
      if (lane > (it.type >= T_RED ? 1 : 0)) fl = nullptr;
      if (lane == 0) { c0 = k0; c1 = it.b * 128; dc0 = 64; dc1 = 0; doff = 0; }
      else { c0 = nb0 + (lane - 1) * 64; c1 = k0; dc0 = 0; dc1 = 64; doff = 8192 + lane * 8192; }
    }
    if (fl) wait_flag_ge(fl, tgt);
    __syncwarp();
    fence_proxy_async();
    if (lane == 0) ISTAMP(idx, 1);
    const int nkb = item_nkb(it.type);
    for (int kb = 0; kb < nkb; kb++) {
      const unsigned mb = bar + 8 * (MB_FULL + st);
      mbar_wait(bar + 8 * (MB_EMPTY + st), ph ^ 1);
      if (lane == 0) {
        if (kb == 0) misc[seq & 3] = idx | rdy;
        if (it.type >= T_RED) mbar_arrive(mb); else mbar_expect_tx(mb, STAGE_BYTES);
      }
      if (it.type == T_ATT) { if (lane < 12) tma_load_2d(sb + st * STAGE_BYTES + doff, mp, c0 + (kb & 1) * 128, c1 + (kb >> 1) * 64, mb); }
      else if (lane < nbox && it.type < T_RED) tma_load_2d(sb + st * STAGE_BYTES + doff, mp, c0 + kb * dc0, c1 + kb * dc1, mb);
      __syncwarp();
      if (++st == NSTAGE) { st = 0; ph ^= 1; }
    }
    seq++;
  }
}
__device__ __forceinline__ void bulk_store(const Maps& maps, unsigned sb, volatile int* misc) {
  const unsigned bar = sb + SM_BAR;
  unsigned ph = 0;
  while (true) {
    mbar_wait(bar + 8 * MB_STGF, ph); ph ^= 1;
    int idx = misc[4];
    if (idx < 0) break;
    Item it = decode_item(idx);
    const CUtensorMap* mp = it.type == T_QKV ? &maps.qkv_st : (it.type == T_M1 ? &maps.h1 : (it.type == T_M2 ? &maps.g : &maps.o));
    unsigned* flag = it.type == T_QKV ? &g_flags.qkv[it.b * 48 + it.c] : (it.type == T_M1 ? &g_flags.h1[it.b] : (it.type == T_M2 ? &g_flags.g[it.b] : (it.b == 15 ? &g_flags.o16[it.c] : &g_flags.o[it.b * 4 + (it.c >> 2)])));
    for (int i = 0; i < 4; i++) tma_store_2d(mp, sb + B_STG + i * 16384, it.c * 256 + i * 64, it.b * 128);
    asm volatile("cp.async.bulk.commit_group;" ::: "memory");
    asm volatile("cp.async.bulk.wait_group.read 0;" ::: "memory");
    mbar_arrive(bar + 8 * MB_STGE);
    asm volatile("cp.async.bulk.wait_group 0;" ::: "memory");
    fence_proxy_async();
    red_release_add(flag, 1);
    ISTAMP(idx, 3);
  }
}
__device__ __forceinline__ float rcpf(float x) { float y; asm("rcp.approx.ftz.f32 %0, %1;" : "=f"(y) : "f"(x)); return y; }
__device__ __forceinline__ float gelu_t(float x) {
  float e = ex2f(x * fmaf(x * x, -2.0f * LOG2E * 0.7978845608028654f * 0.044715f, -2.0f * LOG2E * 0.7978845608028654f));
  return x * rcpf(1.0f + e);
}
__device__ __forceinline__ float silu_f(float x) { return x * rcpf(1.0f + ex2f(-LOG2E * x)); }
__device__ __forceinline__ unsigned badd2(unsigned a, unsigned b) { unsigned r; asm("add.rn.bf16x2 %0, %1, %2;" : "=r"(r) : "r"(a), "r"(b)); return r; }

__device__ __forceinline__ void final_out(bf16* __restrict__ out, const bf16* __restrict__ x, size_t o, float4 s) {
  uint2 gv = __ldcg(reinterpret_cast<const uint2*>(g_g + o)), xv = __ldg(reinterpret_cast<const uint2*>(x + o));
  uint2 r;
  r.x = pack_bf16(bf_lo(xv.x) + bf16r(bf16r(s.x) * bf_lo(gv.x)), bf_hi(xv.x) + bf16r(bf16r(s.y) * bf_hi(gv.x)));
  r.y = pack_bf16(bf_lo(xv.y) + bf16r(bf16r(s.z) * bf_lo(gv.y)), bf_hi(xv.y) + bf16r(bf16r(s.w) * bf_hi(gv.y)));
  *reinterpret_cast<uint2*>(out + o) = r;
}
__device__ __forceinline__ void bulk_att_load(unsigned* km, unsigned* vm, int b, int hp, int kb, int w, int lane) {
  const int g = lane >> 2, tq = lane & 3, seg = w >> 2, eh = w & 1;
  const int head = hp * 2 + (kb & 1), sg = b * 4 + (kb >> 1) * 2 + seg;
  const unsigned* kmp = reinterpret_cast<const unsigned*>(g_km + ((size_t)(sg * NH + head) * NMEM + g) * DH) + tq;
  const unsigned* vmp = reinterpret_cast<const unsigned*>(g_vmt) + ((size_t)(sg * NH + head) * DH + eh * 64) * 4 + lane;
#pragma unroll
  for (int i = 0; i < 16; i++) asm volatile("ld.global.cg.u32 %0, [%1];" : "=r"(km[i]) : "l"(kmp + i * 4) : "memory");
#pragma unroll
  for (int i = 0; i < 8; i++) asm volatile("ld.global.cg.u32 %0, [%1];" : "=r"(vm[i]) : "l"(vmp + i * 32) : "memory");
}
__device__ __forceinline__ void bulk_att_stage(unsigned sa, unsigned stg, const unsigned* km, const unsigned* vm, int kb, int w, int lane) {
  const int g = lane >> 2, tq = lane & 3, m = lane >> 3, r8 = lane & 7;
  const int seg = w >> 2, mt = (w >> 1) & 1, eh = w & 1;
  float s[5][4];
#pragma unroll
  for (int i = 0; i < 5; i++) { s[i][0] = s[i][1] = s[i][2] = s[i][3] = 0; }
  const unsigned qb = sa + (0 * 2 + seg) * 8192, kbs = sa + (1 * 2 + seg) * 8192, vb = sa + (2 * 2 + seg) * 8192 + eh * 4096;
  unsigned qa[8][4];
#pragma unroll
  for (int ks = 0; ks < 8; ks++) {
    int row = mt * 16 + (m & 1) * 8 + r8;
    ldsm_x4(qa[ks], qb + (ks >> 2) * 4096 + row * 128 + ((((ks & 3) * 2 + (m >> 1)) ^ r8) << 4));
    unsigned kf[4];
    int krow = (m >> 1) * 8 + r8;
    unsigned ka = kbs + (ks >> 2) * 4096 + krow * 128 + ((((ks & 3) * 2 + (m & 1)) ^ r8) << 4);
    ldsm_x4(kf, ka);
    mma16816(s[0], qa[ks], kf[0], kf[1]); mma16816(s[1], qa[ks], kf[2], kf[3]);
    if (mt) { ldsm_x4(kf, ka + 2048); mma16816(s[2], qa[ks], kf[0], kf[1]); mma16816(s[3], qa[ks], kf[2], kf[3]); }
  }
#pragma unroll
  for (int ks = 0; ks < 8; ks++) mma16816(s[4], qa[ks], km[2 * ks], km[2 * ks + 1]);
  float mx0 = -INFINITY, mx1 = -INFINITY;
  const int t0 = mt * 16 + g, t1 = t0 + 8;
#pragma unroll
  for (int i = 0; i < 5; i++) {
#pragma unroll
    for (int e = 0; e < 4; e++) {
      float v = s[i][e];
      if (i < 4) { int kj = i * 8 + 2 * tq + (e & 1); if (kj > (e < 2 ? t0 : t1)) v = -INFINITY; }
      s[i][e] = v;
      if (e < 2) mx0 = fmaxf(mx0, v); else mx1 = fmaxf(mx1, v);
    }
  }
  mx0 = fmaxf(mx0, __shfl_xor_sync(~0u, mx0, 1)); mx0 = fmaxf(mx0, __shfl_xor_sync(~0u, mx0, 2));
  mx1 = fmaxf(mx1, __shfl_xor_sync(~0u, mx1, 1)); mx1 = fmaxf(mx1, __shfl_xor_sync(~0u, mx1, 2));
  float sm0 = 0, sm1 = 0;
#pragma unroll
  for (int i = 0; i < 5; i++) {
    s[i][0] = ex2f((s[i][0] - mx0) * (SCALE_QK * LOG2E)); s[i][1] = ex2f((s[i][1] - mx0) * (SCALE_QK * LOG2E));
    s[i][2] = ex2f((s[i][2] - mx1) * (SCALE_QK * LOG2E)); s[i][3] = ex2f((s[i][3] - mx1) * (SCALE_QK * LOG2E));
    sm0 += s[i][0] + s[i][1]; sm1 += s[i][2] + s[i][3];
  }
  sm0 += __shfl_xor_sync(~0u, sm0, 1); sm0 += __shfl_xor_sync(~0u, sm0, 2);
  sm1 += __shfl_xor_sync(~0u, sm1, 1); sm1 += __shfl_xor_sync(~0u, sm1, 2);
  const float i0 = __fdividef(1.0f, sm0), i1 = __fdividef(1.0f, sm1);
  unsigned pa[2][4], pm0, pm1;
#pragma unroll
  for (int kk = 0; kk < 2; kk++) {
    pa[kk][0] = pack_bf16(s[2 * kk][0] * i0, s[2 * kk][1] * i0); pa[kk][1] = pack_bf16(s[2 * kk][2] * i1, s[2 * kk][3] * i1);
    pa[kk][2] = pack_bf16(s[2 * kk + 1][0] * i0, s[2 * kk + 1][1] * i0); pa[kk][3] = pack_bf16(s[2 * kk + 1][2] * i1, s[2 * kk + 1][3] * i1);
  }
  pm0 = pack_bf16(s[4][0] * i0, s[4][1] * i0); pm1 = pack_bf16(s[4][2] * i1, s[4][3] * i1);
  const int orow = (kb >> 1) * 64 + seg * 32 + mt * 16 + (m & 1) * 8 + r8;
  const unsigned ob = stg + ((kb & 1) * 2 + eh) * 16384 + orow * 128;
#pragma unroll
  for (int cp = 0; cp < 4; cp++) {
    float o0[4] = {0, 0, 0, 0}, o1[4] = {0, 0, 0, 0};
    mma1688(o0, pm0, pm1, vm[2 * cp]); mma1688(o1, pm0, pm1, vm[2 * cp + 1]);
    unsigned vf[4];
    int row = (m & 1) * 8 + r8;
    unsigned va = vb + row * 128 + (((cp * 2 + (m >> 1)) ^ r8) << 4);
    ldsm_x4_t(vf, va);
    mma16816(o0, pa[0], vf[0], vf[1]); mma16816(o1, pa[0], vf[2], vf[3]);
    if (mt) { ldsm_x4_t(vf, va + 2048); mma16816(o0, pa[1], vf[0], vf[1]); mma16816(o1, pa[1], vf[2], vf[3]); }
    stsm_x4(ob + (((cp * 2 + (m >> 1)) ^ r8) << 4), pack_bf16(o0[0], o0[1]), pack_bf16(o0[2], o0[3]), pack_bf16(o1[0], o1[1]), pack_bf16(o1[2], o1[3]));
  }
}

__device__ __forceinline__ void bulk_worker(unsigned sb, volatile int* misc, const bf16* __restrict__ x, const bf16* __restrict__ b1, const bf16* __restrict__ b2, bf16* __restrict__ out) {
  const int t = threadIdx.x, lane = t & 31, w = t >> 5, wg = w >> 2, g = lane >> 2, tq = lane & 3, m = lane >> 3, r8 = lane & 7;
  const unsigned bar = sb + SM_BAR;
  unsigned st = 0, ph = 0, seq = 0, sph = 0;
  float d[128];
  while (true) {
    mbar_wait(bar + 8 * (MB_FULL + st), ph);
    const int idr = misc[seq & 3]; seq++;
    const int idx = idr & 65535;
    if (idr < 0 || idx >= N_ITEMS) break;
    if (t == 0) ISTAMP(idx, 2);
    const Item it = decode_item(idx);
    const int nkb = item_nkb(it.type);
    if (it.type == T_ATT) {
      unsigned km[16], vm[8], kn[16], vn[8];
      const bool pref = idr >= 65536;
      if (pref) bulk_att_load(kn, vn, it.b, it.c, 0, w, lane);
      mbar_wait(bar + 8 * MB_STGE, sph ^ 1);
#pragma unroll 1
      for (int kb = 0; kb < 4; kb++) {
        if (!pref) {
          if (lane < 2) wait_flag_ge(&g_flags.rec[it.c * 4 + (kb & 1) * 2 + lane], it.b * 4 + (kb >> 1) * 2 + wg + 1);
          __syncwarp();
          bulk_att_load(kn, vn, it.b, it.c, kb, w, lane);
        }
        if (kb) mbar_wait(bar + 8 * (MB_FULL + st), ph);
#pragma unroll
        for (int i = 0; i < 16; i++) km[i] = kn[i];
#pragma unroll
        for (int i = 0; i < 8; i++) vm[i] = vn[i];
        if (pref && kb != 3) bulk_att_load(kn, vn, it.b, it.c, kb + 1, w, lane);
        bulk_att_stage(sb + st * STAGE_BYTES, sb + B_STG, km, vm, kb, w, lane);
        __syncwarp();
        if (lane == 0) mbar_arrive(bar + 8 * (MB_EMPTY + st));
        if (++st == NSTAGE) { st = 0; ph ^= 1; }
      }
      if (t == 0) misc[4] = idx;
      fence_proxy_async_smem();
      mbar_arrive(bar + 8 * MB_STGF); sph ^= 1;
      continue;
    }
    if (it.type >= T_RED) {
      __syncwarp();
      if (lane == 0) mbar_arrive(bar + 8 * (MB_EMPTY + st));
      if (++st == NSTAGE) { st = 0; ph ^= 1; }
      if (it.type == T_RED) {
#pragma unroll 2
        for (int i = 0; i < 8; i++) {
          size_t o = ((size_t)it.b * 128 + it.c * 16 + i * 2 + (t >> 7)) * DM + (t & 127) * 4;
          float4 a = __ldcg(reinterpret_cast<const float4*>(g_opart + o)), b = __ldcg(reinterpret_cast<const float4*>(g_opart + o + (size_t)S_TOK * DM));
          float4 c = __ldcg(reinterpret_cast<const float4*>(g_opart + o + (size_t)2 * S_TOK * DM)), e = __ldcg(reinterpret_cast<const float4*>(g_opart + o + (size_t)3 * S_TOK * DM));
          final_out(out, x, o, make_float4((a.x + b.x) + (c.x + e.x), (a.y + b.y) + (c.y + e.y), (a.z + b.z) + (c.z + e.z), (a.w + b.w) + (c.w + e.w)));
        }
      } else {
        size_t ol = ((size_t)it.c * 2 + (t >> 7)) * DM + (t & 127) * 4;
        float4 v[16];
#pragma unroll
        for (int i = 0; i < 16; i++) v[i] = __ldcg(reinterpret_cast<const float4*>(g_opl + ol + (size_t)i * 128 * DM));
#pragma unroll
        for (int st2 = 1; st2 < 16; st2 <<= 1)
#pragma unroll
          for (int i = 0; i < 16; i += 2 * st2) { v[i].x += v[i + st2].x; v[i].y += v[i + st2].y; v[i].z += v[i + st2].z; v[i].w += v[i + st2].w; }
        final_out(out, x, ol + (size_t)15 * 128 * DM, v[0]);
      }
      if (t == 0) ISTAMP(idx, 3);
      continue;
    }
    unsigned pst = 0, bv[32];
#pragma unroll
    for (int i = 0; i < 128; i++) d[i] = 0.0f;
    if (it.type == T_M1 || it.type == T_M2) {
      const unsigned* bp = reinterpret_cast<const unsigned*>((it.type == T_M1 ? b1 : b2) + it.c * 256) + tq;
#pragma unroll
      for (int i = 0; i < 32; i++) asm volatile("ld.global.nc.u32 %0, [%1];" : "=r"(bv[i]) : "l"(bp + i * 4));
    } else {
#pragma unroll
      for (int i = 0; i < 32; i++) bv[i] = 0;
    }
    for (int kb = 0; kb < nkb; kb++) {
      if (kb) mbar_wait(bar + 8 * (MB_FULL + st), ph);
      unsigned sa = sb + st * STAGE_BYTES;
      uint64_t ad = mkdesc(sa + wg * 8192, 16, 1024), bd = mkdesc(sa + 16384, 8192, 1024);
      asm volatile("wgmma.fence.sync.aligned;" ::: "memory");
#pragma unroll
      for (int k = 0; k < 4; k++) wgmma_n256(d, ad + k * 2, bd + k * 128, (kb | k) != 0);
      asm volatile("wgmma.commit_group.sync.aligned;" ::: "memory");
      if (kb) {
        asm volatile("wgmma.wait_group.sync.aligned 1;" ::: "memory");
        if (lane == 0) mbar_arrive(bar + 8 * (MB_EMPTY + pst));
      }
      pst = st;
      if (++st == NSTAGE) { st = 0; ph ^= 1; }
    }
    asm volatile("wgmma.wait_group.sync.aligned 0;" ::: "memory");
    if (lane == 0) mbar_arrive(bar + 8 * (MB_EMPTY + pst));
    if (it.type >= T_OUT) {
      const int col = it.c * 256 + 2 * tq;
      float* pp = it.type == T_OUT ? g_opart + ((size_t)it.ks * S_TOK + it.b * 128 + w * 16 + g) * DM + col : g_opl + ((size_t)it.ks * 128 + w * 16 + g) * DM + col;
#pragma unroll
      for (int i = 0; i < 32; i++) {
        __stcg(reinterpret_cast<float2*>(pp + i * 8), make_float2(d[4 * i], d[4 * i + 1]));
        __stcg(reinterpret_cast<float2*>(pp + 8 * DM + i * 8), make_float2(d[4 * i + 2], d[4 * i + 3]));
      }
      bar_sync(1, 256);
      if (t == 0) { red_release_add(&g_flags.p[it.b], 1); ISTAMP(idx, 3); }
      continue;
    }
#define ACT(F) _Pragma("unroll") for (int i = 0; i < 32; i++) { \
        unsigned u0 = badd2(pack_bf16(d[4 * i], d[4 * i + 1]), bv[i]), u1 = badd2(pack_bf16(d[4 * i + 2], d[4 * i + 3]), bv[i]); \
        d[4 * i] = F(bf_lo(u0)); d[4 * i + 1] = F(bf_hi(u0)); d[4 * i + 2] = F(bf_lo(u1)); d[4 * i + 3] = F(bf_hi(u1)); }
    if (it.type == T_M1) { ACT(gelu_t) } else if (it.type == T_M2) { ACT(silu_f) }
    mbar_wait(bar + 8 * MB_STGE, sph ^ 1);
    {
      const unsigned ob = sb + B_STG + (w * 16 + (m & 1) * 8 + r8) * 128;
#pragma unroll
      for (int i = 0; i < 16; i++)
        stsm_x4(ob + (i >> 2) * 16384 + ((((i & 3) * 2 + (m >> 1)) ^ r8) << 4), pack_bf16(d[8 * i], d[8 * i + 1]), pack_bf16(d[8 * i + 2], d[8 * i + 3]),
                pack_bf16(d[8 * i + 4], d[8 * i + 5]), pack_bf16(d[8 * i + 6], d[8 * i + 7]));
    }
    if (t == 0) misc[4] = idx;
    fence_proxy_async_smem();
    mbar_arrive(bar + 8 * MB_STGF); sph ^= 1;
  }
  mbar_wait(bar + 8 * MB_STGE, sph ^ 1);
  if (t == 0) misc[4] = -1;
  mbar_arrive(bar + 8 * MB_STGF);
}

__global__ void __launch_bounds__(384, 1)
k_main(const __grid_constant__ Maps maps, const bf16* __restrict__ x, const bf16* __restrict__ mem0, const bf16* __restrict__ b1, const bf16* __restrict__ b2, bf16* __restrict__ out, int helper) {
  extern __shared__ unsigned char smem_raw[];
  const unsigned sraw = smem_u32(smem_raw);
  const unsigned sb = (sraw + 1023u) & ~1023u;
  int* misc = reinterpret_cast<int*>(smem_raw + (sb - sraw) + SM_MISC);
  const int w = threadIdx.x >> 5;
  const bool rec = !helper && blockIdx.x < NREC;
  if (!helper) asm volatile("griddepcontrol.launch_dependents;");
  if (threadIdx.x == 0) {
    const unsigned bar = sb + SM_BAR;
    for (int i = 0; i < 8; i++) { mbar_init(bar + 8 * (MB_FULL + i), 1); mbar_init(bar + 8 * (MB_EMPTY + i), rec ? 1 : 8); }
    mbar_init(bar + 8 * MB_STGF, 256); mbar_init(bar + 8 * MB_STGE, 1);
    for (int i = MB_W0; i <= MB_AG; i++) mbar_init(bar + 8 * i, 1);
    if (rec) { mbar_expect_tx(bar + 8 * MB_S, 2560); mbar_expect_tx(bar + 8 * MB_V, 2048); mbar_expect_tx(bar + 8 * MB_RS, 8192); mbar_expect_tx(bar + 8 * MB_AG, 8192); }
    asm volatile("fence.mbarrier_init.release.cluster;" ::: "memory");
  }
  __syncthreads();
  asm volatile("barrier.cluster.arrive.release.aligned;\nbarrier.cluster.wait.acquire.aligned;" ::: "memory");
  if (DBGMODE && !rec) { if (helper) asm volatile("griddepcontrol.wait;" ::: "memory"); return; }
  if (w >= 8) {
    asm volatile("setmaxnreg.dec.sync.aligned.u32 24;");
    if (rec) { if (w == 8) rec_ring(maps, sb); else if (w == 9) rec_copy(sb); }
    else if (w == 8) bulk_producer(maps, sb, misc);
    else if ((threadIdx.x & 31) == 0) { if (w == 9) bulk_store(maps, sb, misc);
      else if (w == 10 && helper) asm volatile("griddepcontrol.wait;" ::: "memory"); }
  } else {
    if (rec) { asm volatile("setmaxnreg.inc.sync.aligned.u32 240;"); rec_worker(maps, sb, mem0); }
    else { asm volatile("setmaxnreg.inc.sync.aligned.u32 240;"); bulk_worker(sb, misc, x, b1, b2, out); }
  }
}

typedef CUresult (*EncFn)(CUtensorMap*, CUtensorMapDataType, cuuint32_t, void*, const cuuint64_t*, const cuuint64_t*, const cuuint32_t*, const cuuint32_t*,
                          CUtensorMapInterleave, CUtensorMapSwizzle, CUtensorMapL2promotion, CUtensorMapFloatOOBfill);
static void mk_map(EncFn enc, CUtensorMap* m, const void* ptr, uint64_t rows, uint64_t cols, uint32_t box_rows) {
  cuuint64_t dims[2] = {cols, rows}; cuuint64_t strides[1] = {cols * 2};
  cuuint32_t box[2] = {64, box_rows}, es[2] = {1, 1};
  enc(m, CU_TENSOR_MAP_DATA_TYPE_BFLOAT16, 2, const_cast<void*>(ptr), dims, strides, box, es, CU_TENSOR_MAP_INTERLEAVE_NONE, CU_TENSOR_MAP_SWIZZLE_128B,
      CU_TENSOR_MAP_L2_PROMOTION_L2_256B, CU_TENSOR_MAP_FLOAT_OOB_FILL_NONE);
}
extern "C" void kernel_launch(void* const* d_in, const int* in_sizes, int n_in, void* d_out, int out_size) {
  static EncFn enc = nullptr;
  static int ncl = 0, nhelp = 0;
  static void *p_xn, *p_y, *p_h1, *p_o, *p_qkv, *p_g;
  if (!enc) {
    void* fn = nullptr; cudaDriverEntryPointQueryResult qr;
    cudaGetDriverEntryPoint("cuTensorMapEncodeTiled", &fn, cudaEnableDefault, &qr);
    enc = (EncFn)fn;
    cudaGetSymbolAddress(&p_xn, g_xn); cudaGetSymbolAddress(&p_y, g_y); cudaGetSymbolAddress(&p_h1, g_h1);
    cudaGetSymbolAddress(&p_o, g_o); cudaGetSymbolAddress(&p_qkv, g_qkv); cudaGetSymbolAddress(&p_g, g_g);
    cudaFuncSetAttribute(k_main, cudaFuncAttributeMaxDynamicSharedMemorySize, SMEM_TOTAL);
    cudaLaunchConfig_t cfg = {}; cfg.gridDim = dim3(128); cfg.blockDim = dim3(384); cfg.dynamicSmemBytes = SMEM_TOTAL;
    cudaLaunchAttribute at[1]; at[0].id = cudaLaunchAttributeClusterDimension; at[0].val.clusterDim.x = CLS; at[0].val.clusterDim.y = 1; at[0].val.clusterDim.z = 1;
    cfg.attrs = at; cfg.numAttrs = 1;
    if (cudaOccupancyMaxActiveClusters(&ncl, k_main, &cfg) != cudaSuccess) { cudaGetLastError(); ncl = 14; }
    ncl = ncl > 16 ? 16 : (ncl < 9 ? 9 : ncl);
    int nsm = 0, dev = 0; cudaGetDevice(&dev); cudaDeviceGetAttribute(&nsm, cudaDevAttrMultiProcessorCount, dev);
    nhelp = nsm - ncl * CLS;
  }
  Maps maps;
  mk_map(enc, &maps.xn, p_xn, S_TOK, DM, 128); mk_map(enc, &maps.y, p_y, S_TOK, DM, 128); mk_map(enc, &maps.h1, p_h1, S_TOK, FF, 128);
  mk_map(enc, &maps.o, p_o, S_TOK, HD, 128); mk_map(enc, &maps.qkv_st, p_qkv, S_TOK, 3 * HD, 128); mk_map(enc, &maps.qkv_ld, p_qkv, S_TOK, 3 * HD, 32);
  mk_map(enc, &maps.g, p_g, S_TOK, DM, 128);
  mk_map(enc, &maps.wq, d_in[2], DM, HD, 64); mk_map(enc, &maps.wk, d_in[3], DM, HD, 64); mk_map(enc, &maps.wv, d_in[4], DM, HD, 64);
  mk_map(enc, &maps.wo, d_in[5], HD, DM, 64); mk_map(enc, &maps.w1, d_in[8], DM, FF, 64); mk_map(enc, &maps.w2, d_in[10], FF, DM, 64);
  cudaStream_t st = cudaStreamPerThread;
  k_pre<<<256, 256, 0, st>>>((const bf16*)d_in[0]);
  cudaLaunchConfig_t cfg = {}; cfg.gridDim = dim3(ncl * CLS); cfg.blockDim = dim3(384); cfg.dynamicSmemBytes = SMEM_TOTAL; cfg.stream = st;
  cudaLaunchAttribute at[1]; at[0].id = cudaLaunchAttributeClusterDimension; at[0].val.clusterDim.x = CLS; at[0].val.clusterDim.y = 1; at[0].val.clusterDim.z = 1;
  cfg.attrs = at; cfg.numAttrs = 1;
  cudaLaunchKernelEx(&cfg, k_main, maps, (const bf16*)d_in[0], (const bf16*)d_in[1], (const bf16*)d_in[9], (const bf16*)d_in[11], (bf16*)d_out, 0);
  if (nhelp > 0) {
    cfg.gridDim = dim3(nhelp);
    at[0].id = cudaLaunchAttributeProgrammaticStreamSerialization; at[0].val.programmaticStreamSerializationAllowed = 1;
    cudaLaunchKernelEx(&cfg, k_main, maps, (const bf16*)d_in[0], (const bf16*)d_in[1], (const bf16*)d_in[9], (const bf16*)d_in[11], (bf16*)d_out, 1);
  }
}
```

```cpp
#include <cuda_runtime.h>
#include <cuda_bf16.h>
#include <cuda.h>
#include <stdint.h>

typedef __nv_bfloat16 bf16;

#define S_TOK 2048
#define DM 512
#define NH 32
#define DH 128
#define HD 4096
#define NMEM 8
#define SEG 32
#define NSEG 64
#define FF 1792
#define NBLK 16
#define NREC 64
#define REPL 0
#define CLS 8

__device__ __align__(1024) bf16 g_xn[S_TOK * DM];
__device__ __align__(1024) bf16 g_y[S_TOK * DM];
__device__ __align__(1024) bf16 g_qkv[(size_t)S_TOK * 3 * HD];
__device__ __align__(1024) bf16 g_h1[S_TOK * FF];
__device__ __align__(1024) bf16 g_g[S_TOK * DM];
__device__ __align__(1024) bf16 g_o[(size_t)S_TOK * HD];
__device__ __align__(1024) bf16 g_km[NSEG * NH * NMEM * DH];
__device__ __align__(1024) bf16 g_vmt[NSEG * NH * DH * NMEM];
__device__ __align__(1024) float g_opart[(size_t)4 * S_TOK * DM];
__device__ __align__(1024) float g_opl[(size_t)16 * 128 * DM];
__device__ __align__(1024) unsigned g_part[8 * 2 * 8 * 8 * 512];
struct Flags {
  unsigned qkv[NBLK * 48];
  unsigned h1[NBLK];
  unsigned g[NBLK];
  unsigned o[NBLK * 4];
  unsigned p[NBLK];
  unsigned o16[16];
  unsigned ctr;
  unsigned rec[NREC];
  unsigned abort_;
};
__device__ __align__(1024) Flags g_flags;

#define RSTAMP(k)
#define DBGMODE 0
#define ISTAMP(i, k)
__device__ __forceinline__ unsigned smem_u32(const void* p) { return (unsigned)__cvta_generic_to_shared(p); }
__device__ __forceinline__ float bf16r(float x) { unsigned u; asm("cvt.rn.bf16x2.f32 %0, %1, %2;" : "=r"(u) : "f"(x), "f"(0.0f)); return __uint_as_float(u); }
__device__ __forceinline__ unsigned pack_bf16(float lo, float hi) {
  __nv_bfloat162 v = __floats2bfloat162_rn(lo, hi);
  return *reinterpret_cast<unsigned*>(&v);
}
__device__ __forceinline__ float bf_lo(unsigned u) { return __uint_as_float(u << 16); }
__device__ __forceinline__ float bf_hi(unsigned u) { return __uint_as_float(u & 0xffff0000u); }

#define SPIN_LIMIT (1u << 20)
#define TRAP_IF(x) if ((x) > SPIN_LIMIT) { asm volatile("st.global.u32 [%0], %1;" ::"l"(0ull), "r"(0u) : "memory"); break; }
__device__ __forceinline__ unsigned ld_acquire(const unsigned* p) {
  unsigned v; asm volatile("ld.acquire.gpu.global.u32 %0, [%1];" : "=r"(v) : "l"(p) : "memory"); return v;
}
__device__ __forceinline__ unsigned ld_relaxed(const unsigned* p) {
  unsigned v; asm volatile("ld.relaxed.gpu.global.u32 %0, [%1];" : "=r"(v) : "l"(p) : "memory"); return v;
}
__device__ __forceinline__ void red_release_add(unsigned* p, unsigned v) {
  asm volatile("red.release.gpu.global.add.u32 [%0], %1;" ::"l"(p), "r"(v) : "memory");
}
__device__ __forceinline__ void st_release(unsigned* p, unsigned v) {
  asm volatile("st.release.gpu.global.u32 [%0], %1;" ::"l"(p), "r"(v) : "memory");
}
__device__ __forceinline__ void wait_flag_ge(const unsigned* p, unsigned target) {
  unsigned it = 0;
  while (ld_acquire(p) < target) {
    __nanosleep(64);
    TRAP_IF(++it);
  }
}
__device__ __forceinline__ uint4 ldv4_relaxed(const void* p) {
  uint4 a; asm volatile("ld.relaxed.gpu.global.v4.u32 {%0,%1,%2,%3}, [%4];" : "=r"(a.x), "=r"(a.y), "=r"(a.z), "=r"(a.w) : "l"(p) : "memory"); return a;
}
__device__ __forceinline__ uint2 ldv2_relaxed(const void* p) {
  uint2 a; asm volatile("ld.relaxed.gpu.global.v2.u32 {%0,%1}, [%2];" : "=r"(a.x), "=r"(a.y) : "l"(p) : "memory"); return a;
}
__device__ __forceinline__ void mbar_init(unsigned mb, unsigned cnt) { asm volatile("mbarrier.init.shared::cta.b64 [%0], %1;" ::"r"(mb), "r"(cnt) : "memory"); }
__device__ __forceinline__ void mbar_expect_tx(unsigned mb, unsigned bytes) { asm volatile("mbarrier.arrive.expect_tx.shared::cta.b64 _, [%0], %1;" ::"r"(mb), "r"(bytes) : "memory"); }
__device__ __forceinline__ void mbar_arrive(unsigned mb) { asm volatile("mbarrier.arrive.shared::cta.b64 _, [%0];" ::"r"(mb) : "memory"); }
__device__ __forceinline__ void mbar_wait(unsigned mb, unsigned parity) {
  unsigned ok, it = 0;
  while (true) {
    asm volatile("{.reg .pred p; mbarrier.try_wait.parity.shared::cta.b64 p, [%1], %2; selp.u32 %0,1,0,p;}" : "=r"(ok) : "r"(mb), "r"(parity) : "memory");
    if (ok) break;
    TRAP_IF(++it);
  }
}
__device__ __forceinline__ void mbar_wait_sleep(unsigned mb, unsigned parity) {
  unsigned ok, it = 0;
  while (true) {
    asm volatile("{.reg .pred p; mbarrier.test_wait.parity.shared::cta.b64 p, [%1], %2; selp.u32 %0,1,0,p;}" : "=r"(ok) : "r"(mb), "r"(parity) : "memory");
    if (ok) break;
    __nanosleep(200);
    TRAP_IF(++it);
  }
}
__device__ __forceinline__ float ex2f(float x) { float y; asm("ex2.approx.ftz.f32 %0, %1;" : "=f"(y) : "f"(x)); return y; }
__device__ __forceinline__ int opaque_tid() { int t = threadIdx.x; t = __shfl_sync(~0u, t, t & 31); return t; }
#define LOG2E 1.4426950408889634f
__device__ __forceinline__ void mbar_wait_cluster(unsigned mb, unsigned parity) {
  unsigned ok, it = 0;
  while (true) {
    asm volatile("{.reg .pred p; mbarrier.try_wait.parity.acquire.cluster.shared::cta.b64 p, [%1], %2; selp.u32 %0,1,0,p;}" : "=r"(ok) : "r"(mb), "r"(parity) : "memory");
    if (ok) break;
    TRAP_IF(++it);
  }
}
__device__ __forceinline__ void bar_sync(int id, int n) { asm volatile("bar.sync %0, %1;" ::"r"(id), "r"(n) : "memory"); }
__device__ __forceinline__ void bar_arrive(int id, int n) { asm volatile("bar.arrive %0, %1;" ::"r"(id), "r"(n) : "memory"); }
__device__ __forceinline__ void tma_load_2d(unsigned dst, const CUtensorMap* map, int c0, int c1, unsigned mb) {
  asm volatile("cp.async.bulk.tensor.2d.shared::cluster.global.mbarrier::complete_tx::bytes [%0], [%1, {%3, %4}], [%2];"
               ::"r"(dst), "l"((uint64_t)map), "r"(mb), "r"(c0), "r"(c1) : "memory");
}
__device__ __forceinline__ void tma_store_2d(const CUtensorMap* map, unsigned src, int c0, int c1) {
  asm volatile("cp.async.bulk.tensor.2d.global.shared::cta.bulk_group [%0, {%2, %3}], [%1];"
               ::"l"((uint64_t)map), "r"(src), "r"(c0), "r"(c1) : "memory");
}
__device__ __forceinline__ void fence_proxy_async() { asm volatile("fence.proxy.async;" ::: "memory"); }
__device__ __forceinline__ void fence_proxy_async_smem() { asm volatile("fence.proxy.async.shared::cta;" ::: "memory"); }
__device__ __forceinline__ void ldsm_x4(unsigned* r, unsigned addr) {
  asm volatile("ldmatrix.sync.aligned.m8n8.x4.shared.b16 {%0,%1,%2,%3}, [%4];" : "=r"(r[0]), "=r"(r[1]), "=r"(r[2]), "=r"(r[3]) : "r"(addr) : "memory");
}
__device__ __forceinline__ void ldsm_x4_t(unsigned* r, unsigned addr) {
  asm volatile("ldmatrix.sync.aligned.m8n8.x4.trans.shared.b16 {%0,%1,%2,%3}, [%4];" : "=r"(r[0]), "=r"(r[1]), "=r"(r[2]), "=r"(r[3]) : "r"(addr) : "memory");
}
__device__ __forceinline__ void stsm_x2_t(unsigned addr, unsigned r0, unsigned r1) {
  asm volatile("stmatrix.sync.aligned.m8n8.x2.trans.shared.b16 [%0], {%1,%2};" ::"r"(addr), "r"(r0), "r"(r1) : "memory");
}
__device__ __forceinline__ void stsm_x4(unsigned addr, unsigned r0, unsigned r1, unsigned r2, unsigned r3) {
  asm volatile("stmatrix.sync.aligned.m8n8.x4.shared.b16 [%0], {%1,%2,%3,%4};" ::"r"(addr), "r"(r0), "r"(r1), "r"(r2), "r"(r3) : "memory");
}
__device__ __forceinline__ void mma16816(float* d, const unsigned* a, unsigned b0, unsigned b1) {
  asm volatile("mma.sync.aligned.m16n8k16.row.col.f32.bf16.bf16.f32 {%0,%1,%2,%3}, {%4,%5,%6,%7}, {%8,%9}, {%0,%1,%2,%3};"
               : "+f"(d[0]), "+f"(d[1]), "+f"(d[2]), "+f"(d[3]) : "r"(a[0]), "r"(a[1]), "r"(a[2]), "r"(a[3]), "r"(b0), "r"(b1));
}
__device__ __forceinline__ void mma1688(float* d, unsigned a0, unsigned a1, unsigned b0) {
  asm volatile("mma.sync.aligned.m16n8k8.row.col.f32.bf16.bf16.f32 {%0,%1,%2,%3}, {%4,%5}, {%6}, {%0,%1,%2,%3};"
               : "+f"(d[0]), "+f"(d[1]), "+f"(d[2]), "+f"(d[3]) : "r"(a0), "r"(a1), "r"(b0));
}
__device__ __forceinline__ uint64_t mkdesc(unsigned addr, unsigned lbo, unsigned sbo) {
  return (uint64_t)((addr >> 4) & 0x3fff) | ((uint64_t)(lbo >> 4) << 16) | ((uint64_t)(sbo >> 4) << 32) | (1ull << 62);
}
#define R8(b) "+f"(d[b]), "+f"(d[b + 1]), "+f"(d[b + 2]), "+f"(d[b + 3]), "+f"(d[b + 4]), "+f"(d[b + 5]), "+f"(d[b + 6]), "+f"(d[b + 7])
#define R32(b) R8(b), R8(b + 8), R8(b + 16), R8(b + 24)
__device__ __forceinline__ void wgmma_n256(float* d, uint64_t ad, uint64_t bd, int acc) {
  asm volatile(
      "{.reg .pred p; setp.ne.b32 p, %130, 0;\n"
      "wgmma.mma_async.sync.aligned.m64n256k16.f32.bf16.bf16 "
      "{%0,%1,%2,%3,%4,%5,%6,%7,%8,%9,%10,%11,%12,%13,%14,%15,%16,%17,%18,%19,%20,%21,%22,%23,%24,%25,%26,%27,%28,%29,%30,%31,"
      "%32,%33,%34,%35,%36,%37,%38,%39,%40,%41,%42,%43,%44,%45,%46,%47,%48,%49,%50,%51,%52,%53,%54,%55,%56,%57,%58,%59,%60,%61,%62,%63,"
      "%64,%65,%66,%67,%68,%69,%70,%71,%72,%73,%74,%75,%76,%77,%78,%79,%80,%81,%82,%83,%84,%85,%86,%87,%88,%89,%90,%91,%92,%93,%94,%95,"
      "%96,%97,%98,%99,%100,%101,%102,%103,%104,%105,%106,%107,%108,%109,%110,%111,%112,%113,%114,%115,%116,%117,%118,%119,%120,%121,%122,%123,%124,%125,%126,%127},"
      "%128, %129, p, 1, 1, 0, 1;}\n"
      : R32(0), R32(32), R32(64), R32(96)
      : "l"(ad), "l"(bd), "r"(acc));
}

__device__ __forceinline__ void ln16(const float* x, float* o) {
  float s = 0;
#pragma unroll
  for (int i = 0; i < 16; i++) s += x[i];
#pragma unroll
  for (int of = 16; of > 0; of >>= 1) s += __shfl_xor_sync(~0u, s, of);
  float mean = s * (1.0f / DM);
  float v = 0;
#pragma unroll
  for (int i = 0; i < 16; i++) { float dd = x[i] - mean; v += dd * dd; }
#pragma unroll
  for (int of = 16; of > 0; of >>= 1) v += __shfl_xor_sync(~0u, v, of);
  float mb = bf16r(mean);
  float vb = bf16r(v * (1.0f / DM));
  float den = bf16r(sqrtf(bf16r(vb + 1e-5f)));
#pragma unroll
  for (int i = 0; i < 16; i++) o[i] = bf16r(__fdiv_rn(bf16r(x[i] - mb), den));
}
__global__ void __launch_bounds__(256) k_pre(const bf16* __restrict__ x) {
  int t = threadIdx.x, lane = t & 31, w = t >> 5;
  int row = blockIdx.x * 8 + w;
  const uint4* src = reinterpret_cast<const uint4*>(x + (size_t)row * DM);
  uint4 a = src[lane], b = src[lane + 32];
  unsigned u[8] = {a.x, a.y, a.z, a.w, b.x, b.y, b.z, b.w};
  float f[16], o[16], o2[16];
#pragma unroll
  for (int i = 0; i < 8; i++) { f[2 * i] = bf_lo(u[i]); f[2 * i + 1] = bf_hi(u[i]); }
  ln16(f, o);
  ln16(o, o2);
  uint4* d1 = reinterpret_cast<uint4*>(g_xn + (size_t)row * DM);
  uint4* d2 = reinterpret_cast<uint4*>(g_y + (size_t)row * DM);
  d1[lane] = make_uint4(pack_bf16(o[0], o[1]), pack_bf16(o[2], o[3]), pack_bf16(o[4], o[5]), pack_bf16(o[6], o[7]));
  d1[lane + 32] = make_uint4(pack_bf16(o[8], o[9]), pack_bf16(o[10], o[11]), pack_bf16(o[12], o[13]), pack_bf16(o[14], o[15]));
  d2[lane] = make_uint4(pack_bf16(o2[0], o2[1]), pack_bf16(o2[2], o2[3]), pack_bf16(o2[4], o2[5]), pack_bf16(o2[6], o2[7]));
  d2[lane + 32] = make_uint4(pack_bf16(o2[8], o2[9]), pack_bf16(o2[10], o2[11]), pack_bf16(o2[12], o2[13]), pack_bf16(o2[14], o2[15]));
  int gt = blockIdx.x * 256 + t;
  uint4 z = make_uint4(0, 0, 0, 0);
  if (gt < 16384) reinterpret_cast<uint4*>(g_part)[gt] = z;
  if (gt < (int)(sizeof(Flags) / 4)) reinterpret_cast<unsigned*>(&g_flags)[gt] = 0;
}

struct Maps { CUtensorMap xn, y, h1, o, qkv_st, qkv_ld, g, wq, wk, wv, wo, w1, w2; };

#define NSTAGE 3
#define STAGE_BYTES 49152
#define B_STG (NSTAGE * STAGE_BYTES)
#define R_WO 0
#define R_T1 65536
#define R_T2 131072
#define R_RING 65536
#define RING_N 4
#define RING_BYTES 12288
#define R_MEM 196608
#define R_QS (R_MEM + 8448)
#define R_KS (R_QS + 1152)
#define R_OS (R_KS + 1152)
#define R_SOWN (R_OS + 2176)
#define R_SPEER (R_SOWN + 1280)
#define R_VM (R_SPEER + 1280)
#define R_VRED (R_VM + 2048)
#define R_RS (R_VRED + 6144)
#define SM_BAR (R_RS + 8192)
#define SMEM_TOTAL (SM_BAR + 256 + 1024)
#define MB_FULL 0
#define MB_EMPTY 8
#define MB_STGF 16
#define MB_STGE 17
#define MB_W0 18
#define MB_W1 19
#define MB_WO 20
#define MB_S 21
#define MB_V 22
#define MB_KVR 23
#define MB_KVF 24
#define MB_RS 25
#define MB_AG 26
#define SM_MISC (SM_BAR + 224)

#define N_KV 512
#define I_M1 512
#define I_Q 624
#define I_M2 880
#define I_POST 912
#define I_TAIL (I_POST + 16 * 32)
#define N_ITEMS (I_TAIL + 5 * 8 + 32 + 8 + 64)
enum { T_QKV = 0, T_M1 = 1, T_M2 = 2, T_ATT = 3, T_OUT = 4, T_OUTL = 5, T_RED = 6, T_REDL = 7 };
struct Item { int type, b, c, ks; };
__device__ __forceinline__ Item decode_item(int i) {
  Item it; it.ks = 0;
  if (i < N_KV) { it.type = T_QKV; it.b = i >> 5; it.c = 16 + (i & 31); }
  else if (i < I_Q) { it.type = T_M1; it.b = (i - I_M1) / 7; it.c = (i - I_M1) % 7; }
  else if (i < I_M2) { it.type = T_QKV; it.b = (i - I_Q) >> 4; it.c = (i - I_Q) & 15; }
  else if (i < I_POST) { it.type = T_M2; it.b = (i - I_M2) >> 1; it.c = (i - I_M2) & 1; }
  else if (i < I_TAIL) {
    int x = i - I_POST, p = x >> 5, r = x & 31;
    if (r < 16) { it.type = T_ATT; it.b = p; it.c = r; }
    else if (r < 24) { it.type = T_OUT; it.b = p - 3; it.c = r & 1; it.ks = (r - 16) >> 1; }
    else { it.type = T_RED; it.b = p - 5; it.c = r - 24; }
  } else {
    int x = i - I_TAIL, r = x & 7;
    if (x < 40) {
      int q = x >> 3;
      if (q == 0 || q == 2) { it.type = T_OUT; it.b = 13 + (q >> 1); it.c = r & 1; it.ks = r >> 1; }
      else { it.type = T_RED; it.b = q == 1 ? 11 : 9 + q; it.c = r; }
    }
    else if (x < 72) { it.type = T_OUTL; it.b = 15; it.c = x & 1; it.ks = (x - 40) >> 1; }
    else if (x < 80) { it.type = T_RED; it.b = 14; it.c = r; }
    else { it.type = T_REDL; it.b = 15; it.c = x - 80; }
  }
  return it;
}
__device__ __forceinline__ int item_nkb(int type) { return type == T_M2 ? 28 : (type == T_OUT ? 16 : (type >= T_RED ? 1 : (type >= T_ATT ? 4 : 8))); }

__device__ __forceinline__ void st_async_b64(unsigned raddr, unsigned lo, unsigned hi, unsigned rmb) {
  asm volatile("st.async.weak.shared::cluster.mbarrier::complete_tx::bytes.v2.b32 [%0], {%1,%2}, [%3];" ::"r"(raddr), "r"(lo), "r"(hi), "r"(rmb) : "memory");
}
__device__ __forceinline__ void st_async_b32(unsigned raddr, unsigned v, unsigned rmb) {
  asm volatile("st.async.weak.shared::cluster.mbarrier::complete_tx::bytes.b32 [%0], %1, [%2];" ::"r"(raddr), "r"(v), "r"(rmb) : "memory");
}
__device__ __forceinline__ unsigned mapa(unsigned a, unsigned rank) {
  unsigned r; asm volatile("mapa.shared::cluster.u32 %0, %1, %2;" : "=r"(r) : "r"(a), "r"(rank)); return r;
}
__device__ __forceinline__ void sts64(unsigned a, unsigned x, unsigned y) { asm volatile("st.shared.v2.b32 [%0], {%1,%2};" ::"r"(a), "r"(x), "r"(y) : "memory"); }
__device__ __forceinline__ void sts128(unsigned a, uint4 v) { asm volatile("st.shared.v4.b32 [%0], {%1,%2,%3,%4};" ::"r"(a), "r"(v.x), "r"(v.y), "r"(v.z), "r"(v.w) : "memory"); }
__device__ __forceinline__ uint2 lds64(unsigned a) { uint2 v; asm volatile("ld.shared.v2.b32 {%0,%1}, [%2];" : "=r"(v.x), "=r"(v.y) : "r"(a) : "memory"); return v; }
__device__ __forceinline__ uint4 lds128(unsigned a) { uint4 v; asm volatile("ld.shared.v4.b32 {%0,%1,%2,%3}, [%4];" : "=r"(v.x), "=r"(v.y), "=r"(v.z), "=r"(v.w) : "r"(a) : "memory"); return v; }
__device__ __forceinline__ float lds32f(unsigned a) { float v; asm volatile("ld.shared.f32 %0, [%1];" : "=f"(v) : "r"(a) : "memory"); return v; }
#define spin_check(it) TRAP_IF(++it)
#define POLLV 0
#define BAR8 0
#define D_STAG 150
#define D_RED 480
#define D_PUB 0
#define DELAY(n) do { unsigned c0_, c1_; asm volatile("mov.u32 %0, %%clock;" : "=r"(c0_)); do { asm volatile("mov.u32 %0, %%clock;" : "=r"(c1_)); } while (c1_ - c0_ < (n)); } while (0)
#define NPRE1 0
#define VD 2
#define ZS 0
#define MBL 1
#define SCALE_QK 0.08838834764831845f

__device__ __forceinline__ void rec_worker(const Maps& maps, unsigned sb, const bf16* __restrict__ mem0) {
  const int c = blockIdx.x, h = c >> 1, j = c & 1;
  const int t = opaque_tid(), lane = t & 31, w = t >> 5, g = lane >> 2, tq = lane & 3;
  const int m = lane >> 3, r8 = lane & 7, kh = w >> 2, et = w & 3;
  const unsigned bar = sb + SM_BAR;
  unsigned wq[16][4], wk[16][4], wo[8][4];
  const unsigned woff = (kh * 4) * 8192 + ((m >> 1) * 8 + r8) * 128 + (((et * 2 + (m & 1)) ^ r8) << 4);
  mbar_wait(bar + 8 * MB_W0, 0);
#pragma unroll
  for (int i = 0; i < 16; i++) {
    ldsm_x4_t(wq[i], sb + R_WO + woff + (i >> 2) * 8192 + (i & 3) * 2048);
    ldsm_x4_t(wk[i], sb + R_T1 + woff + (i >> 2) * 8192 + (i & 3) * 2048);
  }
  bar_sync(2, 288);
  if (t == 0) {
    fence_proxy_async_smem();
    mbar_expect_tx(bar + 8 * MB_WO, 65536);
    for (int kb = 0; kb < 2; kb++)
      for (int cb = 0; cb < 4; cb++) tma_load_2d(sb + R_WO + (kb * 4 + cb) * 8192, &maps.wo, j * 256 + cb * 64, h * 128 + kb * 64, bar + 8 * MB_WO);
  }
  mbar_wait(bar + 8 * MB_W1, 0);
  const unsigned pV = sb + R_T2 + woff;
  const unsigned rk = c & 7, peer = rk ^ 1, cl = c >> 3;
#define KEEP(x) x = __shfl_sync(~0u, x, lane)
  unsigned pA = sb + R_MEM + kh * 4096 + lane * 16;
  unsigned pW0 = sb + R_WO + (w >> 1) * 8192 + ((m >> 1) * 8 + r8) * 128 + ((((w & 1) * 4 + (m & 1)) ^ r8) << 4);
#define pW1 (pW0 ^ 32)
  unsigned pVk = mapa(sb + R_VM + (j * 4 + et) * 256 + lane * 8, peer);
  unsigned aX = sb + R_VRED + et * 512 + lane * 16;
  unsigned aQKst = sb + (kh ? R_KS : R_QS) + r8 * 144 + (et * 16 + (m & 1) * 8) * 2;
  unsigned aL8_ = sb + lane * 8;
  unsigned aSl_ = mapa(sb + R_SOWN + w * 256 + lane * 8, rk), aSr_ = mapa(sb + R_SPEER + w * 256 + lane * 8, peer);
  const unsigned mbSl = mapa(bar + 8 * MB_S, rk), mbSr = mapa(bar + 8 * MB_S, peer), mbVl = mbSl + 8, mbVr = mbSr + 8;
  unsigned aQ_ = sb + R_QS + r8 * 144 + m * 16;
  unsigned oKx_ = (et * 8 + r8) * 128 + ((m ^ r8) << 4);
  unsigned oVx_ = 4096 + (et >> 1) * 4096 + ((m >> 1) * 8 + r8) * 128 + ((((et & 1) * 4 + (m & 1)) ^ r8) << 4);
  unsigned aOst_ = sb + R_OS + r8 * 272 + (et * 32 + m * 8) * 2;
  unsigned aOld = sb + R_OS + r8 * 272 + m * 16;
  unsigned aVm_ = sb + R_VM + et * 512 + lane * 8;
  unsigned aRSr = mapa(sb + R_RS + (h & 3) * 2048 + (w & 1) * 1024 + lane * 8, j * 4 + (w >> 1));
  unsigned t8 = t * 8;
  unsigned r1 = kh ? aL8_ : aSl_, r2 = kh ? oVx_ : aSr_, r3 = kh ? aOst_ : aQ_, r4 = kh ? aVm_ : oKx_;
#define aL8 r1
#define aSl r1
#define oVx r2
#define aSr r2
#define aOst r3
#define aQ r3
#define aVm r4
#define oKx r4
#define aVr pVk
  const unsigned dLR = mbSl - mbSr;
  KEEP(pA); KEEP(pW0); KEEP(pVk); KEEP(aX); KEEP(aQKst); KEEP(r1); KEEP(r2); KEEP(r3); KEEP(r4);
  KEEP(aOld); KEEP(aRSr); KEEP(t8);
  mbar_wait(bar + 8 * MB_WO, 0);
#pragma unroll
  for (int ks = 0; ks < 4; ks++) { ldsm_x4_t(wo[2 * ks], pW0 + ks * 2048); ldsm_x4_t(wo[2 * ks + 1], pW1 + ks * 2048); }
  {
    unsigned v[8];
#pragma unroll
    for (int q = 0; q < 8; q++) v[q] = __ldg(reinterpret_cast<const unsigned*>(mem0) + q * 256 + t);
    sts128(sb + R_MEM + t * 32, make_uint4(__byte_perm(v[0], v[1], 0x5410), __byte_perm(v[2], v[3], 0x5410), __byte_perm(v[4], v[5], 0x5410), __byte_perm(v[6], v[7], 0x5410)));
    sts128(sb + R_MEM + t * 32 + 16, make_uint4(__byte_perm(v[0], v[1], 0x7632), __byte_perm(v[2], v[3], 0x7632), __byte_perm(v[4], v[5], 0x7632), __byte_perm(v[6], v[7], 0x7632)));
  }
  fence_proxy_async_smem();
  bar_sync(1, 256);

#pragma unroll 1
  for (int s = 0;; s++) {
    const unsigned par = s & 1;
    const unsigned slot = s & (RING_N - 1), rpar = (s / RING_N) & 1;
    const unsigned ring = sb + R_RING + slot * RING_BYTES;
    RSTAMP(1);
    RSTAMP(2);
    float aq[4] = {0, 0, 0, 0}, ak[4] = {0, 0, 0, 0};
    {
      float aq1[4] = {0, 0, 0, 0}, ak1[4] = {0, 0, 0, 0};
      unsigned b[8][4];
#pragma unroll
      for (int i = 0; i < 4; i++) ldsm_x4_t(b[i], pA + i * 512);
#pragma unroll
      for (int i = 0; i < 8; i++) {
        mma16816(aq, wq[2 * i], b[i][0], b[i][1]); mma16816(ak, wk[2 * i], b[i][0], b[i][1]);
        mma16816(aq1, wq[2 * i + 1], b[i][2], b[i][3]); mma16816(ak1, wk[2 * i + 1], b[i][2], b[i][3]);
        if (i < 4) ldsm_x4_t(b[i + 4], pA + (i + 4) * 512);
      }
#pragma unroll
      for (int i = 0; i < 4; i++) { aq[i] += aq1[i]; ak[i] += ak1[i]; }
    }
    RSTAMP(3);
#define STSF4(a, v) asm volatile("st.shared.v4.f32 [%0], {%1,%2,%3,%4};" ::"r"(a), "f"(v[0]), "f"(v[1]), "f"(v[2]), "f"(v[3]) : "memory")
#define VLD(i) do { ldsm_x4_t(b[i], pA + (i) * 512); ldsm_x4_t(f0[i], pVk + ((i) >> 1) * 8192 + ((i) & 1) * 4096); ldsm_x4_t(f1[i], pVk + ((i) >> 1) * 8192 + ((i) & 1) * 4096 + 2048); } while (0)
#define VPASS() float av[4] = {0, 0, 0, 0}; { float av1[4] = {0, 0, 0, 0}; unsigned b[8][4], f1[8][4], f0[8][4]; VLD(0); if (VD > 1) VLD(1); \
      _Pragma("unroll") for (int i = 0; i < 8; i++) { if (i + VD < 8) VLD(i + VD); \
        mma16816(av, f0[i], b[i][0], b[i][1]); mma16816(av1, f1[i], b[i][2], b[i][3]); } \
      _Pragma("unroll") for (int i = 0; i < 4; i++) av[i] += av1[i]; }
    unsigned f[8][4];
#define WO_LD(i0, i1) do { _Pragma("unroll") for (int i = i0; i < i1; i++) { ldsm_x4_t(f[2 * i], pW0 + 32768 + i * 2048); ldsm_x4_t(f[2 * i + 1], pW1 + 32768 + i * 2048); } } while (0)
    if (kh) {
      STSF4(aX, aq);
      float av[4] = {0, 0, 0, 0};
      {
        const uint64_t ad = mkdesc(sb + R_T2, 8192, 1024), bd = (uint64_t)(((sb + R_MEM) >> 4) & 0x3fff) | (8ull << 16) | (8ull << 32);
        asm volatile("wgmma.fence.sync.aligned;" ::: "memory");
#pragma unroll
        for (int i = 0; i < 32; i++)
          asm volatile("wgmma.mma_async.sync.aligned.m64n8k16.f32.bf16.bf16 {%0,%1,%2,%3}, %4, %5, 1, 1, 1, 1, 1;"
                       : "+f"(av[0]), "+f"(av[1]), "+f"(av[2]), "+f"(av[3]) : "l"(ad + i * 128), "l"(bd + i * 16));
        asm volatile("wgmma.commit_group.sync.aligned;" ::: "memory");
      }
      bar_sync(4 + et, 64);
      uint4 o = lds128(aX + 2048);
      stsm_x2_t(aQKst, pack_bf16(ak[0] + __uint_as_float(o.x), ak[1] + __uint_as_float(o.y)), pack_bf16(ak[2] + __uint_as_float(o.z), ak[3] + __uint_as_float(o.w)));
      bar_arrive(1, 256);
      RSTAMP(4);
      asm volatile("wgmma.wait_group.sync.aligned 0;" : "+f"(av[0]), "+f"(av[1]), "+f"(av[2]), "+f"(av[3])::"memory");
      {
        unsigned x = pack_bf16(av[0], av[1]), y = pack_bf16(av[2], av[3]);
        st_async_b64(aVr, x, y, mbVr);
        st_async_b64(aVr + dLR, x, y, mbVl);
      }
      RSTAMP(5);
      if (s == NSEG - 1) {
        mbar_wait(bar + 8 * MB_V, par);
        if (t == 128) mbar_arrive(bar + 8 * MB_KVR);
        break;
      }
      mbar_wait(bar + 8 * (MB_FULL + slot), rpar);
      unsigned vx[4][4];
      ldsm_x4_t(vx[0], ring + oVx); ldsm_x4_t(vx[1], ring + oVx + 2048); ldsm_x4_t(vx[2], ring + (oVx ^ 32)); ldsm_x4_t(vx[3], ring + (oVx ^ 32) + 2048);
      WO_LD(0, NPRE1);
      RSTAMP(6); RSTAMP(7);
      mbar_wait(bar + 8 * MB_S, par);
      RSTAMP(8);
      float sc[10];
#pragma unroll
      for (int i = 0; i < 5; i++) {
        uint2 o = lds64(aL8 + R_SOWN + i * 256), p = lds64(aL8 + R_SPEER + i * 256);
        sc[2 * i] = __uint_as_float(o.x) + __uint_as_float(p.x); sc[2 * i + 1] = __uint_as_float(o.y) + __uint_as_float(p.y);
      }
      float mx = fmaxf(fmaxf(fmaxf(sc[0], sc[1]), fmaxf(sc[2], sc[3])), fmaxf(fmaxf(fmaxf(sc[4], sc[5]), fmaxf(sc[6], sc[7])), fmaxf(sc[8], sc[9])));
      mx = fmaxf(mx, __shfl_xor_sync(~0u, mx, 1)); mx = fmaxf(mx, __shfl_xor_sync(~0u, mx, 2));
      const float nm = -mx * (SCALE_QK * LOG2E);
      unsigned p[5];
#pragma unroll
      for (int i = 0; i < 5; i++) p[i] = pack_bf16(ex2f(fmaf(sc[2 * i], SCALE_QK * LOG2E, nm)), ex2f(fmaf(sc[2 * i + 1], SCALE_QK * LOG2E, nm)));
      RSTAMP(9);
      float o0[4] = {0, 0, 0, 0}, o1[4] = {0, 0, 0, 0}, o3[4] = {0, 0, 0, 0}, o4[4] = {0, 0, 0, 0}, z0[4] = {0, 0, 0, 0}, z1[4] = {0, 0, 0, 0};
      const unsigned ones[4] = {0x3F803F80u, 0u, 0x3F803F80u, 0u};
      mma16816(z0, ones, p[0], p[1]); mma16816(ZS ? z0 : z1, ones, p[2], p[3]);
      mma16816(o0, vx[0], p[0], p[1]); mma16816(o3, vx[2], p[0], p[1]); mma16816(o1, vx[1], p[2], p[3]); mma16816(o4, vx[3], p[2], p[3]);
      mma1688(z0, 0x3F803F80u, 0u, p[4]);
      mbar_wait(bar + 8 * MB_V, par);
      uint2 vm0 = lds64(aVm), vm1 = lds64(aVm + 256);
      mma1688(o0, vm0.x, vm0.y, p[4]); mma1688(o3, vm1.x, vm1.y, p[4]);
      float i0, i1;
      asm("rcp.approx.ftz.f32 %0, %1;" : "=f"(i0) : "f"(z0[0] + z1[0])); asm("rcp.approx.ftz.f32 %0, %1;" : "=f"(i1) : "f"(z0[1] + z1[1]));
      asm volatile("stmatrix.sync.aligned.m8n8.x4.trans.shared.b16 [%0], {%1,%2,%3,%4};" ::"r"(aOst), "r"(pack_bf16((o0[0] + o1[0]) * i0, (o0[1] + o1[1]) * i1)), "r"(pack_bf16((o0[2] + o1[2]) * i0, (o0[3] + o1[3]) * i1)),
                   "r"(pack_bf16((o3[0] + o4[0]) * i0, (o3[1] + o4[1]) * i1)), "r"(pack_bf16((o3[2] + o4[2]) * i0, (o3[3] + o4[3]) * i1)) : "memory");
      RSTAMP(10);
      bar_sync(1, 256);
      WO_LD(NPRE1, 3);
    } else {
      STSF4(aX + 2048, ak);
      unsigned kb[8];
      mbar_wait(bar + 8 * (MB_FULL + slot), rpar);
      ldsm_x4(kb, ring + oKx); ldsm_x4(kb + 4, ring + (oKx ^ 64));
      bar_sync(4 + et, 64);
      uint4 o = lds128(aX);
      stsm_x2_t(aQKst, pack_bf16(aq[0] + __uint_as_float(o.x), aq[1] + __uint_as_float(o.y)), pack_bf16(aq[2] + __uint_as_float(o.z), aq[3] + __uint_as_float(o.w)));
      RSTAMP(4);
      bar_sync(1, 256);
      RSTAMP(5);
      if (s != NSEG - 1) {
        unsigned qa[8], km[8];
        ldsm_x4(qa, aQ); ldsm_x4(qa + 4, aQ + 64);
        if (w == 3) { ldsm_x4(km, aQ + 1152); ldsm_x4(km + 4, aQ + 1152 + 64); }
        float s0[4] = {0, 0, 0, 0}, s1[4] = {0, 0, 0, 0};
        unsigned af[4][4];
#pragma unroll
        for (int i = 0; i < 4; i++) { af[i][0] = qa[2 * i]; af[i][1] = 0; af[i][2] = qa[2 * i + 1]; af[i][3] = 0; }
        mma16816(s0, af[0], kb[0], kb[1]); mma16816(s1, af[1], kb[2], kb[3]);
        mma16816(s0, af[2], kb[4], kb[5]); mma16816(s1, af[3], kb[6], kb[7]);
        if (w == 3) {
          float m0[4] = {0, 0, 0, 0}, m1[4] = {0, 0, 0, 0};
          mma16816(m0, af[0], km[0], km[1]); mma16816(m1, af[1], km[2], km[3]);
          mma16816(m0, af[2], km[4], km[5]); mma16816(m1, af[3], km[6], km[7]);
          unsigned x = __float_as_uint(m0[0] + m1[0]), y = __float_as_uint(m0[1] + m1[1]);
          st_async_b64(aSr + 256, x, y, mbSr); st_async_b64(aSl + 256, x, y, mbSl);
        }
        unsigned x = __float_as_uint(s0[0] + s1[0]), y = __float_as_uint(s0[1] + s1[1]);
        st_async_b64(aSr, x, y, mbSr); st_async_b64(aSl, x, y, mbSl);
      }
      RSTAMP(6);
      RSTAMP(7); RSTAMP(8);
      if (s == NSEG - 1) break;
      WO_LD(0, 3);
      RSTAMP(9); RSTAMP(10);
      bar_sync(1, 256);
    }
    RSTAMP(11);
    float d0[4] = {0, 0, 0, 0}, d1[4] = {0, 0, 0, 0}, e0[4] = {0, 0, 0, 0}, e1[4] = {0, 0, 0, 0};
    unsigned ob[4][4];
    ldsm_x4(ob[0], aOld); ldsm_x4(ob[1], aOld + 64);
    mma16816(d0, wo[0], ob[0][0], ob[0][1]); mma16816(d1, wo[1], ob[0][0], ob[0][1]);
    mma16816(e0, wo[2], ob[0][2], ob[0][3]); mma16816(e1, wo[3], ob[0][2], ob[0][3]);
    ldsm_x4(ob[2], aOld + 128);
    mma16816(d0, wo[4], ob[1][0], ob[1][1]); mma16816(d1, wo[5], ob[1][0], ob[1][1]);
    mma16816(e0, wo[6], ob[1][2], ob[1][3]); mma16816(e1, wo[7], ob[1][2], ob[1][3]);
    ldsm_x4(ob[3], aOld + 192);
    mma16816(d0, f[0], ob[2][0], ob[2][1]); mma16816(d1, f[1], ob[2][0], ob[2][1]);
    WO_LD(3, 4);
    mma16816(e0, f[2], ob[2][2], ob[2][3]); mma16816(e1, f[3], ob[2][2], ob[2][3]);
    const unsigned mbRSr = mapa(bar + 8 * MB_RS, j * 4 + (t8 >> 9));
    mma16816(d0, f[4], ob[3][0], ob[3][1]); mma16816(d1, f[5], ob[3][0], ob[3][1]);
    mma16816(e0, f[6], ob[3][2], ob[3][3]); mma16816(e1, f[7], ob[3][2], ob[3][3]);
    st_async_b64(aRSr, __float_as_uint(d0[0] + e0[0]), __float_as_uint(d0[1] + e0[1]), mbRSr);
    st_async_b64(aRSr + 256, __float_as_uint(d0[2] + e0[2]), __float_as_uint(d0[3] + e0[3]), mbRSr);
    st_async_b64(aRSr + 512, __float_as_uint(d1[0] + e1[0]), __float_as_uint(d1[1] + e1[1]), mbRSr);
    st_async_b64(aRSr + 768, __float_as_uint(d1[2] + e1[2]), __float_as_uint(d1[3] + e1[3]), mbRSr);
    RSTAMP(12);
    if (t == 128) {
      mbar_arrive(bar + 8 * (MB_EMPTY + slot)); mbar_arrive(bar + 8 * MB_KVR);
      mbar_expect_tx(bar + 8 * MB_S, 2560); mbar_expect_tx(bar + 8 * MB_V, 2048);
    }
    const unsigned tag = ((s >> 1) & 1) ^ 1;
    const char* gp = reinterpret_cast<const char*>(g_part) + (par * 8 + rk) * 16384 + t8;
    unsigned mbA[8];
#pragma unroll
    for (int i = 0; i < 8; i++) if (!MBL) mbA[i] = mapa(bar + 8 * MB_AG, i);
    const unsigned dlt = (R_MEM + rk * 1024) - (SM_BAR + 8 * MB_AG) + (t8 >> 1);
    mbar_wait(bar + 8 * MB_RS, par);
    RSTAMP(13);
    uint2 a[8];
    {
      uint2 x0 = lds64(sb + R_RS + t8), x1 = lds64(sb + R_RS + 2048 + t8), x2 = lds64(sb + R_RS + 4096 + t8), x3 = lds64(sb + R_RS + 6144 + t8);
      float q0 = (__uint_as_float(x0.x) + __uint_as_float(x1.x)) + (__uint_as_float(x2.x) + __uint_as_float(x3.x));
      float q1 = (__uint_as_float(x0.y) + __uint_as_float(x1.y)) + (__uint_as_float(x2.y) + __uint_as_float(x3.y));
      a[0].x = (__float_as_uint(q0) & ~1u) | tag; a[0].y = (__float_as_uint(q1) & ~1u) | tag;
      asm volatile("st.relaxed.gpu.global.v2.u32 [%0], {%1,%2};" ::"l"(gp + cl * 2048), "r"(a[0].x), "r"(a[0].y) : "memory");
    }
    RSTAMP(14);
    if (t == 128) mbar_expect_tx(bar + 8 * MB_RS, 8192);
    {
      unsigned it = 0;
#define PLOAD(a) _Pragma("unroll") for (int i = 1; i < 8; i++) a[i] = ldv2_relaxed(gp + (cl ^ i) * 2048)
#define PAND(a) (((a[1].x & a[1].y) & (a[2].x & a[2].y) & (a[3].x & a[3].y)) & ((a[4].x & a[4].y) & (a[5].x & a[5].y)) & ((a[6].x & a[6].y) & (a[7].x & a[7].y)))
#define POR(a) (((a[1].x | a[1].y) | (a[2].x | a[2].y) | (a[3].x | a[3].y)) | ((a[4].x | a[4].y) | (a[5].x | a[5].y)) | ((a[6].x | a[6].y) | (a[7].x | a[7].y)))
#define POK(a) (((tag ? PAND(a) : ~POR(a)) & 1u) != 0)
      if (D_RED) DELAY(D_RED);
      while (true) { PLOAD(a); if (POK(a)) break; if (D_PUB) DELAY(D_PUB); spin_check(it); }
    }
    RSTAMP(15);
    {
#define AF(i, c) __uint_as_float(a[i].c)
      unsigned u = pack_bf16(((AF(0, x) + AF(1, x)) + (AF(2, x) + AF(3, x))) + ((AF(4, x) + AF(5, x)) + (AF(6, x) + AF(7, x))),
                             ((AF(0, y) + AF(1, y)) + (AF(2, y) + AF(3, y))) + ((AF(4, y) + AF(5, y)) + (AF(6, y) + AF(7, y))));
      __syncwarp();
#pragma unroll
      for (int i = 0; i < 8; i++) { if (MBL) mbA[i] = mapa(bar + 8 * MB_AG, i); st_async_b32(mbA[i] + dlt, u, mbA[i]); }
    }
    mbar_wait(bar + 8 * MB_KVF, par);
    mbar_wait(bar + 8 * MB_AG, par);
    if (t == 128) mbar_expect_tx(bar + 8 * MB_AG, 8192);
  }
}

__device__ __forceinline__ void rec_ring(const Maps& maps, unsigned sb) {
  const int c = blockIdx.x, h = c >> 1, j = c & 1;
  const unsigned bar = sb + SM_BAR;
  const int lane = threadIdx.x & 31;
  if (lane == 0) {
    mbar_expect_tx(bar + 8 * MB_W0, 131072);
    for (int kb = 0; kb < 8; kb++) tma_load_2d(sb + R_WO + kb * 8192, &maps.wq, h * 128 + j * 64, kb * 64, bar + 8 * MB_W0);
    for (int kb = 0; kb < 8; kb++) tma_load_2d(sb + R_T1 + kb * 8192, &maps.wk, h * 128 + j * 64, kb * 64, bar + 8 * MB_W0);
    mbar_expect_tx(bar + 8 * MB_W1, 65536);
    for (int kb = 0; kb < 8; kb++) tma_load_2d(sb + R_T2 + kb * 8192, &maps.wv, h * 128 + j * 64, kb * 64, bar + 8 * MB_W1);
  }
  __syncwarp();
  bar_sync(2, 288);
  if (lane == 0) {
    fence_proxy_async_smem();
    for (int s = 0; s < NSEG; s++) {
      unsigned slot = s & (RING_N - 1);
      if ((s & 3) == 0 && !DBGMODE) {
        wait_flag_ge(&g_flags.qkv[(s >> 2) * 48 + 16 + (h >> 1)], 1);
        wait_flag_ge(&g_flags.qkv[(s >> 2) * 48 + 32 + (h >> 1)], 1);
        fence_proxy_async();
      }
      if (s >= RING_N) mbar_wait_sleep(bar + 8 * (MB_EMPTY + slot), ((s / RING_N) - 1) & 1);
      unsigned dst = sb + R_RING + slot * RING_BYTES, mb = bar + 8 * (MB_FULL + slot);
      mbar_expect_tx(mb, RING_BYTES);
      tma_load_2d(dst, &maps.qkv_ld, HD + h * 128 + j * 64, s * SEG, mb);
      tma_load_2d(dst + 4096, &maps.qkv_ld, 2 * HD + h * 128, s * SEG, mb);
      tma_load_2d(dst + 8192, &maps.qkv_ld, 2 * HD + h * 128 + 64, s * SEG, mb);
    }
  }
}
__device__ __forceinline__ void rec_copy(unsigned sb) {
  const int c = blockIdx.x, h = c >> 1, j = c & 1;
  const unsigned bar = sb + SM_BAR;
  const int lane = threadIdx.x & 31;
  for (int s = 0; s < NSEG; s++) {
    mbar_wait_sleep(bar + 8 * MB_KVR, s & 1);
    uint4 k0 = lds128(sb + R_KS + (lane >> 3) * 144 + (lane & 7) * 16), k1 = lds128(sb + R_KS + (4 + (lane >> 3)) * 144 + (lane & 7) * 16);
    uint2 v[4];
#pragma unroll
    for (int i = 0; i < 4; i++) v[i] = lds64(sb + R_VM + (j * 4 + i) * 256 + lane * 8);
    __syncwarp();
    if (lane == 0) mbar_arrive(bar + 8 * MB_KVF);
    bf16* kd = g_km + ((size_t)(s * NH + h) * NMEM) * DH + j * 64;
    *reinterpret_cast<uint4*>(kd + (lane >> 3) * DH + (lane & 7) * 8) = k0;
    *reinterpret_cast<uint4*>(kd + (4 + (lane >> 3)) * DH + (lane & 7) * 8) = k1;
    unsigned* vd = reinterpret_cast<unsigned*>(g_vmt) + ((size_t)(s * NH + h) * DH + j * 64) * 4;
#pragma unroll
    for (int i = 0; i < 4; i++) { vd[(i * 16) * 4 + lane] = v[i].x; vd[(i * 16 + 8) * 4 + lane] = v[i].y; }
    __syncwarp();
    if (lane == 0) st_release(&g_flags.rec[c], s + 1);
  }
}

__device__ __forceinline__ void bulk_producer(const Maps& maps, unsigned sb, int* misc) {
  const unsigned bar = sb + SM_BAR;
  const int lane = threadIdx.x & 31;
  unsigned st = 0, ph = 0, seq = 0;
  while (true) {
    int idx = 0;
    if (lane == 0) idx = (int)atomicAdd(&g_flags.ctr, 1u);
    idx = __shfl_sync(~0u, idx, 0);
    if (idx >= N_ITEMS) {
      if (lane == 0) {
        mbar_wait(bar + 8 * (MB_EMPTY + st), ph ^ 1);
        misc[seq & 3] = -1;
        mbar_arrive(bar + 8 * (MB_FULL + st));
      }
      break;
    }
    if (lane == 0) ISTAMP(idx, 0);
    Item it = decode_item(idx);
    if (it.b < 0) continue;
    const CUtensorMap* mp; int c0, c1, dc0, dc1; unsigned doff;
    const unsigned* fl = nullptr; unsigned tgt = 1; int nbox = 5, rdy = 0;
    if (it.type == T_ATT) {
      mp = &maps.qkv_ld; nbox = 12; doff = lane * 4096;
      c0 = (lane >> 2) * HD + it.c * 256 + (lane & 1) * 64; c1 = it.b * 128 + ((lane >> 1) & 1) * 32; dc0 = dc1 = 0;
      if (lane < 3) fl = &g_flags.qkv[it.b * 48 + lane * 16 + it.c];
      bool ok = true;
      if (lane >= 4 && lane < 8) ok = ld_acquire(&g_flags.rec[it.c * 4 + lane - 4]) >= (unsigned)(it.b * 4 + 4);
      rdy = __all_sync(~0u, ok) ? 65536 : 0;
    } else {
      int k0 = 0, nb0 = it.c * 256;
      if (it.type == T_QKV) { mp = lane == 0 ? &maps.xn : (it.c < 16 ? &maps.wq : (it.c < 32 ? &maps.wk : &maps.wv)); nb0 = (it.c & 15) * 256; }
      else if (it.type == T_M1) mp = lane == 0 ? &maps.y : &maps.w1;
      else if (it.type == T_M2) { mp = lane == 0 ? &maps.h1 : &maps.w2; fl = &g_flags.h1[it.b]; tgt = 7; }
      else {
        mp = lane == 0 ? &maps.o : &maps.wo;
        if (it.type == T_OUT) { k0 = it.ks * 1024; fl = &g_flags.o[it.b * 4 + it.ks]; tgt = 4; }
        else if (it.type == T_OUTL) { k0 = it.ks * 256; fl = &g_flags.o16[it.ks]; }
        else if (lane == 1) { fl = &g_flags.g[it.b]; tgt = 2; }
        else { fl = &g_flags.p[it.b]; tgt = it.type == T_RED ? 8 : 32; }
      }
      if (lane > (it.type >= T_RED ? 1 : 0)) fl = nullptr;
      if (lane == 0) { c0 = k0; c1 = it.b * 128; dc0 = 64; dc1 = 0; doff = 0; }
      else { c0 = nb0 + (lane - 1) * 64; c1 = k0; dc0 = 0; dc1 = 64; doff = 8192 + lane * 8192; }
    }
    if (fl) wait_flag_ge(fl, tgt);
    __syncwarp();
    fence_proxy_async();
    if (lane == 0) ISTAMP(idx, 1);
    const int nkb = item_nkb(it.type);
    for (int kb = 0; kb < nkb; kb++) {
      const unsigned mb = bar + 8 * (MB_FULL + st);
      mbar_wait(bar + 8 * (MB_EMPTY + st), ph ^ 1);
      if (lane == 0) {
        if (kb == 0) misc[seq & 3] = idx | rdy;
        if (it.type >= T_RED) mbar_arrive(mb); else mbar_expect_tx(mb, STAGE_BYTES);
      }
      if (it.type == T_ATT) { if (lane < 12) tma_load_2d(sb + st * STAGE_BYTES + doff, mp, c0 + (kb & 1) * 128, c1 + (kb >> 1) * 64, mb); }
      else if (lane < nbox && it.type < T_RED) tma_load_2d(sb + st * STAGE_BYTES + doff, mp, c0 + kb * dc0, c1 + kb * dc1, mb);
      __syncwarp();
      if (++st == NSTAGE) { st = 0; ph ^= 1; }
    }
    seq++;
  }
}
__device__ __forceinline__ void bulk_store(const Maps& maps, unsigned sb, volatile int* misc) {
  const unsigned bar = sb + SM_BAR;
  unsigned ph = 0;
  while (true) {
    mbar_wait(bar + 8 * MB_STGF, ph); ph ^= 1;
    int idx = misc[4];
    if (idx < 0) break;
    Item it = decode_item(idx);
    const CUtensorMap* mp = it.type == T_QKV ? &maps.qkv_st : (it.type == T_M1 ? &maps.h1 : (it.type == T_M2 ? &maps.g : &maps.o));
    unsigned* flag = it.type == T_QKV ? &g_flags.qkv[it.b * 48 + it.c] : (it.type == T_M1 ? &g_flags.h1[it.b] : (it.type == T_M2 ? &g_flags.g[it.b] : (it.b == 15 ? &g_flags.o16[it.c] : &g_flags.o[it.b * 4 + (it.c >> 2)])));
    for (int i = 0; i < 4; i++) tma_store_2d(mp, sb + B_STG + i * 16384, it.c * 256 + i * 64, it.b * 128);
    asm volatile("cp.async.bulk.commit_group;" ::: "memory");
    asm volatile("cp.async.bulk.wait_group.read 0;" ::: "memory");
    mbar_arrive(bar + 8 * MB_STGE);
    asm volatile("cp.async.bulk.wait_group 0;" ::: "memory");
    fence_proxy_async();
    red_release_add(flag, 1);
    ISTAMP(idx, 3);
  }
}
__device__ __forceinline__ float rcpf(float x) { float y; asm("rcp.approx.ftz.f32 %0, %1;" : "=f"(y) : "f"(x)); return y; }
__device__ __forceinline__ float gelu_t(float x) {
  float e = ex2f(x * fmaf(x * x, -2.0f * LOG2E * 0.7978845608028654f * 0.044715f, -2.0f * LOG2E * 0.7978845608028654f));
  return x * rcpf(1.0f + e);
}
__device__ __forceinline__ float silu_f(float x) { return x * rcpf(1.0f + ex2f(-LOG2E * x)); }
__device__ __forceinline__ unsigned badd2(unsigned a, unsigned b) { unsigned r; asm("add.rn.bf16x2 %0, %1, %2;" : "=r"(r) : "r"(a), "r"(b)); return r; }

__device__ __forceinline__ void final_out(bf16* __restrict__ out, const bf16* __restrict__ x, size_t o, float4 s) {
  uint2 gv = __ldcg(reinterpret_cast<const uint2*>(g_g + o)), xv = __ldg(reinterpret_cast<const uint2*>(x + o));
  uint2 r;
  r.x = pack_bf16(bf_lo(xv.x) + bf16r(bf16r(s.x) * bf_lo(gv.x)), bf_hi(xv.x) + bf16r(bf16r(s.y) * bf_hi(gv.x)));
  r.y = pack_bf16(bf_lo(xv.y) + bf16r(bf16r(s.z) * bf_lo(gv.y)), bf_hi(xv.y) + bf16r(bf16r(s.w) * bf_hi(gv.y)));
  *reinterpret_cast<uint2*>(out + o) = r;
}
__device__ __forceinline__ void bulk_att_load(unsigned* km, unsigned* vm, int b, int hp, int kb, int w, int lane) {
  const int g = lane >> 2, tq = lane & 3, seg = w >> 2, eh = w & 1;
  const int head = hp * 2 + (kb & 1), sg = b * 4 + (kb >> 1) * 2 + seg;
  const unsigned* kmp = reinterpret_cast<const unsigned*>(g_km + ((size_t)(sg * NH + head) * NMEM + g) * DH) + tq;
  const unsigned* vmp = reinterpret_cast<const unsigned*>(g_vmt) + ((size_t)(sg * NH + head) * DH + eh * 64) * 4 + lane;
#pragma unroll
  for (int i = 0; i < 16; i++) asm volatile("ld.global.cg.u32 %0, [%1];" : "=r"(km[i]) : "l"(kmp + i * 4) : "memory");
#pragma unroll
  for (int i = 0; i < 8; i++) asm volatile("ld.global.cg.u32 %0, [%1];" : "=r"(vm[i]) : "l"(vmp + i * 32) : "memory");
}
__device__ __forceinline__ void bulk_att_stage(unsigned sa, unsigned stg, const unsigned* km, const unsigned* vm, int kb, int w, int lane) {
  const int g = lane >> 2, tq = lane & 3, m = lane >> 3, r8 = lane & 7;
  const int seg = w >> 2, mt = (w >> 1) & 1, eh = w & 1;
  float s[5][4];
#pragma unroll
  for (int i = 0; i < 5; i++) { s[i][0] = s[i][1] = s[i][2] = s[i][3] = 0; }
  const unsigned qb = sa + (0 * 2 + seg) * 8192, kbs = sa + (1 * 2 + seg) * 8192, vb = sa + (2 * 2 + seg) * 8192 + eh * 4096;
  unsigned qa[8][4];
#pragma unroll
  for (int ks = 0; ks < 8; ks++) {
    int row = mt * 16 + (m & 1) * 8 + r8;
    ldsm_x4(qa[ks], qb + (ks >> 2) * 4096 + row * 128 + ((((ks & 3) * 2 + (m >> 1)) ^ r8) << 4));
    unsigned kf[4];
    int krow = (m >> 1) * 8 + r8;
    unsigned ka = kbs + (ks >> 2) * 4096 + krow * 128 + ((((ks & 3) * 2 + (m & 1)) ^ r8) << 4);
    ldsm_x4(kf, ka);
    mma16816(s[0], qa[ks], kf[0], kf[1]); mma16816(s[1], qa[ks], kf[2], kf[3]);
    if (mt) { ldsm_x4(kf, ka + 2048); mma16816(s[2], qa[ks], kf[0], kf[1]); mma16816(s[3], qa[ks], kf[2], kf[3]); }
  }
#pragma unroll
  for (int ks = 0; ks < 8; ks++) mma16816(s[4], qa[ks], km[2 * ks], km[2 * ks + 1]);
  float mx0 = -INFINITY, mx1 = -INFINITY;
  const int t0 = mt * 16 + g, t1 = t0 + 8;
#pragma unroll
  for (int i = 0; i < 5; i++) {
#pragma unroll
    for (int e = 0; e < 4; e++) {
      float v = s[i][e];
      if (i < 4) { int kj = i * 8 + 2 * tq + (e & 1); if (kj > (e < 2 ? t0 : t1)) v = -INFINITY; }
      s[i][e] = v;
      if (e < 2) mx0 = fmaxf(mx0, v); else mx1 = fmaxf(mx1, v);
    }
  }
  mx0 = fmaxf(mx0, __shfl_xor_sync(~0u, mx0, 1)); mx0 = fmaxf(mx0, __shfl_xor_sync(~0u, mx0, 2));
  mx1 = fmaxf(mx1, __shfl_xor_sync(~0u, mx1, 1)); mx1 = fmaxf(mx1, __shfl_xor_sync(~0u, mx1, 2));
  float sm0 = 0, sm1 = 0;
#pragma unroll
  for (int i = 0; i < 5; i++) {
    s[i][0] = ex2f((s[i][0] - mx0) * (SCALE_QK * LOG2E)); s[i][1] = ex2f((s[i][1] - mx0) * (SCALE_QK * LOG2E));
    s[i][2] = ex2f((s[i][2] - mx1) * (SCALE_QK * LOG2E)); s[i][3] = ex2f((s[i][3] - mx1) * (SCALE_QK * LOG2E));
    sm0 += s[i][0] + s[i][1]; sm1 += s[i][2] + s[i][3];
  }
  sm0 += __shfl_xor_sync(~0u, sm0, 1); sm0 += __shfl_xor_sync(~0u, sm0, 2);
  sm1 += __shfl_xor_sync(~0u, sm1, 1); sm1 += __shfl_xor_sync(~0u, sm1, 2);
  const float i0 = __fdividef(1.0f, sm0), i1 = __fdividef(1.0f, sm1);
  unsigned pa[2][4], pm0, pm1;
#pragma unroll
  for (int kk = 0; kk < 2; kk++) {
    pa[kk][0] = pack_bf16(s[2 * kk][0] * i0, s[2 * kk][1] * i0); pa[kk][1] = pack_bf16(s[2 * kk][2] * i1, s[2 * kk][3] * i1);
    pa[kk][2] = pack_bf16(s[2 * kk + 1][0] * i0, s[2 * kk + 1][1] * i0); pa[kk][3] = pack_bf16(s[2 * kk + 1][2] * i1, s[2 * kk + 1][3] * i1);
  }
  pm0 = pack_bf16(s[4][0] * i0, s[4][1] * i0); pm1 = pack_bf16(s[4][2] * i1, s[4][3] * i1);
  const int orow = (kb >> 1) * 64 + seg * 32 + mt * 16 + (m & 1) * 8 + r8;
  const unsigned ob = stg + ((kb & 1) * 2 + eh) * 16384 + orow * 128;
#pragma unroll
  for (int cp = 0; cp < 4; cp++) {
    float o0[4] = {0, 0, 0, 0}, o1[4] = {0, 0, 0, 0};
    mma1688(o0, pm0, pm1, vm[2 * cp]); mma1688(o1, pm0, pm1, vm[2 * cp + 1]);
    unsigned vf[4];
    int row = (m & 1) * 8 + r8;
    unsigned va = vb + row * 128 + (((cp * 2 + (m >> 1)) ^ r8) << 4);
    ldsm_x4_t(vf, va);
    mma16816(o0, pa[0], vf[0], vf[1]); mma16816(o1, pa[0], vf[2], vf[3]);
    if (mt) { ldsm_x4_t(vf, va + 2048); mma16816(o0, pa[1], vf[0], vf[1]); mma16816(o1, pa[1], vf[2], vf[3]); }
    stsm_x4(ob + (((cp * 2 + (m >> 1)) ^ r8) << 4), pack_bf16(o0[0], o0[1]), pack_bf16(o0[2], o0[3]), pack_bf16(o1[0], o1[1]), pack_bf16(o1[2], o1[3]));
  }
}

__device__ __forceinline__ void bulk_worker(unsigned sb, volatile int* misc, const bf16* __restrict__ x, const bf16* __restrict__ b1, const bf16* __restrict__ b2, bf16* __restrict__ out) {
  const int t = threadIdx.x, lane = t & 31, w = t >> 5, wg = w >> 2, g = lane >> 2, tq = lane & 3, m = lane >> 3, r8 = lane & 7;
  const unsigned bar = sb + SM_BAR;
  unsigned st = 0, ph = 0, seq = 0, sph = 0;
  float d[128];
  while (true) {
    mbar_wait(bar + 8 * (MB_FULL + st), ph);
    const int idr = misc[seq & 3]; seq++;
    const int idx = idr & 65535;
    if (idr < 0 || idx >= N_ITEMS) break;
    if (t == 0) ISTAMP(idx, 2);
    const Item it = decode_item(idx);
    const int nkb = item_nkb(it.type);
    if (it.type == T_ATT) {
      unsigned km[16], vm[8], kn[16], vn[8];
      const bool pref = idr >= 65536;
      if (pref) bulk_att_load(kn, vn, it.b, it.c, 0, w, lane);
      mbar_wait(bar + 8 * MB_STGE, sph ^ 1);
#pragma unroll 1
      for (int kb = 0; kb < 4; kb++) {
        if (!pref) {
          if (lane < 2) wait_flag_ge(&g_flags.rec[it.c * 4 + (kb & 1) * 2 + lane], it.b * 4 + (kb >> 1) * 2 + wg + 1);
          __syncwarp();
          bulk_att_load(kn, vn, it.b, it.c, kb, w, lane);
        }
        if (kb) mbar_wait(bar + 8 * (MB_FULL + st), ph);
#pragma unroll
        for (int i = 0; i < 16; i++) km[i] = kn[i];
#pragma unroll
        for (int i = 0; i < 8; i++) vm[i] = vn[i];
        if (pref && kb != 3) bulk_att_load(kn, vn, it.b, it.c, kb + 1, w, lane);
        bulk_att_stage(sb + st * STAGE_BYTES, sb + B_STG, km, vm, kb, w, lane);
        __syncwarp();
        if (lane == 0) mbar_arrive(bar + 8 * (MB_EMPTY + st));
        if (++st == NSTAGE) { st = 0; ph ^= 1; }
      }
      if (t == 0) misc[4] = idx;
      fence_proxy_async_smem();
      mbar_arrive(bar + 8 * MB_STGF); sph ^= 1;
      continue;
    }
    if (it.type >= T_RED) {
      __syncwarp();
      if (lane == 0) mbar_arrive(bar + 8 * (MB_EMPTY + st));
      if (++st == NSTAGE) { st = 0; ph ^= 1; }
      if (it.type == T_RED) {
#pragma unroll 2
        for (int i = 0; i < 8; i++) {
          size_t o = ((size_t)it.b * 128 + it.c * 16 + i * 2 + (t >> 7)) * DM + (t & 127) * 4;
          float4 a = __ldcg(reinterpret_cast<const float4*>(g_opart + o)), b = __ldcg(reinterpret_cast<const float4*>(g_opart + o + (size_t)S_TOK * DM));
          float4 c = __ldcg(reinterpret_cast<const float4*>(g_opart + o + (size_t)2 * S_TOK * DM)), e = __ldcg(reinterpret_cast<const float4*>(g_opart + o + (size_t)3 * S_TOK * DM));
          final_out(out, x, o, make_float4((a.x + b.x) + (c.x + e.x), (a.y + b.y) + (c.y + e.y), (a.z + b.z) + (c.z + e.z), (a.w + b.w) + (c.w + e.w)));
        }
      } else {
        size_t ol = ((size_t)it.c * 2 + (t >> 7)) * DM + (t & 127) * 4;
        float4 v[16];
#pragma unroll
        for (int i = 0; i < 16; i++) v[i] = __ldcg(reinterpret_cast<const float4*>(g_opl + ol + (size_t)i * 128 * DM));
#pragma unroll
        for (int st2 = 1; st2 < 16; st2 <<= 1)
#pragma unroll
          for (int i = 0; i < 16; i += 2 * st2) { v[i].x += v[i + st2].x; v[i].y += v[i + st2].y; v[i].z += v[i + st2].z; v[i].w += v[i + st2].w; }
        final_out(out, x, ol + (size_t)15 * 128 * DM, v[0]);
      }
      if (t == 0) ISTAMP(idx, 3);
      continue;
    }
    unsigned pst = 0, bv[32];
#pragma unroll
    for (int i = 0; i < 128; i++) d[i] = 0.0f;
    if (it.type == T_M1 || it.type == T_M2) {
      const unsigned* bp = reinterpret_cast<const unsigned*>((it.type == T_M1 ? b1 : b2) + it.c * 256) + tq;
#pragma unroll
      for (int i = 0; i < 32; i++) asm volatile("ld.global.nc.u32 %0, [%1];" : "=r"(bv[i]) : "l"(bp + i * 4));
    } else {
#pragma unroll
      for (int i = 0; i < 32; i++) bv[i] = 0;
    }
    for (int kb = 0; kb < nkb; kb++) {
      if (kb) mbar_wait(bar + 8 * (MB_FULL + st), ph);
      unsigned sa = sb + st * STAGE_BYTES;
      uint64_t ad = mkdesc(sa + wg * 8192, 16, 1024), bd = mkdesc(sa + 16384, 8192, 1024);
      asm volatile("wgmma.fence.sync.aligned;" ::: "memory");
#pragma unroll
      for (int k = 0; k < 4; k++) wgmma_n256(d, ad + k * 2, bd + k * 128, (kb | k) != 0);
      asm volatile("wgmma.commit_group.sync.aligned;" ::: "memory");
      if (kb) {
        asm volatile("wgmma.wait_group.sync.aligned 1;" ::: "memory");
        if (lane == 0) mbar_arrive(bar + 8 * (MB_EMPTY + pst));
      }
      pst = st;
      if (++st == NSTAGE) { st = 0; ph ^= 1; }
    }
    asm volatile("wgmma.wait_group.sync.aligned 0;" ::: "memory");
    if (lane == 0) mbar_arrive(bar + 8 * (MB_EMPTY + pst));
    if (it.type >= T_OUT) {
      const int col = it.c * 256 + 2 * tq;
      float* pp = it.type == T_OUT ? g_opart + ((size_t)it.ks * S_TOK + it.b * 128 + w * 16 + g) * DM + col : g_opl + ((size_t)it.ks * 128 + w * 16 + g) * DM + col;
#pragma unroll
      for (int i = 0; i < 32; i++) {
        __stcg(reinterpret_cast<float2*>(pp + i * 8), make_float2(d[4 * i], d[4 * i + 1]));
        __stcg(reinterpret_cast<float2*>(pp + 8 * DM + i * 8), make_float2(d[4 * i + 2], d[4 * i + 3]));
      }
      bar_sync(1, 256);
      if (t == 0) { red_release_add(&g_flags.p[it.b], 1); ISTAMP(idx, 3); }
      continue;
    }
#define ACT(F) _Pragma("unroll") for (int i = 0; i < 32; i++) { \
        unsigned u0 = badd2(pack_bf16(d[4 * i], d[4 * i + 1]), bv[i]), u1 = badd2(pack_bf16(d[4 * i + 2], d[4 * i + 3]), bv[i]); \
        d[4 * i] = F(bf_lo(u0)); d[4 * i + 1] = F(bf_hi(u0)); d[4 * i + 2] = F(bf_lo(u1)); d[4 * i + 3] = F(bf_hi(u1)); }
    if (it.type == T_M1) { ACT(gelu_t) } else if (it.type == T_M2) { ACT(silu_f) }
    mbar_wait(bar + 8 * MB_STGE, sph ^ 1);
    {
      const unsigned ob = sb + B_STG + (w * 16 + (m & 1) * 8 + r8) * 128;
#pragma unroll
      for (int i = 0; i < 16; i++)
        stsm_x4(ob + (i >> 2) * 16384 + ((((i & 3) * 2 + (m >> 1)) ^ r8) << 4), pack_bf16(d[8 * i], d[8 * i + 1]), pack_bf16(d[8 * i + 2], d[8 * i + 3]),
                pack_bf16(d[8 * i + 4], d[8 * i + 5]), pack_bf16(d[8 * i + 6], d[8 * i + 7]));
    }
    if (t == 0) misc[4] = idx;
    fence_proxy_async_smem();
    mbar_arrive(bar + 8 * MB_STGF); sph ^= 1;
  }
  mbar_wait(bar + 8 * MB_STGE, sph ^ 1);
  if (t == 0) misc[4] = -1;
  mbar_arrive(bar + 8 * MB_STGF);
}

__global__ void __launch_bounds__(384, 1)
k_main(const __grid_constant__ Maps maps, const bf16* __restrict__ x, const bf16* __restrict__ mem0, const bf16* __restrict__ b1, const bf16* __restrict__ b2, bf16* __restrict__ out, int helper) {
  extern __shared__ unsigned char smem_raw[];
  const unsigned sraw = smem_u32(smem_raw);
  const unsigned sb = (sraw + 1023u) & ~1023u;
  int* misc = reinterpret_cast<int*>(smem_raw + (sb - sraw) + SM_MISC);
  const int w = threadIdx.x >> 5;
  const bool rec = !helper && blockIdx.x < NREC;
  if (!helper) asm volatile("griddepcontrol.launch_dependents;");
  if (threadIdx.x == 0) {
    const unsigned bar = sb + SM_BAR;
    for (int i = 0; i < 8; i++) { mbar_init(bar + 8 * (MB_FULL + i), 1); mbar_init(bar + 8 * (MB_EMPTY + i), rec ? 1 : 8); }
    mbar_init(bar + 8 * MB_STGF, 256); mbar_init(bar + 8 * MB_STGE, 1);
    for (int i = MB_W0; i <= MB_AG; i++) mbar_init(bar + 8 * i, 1);
    if (rec) { mbar_expect_tx(bar + 8 * MB_S, 2560); mbar_expect_tx(bar + 8 * MB_V, 2048); mbar_expect_tx(bar + 8 * MB_RS, 8192); mbar_expect_tx(bar + 8 * MB_AG, 8192); }
    asm volatile("fence.mbarrier_init.release.cluster;" ::: "memory");
  }
  __syncthreads();
  asm volatile("barrier.cluster.arrive.release.aligned;\nbarrier.cluster.wait.acquire.aligned;" ::: "memory");
  if (DBGMODE && !rec) { if (helper) asm volatile("griddepcontrol.wait;" ::: "memory"); return; }
  if (w >= 8) {
    asm volatile("setmaxnreg.dec.sync.aligned.u32 24;");
    if (rec) { if (w == 8) rec_ring(maps, sb); else if (w == 9) rec_copy(sb); }
    else if (w == 8) bulk_producer(maps, sb, misc);
    else if ((threadIdx.x & 31) == 0) { if (w == 9) bulk_store(maps, sb, misc);
      else if (w == 10 && helper) asm volatile("griddepcontrol.wait;" ::: "memory"); }
  } else {
    if (rec) { asm volatile("setmaxnreg.inc.sync.aligned.u32 240;"); rec_worker(maps, sb, mem0); }
    else { asm volatile("setmaxnreg.inc.sync.aligned.u32 240;"); bulk_worker(sb, misc, x, b1, b2, out); }
  }
}

typedef CUresult (*EncFn)(CUtensorMap*, CUtensorMapDataType, cuuint32_t, void*, const cuuint64_t*, const cuuint64_t*, const cuuint32_t*, const cuuint32_t*,
                          CUtensorMapInterleave, CUtensorMapSwizzle, CUtensorMapL2promotion, CUtensorMapFloatOOBfill);
static void mk_map(EncFn enc, CUtensorMap* m, const void* ptr, uint64_t rows, uint64_t cols, uint32_t box_rows) {
  cuuint64_t dims[2] = {cols, rows}; cuuint64_t strides[1] = {cols * 2};
  cuuint32_t box[2] = {64, box_rows}, es[2] = {1, 1};
  enc(m, CU_TENSOR_MAP_DATA_TYPE_BFLOAT16, 2, const_cast<void*>(ptr), dims, strides, box, es, CU_TENSOR_MAP_INTERLEAVE_NONE, CU_TENSOR_MAP_SWIZZLE_128B,
      CU_TENSOR_MAP_L2_PROMOTION_L2_256B, CU_TENSOR_MAP_FLOAT_OOB_FILL_NONE);
}
extern "C" void kernel_launch(void* const* d_in, const int* in_sizes, int n_in, void* d_out, int out_size) {
  static EncFn enc = nullptr;
  static int ncl = 0, nhelp = 0;
  static void *p_xn, *p_y, *p_h1, *p_o, *p_qkv, *p_g;
  if (!enc) {
    void* fn = nullptr; cudaDriverEntryPointQueryResult qr;
    cudaGetDriverEntryPoint("cuTensorMapEncodeTiled", &fn, cudaEnableDefault, &qr);
    enc = (EncFn)fn;
    cudaGetSymbolAddress(&p_xn, g_xn); cudaGetSymbolAddress(&p_y, g_y); cudaGetSymbolAddress(&p_h1, g_h1);
    cudaGetSymbolAddress(&p_o, g_o); cudaGetSymbolAddress(&p_qkv, g_qkv); cudaGetSymbolAddress(&p_g, g_g);
    cudaFuncSetAttribute(k_main, cudaFuncAttributeMaxDynamicSharedMemorySize, SMEM_TOTAL);
    cudaLaunchConfig_t cfg = {}; cfg.gridDim = dim3(128); cfg.blockDim = dim3(384); cfg.dynamicSmemBytes = SMEM_TOTAL;
    cudaLaunchAttribute at[1]; at[0].id = cudaLaunchAttributeClusterDimension; at[0].val.clusterDim.x = CLS; at[0].val.clusterDim.y = 1; at[0].val.clusterDim.z = 1;
    cfg.attrs = at; cfg.numAttrs = 1;
    if (cudaOccupancyMaxActiveClusters(&ncl, k_main, &cfg) != cudaSuccess) { cudaGetLastError(); ncl = 14; }
    ncl = ncl > 16 ? 16 : (ncl < 9 ? 9 : ncl);
    int nsm = 0, dev = 0; cudaGetDevice(&dev); cudaDeviceGetAttribute(&nsm, cudaDevAttrMultiProcessorCount, dev);
    nhelp = nsm - ncl * CLS;
  }
  Maps maps;
  mk_map(enc, &maps.xn, p_xn, S_TOK, DM, 128); mk_map(enc, &maps.y, p_y, S_TOK, DM, 128); mk_map(enc, &maps.h1, p_h1, S_TOK, FF, 128);
  mk_map(enc, &maps.o, p_o, S_TOK, HD, 128); mk_map(enc, &maps.qkv_st, p_qkv, S_TOK, 3 * HD, 128); mk_map(enc, &maps.qkv_ld, p_qkv, S_TOK, 3 * HD, 32);
  mk_map(enc, &maps.g, p_g, S_TOK, DM, 128);
  mk_map(enc, &maps.wq, d_in[2], DM, HD, 64); mk_map(enc, &maps.wk, d_in[3], DM, HD, 64); mk_map(enc, &maps.wv, d_in[4], DM, HD, 64);
  mk_map(enc, &maps.wo, d_in[5], HD, DM, 64); mk_map(enc, &maps.w1, d_in[8], DM, FF, 64); mk_map(enc, &maps.w2, d_in[10], FF, DM, 64);
  cudaStream_t st = cudaStreamPerThread;
  k_pre<<<256, 256, 0, st>>>((const bf16*)d_in[0]);
  cudaLaunchConfig_t cfg = {}; cfg.gridDim = dim3(ncl * CLS); cfg.blockDim = dim3(384); cfg.dynamicSmemBytes = SMEM_TOTAL; cfg.stream = st;
  cudaLaunchAttribute at[1]; at[0].id = cudaLaunchAttributeClusterDimension; at[0].val.clusterDim.x = CLS; at[0].val.clusterDim.y = 1; at[0].val.clusterDim.z = 1;
  cfg.attrs = at; cfg.numAttrs = 1;
  cudaLaunchKernelEx(&cfg, k_main, maps, (const bf16*)d_in[0], (const bf16*)d_in[1], (const bf16*)d_in[9], (const bf16*)d_in[11], (bf16*)d_out, 0);
  if (nhelp > 0) {
    cfg.gridDim = dim3(nhelp);
    at[0].id = cudaLaunchAttributeProgrammaticStreamSerialization; at[0].val.programmaticStreamSerializationAllowed = 1;
    cudaLaunchKernelEx(&cfg, k_main, maps, (const bf16*)d_in[0], (const bf16*)d_in[1], (const bf16*)d_in[9], (const bf16*)d_in[11], (bf16*)d_out, 1);
  }
}
```

```cpp
#include <cuda_runtime.h>
#include <cuda_bf16.h>
#include <cuda.h>
#include <stdint.h>

typedef __nv_bfloat16 bf16;

#define S_TOK 2048
#define DM 512
#define NH 32
#define DH 128
#define HD 4096
#define NMEM 8
#define SEG 32
#define NSEG 64
#define FF 1792
#define NBLK 16
#define NREC 64
#define REPL 0
#define CLS 8

__device__ __align__(1024) bf16 g_xn[S_TOK * DM];
__device__ __align__(1024) bf16 g_y[S_TOK * DM];
__device__ __align__(1024) bf16 g_qkv[(size_t)S_TOK * 3 * HD];
__device__ __align__(1024) bf16 g_h1[S_TOK * FF];
__device__ __align__(1024) bf16 g_g[S_TOK * DM];
__device__ __align__(1024) bf16 g_o[(size_t)S_TOK * HD];
__device__ __align__(1024) bf16 g_km[NSEG * NH * NMEM * DH];
__device__ __align__(1024) bf16 g_vmt[NSEG * NH * DH * NMEM];
__device__ __align__(1024) float g_opart[(size_t)4 * S_TOK * DM];
__device__ __align__(1024) float g_opl[(size_t)16 * 128 * DM];
__device__ __align__(1024) unsigned g_part[8 * 2 * 8 * 8 * 512];
struct Flags {
  unsigned qkv[NBLK * 48];
  unsigned h1[NBLK];
  unsigned g[NBLK];
  unsigned o[NBLK * 4];
  unsigned p[NBLK];
  unsigned o16[16];
  unsigned ctr;
  unsigned rec[NREC];
  unsigned abort_;
};
__device__ __align__(1024) Flags g_flags;

#define RSTAMP(k)
#define DBGMODE 0
#define ISTAMP(i, k)
__device__ __forceinline__ unsigned smem_u32(const void* p) { return (unsigned)__cvta_generic_to_shared(p); }
__device__ __forceinline__ float bf16r(float x) { unsigned u; asm("cvt.rn.bf16x2.f32 %0, %1, %2;" : "=r"(u) : "f"(x), "f"(0.0f)); return __uint_as_float(u); }
__device__ __forceinline__ unsigned pack_bf16(float lo, float hi) {
  __nv_bfloat162 v = __floats2bfloat162_rn(lo, hi);
  return *reinterpret_cast<unsigned*>(&v);
}
__device__ __forceinline__ float bf_lo(unsigned u) { return __uint_as_float(u << 16); }
__device__ __forceinline__ float bf_hi(unsigned u) { return __uint_as_float(u & 0xffff0000u); }

#define SPIN_LIMIT (1u << 20)
#define TRAP_IF(x) if ((x) > SPIN_LIMIT) { asm volatile("st.global.u32 [%0], %1;" ::"l"(0ull), "r"(0u) : "memory"); break; }
__device__ __forceinline__ unsigned ld_acquire(const unsigned* p) {
  unsigned v; asm volatile("ld.acquire.gpu.global.u32 %0, [%1];" : "=r"(v) : "l"(p) : "memory"); return v;
}
__device__ __forceinline__ unsigned ld_relaxed(const unsigned* p) {
  unsigned v; asm volatile("ld.relaxed.gpu.global.u32 %0, [%1];" : "=r"(v) : "l"(p) : "memory"); return v;
}
__device__ __forceinline__ void red_release_add(unsigned* p, unsigned v) {
  asm volatile("red.release.gpu.global.add.u32 [%0], %1;" ::"l"(p), "r"(v) : "memory");
}
__device__ __forceinline__ void st_release(unsigned* p, unsigned v) {
  asm volatile("st.release.gpu.global.u32 [%0], %1;" ::"l"(p), "r"(v) : "memory");
}
__device__ __forceinline__ void wait_flag_ge(const unsigned* p, unsigned target) {
  unsigned it = 0;
  while (ld_acquire(p) < target) {
    __nanosleep(64);
    TRAP_IF(++it);
  }
}
__device__ __forceinline__ uint4 ldv4_relaxed(const void* p) {
  uint4 a; asm volatile("ld.relaxed.gpu.global.v4.u32 {%0,%1,%2,%3}, [%4];" : "=r"(a.x), "=r"(a.y), "=r"(a.z), "=r"(a.w) : "l"(p) : "memory"); return a;
}
__device__ __forceinline__ uint2 ldv2_relaxed(const void* p) {
  uint2 a; asm volatile("ld.relaxed.gpu.global.v2.u32 {%0,%1}, [%2];" : "=r"(a.x), "=r"(a.y) : "l"(p) : "memory"); return a;
}
__device__ __forceinline__ void mbar_init(unsigned mb, unsigned cnt) { asm volatile("mbarrier.init.shared::cta.b64 [%0], %1;" ::"r"(mb), "r"(cnt) : "memory"); }
__device__ __forceinline__ void mbar_expect_tx(unsigned mb, unsigned bytes) { asm volatile("mbarrier.arrive.expect_tx.shared::cta.b64 _, [%0], %1;" ::"r"(mb), "r"(bytes) : "memory"); }
__device__ __forceinline__ void mbar_arrive(unsigned mb) { asm volatile("mbarrier.arrive.shared::cta.b64 _, [%0];" ::"r"(mb) : "memory"); }
__device__ __forceinline__ void mbar_wait(unsigned mb, unsigned parity) {
  unsigned ok, it = 0;
  while (true) {
    asm volatile("{.reg .pred p; mbarrier.try_wait.parity.shared::cta.b64 p, [%1], %2; selp.u32 %0,1,0,p;}" : "=r"(ok) : "r"(mb), "r"(parity) : "memory");
    if (ok) break;
    TRAP_IF(++it);
  }
}
__device__ __forceinline__ void mbar_wait_sleep(unsigned mb, unsigned parity) {
  unsigned ok, it = 0;
  while (true) {
    asm volatile("{.reg .pred p; mbarrier.test_wait.parity.shared::cta.b64 p, [%1], %2; selp.u32 %0,1,0,p;}" : "=r"(ok) : "r"(mb), "r"(parity) : "memory");
    if (ok) break;
    __nanosleep(200);
    TRAP_IF(++it);
  }
}
__device__ __forceinline__ float ex2f(float x) { float y; asm("ex2.approx.ftz.f32 %0, %1;" : "=f"(y) : "f"(x)); return y; }
__device__ __forceinline__ int opaque_tid() { int t = threadIdx.x; t = __shfl_sync(~0u, t, t & 31); return t; }
#define LOG2E 1.4426950408889634f
__device__ __forceinline__ void mbar_wait_cluster(unsigned mb, unsigned parity) {
  unsigned ok, it = 0;
  while (true) {
    asm volatile("{.reg .pred p; mbarrier.try_wait.parity.acquire.cluster.shared::cta.b64 p, [%1], %2; selp.u32 %0,1,0,p;}" : "=r"(ok) : "r"(mb), "r"(parity) : "memory");
    if (ok) break;
    TRAP_IF(++it);
  }
}
__device__ __forceinline__ void bar_sync(int id, int n) { asm volatile("bar.sync %0, %1;" ::"r"(id), "r"(n) : "memory"); }
__device__ __forceinline__ void bar_arrive(int id, int n) { asm volatile("bar.arrive %0, %1;" ::"r"(id), "r"(n) : "memory"); }
__device__ __forceinline__ void tma_load_2d(unsigned dst, const CUtensorMap* map, int c0, int c1, unsigned mb) {
  asm volatile("cp.async.bulk.tensor.2d.shared::cluster.global.mbarrier::complete_tx::bytes [%0], [%1, {%3, %4}], [%2];"
               ::"r"(dst), "l"((uint64_t)map), "r"(mb), "r"(c0), "r"(c1) : "memory");
}
__device__ __forceinline__ void tma_store_2d(const CUtensorMap* map, unsigned src, int c0, int c1) {
  asm volatile("cp.async.bulk.tensor.2d.global.shared::cta.bulk_group [%0, {%2, %3}], [%1];"
               ::"l"((uint64_t)map), "r"(src), "r"(c0), "r"(c1) : "memory");
}
__device__ __forceinline__ void fence_proxy_async() { asm volatile("fence.proxy.async;" ::: "memory"); }
__device__ __forceinline__ void fence_proxy_async_smem() { asm volatile("fence.proxy.async.shared::cta;" ::: "memory"); }
__device__ __forceinline__ void ldsm_x4(unsigned* r, unsigned addr) {
  asm volatile("ldmatrix.sync.aligned.m8n8.x4.shared.b16 {%0,%1,%2,%3}, [%4];" : "=r"(r[0]), "=r"(r[1]), "=r"(r[2]), "=r"(r[3]) : "r"(addr) : "memory");
}
__device__ __forceinline__ void ldsm_x4_t(unsigned* r, unsigned addr) {
  asm volatile("ldmatrix.sync.aligned.m8n8.x4.trans.shared.b16 {%0,%1,%2,%3}, [%4];" : "=r"(r[0]), "=r"(r[1]), "=r"(r[2]), "=r"(r[3]) : "r"(addr) : "memory");
}
__device__ __forceinline__ void stsm_x2_t(unsigned addr, unsigned r0, unsigned r1) {
  asm volatile("stmatrix.sync.aligned.m8n8.x2.trans.shared.b16 [%0], {%1,%2};" ::"r"(addr), "r"(r0), "r"(r1) : "memory");
}
__device__ __forceinline__ void stsm_x4(unsigned addr, unsigned r0, unsigned r1, unsigned r2, unsigned r3) {
  asm volatile("stmatrix.sync.aligned.m8n8.x4.shared.b16 [%0], {%1,%2,%3,%4};" ::"r"(addr), "r"(r0), "r"(r1), "r"(r2), "r"(r3) : "memory");
}
__device__ __forceinline__ void mma16816(float* d, const unsigned* a, unsigned b0, unsigned b1) {
  asm volatile("mma.sync.aligned.m16n8k16.row.col.f32.bf16.bf16.f32 {%0,%1,%2,%3}, {%4,%5,%6,%7}, {%8,%9}, {%0,%1,%2,%3};"
               : "+f"(d[0]), "+f"(d[1]), "+f"(d[2]), "+f"(d[3]) : "r"(a[0]), "r"(a[1]), "r"(a[2]), "r"(a[3]), "r"(b0), "r"(b1));
}
__device__ __forceinline__ void mma1688(float* d, unsigned a0, unsigned a1, unsigned b0) {
  asm volatile("mma.sync.aligned.m16n8k8.row.col.f32.bf16.bf16.f32 {%0,%1,%2,%3}, {%4,%5}, {%6}, {%0,%1,%2,%3};"
               : "+f"(d[0]), "+f"(d[1]), "+f"(d[2]), "+f"(d[3]) : "r"(a0), "r"(a1), "r"(b0));
}
__device__ __forceinline__ uint64_t mkdesc(unsigned addr, unsigned lbo, unsigned sbo) {
  return (uint64_t)((addr >> 4) & 0x3fff) | ((uint64_t)(lbo >> 4) << 16) | ((uint64_t)(sbo >> 4) << 32) | (1ull << 62);
}
#define R8(b) "+f"(d[b]), "+f"(d[b + 1]), "+f"(d[b + 2]), "+f"(d[b + 3]), "+f"(d[b + 4]), "+f"(d[b + 5]), "+f"(d[b + 6]), "+f"(d[b + 7])
#define R32(b) R8(b), R8(b + 8), R8(b + 16), R8(b + 24)
__device__ __forceinline__ void wgmma_n256(float* d, uint64_t ad, uint64_t bd, int acc) {
  asm volatile(
      "{.reg .pred p; setp.ne.b32 p, %130, 0;\n"
      "wgmma.mma_async.sync.aligned.m64n256k16.f32.bf16.bf16 "
      "{%0,%1,%2,%3,%4,%5,%6,%7,%8,%9,%10,%11,%12,%13,%14,%15,%16,%17,%18,%19,%20,%21,%22,%23,%24,%25,%26,%27,%28,%29,%30,%31,"
      "%32,%33,%34,%35,%36,%37,%38,%39,%40,%41,%42,%43,%44,%45,%46,%47,%48,%49,%50,%51,%52,%53,%54,%55,%56,%57,%58,%59,%60,%61,%62,%63,"
      "%64,%65,%66,%67,%68,%69,%70,%71,%72,%73,%74,%75,%76,%77,%78,%79,%80,%81,%82,%83,%84,%85,%86,%87,%88,%89,%90,%91,%92,%93,%94,%95,"
      "%96,%97,%98,%99,%100,%101,%102,%103,%104,%105,%106,%107,%108,%109,%110,%111,%112,%113,%114,%115,%116,%117,%118,%119,%120,%121,%122,%123,%124,%125,%126,%127},"
      "%128, %129, p, 1, 1, 0, 1;}\n"
      : R32(0), R32(32), R32(64), R32(96)
      : "l"(ad), "l"(bd), "r"(acc));
}

__device__ __forceinline__ void ln16(const float* x, float* o) {
  float s = 0;
#pragma unroll
  for (int i = 0; i < 16; i++) s += x[i];
#pragma unroll
  for (int of = 16; of > 0; of >>= 1) s += __shfl_xor_sync(~0u, s, of);
  float mean = s * (1.0f / DM);
  float v = 0;
#pragma unroll
  for (int i = 0; i < 16; i++) { float dd = x[i] - mean; v += dd * dd; }
#pragma unroll
  for (int of = 16; of > 0; of >>= 1) v += __shfl_xor_sync(~0u, v, of);
  float mb = bf16r(mean);
  float vb = bf16r(v * (1.0f / DM));
  float den = bf16r(sqrtf(bf16r(vb + 1e-5f)));
#pragma unroll
  for (int i = 0; i < 16; i++) o[i] = bf16r(__fdiv_rn(bf16r(x[i] - mb), den));
}
__global__ void __launch_bounds__(256) k_pre(const bf16* __restrict__ x) {
  int t = threadIdx.x, lane = t & 31, w = t >> 5;
  int row = blockIdx.x * 8 + w;
  const uint4* src = reinterpret_cast<const uint4*>(x + (size_t)row * DM);
  uint4 a = src[lane], b = src[lane + 32];
  unsigned u[8] = {a.x, a.y, a.z, a.w, b.x, b.y, b.z, b.w};
  float f[16], o[16], o2[16];
#pragma unroll
  for (int i = 0; i < 8; i++) { f[2 * i] = bf_lo(u[i]); f[2 * i + 1] = bf_hi(u[i]); }
  ln16(f, o);
  ln16(o, o2);
  uint4* d1 = reinterpret_cast<uint4*>(g_xn + (size_t)row * DM);
  uint4* d2 = reinterpret_cast<uint4*>(g_y + (size_t)row * DM);
  d1[lane] = make_uint4(pack_bf16(o[0], o[1]), pack_bf16(o[2], o[3]), pack_bf16(o[4], o[5]), pack_bf16(o[6], o[7]));
  d1[lane + 32] = make_uint4(pack_bf16(o[8], o[9]), pack_bf16(o[10], o[11]), pack_bf16(o[12], o[13]), pack_bf16(o[14], o[15]));
  d2[lane] = make_uint4(pack_bf16(o2[0], o2[1]), pack_bf16(o2[2], o2[3]), pack_bf16(o2[4], o2[5]), pack_bf16(o2[6], o2[7]));
  d2[lane + 32] = make_uint4(pack_bf16(o2[8], o2[9]), pack_bf16(o2[10], o2[11]), pack_bf16(o2[12], o2[13]), pack_bf16(o2[14], o2[15]));
  int gt = blockIdx.x * 256 + t;
  uint4 z = make_uint4(0, 0, 0, 0);
  if (gt < 16384) reinterpret_cast<uint4*>(g_part)[gt] = z;
  if (gt < (int)(sizeof(Flags) / 4)) reinterpret_cast<unsigned*>(&g_flags)[gt] = 0;
}

struct Maps { CUtensorMap xn, y, h1, o, qkv_st, qkv_ld, g, wq, wk, wv, wo, w1, w2; };

#define NSTAGE 3
#define STAGE_BYTES 49152
#define B_STG (NSTAGE * STAGE_BYTES)
#define R_WO 0
#define R_T1 65536
#define R_T2 131072
#define R_RING 65536
#define RING_N 4
#define RING_BYTES 12288
#define R_MEM 196608
#define R_QS (R_MEM + 8448)
#define R_KS (R_QS + 1152)
#define R_OS (R_KS + 1152)
#define R_SOWN (R_OS + 2176)
#define R_SPEER (R_SOWN + 1280)
#define R_VM (R_SPEER + 1280)
#define R_VRED (R_VM + 2048)
#define R_RS (R_VRED + 6144)
#define SM_BAR (R_RS + 8192)
#define SMEM_TOTAL (SM_BAR + 256 + 1024)
#define MB_FULL 0
#define MB_EMPTY 8
#define MB_STGF 16
#define MB_STGE 17
#define MB_W0 18
#define MB_W1 19
#define MB_WO 20
#define MB_S 21
#define MB_V 22
#define MB_KVR 23
#define MB_KVF 24
#define MB_RS 25
#define MB_AG 26
#define SM_MISC (SM_BAR + 224)

#define N_KV 512
#define I_M1 512
#define I_Q 624
#define I_M2 880
#define I_POST 912
#define I_TAIL (I_POST + 16 * 32)
#define N_ITEMS (I_TAIL + 5 * 8 + 32 + 8 + 64)
enum { T_QKV = 0, T_M1 = 1, T_M2 = 2, T_ATT = 3, T_OUT = 4, T_OUTL = 5, T_RED = 6, T_REDL = 7 };
struct Item { int type, b, c, ks; };
__device__ __forceinline__ Item decode_item(int i) {
  Item it; it.ks = 0;
  if (i < N_KV) { it.type = T_QKV; it.b = i >> 5; it.c = 16 + (i & 31); }
  else if (i < I_Q) { it.type = T_M1; it.b = (i - I_M1) / 7; it.c = (i - I_M1) % 7; }
  else if (i < I_M2) { it.type = T_QKV; it.b = (i - I_Q) >> 4; it.c = (i - I_Q) & 15; }
  else if (i < I_POST) { it.type = T_M2; it.b = (i - I_M2) >> 1; it.c = (i - I_M2) & 1; }
  else if (i < I_TAIL) {
    int x = i - I_POST, p = x >> 5, r = x & 31;
    if (r < 16) { it.type = T_ATT; it.b = p; it.c = r; }
    else if (r < 24) { it.type = T_OUT; it.b = p - 3; it.c = r & 1; it.ks = (r - 16) >> 1; }
    else { it.type = T_RED; it.b = p - 5; it.c = r - 24; }
  } else {
    int x = i - I_TAIL, r = x & 7;
    if (x < 40) {
      int q = x >> 3;
      if (q == 0 || q == 2) { it.type = T_OUT; it.b = 13 + (q >> 1); it.c = r & 1; it.ks = r >> 1; }
      else { it.type = T_RED; it.b = q == 1 ? 11 : 9 + q; it.c = r; }
    }
    else if (x < 72) { it.type = T_OUTL; it.b = 15; it.c = x & 1; it.ks = (x - 40) >> 1; }
    else if (x < 80) { it.type = T_RED; it.b = 14; it.c = r; }
    else { it.type = T_REDL; it.b = 15; it.c = x - 80; }
  }
  return it;
}
__device__ __forceinline__ int item_nkb(int type) { return type == T_M2 ? 28 : (type == T_OUT ? 16 : (type >= T_RED ? 1 : (type >= T_ATT ? 4 : 8))); }

__device__ __forceinline__ void st_async_b64(unsigned raddr, unsigned lo, unsigned hi, unsigned rmb) {
  asm volatile("st.async.weak.shared::cluster.mbarrier::complete_tx::bytes.v2.b32 [%0], {%1,%2}, [%3];" ::"r"(raddr), "r"(lo), "r"(hi), "r"(rmb) : "memory");
}
__device__ __forceinline__ void st_async_b32(unsigned raddr, unsigned v, unsigned rmb) {
  asm volatile("st.async.weak.shared::cluster.mbarrier::complete_tx::bytes.b32 [%0], %1, [%2];" ::"r"(raddr), "r"(v), "r"(rmb) : "memory");
}
__device__ __forceinline__ unsigned mapa(unsigned a, unsigned rank) {
  unsigned r; asm volatile("mapa.shared::cluster.u32 %0, %1, %2;" : "=r"(r) : "r"(a), "r"(rank)); return r;
}
__device__ __forceinline__ void sts64(unsigned a, unsigned x, unsigned y) { asm volatile("st.shared.v2.b32 [%0], {%1,%2};" ::"r"(a), "r"(x), "r"(y) : "memory"); }
__device__ __forceinline__ void sts128(unsigned a, uint4 v) { asm volatile("st.shared.v4.b32 [%0], {%1,%2,%3,%4};" ::"r"(a), "r"(v.x), "r"(v.y), "r"(v.z), "r"(v.w) : "memory"); }
__device__ __forceinline__ uint2 lds64(unsigned a) { uint2 v; asm volatile("ld.shared.v2.b32 {%0,%1}, [%2];" : "=r"(v.x), "=r"(v.y) : "r"(a) : "memory"); return v; }
__device__ __forceinline__ uint4 lds128(unsigned a) { uint4 v; asm volatile("ld.shared.v4.b32 {%0,%1,%2,%3}, [%4];" : "=r"(v.x), "=r"(v.y), "=r"(v.z), "=r"(v.w) : "r"(a) : "memory"); return v; }
__device__ __forceinline__ float lds32f(unsigned a) { float v; asm volatile("ld.shared.f32 %0, [%1];" : "=f"(v) : "r"(a) : "memory"); return v; }
#define spin_check(it) TRAP_IF(++it)
#define POLLV 0
#define BAR8 0
#define D_STAG 150
#define D_RED 480
#define D_PUB 0
#define DELAY(n) do { unsigned c0_, c1_; asm volatile("mov.u32 %0, %%clock;" : "=r"(c0_)); do { asm volatile("mov.u32 %0, %%clock;" : "=r"(c1_)); } while (c1_ - c0_ < (n)); } while (0)
#define NPRE1 0
#define VD 2
#define ZS 0
#define MBL 1
#define SCALE_QK 0.08838834764831845f

__device__ __forceinline__ void rec_worker(const Maps& maps, unsigned sb, const bf16* __restrict__ mem0) {
  const int c = blockIdx.x, h = c >> 1, j = c & 1;
  const int t = opaque_tid(), lane = t & 31, w = t >> 5, g = lane >> 2, tq = lane & 3;
  const int m = lane >> 3, r8 = lane & 7, kh = w >> 2, et = w & 3;
  const unsigned bar = sb + SM_BAR;
  unsigned wq[16][4], wk[16][4], wo[8][4];
  const unsigned woff = (kh * 4) * 8192 + ((m >> 1) * 8 + r8) * 128 + (((et * 2 + (m & 1)) ^ r8) << 4);
  mbar_wait(bar + 8 * MB_W0, 0);
#pragma unroll
  for (int i = 0; i < 16; i++) {
    ldsm_x4_t(wq[i], sb + R_WO + woff + (i >> 2) * 8192 + (i & 3) * 2048);
    ldsm_x4_t(wk[i], sb + R_T1 + woff + (i >> 2) * 8192 + (i & 3) * 2048);
  }
  bar_sync(2, 288);
  if (t == 0) {
    fence_proxy_async_smem();
    mbar_expect_tx(bar + 8 * MB_WO, 65536);
    for (int kb = 0; kb < 2; kb++)
      for (int cb = 0; cb < 4; cb++) tma_load_2d(sb + R_WO + (kb * 4 + cb) * 8192, &maps.wo, j * 256 + cb * 64, h * 128 + kb * 64, bar + 8 * MB_WO);
  }
  mbar_wait(bar + 8 * MB_W1, 0);
  const unsigned pV = sb + R_T2 + woff;
  const unsigned rk = c & 7, peer = rk ^ 1, cl = c >> 3;
#define KEEP(x) x = __shfl_sync(~0u, x, lane)
  unsigned pA = sb + R_MEM + kh * 4096 + lane * 16;
  unsigned pW0 = sb + R_WO + (w >> 1) * 8192 + ((m >> 1) * 8 + r8) * 128 + ((((w & 1) * 4 + (m & 1)) ^ r8) << 4);
#define pW1 (pW0 ^ 32)
  unsigned pVk = mapa(sb + R_VM + (j * 4 + et) * 256 + lane * 8, peer);
  unsigned aX = sb + R_VRED + et * 512 + lane * 16;
  unsigned aQKst = sb + (kh ? R_KS : R_QS) + r8 * 144 + (et * 16 + (m & 1) * 8) * 2;
  unsigned aL8_ = sb + lane * 8;
  unsigned aSl_ = mapa(sb + R_SOWN + w * 256 + lane * 8, rk), aSr_ = mapa(sb + R_SPEER + w * 256 + lane * 8, peer);
  const unsigned mbSl = mapa(bar + 8 * MB_S, rk), mbSr = mapa(bar + 8 * MB_S, peer), mbVl = mbSl + 8, mbVr = mbSr + 8;
  unsigned aQ_ = sb + R_QS + r8 * 144 + m * 16;
  unsigned oKx_ = (et * 8 + r8) * 128 + ((m ^ r8) << 4);
  unsigned oVx_ = 4096 + (et >> 1) * 4096 + ((m >> 1) * 8 + r8) * 128 + ((((et & 1) * 4 + (m & 1)) ^ r8) << 4);
  unsigned aOst_ = sb + R_OS + r8 * 272 + (et * 32 + m * 8) * 2;
  unsigned aOld = sb + R_OS + r8 * 272 + m * 16;
  unsigned aVm_ = sb + R_VM + et * 512 + lane * 8;
  unsigned aRSr = mapa(sb + R_RS + (h & 3) * 2048 + (w & 1) * 1024 + lane * 8, j * 4 + (w >> 1));
  unsigned t8 = t * 8;
  unsigned r1 = kh ? aL8_ : aSl_, r2 = kh ? oVx_ : aSr_, r3 = kh ? aOst_ : aQ_, r4 = kh ? aVm_ : oKx_;
#define aL8 r1
#define aSl r1
#define oVx r2
#define aSr r2
#define aOst r3
#define aQ r3
#define aVm r4
#define oKx r4
#define aVr pVk
  const unsigned dLR = mbSl - mbSr;
  KEEP(pA); KEEP(pW0); KEEP(pVk); KEEP(aX); KEEP(aQKst); KEEP(r1); KEEP(r2); KEEP(r3); KEEP(r4);
  KEEP(aOld); KEEP(aRSr); KEEP(t8);
  mbar_wait(bar + 8 * MB_WO, 0);
#pragma unroll
  for (int ks = 0; ks < 4; ks++) { ldsm_x4_t(wo[2 * ks], pW0 + ks * 2048); ldsm_x4_t(wo[2 * ks + 1], pW1 + ks * 2048); }
  {
    unsigned v[8];
#pragma unroll
    for (int q = 0; q < 8; q++) v[q] = __ldg(reinterpret_cast<const unsigned*>(mem0) + q * 256 + t);
    sts128(sb + R_MEM + t * 32, make_uint4(__byte_perm(v[0], v[1], 0x5410), __byte_perm(v[2], v[3], 0x5410), __byte_perm(v[4], v[5], 0x5410), __byte_perm(v[6], v[7], 0x5410)));
    sts128(sb + R_MEM + t * 32 + 16, make_uint4(__byte_perm(v[0], v[1], 0x7632), __byte_perm(v[2], v[3], 0x7632), __byte_perm(v[4], v[5], 0x7632), __byte_perm(v[6], v[7], 0x7632)));
  }
  fence_proxy_async_smem();
  bar_sync(1, 256);

#pragma unroll 1
  for (int s = 0;; s++) {
    const unsigned par = s & 1;
    const unsigned slot = s & (RING_N - 1), rpar = (s / RING_N) & 1;
    const unsigned ring = sb + R_RING + slot * RING_BYTES;
    asm volatile("" : "+r"(t8), "+r"(pW0), "+r"(r1), "+r"(r2), "+r"(r4), "+r"(pVk));
    RSTAMP(1);
    RSTAMP(2);
    float aq[4] = {0, 0, 0, 0}, ak[4] = {0, 0, 0, 0};
    {
      float aq1[4] = {0, 0, 0, 0}, ak1[4] = {0, 0, 0, 0};
      unsigned b[8][4];
#pragma unroll
      for (int i = 0; i < 4; i++) ldsm_x4_t(b[i], pA + i * 512);
#pragma unroll
      for (int i = 0; i < 8; i++) {
        mma16816(aq, wq[2 * i], b[i][0], b[i][1]); mma16816(ak, wk[2 * i], b[i][0], b[i][1]);
        mma16816(aq1, wq[2 * i + 1], b[i][2], b[i][3]); mma16816(ak1, wk[2 * i + 1], b[i][2], b[i][3]);
        if (i < 4) ldsm_x4_t(b[i + 4], pA + (i + 4) * 512);
      }
#pragma unroll
      for (int i = 0; i < 4; i++) { aq[i] += aq1[i]; ak[i] += ak1[i]; }
    }
    RSTAMP(3);
#define STSF4(a, v) asm volatile("st.shared.v4.f32 [%0], {%1,%2,%3,%4};" ::"r"(a), "f"(v[0]), "f"(v[1]), "f"(v[2]), "f"(v[3]) : "memory")
#define VLD(i) do { ldsm_x4_t(b[i], pA + (i) * 512); ldsm_x4_t(f0[i], pVk + ((i) >> 1) * 8192 + ((i) & 1) * 4096); ldsm_x4_t(f1[i], pVk + ((i) >> 1) * 8192 + ((i) & 1) * 4096 + 2048); } while (0)
#define VPASS() float av[4] = {0, 0, 0, 0}; { float av1[4] = {0, 0, 0, 0}; unsigned b[8][4], f1[8][4], f0[8][4]; VLD(0); if (VD > 1) VLD(1); \
      _Pragma("unroll") for (int i = 0; i < 8; i++) { if (i + VD < 8) VLD(i + VD); \
        mma16816(av, f0[i], b[i][0], b[i][1]); mma16816(av1, f1[i], b[i][2], b[i][3]); } \
      _Pragma("unroll") for (int i = 0; i < 4; i++) av[i] += av1[i]; }
    unsigned f[8][4];
#define WO_LD(i0, i1) do { _Pragma("unroll") for (int i = i0; i < i1; i++) { ldsm_x4_t(f[2 * i], pW0 + 32768 + i * 2048); ldsm_x4_t(f[2 * i + 1], pW1 + 32768 + i * 2048); } } while (0)
    if (kh) {
      STSF4(aX, aq);
      float av[4];
      {
        const uint64_t ad = mkdesc(sb + R_T2, 8192, 1024), bd = (uint64_t)(((sb + R_MEM) >> 4) & 0x3fff) | (8ull << 16) | (8ull << 32);
        asm volatile("wgmma.fence.sync.aligned;" ::: "memory");
        asm volatile("wgmma.mma_async.sync.aligned.m64n8k16.f32.bf16.bf16 {%0,%1,%2,%3}, %4, %5, 0, 1, 1, 1, 1;"
                     : "=f"(av[0]), "=f"(av[1]), "=f"(av[2]), "=f"(av[3]) : "l"(ad), "l"(bd));
#pragma unroll
        for (int i = 1; i < 32; i++)
          asm volatile("wgmma.mma_async.sync.aligned.m64n8k16.f32.bf16.bf16 {%0,%1,%2,%3}, %4, %5, 1, 1, 1, 1, 1;"
                       : "+f"(av[0]), "+f"(av[1]), "+f"(av[2]), "+f"(av[3]) : "l"(ad + i * 128), "l"(bd + i * 16));
        asm volatile("wgmma.commit_group.sync.aligned;" ::: "memory");
      }
      bar_sync(4 + et, 64);
      uint4 o = lds128(aX + 2048);
      stsm_x2_t(aQKst, pack_bf16(ak[0] + __uint_as_float(o.x), ak[1] + __uint_as_float(o.y)), pack_bf16(ak[2] + __uint_as_float(o.z), ak[3] + __uint_as_float(o.w)));
      bar_arrive(1, 256);
      RSTAMP(4);
      asm volatile("wgmma.wait_group.sync.aligned 0;" : "+f"(av[0]), "+f"(av[1]), "+f"(av[2]), "+f"(av[3])::"memory");
      {
        unsigned x = pack_bf16(av[0], av[1]), y = pack_bf16(av[2], av[3]);
        st_async_b64(aVr, x, y, mbVr);
        st_async_b64(aVr + dLR, x, y, mbVl);
      }
      RSTAMP(5);
      if (s == NSEG - 1) {
        mbar_wait(bar + 8 * MB_V, par);
        if (t == 128) mbar_arrive(bar + 8 * MB_KVR);
        break;
      }
      mbar_wait(bar + 8 * (MB_FULL + slot), rpar);
      unsigned vx[4][4];
      ldsm_x4_t(vx[0], ring + oVx); ldsm_x4_t(vx[1], ring + oVx + 2048); ldsm_x4_t(vx[2], ring + (oVx ^ 32)); ldsm_x4_t(vx[3], ring + (oVx ^ 32) + 2048);
      WO_LD(0, NPRE1);
      RSTAMP(6); RSTAMP(7);
      mbar_wait(bar + 8 * MB_S, par);
      RSTAMP(8);
      float sc[10];
#pragma unroll
      for (int i = 0; i < 5; i++) {
        uint2 o = lds64(aL8 + R_SOWN + i * 256), p = lds64(aL8 + R_SPEER + i * 256);
        sc[2 * i] = __uint_as_float(o.x) + __uint_as_float(p.x); sc[2 * i + 1] = __uint_as_float(o.y) + __uint_as_float(p.y);
      }
      float mx = fmaxf(fmaxf(fmaxf(sc[0], sc[1]), fmaxf(sc[2], sc[3])), fmaxf(fmaxf(fmaxf(sc[4], sc[5]), fmaxf(sc[6], sc[7])), fmaxf(sc[8], sc[9])));
      mx = fmaxf(mx, __shfl_xor_sync(~0u, mx, 1)); mx = fmaxf(mx, __shfl_xor_sync(~0u, mx, 2));
      const float nm = -mx * (SCALE_QK * LOG2E);
      unsigned p[5];
#pragma unroll
      for (int i = 0; i < 5; i++) p[i] = pack_bf16(ex2f(fmaf(sc[2 * i], SCALE_QK * LOG2E, nm)), ex2f(fmaf(sc[2 * i + 1], SCALE_QK * LOG2E, nm)));
      RSTAMP(9);
      float o0[4] = {0, 0, 0, 0}, o1[4] = {0, 0, 0, 0}, o3[4] = {0, 0, 0, 0}, o4[4] = {0, 0, 0, 0}, z0[4] = {0, 0, 0, 0}, z1[4] = {0, 0, 0, 0};
      const unsigned ones[4] = {0x3F803F80u, 0u, 0x3F803F80u, 0u};
      mma16816(z0, ones, p[0], p[1]); mma16816(ZS ? z0 : z1, ones, p[2], p[3]);
      mma16816(o0, vx[0], p[0], p[1]); mma16816(o3, vx[2], p[0], p[1]); mma16816(o1, vx[1], p[2], p[3]); mma16816(o4, vx[3], p[2], p[3]);
      mma1688(z0, 0x3F803F80u, 0u, p[4]);
      mbar_wait(bar + 8 * MB_V, par);
      uint2 vm0 = lds64(aVm), vm1 = lds64(aVm + 256);
      mma1688(o0, vm0.x, vm0.y, p[4]); mma1688(o3, vm1.x, vm1.y, p[4]);
      float i0, i1;
      asm("rcp.approx.ftz.f32 %0, %1;" : "=f"(i0) : "f"(z0[0] + z1[0])); asm("rcp.approx.ftz.f32 %0, %1;" : "=f"(i1) : "f"(z0[1] + z1[1]));
      asm volatile("stmatrix.sync.aligned.m8n8.x4.trans.shared.b16 [%0], {%1,%2,%3,%4};" ::"r"(aOst), "r"(pack_bf16((o0[0] + o1[0]) * i0, (o0[1] + o1[1]) * i1)), "r"(pack_bf16((o0[2] + o1[2]) * i0, (o0[3] + o1[3]) * i1)),
                   "r"(pack_bf16((o3[0] + o4[0]) * i0, (o3[1] + o4[1]) * i1)), "r"(pack_bf16((o3[2] + o4[2]) * i0, (o3[3] + o4[3]) * i1)) : "memory");
      RSTAMP(10);
      bar_sync(1, 256);
      WO_LD(NPRE1, 3);
    } else {
      STSF4(aX + 2048, ak);
      unsigned kb[8];
      mbar_wait(bar + 8 * (MB_FULL + slot), rpar);
      ldsm_x4(kb, ring + oKx); ldsm_x4(kb + 4, ring + (oKx ^ 64));
      bar_sync(4 + et, 64);
      uint4 o = lds128(aX);
      stsm_x2_t(aQKst, pack_bf16(aq[0] + __uint_as_float(o.x), aq[1] + __uint_as_float(o.y)), pack_bf16(aq[2] + __uint_as_float(o.z), aq[3] + __uint_as_float(o.w)));
      RSTAMP(4);
      bar_sync(1, 256);
      RSTAMP(5);
      if (s != NSEG - 1) {
        unsigned qa[8], km[8];
        ldsm_x4(qa, aQ); ldsm_x4(qa + 4, aQ + 64);
        if (w == 3) { ldsm_x4(km, aQ + 1152); ldsm_x4(km + 4, aQ + 1152 + 64); }
        float s0[4] = {0, 0, 0, 0}, s1[4] = {0, 0, 0, 0};
        unsigned af[4][4];
#pragma unroll
        for (int i = 0; i < 4; i++) { af[i][0] = qa[2 * i]; af[i][1] = 0; af[i][2] = qa[2 * i + 1]; af[i][3] = 0; }
        mma16816(s0, af[0], kb[0], kb[1]); mma16816(s1, af[1], kb[2], kb[3]);
        mma16816(s0, af[2], kb[4], kb[5]); mma16816(s1, af[3], kb[6], kb[7]);
        if (w == 3) {
          float m0[4] = {0, 0, 0, 0}, m1[4] = {0, 0, 0, 0};
          mma16816(m0, af[0], km[0], km[1]); mma16816(m1, af[1], km[2], km[3]);
          mma16816(m0, af[2], km[4], km[5]); mma16816(m1, af[3], km[6], km[7]);
          unsigned x = __float_as_uint(m0[0] + m1[0]), y = __float_as_uint(m0[1] + m1[1]);
          st_async_b64(aSr + 256, x, y, mbSr); st_async_b64(aSl + 256, x, y, mbSl);
        }
        unsigned x = __float_as_uint(s0[0] + s1[0]), y = __float_as_uint(s0[1] + s1[1]);
        st_async_b64(aSr, x, y, mbSr); st_async_b64(aSl, x, y, mbSl);
      }
      RSTAMP(6);
      RSTAMP(7); RSTAMP(8);
      if (s == NSEG - 1) break;
      WO_LD(0, 3);
      RSTAMP(9); RSTAMP(10);
      bar_sync(1, 256);
    }
    RSTAMP(11);
    float d0[4] = {0, 0, 0, 0}, d1[4] = {0, 0, 0, 0}, e0[4] = {0, 0, 0, 0}, e1[4] = {0, 0, 0, 0};
    unsigned ob[4][4];
    ldsm_x4(ob[0], aOld); ldsm_x4(ob[1], aOld + 64);
    mma16816(d0, wo[0], ob[0][0], ob[0][1]); mma16816(d1, wo[1], ob[0][0], ob[0][1]);
    mma16816(e0, wo[2], ob[0][2], ob[0][3]); mma16816(e1, wo[3], ob[0][2], ob[0][3]);
    ldsm_x4(ob[2], aOld + 128);
    mma16816(d0, wo[4], ob[1][0], ob[1][1]); mma16816(d1, wo[5], ob[1][0], ob[1][1]);
    mma16816(e0, wo[6], ob[1][2], ob[1][3]); mma16816(e1, wo[7], ob[1][2], ob[1][3]);
    ldsm_x4(ob[3], aOld + 192);
    mma16816(d0, f[0], ob[2][0], ob[2][1]); mma16816(d1, f[1], ob[2][0], ob[2][1]);
    WO_LD(3, 4);
    mma16816(e0, f[2], ob[2][2], ob[2][3]); mma16816(e1, f[3], ob[2][2], ob[2][3]);
    const unsigned mbRSr = mapa(bar + 8 * MB_RS, j * 4 + (t8 >> 9));
    mma16816(d0, f[4], ob[3][0], ob[3][1]); mma16816(d1, f[5], ob[3][0], ob[3][1]);
    mma16816(e0, f[6], ob[3][2], ob[3][3]); mma16816(e1, f[7], ob[3][2], ob[3][3]);
    st_async_b64(aRSr, __float_as_uint(d0[0] + e0[0]), __float_as_uint(d0[1] + e0[1]), mbRSr);
    st_async_b64(aRSr + 256, __float_as_uint(d0[2] + e0[2]), __float_as_uint(d0[3] + e0[3]), mbRSr);
    st_async_b64(aRSr + 512, __float_as_uint(d1[0] + e1[0]), __float_as_uint(d1[1] + e1[1]), mbRSr);
    st_async_b64(aRSr + 768, __float_as_uint(d1[2] + e1[2]), __float_as_uint(d1[3] + e1[3]), mbRSr);
    RSTAMP(12);
    if (t == 128) {
      mbar_arrive(bar + 8 * (MB_EMPTY + slot)); mbar_arrive(bar + 8 * MB_KVR);
      mbar_expect_tx(bar + 8 * MB_S, 2560); mbar_expect_tx(bar + 8 * MB_V, 2048);
    }
    const unsigned tag = ((s >> 1) & 1) ^ 1;
    const char* gp = reinterpret_cast<const char*>(g_part);
    const unsigned goff = (par * 8 + rk) * 16384 + cl * 2048 + t8;
    unsigned mbA[8];
#pragma unroll
    for (int i = 0; i < 8; i++) if (!MBL) mbA[i] = mapa(bar + 8 * MB_AG, i);
    const unsigned dlt = (R_MEM + rk * 1024) - (SM_BAR + 8 * MB_AG) + (t8 >> 1);
    mbar_wait(bar + 8 * MB_RS, par);
    RSTAMP(13);
    uint2 a[8];
    {
      uint2 x0 = lds64(sb + R_RS + t8), x1 = lds64(sb + R_RS + 2048 + t8), x2 = lds64(sb + R_RS + 4096 + t8), x3 = lds64(sb + R_RS + 6144 + t8);
      float q0 = (__uint_as_float(x0.x) + __uint_as_float(x1.x)) + (__uint_as_float(x2.x) + __uint_as_float(x3.x));
      float q1 = (__uint_as_float(x0.y) + __uint_as_float(x1.y)) + (__uint_as_float(x2.y) + __uint_as_float(x3.y));
      a[0].x = (__float_as_uint(q0) & ~1u) | tag; a[0].y = (__float_as_uint(q1) & ~1u) | tag;
      asm volatile("st.relaxed.gpu.global.v2.u32 [%0], {%1,%2};" ::"l"(gp + goff), "r"(a[0].x), "r"(a[0].y) : "memory");
    }
    RSTAMP(14);
    if (t == 128) mbar_expect_tx(bar + 8 * MB_RS, 8192);
    {
      unsigned it = 0;
#define PLOAD(a) _Pragma("unroll") for (int i = 1; i < 8; i++) a[i] = ldv2_relaxed(gp + (goff ^ (i * 2048)))
#define PAND(a) (((a[1].x & a[1].y) & (a[2].x & a[2].y) & (a[3].x & a[3].y)) & ((a[4].x & a[4].y) & (a[5].x & a[5].y)) & ((a[6].x & a[6].y) & (a[7].x & a[7].y)))
#define POR(a) (((a[1].x | a[1].y) | (a[2].x | a[2].y) | (a[3].x | a[3].y)) | ((a[4].x | a[4].y) | (a[5].x | a[5].y)) | ((a[6].x | a[6].y) | (a[7].x | a[7].y)))
#define POK(a) (((tag ? PAND(a) : ~POR(a)) & 1u) != 0)
      if (D_RED) DELAY(D_RED);
      while (true) { PLOAD(a); if (POK(a)) break; if (D_PUB) DELAY(D_PUB); spin_check(it); }
    }
    RSTAMP(15);
    {
#define AF(i, c) __uint_as_float(a[i].c)
      unsigned u = pack_bf16(((AF(0, x) + AF(1, x)) + (AF(2, x) + AF(3, x))) + ((AF(4, x) + AF(5, x)) + (AF(6, x) + AF(7, x))),
                             ((AF(0, y) + AF(1, y)) + (AF(2, y) + AF(3, y))) + ((AF(4, y) + AF(5, y)) + (AF(6, y) + AF(7, y))));
      __syncwarp();
#pragma unroll
      for (int i = 0; i < 8; i++) { if (MBL) mbA[i] = mapa(bar + 8 * MB_AG, i); st_async_b32(mbA[i] + dlt, u, mbA[i]); }
    }
    mbar_wait(bar + 8 * MB_KVF, par);
    mbar_wait(bar + 8 * MB_AG, par);
    if (t == 128) mbar_expect_tx(bar + 8 * MB_AG, 8192);
  }
}

__device__ __forceinline__ void rec_ring(const Maps& maps, unsigned sb) {
  const int c = blockIdx.x, h = c >> 1, j = c & 1;
  const unsigned bar = sb + SM_BAR;
  const int lane = threadIdx.x & 31;
  if (lane == 0) {
    mbar_expect_tx(bar + 8 * MB_W0, 131072);
    for (int kb = 0; kb < 8; kb++) tma_load_2d(sb + R_WO + kb * 8192, &maps.wq, h * 128 + j * 64, kb * 64, bar + 8 * MB_W0);
    for (int kb = 0; kb < 8; kb++) tma_load_2d(sb + R_T1 + kb * 8192, &maps.wk, h * 128 + j * 64, kb * 64, bar + 8 * MB_W0);
    mbar_expect_tx(bar + 8 * MB_W1, 65536);
    for (int kb = 0; kb < 8; kb++) tma_load_2d(sb + R_T2 + kb * 8192, &maps.wv, h * 128 + j * 64, kb * 64, bar + 8 * MB_W1);
  }
  __syncwarp();
  bar_sync(2, 288);
  if (lane == 0) {
    fence_proxy_async_smem();
    for (int s = 0; s < NSEG; s++) {
      unsigned slot = s & (RING_N - 1);
      if ((s & 3) == 0 && !DBGMODE) {
        wait_flag_ge(&g_flags.qkv[(s >> 2) * 48 + 16 + (h >> 1)], 1);
        wait_flag_ge(&g_flags.qkv[(s >> 2) * 48 + 32 + (h >> 1)], 1);
        fence_proxy_async();
      }
      if (s >= RING_N) mbar_wait_sleep(bar + 8 * (MB_EMPTY + slot), ((s / RING_N) - 1) & 1);
      unsigned dst = sb + R_RING + slot * RING_BYTES, mb = bar + 8 * (MB_FULL + slot);
      mbar_expect_tx(mb, RING_BYTES);
      tma_load_2d(dst, &maps.qkv_ld, HD + h * 128 + j * 64, s * SEG, mb);
      tma_load_2d(dst + 4096, &maps.qkv_ld, 2 * HD + h * 128, s * SEG, mb);
      tma_load_2d(dst + 8192, &maps.qkv_ld, 2 * HD + h * 128 + 64, s * SEG, mb);
    }
  }
}
__device__ __forceinline__ void rec_copy(unsigned sb) {
  const int c = blockIdx.x, h = c >> 1, j = c & 1;
  const unsigned bar = sb + SM_BAR;
  const int lane = threadIdx.x & 31;
  for (int s = 0; s < NSEG; s++) {
    mbar_wait_sleep(bar + 8 * MB_KVR, s & 1);
    uint4 k0 = lds128(sb + R_KS + (lane >> 3) * 144 + (lane & 7) * 16), k1 = lds128(sb + R_KS + (4 + (lane >> 3)) * 144 + (lane & 7) * 16);
    uint2 v[4];
#pragma unroll
    for (int i = 0; i < 4; i++) v[i] = lds64(sb + R_VM + (j * 4 + i) * 256 + lane * 8);
    __syncwarp();
    if (lane == 0) mbar_arrive(bar + 8 * MB_KVF);
    bf16* kd = g_km + ((size_t)(s * NH + h) * NMEM) * DH + j * 64;
    *reinterpret_cast<uint4*>(kd + (lane >> 3) * DH + (lane & 7) * 8) = k0;
    *reinterpret_cast<uint4*>(kd + (4 + (lane >> 3)) * DH + (lane & 7) * 8) = k1;
    unsigned* vd = reinterpret_cast<unsigned*>(g_vmt) + ((size_t)(s * NH + h) * DH + j * 64) * 4;
#pragma unroll
    for (int i = 0; i < 4; i++) { vd[(i * 16) * 4 + lane] = v[i].x; vd[(i * 16 + 8) * 4 + lane] = v[i].y; }
    __syncwarp();
    if (lane == 0) st_release(&g_flags.rec[c], s + 1);
  }
}

__device__ __forceinline__ void bulk_producer(const Maps& maps, unsigned sb, int* misc) {
  const unsigned bar = sb + SM_BAR;
  const int lane = threadIdx.x & 31;
  unsigned st = 0, ph = 0, seq = 0;
  while (true) {
    int idx = 0;
    if (lane == 0) idx = (int)atomicAdd(&g_flags.ctr, 1u);
    idx = __shfl_sync(~0u, idx, 0);
    if (idx >= N_ITEMS) {
      if (lane == 0) {
        mbar_wait(bar + 8 * (MB_EMPTY + st), ph ^ 1);
        misc[seq & 3] = -1;
        mbar_arrive(bar + 8 * (MB_FULL + st));
      }
      break;
    }
    if (lane == 0) ISTAMP(idx, 0);
    Item it = decode_item(idx);
    if (it.b < 0) continue;
    const CUtensorMap* mp; int c0, c1, dc0, dc1; unsigned doff;
    const unsigned* fl = nullptr; unsigned tgt = 1; int nbox = 5, rdy = 0;
    if (it.type == T_ATT) {
      mp = &maps.qkv_ld; nbox = 12; doff = lane * 4096;
      c0 = (lane >> 2) * HD + it.c * 256 + (lane & 1) * 64; c1 = it.b * 128 + ((lane >> 1) & 1) * 32; dc0 = dc1 = 0;
      if (lane < 3) fl = &g_flags.qkv[it.b * 48 + lane * 16 + it.c];
      bool ok = true;
      if (lane >= 4 && lane < 8) ok = ld_acquire(&g_flags.rec[it.c * 4 + lane - 4]) >= (unsigned)(it.b * 4 + 4);
      rdy = __all_sync(~0u, ok) ? 65536 : 0;
    } else {
      int k0 = 0, nb0 = it.c * 256;
      if (it.type == T_QKV) { mp = lane == 0 ? &maps.xn : (it.c < 16 ? &maps.wq : (it.c < 32 ? &maps.wk : &maps.wv)); nb0 = (it.c & 15) * 256; }
      else if (it.type == T_M1) mp = lane == 0 ? &maps.y : &maps.w1;
      else if (it.type == T_M2) { mp = lane == 0 ? &maps.h1 : &maps.w2; fl = &g_flags.h1[it.b]; tgt = 7; }
      else {
        mp = lane == 0 ? &maps.o : &maps.wo;
        if (it.type == T_OUT) { k0 = it.ks * 1024; fl = &g_flags.o[it.b * 4 + it.ks]; tgt = 4; }
        else if (it.type == T_OUTL) { k0 = it.ks * 256; fl = &g_flags.o16[it.ks]; }
        else if (lane == 1) { fl = &g_flags.g[it.b]; tgt = 2; }
        else { fl = &g_flags.p[it.b]; tgt = it.type == T_RED ? 8 : 32; }
      }
      if (lane > (it.type >= T_RED ? 1 : 0)) fl = nullptr;
      if (lane == 0) { c0 = k0; c1 = it.b * 128; dc0 = 64; dc1 = 0; doff = 0; }
      else { c0 = nb0 + (lane - 1) * 64; c1 = k0; dc0 = 0; dc1 = 64; doff = 8192 + lane * 8192; }
    }
    if (fl) wait_flag_ge(fl, tgt);
    __syncwarp();
    fence_proxy_async();
    if (lane == 0) ISTAMP(idx, 1);
    const int nkb = item_nkb(it.type);
    for (int kb = 0; kb < nkb; kb++) {
      const unsigned mb = bar + 8 * (MB_FULL + st);
      mbar_wait(bar + 8 * (MB_EMPTY + st), ph ^ 1);
      if (lane == 0) {
        if (kb == 0) misc[seq & 3] = idx | rdy;
        if (it.type >= T_RED) mbar_arrive(mb); else mbar_expect_tx(mb, STAGE_BYTES);
      }
      if (it.type == T_ATT) { if (lane < 12) tma_load_2d(sb + st * STAGE_BYTES + doff, mp, c0 + (kb & 1) * 128, c1 + (kb >> 1) * 64, mb); }
      else if (lane < nbox && it.type < T_RED) tma_load_2d(sb + st * STAGE_BYTES + doff, mp, c0 + kb * dc0, c1 + kb * dc1, mb);
      __syncwarp();
      if (++st == NSTAGE) { st = 0; ph ^= 1; }
    }
    seq++;
  }
}
__device__ __forceinline__ void bulk_store(const Maps& maps, unsigned sb, volatile int* misc) {
  const unsigned bar = sb + SM_BAR;
  unsigned ph = 0;
  while (true) {
    mbar_wait(bar + 8 * MB_STGF, ph); ph ^= 1;
    int idx = misc[4];
    if (idx < 0) break;
    Item it = decode_item(idx);
    const CUtensorMap* mp = it.type == T_QKV ? &maps.qkv_st : (it.type == T_M1 ? &maps.h1 : (it.type == T_M2 ? &maps.g : &maps.o));
    unsigned* flag = it.type == T_QKV ? &g_flags.qkv[it.b * 48 + it.c] : (it.type == T_M1 ? &g_flags.h1[it.b] : (it.type == T_M2 ? &g_flags.g[it.b] : (it.b == 15 ? &g_flags.o16[it.c] : &g_flags.o[it.b * 4 + (it.c >> 2)])));
    for (int i = 0; i < 4; i++) tma_store_2d(mp, sb + B_STG + i * 16384, it.c * 256 + i * 64, it.b * 128);
    asm volatile("cp.async.bulk.commit_group;" ::: "memory");
    asm volatile("cp.async.bulk.wait_group.read 0;" ::: "memory");
    mbar_arrive(bar + 8 * MB_STGE);
    asm volatile("cp.async.bulk.wait_group 0;" ::: "memory");
    fence_proxy_async();
    red_release_add(flag, 1);
    ISTAMP(idx, 3);
  }
}
__device__ __forceinline__ float rcpf(float x) { float y; asm("rcp.approx.ftz.f32 %0, %1;" : "=f"(y) : "f"(x)); return y; }
__device__ __forceinline__ float gelu_t(float x) {
  float e = ex2f(x * fmaf(x * x, -2.0f * LOG2E * 0.7978845608028654f * 0.044715f, -2.0f * LOG2E * 0.7978845608028654f));
  return x * rcpf(1.0f + e);
}
__device__ __forceinline__ float silu_f(float x) { return x * rcpf(1.0f + ex2f(-LOG2E * x)); }
__device__ __forceinline__ unsigned badd2(unsigned a, unsigned b) { unsigned r; asm("add.rn.bf16x2 %0, %1, %2;" : "=r"(r) : "r"(a), "r"(b)); return r; }

__device__ __forceinline__ void final_out(bf16* __restrict__ out, const bf16* __restrict__ x, size_t o, float4 s) {
  uint2 gv = __ldcg(reinterpret_cast<const uint2*>(g_g + o)), xv = __ldg(reinterpret_cast<const uint2*>(x + o));
  uint2 r;
  r.x = pack_bf16(bf_lo(xv.x) + bf16r(bf16r(s.x) * bf_lo(gv.x)), bf_hi(xv.x) + bf16r(bf16r(s.y) * bf_hi(gv.x)));
  r.y = pack_bf16(bf_lo(xv.y) + bf16r(bf16r(s.z) * bf_lo(gv.y)), bf_hi(xv.y) + bf16r(bf16r(s.w) * bf_hi(gv.y)));
  *reinterpret_cast<uint2*>(out + o) = r;
}
__device__ __forceinline__ void bulk_att_load(unsigned* km, unsigned* vm, int b, int hp, int kb, int w, int lane) {
  const int g = lane >> 2, tq = lane & 3, seg = w >> 2, eh = w & 1;
  const int head = hp * 2 + (kb & 1), sg = b * 4 + (kb >> 1) * 2 + seg;
  const unsigned* kmp = reinterpret_cast<const unsigned*>(g_km + ((size_t)(sg * NH + head) * NMEM + g) * DH) + tq;
  const unsigned* vmp = reinterpret_cast<const unsigned*>(g_vmt) + ((size_t)(sg * NH + head) * DH + eh * 64) * 4 + lane;
#pragma unroll
  for (int i = 0; i < 16; i++) asm volatile("ld.global.cg.u32 %0, [%1];" : "=r"(km[i]) : "l"(kmp + i * 4) : "memory");
#pragma unroll
  for (int i = 0; i < 8; i++) asm volatile("ld.global.cg.u32 %0, [%1];" : "=r"(vm[i]) : "l"(vmp + i * 32) : "memory");
}
__device__ __forceinline__ void bulk_att_stage(unsigned sa, unsigned stg, const unsigned* km, const unsigned* vm, int kb, int w, int lane) {
  const int g = lane >> 2, tq = lane & 3, m = lane >> 3, r8 = lane & 7;
  const int seg = w >> 2, mt = (w >> 1) & 1, eh = w & 1;
  float s[5][4];
#pragma unroll
  for (int i = 0; i < 5; i++) { s[i][0] = s[i][1] = s[i][2] = s[i][3] = 0; }
  const unsigned qb = sa + (0 * 2 + seg) * 8192, kbs = sa + (1 * 2 + seg) * 8192, vb = sa + (2 * 2 + seg) * 8192 + eh * 4096;
  unsigned qa[8][4];
#pragma unroll
  for (int ks = 0; ks < 8; ks++) {
    int row = mt * 16 + (m & 1) * 8 + r8;
    ldsm_x4(qa[ks], qb + (ks >> 2) * 4096 + row * 128 + ((((ks & 3) * 2 + (m >> 1)) ^ r8) << 4));
    unsigned kf[4];
    int krow = (m >> 1) * 8 + r8;
    unsigned ka = kbs + (ks >> 2) * 4096 + krow * 128 + ((((ks & 3) * 2 + (m & 1)) ^ r8) << 4);
    ldsm_x4(kf, ka);
    mma16816(s[0], qa[ks], kf[0], kf[1]); mma16816(s[1], qa[ks], kf[2], kf[3]);
    if (mt) { ldsm_x4(kf, ka + 2048); mma16816(s[2], qa[ks], kf[0], kf[1]); mma16816(s[3], qa[ks], kf[2], kf[3]); }
  }
#pragma unroll
  for (int ks = 0; ks < 8; ks++) mma16816(s[4], qa[ks], km[2 * ks], km[2 * ks + 1]);
  float mx0 = -INFINITY, mx1 = -INFINITY;
  const int t0 = mt * 16 + g, t1 = t0 + 8;
#pragma unroll
  for (int i = 0; i < 5; i++) {
#pragma unroll
    for (int e = 0; e < 4; e++) {
      float v = s[i][e];
      if (i < 4) { int kj = i * 8 + 2 * tq + (e & 1); if (kj > (e < 2 ? t0 : t1)) v = -INFINITY; }
      s[i][e] = v;
      if (e < 2) mx0 = fmaxf(mx0, v); else mx1 = fmaxf(mx1, v);
    }
  }
  mx0 = fmaxf(mx0, __shfl_xor_sync(~0u, mx0, 1)); mx0 = fmaxf(mx0, __shfl_xor_sync(~0u, mx0, 2));
  mx1 = fmaxf(mx1, __shfl_xor_sync(~0u, mx1, 1)); mx1 = fmaxf(mx1, __shfl_xor_sync(~0u, mx1, 2));
  float sm0 = 0, sm1 = 0;
#pragma unroll
  for (int i = 0; i < 5; i++) {
    s[i][0] = ex2f((s[i][0] - mx0) * (SCALE_QK * LOG2E)); s[i][1] = ex2f((s[i][1] - mx0) * (SCALE_QK * LOG2E));
    s[i][2] = ex2f((s[i][2] - mx1) * (SCALE_QK * LOG2E)); s[i][3] = ex2f((s[i][3] - mx1) * (SCALE_QK * LOG2E));
    sm0 += s[i][0] + s[i][1]; sm1 += s[i][2] + s[i][3];
  }
  sm0 += __shfl_xor_sync(~0u, sm0, 1); sm0 += __shfl_xor_sync(~0u, sm0, 2);
  sm1 += __shfl_xor_sync(~0u, sm1, 1); sm1 += __shfl_xor_sync(~0u, sm1, 2);
  const float i0 = __fdividef(1.0f, sm0), i1 = __fdividef(1.0f, sm1);
  unsigned pa[2][4], pm0, pm1;
#pragma unroll
  for (int kk = 0; kk < 2; kk++) {
    pa[kk][0] = pack_bf16(s[2 * kk][0] * i0, s[2 * kk][1] * i0); pa[kk][1] = pack_bf16(s[2 * kk][2] * i1, s[2 * kk][3] * i1);
    pa[kk][2] = pack_bf16(s[2 * kk + 1][0] * i0, s[2 * kk + 1][1] * i0); pa[kk][3] = pack_bf16(s[2 * kk + 1][2] * i1, s[2 * kk + 1][3] * i1);
  }
  pm0 = pack_bf16(s[4][0] * i0, s[4][1] * i0); pm1 = pack_bf16(s[4][2] * i1, s[4][3] * i1);
  const int orow = (kb >> 1) * 64 + seg * 32 + mt * 16 + (m & 1) * 8 + r8;
  const unsigned ob = stg + ((kb & 1) * 2 + eh) * 16384 + orow * 128;
#pragma unroll
  for (int cp = 0; cp < 4; cp++) {
    float o0[4] = {0, 0, 0, 0}, o1[4] = {0, 0, 0, 0};
    mma1688(o0, pm0, pm1, vm[2 * cp]); mma1688(o1, pm0, pm1, vm[2 * cp + 1]);
    unsigned vf[4];
    int row = (m & 1) * 8 + r8;
    unsigned va = vb + row * 128 + (((cp * 2 + (m >> 1)) ^ r8) << 4);
    ldsm_x4_t(vf, va);
    mma16816(o0, pa[0], vf[0], vf[1]); mma16816(o1, pa[0], vf[2], vf[3]);
    if (mt) { ldsm_x4_t(vf, va + 2048); mma16816(o0, pa[1], vf[0], vf[1]); mma16816(o1, pa[1], vf[2], vf[3]); }
    stsm_x4(ob + (((cp * 2 + (m >> 1)) ^ r8) << 4), pack_bf16(o0[0], o0[1]), pack_bf16(o0[2], o0[3]), pack_bf16(o1[0], o1[1]), pack_bf16(o1[2], o1[3]));
  }
}

__device__ __forceinline__ void bulk_worker(unsigned sb, volatile int* misc, const bf16* __restrict__ x, const bf16* __restrict__ b1, const bf16* __restrict__ b2, bf16* __restrict__ out) {
  const int t = threadIdx.x, lane = t & 31, w = t >> 5, wg = w >> 2, g = lane >> 2, tq = lane & 3, m = lane >> 3, r8 = lane & 7;
  const unsigned bar = sb + SM_BAR;
  unsigned st = 0, ph = 0, seq = 0, sph = 0;
  float d[128];
  while (true) {
    mbar_wait(bar + 8 * (MB_FULL + st), ph);
    const int idr = misc[seq & 3]; seq++;
    const int idx = idr & 65535;
    if (idr < 0 || idx >= N_ITEMS) break;
    if (t == 0) ISTAMP(idx, 2);
    const Item it = decode_item(idx);
    const int nkb = item_nkb(it.type);
    if (it.type == T_ATT) {
      unsigned km[16], vm[8], kn[16], vn[8];
      const bool pref = idr >= 65536;
      if (pref) bulk_att_load(kn, vn, it.b, it.c, 0, w, lane);
      mbar_wait(bar + 8 * MB_STGE, sph ^ 1);
#pragma unroll 1
      for (int kb = 0; kb < 4; kb++) {
        if (!pref) {
          if (lane < 2) wait_flag_ge(&g_flags.rec[it.c * 4 + (kb & 1) * 2 + lane], it.b * 4 + (kb >> 1) * 2 + wg + 1);
          __syncwarp();
          bulk_att_load(kn, vn, it.b, it.c, kb, w, lane);
        }
        if (kb) mbar_wait(bar + 8 * (MB_FULL + st), ph);
#pragma unroll
        for (int i = 0; i < 16; i++) km[i] = kn[i];
#pragma unroll
        for (int i = 0; i < 8; i++) vm[i] = vn[i];
        if (pref && kb != 3) bulk_att_load(kn, vn, it.b, it.c, kb + 1, w, lane);
        bulk_att_stage(sb + st * STAGE_BYTES, sb + B_STG, km, vm, kb, w, lane);
        __syncwarp();
        if (lane == 0) mbar_arrive(bar + 8 * (MB_EMPTY + st));
        if (++st == NSTAGE) { st = 0; ph ^= 1; }
      }
      if (t == 0) misc[4] = idx;
      fence_proxy_async_smem();
      mbar_arrive(bar + 8 * MB_STGF); sph ^= 1;
      continue;
    }
    if (it.type >= T_RED) {
      __syncwarp();
      if (lane == 0) mbar_arrive(bar + 8 * (MB_EMPTY + st));
      if (++st == NSTAGE) { st = 0; ph ^= 1; }
      if (it.type == T_RED) {
#pragma unroll 2
        for (int i = 0; i < 8; i++) {
          size_t o = ((size_t)it.b * 128 + it.c * 16 + i * 2 + (t >> 7)) * DM + (t & 127) * 4;
          float4 a = __ldcg(reinterpret_cast<const float4*>(g_opart + o)), b = __ldcg(reinterpret_cast<const float4*>(g_opart + o + (size_t)S_TOK * DM));
          float4 c = __ldcg(reinterpret_cast<const float4*>(g_opart + o + (size_t)2 * S_TOK * DM)), e = __ldcg(reinterpret_cast<const float4*>(g_opart + o + (size_t)3 * S_TOK * DM));
          final_out(out, x, o, make_float4((a.x + b.x) + (c.x + e.x), (a.y + b.y) + (c.y + e.y), (a.z + b.z) + (c.z + e.z), (a.w + b.w) + (c.w + e.w)));
        }
      } else {
        size_t ol = ((size_t)it.c * 2 + (t >> 7)) * DM + (t & 127) * 4;
        float4 v[16];
#pragma unroll
        for (int i = 0; i < 16; i++) v[i] = __ldcg(reinterpret_cast<const float4*>(g_opl + ol + (size_t)i * 128 * DM));
#pragma unroll
        for (int st2 = 1; st2 < 16; st2 <<= 1)
#pragma unroll
          for (int i = 0; i < 16; i += 2 * st2) { v[i].x += v[i + st2].x; v[i].y += v[i + st2].y; v[i].z += v[i + st2].z; v[i].w += v[i + st2].w; }
        final_out(out, x, ol + (size_t)15 * 128 * DM, v[0]);
      }
      if (t == 0) ISTAMP(idx, 3);
      continue;
    }
    unsigned pst = 0, bv[32];
#pragma unroll
    for (int i = 0; i < 128; i++) d[i] = 0.0f;
    if (it.type == T_M1 || it.type == T_M2) {
      const unsigned* bp = reinterpret_cast<const unsigned*>((it.type == T_M1 ? b1 : b2) + it.c * 256) + tq;
#pragma unroll
      for (int i = 0; i < 32; i++) asm volatile("ld.global.nc.u32 %0, [%1];" : "=r"(bv[i]) : "l"(bp + i * 4));
    } else {
#pragma unroll
      for (int i = 0; i < 32; i++) bv[i] = 0;
    }
    for (int kb = 0; kb < nkb; kb++) {
      if (kb) mbar_wait(bar + 8 * (MB_FULL + st), ph);
      unsigned sa = sb + st * STAGE_BYTES;
      uint64_t ad = mkdesc(sa + wg * 8192, 16, 1024), bd = mkdesc(sa + 16384, 8192, 1024);
      asm volatile("wgmma.fence.sync.aligned;" ::: "memory");
#pragma unroll
      for (int k = 0; k < 4; k++) wgmma_n256(d, ad + k * 2, bd + k * 128, (kb | k) != 0);
      asm volatile("wgmma.commit_group.sync.aligned;" ::: "memory");
      if (kb) {
        asm volatile("wgmma.wait_group.sync.aligned 1;" ::: "memory");
        if (lane == 0) mbar_arrive(bar + 8 * (MB_EMPTY + pst));
      }
      pst = st;
      if (++st == NSTAGE) { st = 0; ph ^= 1; }
    }
    asm volatile("wgmma.wait_group.sync.aligned 0;" ::: "memory");
    if (lane == 0) mbar_arrive(bar + 8 * (MB_EMPTY + pst));
    if (it.type >= T_OUT) {
      const int col = it.c * 256 + 2 * tq;
      float* pp = it.type == T_OUT ? g_opart + ((size_t)it.ks * S_TOK + it.b * 128 + w * 16 + g) * DM + col : g_opl + ((size_t)it.ks * 128 + w * 16 + g) * DM + col;
#pragma unroll
      for (int i = 0; i < 32; i++) {
        __stcg(reinterpret_cast<float2*>(pp + i * 8), make_float2(d[4 * i], d[4 * i + 1]));
        __stcg(reinterpret_cast<float2*>(pp + 8 * DM + i * 8), make_float2(d[4 * i + 2], d[4 * i + 3]));
      }
      bar_sync(1, 256);
      if (t == 0) { red_release_add(&g_flags.p[it.b], 1); ISTAMP(idx, 3); }
      continue;
    }
#define ACT(F) _Pragma("unroll") for (int i = 0; i < 32; i++) { \
        unsigned u0 = badd2(pack_bf16(d[4 * i], d[4 * i + 1]), bv[i]), u1 = badd2(pack_bf16(d[4 * i + 2], d[4 * i + 3]), bv[i]); \
        d[4 * i] = F(bf_lo(u0)); d[4 * i + 1] = F(bf_hi(u0)); d[4 * i + 2] = F(bf_lo(u1)); d[4 * i + 3] = F(bf_hi(u1)); }
    if (it.type == T_M1) { ACT(gelu_t) } else if (it.type == T_M2) { ACT(silu_f) }
    mbar_wait(bar + 8 * MB_STGE, sph ^ 1);
    {
      const unsigned ob = sb + B_STG + (w * 16 + (m & 1) * 8 + r8) * 128;
#pragma unroll
      for (int i = 0; i < 16; i++)
        stsm_x4(ob + (i >> 2) * 16384 + ((((i & 3) * 2 + (m >> 1)) ^ r8) << 4), pack_bf16(d[8 * i], d[8 * i + 1]), pack_bf16(d[8 * i + 2], d[8 * i + 3]),
                pack_bf16(d[8 * i + 4], d[8 * i + 5]), pack_bf16(d[8 * i + 6], d[8 * i + 7]));
    }
    if (t == 0) misc[4] = idx;
    fence_proxy_async_smem();
    mbar_arrive(bar + 8 * MB_STGF); sph ^= 1;
  }
  mbar_wait(bar + 8 * MB_STGE, sph ^ 1);
  if (t == 0) misc[4] = -1;
  mbar_arrive(bar + 8 * MB_STGF);
}

__global__ void __launch_bounds__(384, 1)
k_main(const __grid_constant__ Maps maps, const bf16* __restrict__ x, const bf16* __restrict__ mem0, const bf16* __restrict__ b1, const bf16* __restrict__ b2, bf16* __restrict__ out, int helper) {
  extern __shared__ unsigned char smem_raw[];
  const unsigned sraw = smem_u32(smem_raw);
  const unsigned sb = (sraw + 1023u) & ~1023u;
  int* misc = reinterpret_cast<int*>(smem_raw + (sb - sraw) + SM_MISC);
  const int w = threadIdx.x >> 5;
  const bool rec = !helper && blockIdx.x < NREC;
  if (!helper) asm volatile("griddepcontrol.launch_dependents;");
  if (threadIdx.x == 0) {
    const unsigned bar = sb + SM_BAR;
    for (int i = 0; i < 8; i++) { mbar_init(bar + 8 * (MB_FULL + i), 1); mbar_init(bar + 8 * (MB_EMPTY + i), rec ? 1 : 8); }
    mbar_init(bar + 8 * MB_STGF, 256); mbar_init(bar + 8 * MB_STGE, 1);
    for (int i = MB_W0; i <= MB_AG; i++) mbar_init(bar + 8 * i, 1);
    if (rec) { mbar_expect_tx(bar + 8 * MB_S, 2560); mbar_expect_tx(bar + 8 * MB_V, 2048); mbar_expect_tx(bar + 8 * MB_RS, 8192); mbar_expect_tx(bar + 8 * MB_AG, 8192); }
    asm volatile("fence.mbarrier_init.release.cluster;" ::: "memory");
  }
  __syncthreads();
  asm volatile("barrier.cluster.arrive.release.aligned;\nbarrier.cluster.wait.acquire.aligned;" ::: "memory");
  if (DBGMODE && !rec) { if (helper) asm volatile("griddepcontrol.wait;" ::: "memory"); return; }
  if (w >= 8) {
    asm volatile("setmaxnreg.dec.sync.aligned.u32 24;");
    if (rec) { if (w == 8) rec_ring(maps, sb); else if (w == 9) rec_copy(sb); }
    else if (w == 8) bulk_producer(maps, sb, misc);
    else if ((threadIdx.x & 31) == 0) { if (w == 9) bulk_store(maps, sb, misc);
      else if (w == 10 && helper) asm volatile("griddepcontrol.wait;" ::: "memory"); }
  } else {
    if (rec) { asm volatile("setmaxnreg.inc.sync.aligned.u32 240;"); rec_worker(maps, sb, mem0); }
    else { asm volatile("setmaxnreg.inc.sync.aligned.u32 240;"); bulk_worker(sb, misc, x, b1, b2, out); }
  }
}

typedef CUresult (*EncFn)(CUtensorMap*, CUtensorMapDataType, cuuint32_t, void*, const cuuint64_t*, const cuuint64_t*, const cuuint32_t*, const cuuint32_t*,
                          CUtensorMapInterleave, CUtensorMapSwizzle, CUtensorMapL2promotion, CUtensorMapFloatOOBfill);
static void mk_map(EncFn enc, CUtensorMap* m, const void* ptr, uint64_t rows, uint64_t cols, uint32_t box_rows) {
  cuuint64_t dims[2] = {cols, rows}; cuuint64_t strides[1] = {cols * 2};
  cuuint32_t box[2] = {64, box_rows}, es[2] = {1, 1};
  enc(m, CU_TENSOR_MAP_DATA_TYPE_BFLOAT16, 2, const_cast<void*>(ptr), dims, strides, box, es, CU_TENSOR_MAP_INTERLEAVE_NONE, CU_TENSOR_MAP_SWIZZLE_128B,
      CU_TENSOR_MAP_L2_PROMOTION_L2_256B, CU_TENSOR_MAP_FLOAT_OOB_FILL_NONE);
}
extern "C" void kernel_launch(void* const* d_in, const int* in_sizes, int n_in, void* d_out, int out_size) {
  static EncFn enc = nullptr;
  static int ncl = 0, nhelp = 0;
  static void *p_xn, *p_y, *p_h1, *p_o, *p_qkv, *p_g;
  if (!enc) {
    void* fn = nullptr; cudaDriverEntryPointQueryResult qr;
    cudaGetDriverEntryPoint("cuTensorMapEncodeTiled", &fn, cudaEnableDefault, &qr);
    enc = (EncFn)fn;
    cudaGetSymbolAddress(&p_xn, g_xn); cudaGetSymbolAddress(&p_y, g_y); cudaGetSymbolAddress(&p_h1, g_h1);
    cudaGetSymbolAddress(&p_o, g_o); cudaGetSymbolAddress(&p_qkv, g_qkv); cudaGetSymbolAddress(&p_g, g_g);
    cudaFuncSetAttribute(k_main, cudaFuncAttributeMaxDynamicSharedMemorySize, SMEM_TOTAL);
    cudaLaunchConfig_t cfg = {}; cfg.gridDim = dim3(128); cfg.blockDim = dim3(384); cfg.dynamicSmemBytes = SMEM_TOTAL;
    cudaLaunchAttribute at[1]; at[0].id = cudaLaunchAttributeClusterDimension; at[0].val.clusterDim.x = CLS; at[0].val.clusterDim.y = 1; at[0].val.clusterDim.z = 1;
    cfg.attrs = at; cfg.numAttrs = 1;
    if (cudaOccupancyMaxActiveClusters(&ncl, k_main, &cfg) != cudaSuccess) { cudaGetLastError(); ncl = 14; }
    ncl = ncl > 16 ? 16 : (ncl < 9 ? 9 : ncl);
    int nsm = 0, dev = 0; cudaGetDevice(&dev); cudaDeviceGetAttribute(&nsm, cudaDevAttrMultiProcessorCount, dev);
    nhelp = nsm - ncl * CLS;
  }
  Maps maps;
  mk_map(enc, &maps.xn, p_xn, S_TOK, DM, 128); mk_map(enc, &maps.y, p_y, S_TOK, DM, 128); mk_map(enc, &maps.h1, p_h1, S_TOK, FF, 128);
  mk_map(enc, &maps.o, p_o, S_TOK, HD, 128); mk_map(enc, &maps.qkv_st, p_qkv, S_TOK, 3 * HD, 128); mk_map(enc, &maps.qkv_ld, p_qkv, S_TOK, 3 * HD, 32);
  mk_map(enc, &maps.g, p_g, S_TOK, DM, 128);
  mk_map(enc, &maps.wq, d_in[2], DM, HD, 64); mk_map(enc, &maps.wk, d_in[3], DM, HD, 64); mk_map(enc, &maps.wv, d_in[4], DM, HD, 64);
  mk_map(enc, &maps.wo, d_in[5], HD, DM, 64); mk_map(enc, &maps.w1, d_in[8], DM, FF, 64); mk_map(enc, &maps.w2, d_in[10], FF, DM, 64);
  cudaStream_t st = cudaStreamPerThread;
  k_pre<<<256, 256, 0, st>>>((const bf16*)d_in[0]);
  cudaLaunchConfig_t cfg = {}; cfg.gridDim = dim3(ncl * CLS); cfg.blockDim = dim3(384); cfg.dynamicSmemBytes = SMEM_TOTAL; cfg.stream = st;
  cudaLaunchAttribute at[1]; at[0].id = cudaLaunchAttributeClusterDimension; at[0].val.clusterDim.x = CLS; at[0].val.clusterDim.y = 1; at[0].val.clusterDim.z = 1;
  cfg.attrs = at; cfg.numAttrs = 1;
  cudaLaunchKernelEx(&cfg, k_main, maps, (const bf16*)d_in[0], (const bf16*)d_in[1], (const bf16*)d_in[9], (const bf16*)d_in[11], (bf16*)d_out, 0);
  if (nhelp > 0) {
    cfg.gridDim = dim3(nhelp);
    at[0].id = cudaLaunchAttributeProgrammaticStreamSerialization; at[0].val.programmaticStreamSerializationAllowed = 1;
    cudaLaunchKernelEx(&cfg, k_main, maps, (const bf16*)d_in[0], (const bf16*)d_in[1], (const bf16*)d_in[9], (const bf16*)d_in[11], (bf16*)d_out, 1);
  }
}
```

```cpp
#include <cuda_runtime.h>
#include <cuda_bf16.h>
#include <cuda.h>
#include <stdint.h>

typedef __nv_bfloat16 bf16;

#define S_TOK 2048
#define DM 512
#define NH 32
#define DH 128
#define HD 4096
#define NMEM 8
#define SEG 32
#define NSEG 64
#define FF 1792
#define NBLK 16
#define NREC 64
#define REPL 0
#define CLS 8

__device__ __align__(1024) bf16 g_xn[S_TOK * DM];
__device__ __align__(1024) bf16 g_y[S_TOK * DM];
__device__ __align__(1024) bf16 g_qkv[(size_t)S_TOK * 3 * HD];
__device__ __align__(1024) bf16 g_h1[S_TOK * FF];
__device__ __align__(1024) bf16 g_g[S_TOK * DM];
__device__ __align__(1024) bf16 g_o[(size_t)S_TOK * HD];
__device__ __align__(1024) bf16 g_km[NSEG * NH * NMEM * DH];
__device__ __align__(1024) bf16 g_vmt[NSEG * NH * DH * NMEM];
__device__ __align__(1024) float g_opart[(size_t)4 * S_TOK * DM];
__device__ __align__(1024) float g_opl[(size_t)16 * 128 * DM];
__device__ __align__(1024) unsigned g_part[8 * 2 * 8 * 8 * 512];
struct Flags {
  unsigned qkv[NBLK * 48];
  unsigned h1[NBLK];
  unsigned g[NBLK];
  unsigned o[NBLK * 4];
  unsigned p[NBLK];
  unsigned o16[16];
  unsigned ctr;
  unsigned rec[NREC];
  unsigned abort_;
};
__device__ __align__(1024) Flags g_flags;

#define RSTAMP(k)
#define DBGMODE 0
#define ISTAMP(i, k)
__device__ __forceinline__ unsigned smem_u32(const void* p) { return (unsigned)__cvta_generic_to_shared(p); }
__device__ __forceinline__ float bf16r(float x) { unsigned u; asm("cvt.rn.bf16x2.f32 %0, %1, %2;" : "=r"(u) : "f"(x), "f"(0.0f)); return __uint_as_float(u); }
__device__ __forceinline__ unsigned pack_bf16(float lo, float hi) {
  __nv_bfloat162 v = __floats2bfloat162_rn(lo, hi);
  return *reinterpret_cast<unsigned*>(&v);
}
__device__ __forceinline__ float bf_lo(unsigned u) { return __uint_as_float(u << 16); }
__device__ __forceinline__ float bf_hi(unsigned u) { return __uint_as_float(u & 0xffff0000u); }

#define SPIN_LIMIT (1u << 20)
#define TRAP_IF(x) if ((x) > SPIN_LIMIT) { asm volatile("st.global.u32 [%0], %1;" ::"l"(0ull), "r"(0u) : "memory"); break; }
__device__ __forceinline__ unsigned ld_acquire(const unsigned* p) {
  unsigned v; asm volatile("ld.acquire.gpu.global.u32 %0, [%1];" : "=r"(v) : "l"(p) : "memory"); return v;
}
__device__ __forceinline__ unsigned ld_relaxed(const unsigned* p) {
  unsigned v; asm volatile("ld.relaxed.gpu.global.u32 %0, [%1];" : "=r"(v) : "l"(p) : "memory"); return v;
}
__device__ __forceinline__ void red_release_add(unsigned* p, unsigned v) {
  asm volatile("red.release.gpu.global.add.u32 [%0], %1;" ::"l"(p), "r"(v) : "memory");
}
__device__ __forceinline__ void st_release(unsigned* p, unsigned v) {
  asm volatile("st.release.gpu.global.u32 [%0], %1;" ::"l"(p), "r"(v) : "memory");
}
__device__ __forceinline__ void wait_flag_ge(const unsigned* p, unsigned target) {
  unsigned it = 0;
  while (ld_acquire(p) < target) {
    __nanosleep(64);
    TRAP_IF(++it);
  }
}
__device__ __forceinline__ uint4 ldv4_relaxed(const void* p) {
  uint4 a; asm volatile("ld.relaxed.gpu.global.v4.u32 {%0,%1,%2,%3}, [%4];" : "=r"(a.x), "=r"(a.y), "=r"(a.z), "=r"(a.w) : "l"(p) : "memory"); return a;
}
__device__ __forceinline__ uint2 ldv2_relaxed(const void* p) {
  uint2 a; asm volatile("ld.relaxed.gpu.global.v2.u32 {%0,%1}, [%2];" : "=r"(a.x), "=r"(a.y) : "l"(p) : "memory"); return a;
}
__device__ __forceinline__ void mbar_init(unsigned mb, unsigned cnt) { asm volatile("mbarrier.init.shared::cta.b64 [%0], %1;" ::"r"(mb), "r"(cnt) : "memory"); }
__device__ __forceinline__ void mbar_expect_tx(unsigned mb, unsigned bytes) { asm volatile("mbarrier.arrive.expect_tx.shared::cta.b64 _, [%0], %1;" ::"r"(mb), "r"(bytes) : "memory"); }
__device__ __forceinline__ void mbar_arrive(unsigned mb) { asm volatile("mbarrier.arrive.shared::cta.b64 _, [%0];" ::"r"(mb) : "memory"); }
__device__ __forceinline__ void mbar_wait(unsigned mb, unsigned parity) {
  unsigned ok, it = 0;
  while (true) {
    asm volatile("{.reg .pred p; mbarrier.try_wait.parity.shared::cta.b64 p, [%1], %2; selp.u32 %0,1,0,p;}" : "=r"(ok) : "r"(mb), "r"(parity) : "memory");
    if (ok) break;
    TRAP_IF(++it);
  }
}
__device__ __forceinline__ void mbar_wait_sleep(unsigned mb, unsigned parity) {
  unsigned ok, it = 0;
  while (true) {
    asm volatile("{.reg .pred p; mbarrier.test_wait.parity.shared::cta.b64 p, [%1], %2; selp.u32 %0,1,0,p;}" : "=r"(ok) : "r"(mb), "r"(parity) : "memory");
    if (ok) break;
    __nanosleep(200);
    TRAP_IF(++it);
  }
}
__device__ __forceinline__ float ex2f(float x) { float y; asm("ex2.approx.ftz.f32 %0, %1;" : "=f"(y) : "f"(x)); return y; }
__device__ __forceinline__ int opaque_tid() { int t = threadIdx.x; t = __shfl_sync(~0u, t, t & 31); return t; }
#define LOG2E 1.4426950408889634f
__device__ __forceinline__ void mbar_wait_cluster(unsigned mb, unsigned parity) {
  unsigned ok, it = 0;
  while (true) {
    asm volatile("{.reg .pred p; mbarrier.try_wait.parity.acquire.cluster.shared::cta.b64 p, [%1], %2; selp.u32 %0,1,0,p;}" : "=r"(ok) : "r"(mb), "r"(parity) : "memory");
    if (ok) break;
    TRAP_IF(++it);
  }
}
__device__ __forceinline__ void bar_sync(int id, int n) { asm volatile("bar.sync %0, %1;" ::"r"(id), "r"(n) : "memory"); }
__device__ __forceinline__ void bar_arrive(int id, int n) { asm volatile("bar.arrive %0, %1;" ::"r"(id), "r"(n) : "memory"); }
__device__ __forceinline__ void tma_load_2d(unsigned dst, const CUtensorMap* map, int c0, int c1, unsigned mb) {
  asm volatile("cp.async.bulk.tensor.2d.shared::cluster.global.mbarrier::complete_tx::bytes [%0], [%1, {%3, %4}], [%2];"
               ::"r"(dst), "l"((uint64_t)map), "r"(mb), "r"(c0), "r"(c1) : "memory");
}
__device__ __forceinline__ void tma_store_2d(const CUtensorMap* map, unsigned src, int c0, int c1) {
  asm volatile("cp.async.bulk.tensor.2d.global.shared::cta.bulk_group [%0, {%2, %3}], [%1];"
               ::"l"((uint64_t)map), "r"(src), "r"(c0), "r"(c1) : "memory");
}
__device__ __forceinline__ void fence_proxy_async() { asm volatile("fence.proxy.async;" ::: "memory"); }
__device__ __forceinline__ void fence_proxy_async_smem() { asm volatile("fence.proxy.async.shared::cta;" ::: "memory"); }
__device__ __forceinline__ void ldsm_x4(unsigned* r, unsigned addr) {
  asm volatile("ldmatrix.sync.aligned.m8n8.x4.shared.b16 {%0,%1,%2,%3}, [%4];" : "=r"(r[0]), "=r"(r[1]), "=r"(r[2]), "=r"(r[3]) : "r"(addr) : "memory");
}
__device__ __forceinline__ void ldsm_x4_t(unsigned* r, unsigned addr) {
  asm volatile("ldmatrix.sync.aligned.m8n8.x4.trans.shared.b16 {%0,%1,%2,%3}, [%4];" : "=r"(r[0]), "=r"(r[1]), "=r"(r[2]), "=r"(r[3]) : "r"(addr) : "memory");
}
__device__ __forceinline__ void stsm_x2_t(unsigned addr, unsigned r0, unsigned r1) {
  asm volatile("stmatrix.sync.aligned.m8n8.x2.trans.shared.b16 [%0], {%1,%2};" ::"r"(addr), "r"(r0), "r"(r1) : "memory");
}
__device__ __forceinline__ void stsm_x4(unsigned addr, unsigned r0, unsigned r1, unsigned r2, unsigned r3) {
  asm volatile("stmatrix.sync.aligned.m8n8.x4.shared.b16 [%0], {%1,%2,%3,%4};" ::"r"(addr), "r"(r0), "r"(r1), "r"(r2), "r"(r3) : "memory");
}
__device__ __forceinline__ void mma16816(float* d, const unsigned* a, unsigned b0, unsigned b1) {
  asm volatile("mma.sync.aligned.m16n8k16.row.col.f32.bf16.bf16.f32 {%0,%1,%2,%3}, {%4,%5,%6,%7}, {%8,%9}, {%0,%1,%2,%3};"
               : "+f"(d[0]), "+f"(d[1]), "+f"(d[2]), "+f"(d[3]) : "r"(a[0]), "r"(a[1]), "r"(a[2]), "r"(a[3]), "r"(b0), "r"(b1));
}
__device__ __forceinline__ void mma1688(float* d, unsigned a0, unsigned a1, unsigned b0) {
  asm volatile("mma.sync.aligned.m16n8k8.row.col.f32.bf16.bf16.f32 {%0,%1,%2,%3}, {%4,%5}, {%6}, {%0,%1,%2,%3};"
               : "+f"(d[0]), "+f"(d[1]), "+f"(d[2]), "+f"(d[3]) : "r"(a0), "r"(a1), "r"(b0));
}
__device__ __forceinline__ uint64_t mkdesc(unsigned addr, unsigned lbo, unsigned sbo) {
  return (uint64_t)((addr >> 4) & 0x3fff) | ((uint64_t)(lbo >> 4) << 16) | ((uint64_t)(sbo >> 4) << 32) | (1ull << 62);
}
#define R8(b) "+f"(d[b]), "+f"(d[b + 1]), "+f"(d[b + 2]), "+f"(d[b + 3]), "+f"(d[b + 4]), "+f"(d[b + 5]), "+f"(d[b + 6]), "+f"(d[b + 7])
#define R32(b) R8(b), R8(b + 8), R8(b + 16), R8(b + 24)
__device__ __forceinline__ void wgmma_n256(float* d, uint64_t ad, uint64_t bd, int acc) {
  asm volatile(
      "{.reg .pred p; setp.ne.b32 p, %130, 0;\n"
      "wgmma.mma_async.sync.aligned.m64n256k16.f32.bf16.bf16 "
      "{%0,%1,%2,%3,%4,%5,%6,%7,%8,%9,%10,%11,%12,%13,%14,%15,%16,%17,%18,%19,%20,%21,%22,%23,%24,%25,%26,%27,%28,%29,%30,%31,"
      "%32,%33,%34,%35,%36,%37,%38,%39,%40,%41,%42,%43,%44,%45,%46,%47,%48,%49,%50,%51,%52,%53,%54,%55,%56,%57,%58,%59,%60,%61,%62,%63,"
      "%64,%65,%66,%67,%68,%69,%70,%71,%72,%73,%74,%75,%76,%77,%78,%79,%80,%81,%82,%83,%84,%85,%86,%87,%88,%89,%90,%91,%92,%93,%94,%95,"
      "%96,%97,%98,%99,%100,%101,%102,%103,%104,%105,%106,%107,%108,%109,%110,%111,%112,%113,%114,%115,%116,%117,%118,%119,%120,%121,%122,%123,%124,%125,%126,%127},"
      "%128, %129, p, 1, 1, 0, 1;}\n"
      : R32(0), R32(32), R32(64), R32(96)
      : "l"(ad), "l"(bd), "r"(acc));
}

__device__ __forceinline__ void ln16(const float* x, float* o) {
  float s = 0;
#pragma unroll
  for (int i = 0; i < 16; i++) s += x[i];
#pragma unroll
  for (int of = 16; of > 0; of >>= 1) s += __shfl_xor_sync(~0u, s, of);
  float mean = s * (1.0f / DM);
  float v = 0;
#pragma unroll
  for (int i = 0; i < 16; i++) { float dd = x[i] - mean; v += dd * dd; }
#pragma unroll
  for (int of = 16; of > 0; of >>= 1) v += __shfl_xor_sync(~0u, v, of);
  float mb = bf16r(mean);
  float vb = bf16r(v * (1.0f / DM));
  float den = bf16r(sqrtf(bf16r(vb + 1e-5f)));
#pragma unroll
  for (int i = 0; i < 16; i++) o[i] = bf16r(__fdiv_rn(bf16r(x[i] - mb), den));
}
__global__ void __launch_bounds__(256) k_pre(const bf16* __restrict__ x) {
  int t = threadIdx.x, lane = t & 31, w = t >> 5;
  int row = blockIdx.x * 8 + w;
  const uint4* src = reinterpret_cast<const uint4*>(x + (size_t)row * DM);
  uint4 a = src[lane], b = src[lane + 32];
  unsigned u[8] = {a.x, a.y, a.z, a.w, b.x, b.y, b.z, b.w};
  float f[16], o[16], o2[16];
#pragma unroll
  for (int i = 0; i < 8; i++) { f[2 * i] = bf_lo(u[i]); f[2 * i + 1] = bf_hi(u[i]); }
  ln16(f, o);
  ln16(o, o2);
  uint4* d1 = reinterpret_cast<uint4*>(g_xn + (size_t)row * DM);
  uint4* d2 = reinterpret_cast<uint4*>(g_y + (size_t)row * DM);
  d1[lane] = make_uint4(pack_bf16(o[0], o[1]), pack_bf16(o[2], o[3]), pack_bf16(o[4], o[5]), pack_bf16(o[6], o[7]));
  d1[lane + 32] = make_uint4(pack_bf16(o[8], o[9]), pack_bf16(o[10], o[11]), pack_bf16(o[12], o[13]), pack_bf16(o[14], o[15]));
  d2[lane] = make_uint4(pack_bf16(o2[0], o2[1]), pack_bf16(o2[2], o2[3]), pack_bf16(o2[4], o2[5]), pack_bf16(o2[6], o2[7]));
  d2[lane + 32] = make_uint4(pack_bf16(o2[8], o2[9]), pack_bf16(o2[10], o2[11]), pack_bf16(o2[12], o2[13]), pack_bf16(o2[14], o2[15]));
  int gt = blockIdx.x * 256 + t;
  uint4 z = make_uint4(0, 0, 0, 0);
  if (gt < 16384) reinterpret_cast<uint4*>(g_part)[gt] = z;
  if (gt < (int)(sizeof(Flags) / 4)) reinterpret_cast<unsigned*>(&g_flags)[gt] = 0;
}

struct Maps { CUtensorMap xn, y, h1, o, qkv_st, qkv_ld, g, wq, wk, wv, wo, w1, w2; };

#define NSTAGE 3
#define STAGE_BYTES 49152
#define B_STG (NSTAGE * STAGE_BYTES)
#define R_WO 0
#define R_T1 65536
#define R_T2 131072
#define R_RING 65536
#define RING_N 4
#define RING_BYTES 12288
#define R_MEM 196608
#define R_QS (R_MEM + 8448)
#define R_KS (R_QS + 1152)
#define R_OS (R_KS + 1152)
#define R_SOWN (R_OS + 2176)
#define R_SPEER (R_SOWN + 1280)
#define R_VM (R_SPEER + 1280)
#define R_VRED (R_VM + 2048)
#define R_RS (R_VRED + 6144)
#define SM_BAR (R_RS + 8192)
#define SMEM_TOTAL (SM_BAR + 256 + 1024)
#define MB_FULL 0
#define MB_EMPTY 8
#define MB_STGF 16
#define MB_STGE 17
#define MB_W0 18
#define MB_W1 19
#define MB_WO 20
#define MB_S 21
#define MB_V 22
#define MB_KVR 23
#define MB_KVF 24
#define MB_RS 25
#define MB_AG 26
#define SM_MISC (SM_BAR + 224)

#define N_KV 512
#define I_M1 512
#define I_Q 624
#define I_M2 880
#define I_POST 912
#define I_TAIL (I_POST + 16 * 32)
#define N_ITEMS (I_TAIL + 5 * 8 + 32 + 8 + 64)
enum { T_QKV = 0, T_M1 = 1, T_M2 = 2, T_ATT = 3, T_OUT = 4, T_OUTL = 5, T_RED = 6, T_REDL = 7 };
struct Item { int type, b, c, ks; };
__device__ __forceinline__ Item decode_item(int i) {
  Item it; it.ks = 0;
  if (i < N_KV) { it.type = T_QKV; it.b = i >> 5; it.c = 16 + (i & 31); }
  else if (i < I_Q) { it.type = T_M1; it.b = (i - I_M1) / 7; it.c = (i - I_M1) % 7; }
  else if (i < I_M2) { it.type = T_QKV; it.b = (i - I_Q) >> 4; it.c = (i - I_Q) & 15; }
  else if (i < I_POST) { it.type = T_M2; it.b = (i - I_M2) >> 1; it.c = (i - I_M2) & 1; }
  else if (i < I_TAIL) {
    int x = i - I_POST, p = x >> 5, r = x & 31;
    if (r < 16) { it.type = T_ATT; it.b = p; it.c = r; }
    else if (r < 24) { it.type = T_OUT; it.b = p - 3; it.c = r & 1; it.ks = (r - 16) >> 1; }
    else { it.type = T_RED; it.b = p - 5; it.c = r - 24; }
  } else {
    int x = i - I_TAIL, r = x & 7;
    if (x < 40) {
      int q = x >> 3;
      if (q == 0 || q == 2) { it.type = T_OUT; it.b = 13 + (q >> 1); it.c = r & 1; it.ks = r >> 1; }
      else { it.type = T_RED; it.b = q == 1 ? 11 : 9 + q; it.c = r; }
    }
    else if (x < 72) { it.type = T_OUTL; it.b = 15; it.c = x & 1; it.ks = (x - 40) >> 1; }
    else if (x < 80) { it.type = T_RED; it.b = 14; it.c = r; }
    else { it.type = T_REDL; it.b = 15; it.c = x - 80; }
  }
  return it;
}
__device__ __forceinline__ int item_nkb(int type) { return type == T_M2 ? 28 : (type == T_OUT ? 16 : (type >= T_RED ? 1 : (type >= T_ATT ? 4 : 8))); }

__device__ __forceinline__ void st_async_b64(unsigned raddr, unsigned lo, unsigned hi, unsigned rmb) {
  asm volatile("st.async.weak.shared::cluster.mbarrier::complete_tx::bytes.v2.b32 [%0], {%1,%2}, [%3];" ::"r"(raddr), "r"(lo), "r"(hi), "r"(rmb) : "memory");
}
__device__ __forceinline__ void st_async_b32(unsigned raddr, unsigned v, unsigned rmb) {
  asm volatile("st.async.weak.shared::cluster.mbarrier::complete_tx::bytes.b32 [%0], %1, [%2];" ::"r"(raddr), "r"(v), "r"(rmb) : "memory");
}
__device__ __forceinline__ unsigned mapa(unsigned a, unsigned rank) {
  unsigned r; asm volatile("mapa.shared::cluster.u32 %0, %1, %2;" : "=r"(r) : "r"(a), "r"(rank)); return r;
}
__device__ __forceinline__ void sts64(unsigned a, unsigned x, unsigned y) { asm volatile("st.shared.v2.b32 [%0], {%1,%2};" ::"r"(a), "r"(x), "r"(y) : "memory"); }
__device__ __forceinline__ void sts128(unsigned a, uint4 v) { asm volatile("st.shared.v4.b32 [%0], {%1,%2,%3,%4};" ::"r"(a), "r"(v.x), "r"(v.y), "r"(v.z), "r"(v.w) : "memory"); }
__device__ __forceinline__ uint2 lds64(unsigned a) { uint2 v; asm volatile("ld.shared.v2.b32 {%0,%1}, [%2];" : "=r"(v.x), "=r"(v.y) : "r"(a) : "memory"); return v; }
__device__ __forceinline__ uint4 lds128(unsigned a) { uint4 v; asm volatile("ld.shared.v4.b32 {%0,%1,%2,%3}, [%4];" : "=r"(v.x), "=r"(v.y), "=r"(v.z), "=r"(v.w) : "r"(a) : "memory"); return v; }
__device__ __forceinline__ float lds32f(unsigned a) { float v; asm volatile("ld.shared.f32 %0, [%1];" : "=f"(v) : "r"(a) : "memory"); return v; }
#define spin_check(it) TRAP_IF(++it)
#define POLLV 0
#define BAR8 0
#define D_STAG 150
#define D_RED 480
#define D_PUB 0
#define DELAY(n) do { unsigned c0_, c1_; asm volatile("mov.u32 %0, %%clock;" : "=r"(c0_)); do { asm volatile("mov.u32 %0, %%clock;" : "=r"(c1_)); } while (c1_ - c0_ < (n)); } while (0)
#define NPRE1 0
#define VD 2
#define ZS 0
#define MBL 1
#define D_V 0
#define SCALE_QK 0.08838834764831845f

__device__ __forceinline__ void rec_worker(const Maps& maps, unsigned sb, const bf16* __restrict__ mem0) {
  const int c = blockIdx.x, h = c >> 1, j = c & 1;
  const int t = opaque_tid(), lane = t & 31, w = t >> 5, g = lane >> 2, tq = lane & 3;
  const int m = lane >> 3, r8 = lane & 7, kh = w >> 2, et = w & 3;
  const unsigned bar = sb + SM_BAR;
  unsigned wq[16][4], wk[16][4], wo[8][4];
  const unsigned woff = (kh * 4) * 8192 + ((m >> 1) * 8 + r8) * 128 + (((et * 2 + (m & 1)) ^ r8) << 4);
  mbar_wait(bar + 8 * MB_W0, 0);
#pragma unroll
  for (int i = 0; i < 16; i++) {
    ldsm_x4_t(wq[i], sb + R_WO + woff + (i >> 2) * 8192 + (i & 3) * 2048);
    ldsm_x4_t(wk[i], sb + R_T1 + woff + (i >> 2) * 8192 + (i & 3) * 2048);
  }
  bar_sync(2, 288);
  if (t == 0) {
    fence_proxy_async_smem();
    mbar_expect_tx(bar + 8 * MB_WO, 65536);
    for (int kb = 0; kb < 2; kb++)
      for (int cb = 0; cb < 4; cb++) tma_load_2d(sb + R_WO + (kb * 4 + cb) * 8192, &maps.wo, j * 256 + cb * 64, h * 128 + kb * 64, bar + 8 * MB_WO);
  }
  const unsigned rk = c & 7, peer = rk ^ 1, cl = c >> 3;
#define KEEP(x) x = __shfl_sync(~0u, x, lane)
  unsigned pA = sb + R_MEM + kh * 4096 + lane * 16;
  unsigned pW0 = sb + R_WO + (w >> 1) * 8192 + ((m >> 1) * 8 + r8) * 128 + ((((w & 1) * 4 + (m & 1)) ^ r8) << 4);
#define pW1 (pW0 ^ 32)
  unsigned aX = sb + R_VRED + et * 512 + lane * 16;
  unsigned aQKst = sb + (kh ? R_KS : R_QS) + r8 * 144 + (et * 16 + (m & 1) * 8) * 2;
  unsigned aL8_ = sb + lane * 8;
  unsigned aSl_ = mapa(sb + R_SOWN + w * 256 + lane * 8, rk), aSr_ = mapa(sb + R_SPEER + w * 256 + lane * 8, peer);
  const unsigned mbSl = mapa(bar + 8 * MB_S, rk), mbSr = mapa(bar + 8 * MB_S, peer), mbVl = mbSl + 8, mbVr = mbSr + 8;
  unsigned aQ_ = sb + R_QS + r8 * 144 + m * 16;
  unsigned oKx_ = (et * 8 + r8) * 128 + ((m ^ r8) << 4);
  unsigned oVx_ = 4096 + (et >> 1) * 4096 + ((m >> 1) * 8 + r8) * 128 + ((((et & 1) * 4 + (m & 1)) ^ r8) << 4);
  unsigned aOst_ = sb + R_OS + r8 * 272 + (et * 32 + m * 8) * 2;
  unsigned aOld = sb + R_OS + r8 * 272 + m * 16;
  unsigned aVm_ = sb + R_VM + et * 512 + lane * 8;
  unsigned aRSr = mapa(sb + R_RS + (h & 3) * 2048 + (w & 1) * 1024 + lane * 8, j * 4 + (w >> 1));
  unsigned t8 = t * 8;
  unsigned r1 = kh ? aL8_ : aSl_, r2 = kh ? oVx_ : aSr_, r3 = kh ? aOst_ : aQ_, r4 = kh ? aVm_ : oKx_;
#define aL8 r1
#define aSl r1
#define oVx r2
#define aSr r2
#define aOst r3
#define aQ r3
#define aVm r4
#define oKx r4
  KEEP(pA); KEEP(pW0); KEEP(aX); KEEP(aQKst); KEEP(r1); KEEP(r2); KEEP(r3); KEEP(r4);
  KEEP(aOld); KEEP(aRSr); KEEP(t8);
  mbar_wait(bar + 8 * MB_WO, 0);
#pragma unroll
  for (int ks = 0; ks < 4; ks++) { ldsm_x4_t(wo[2 * ks], pW0 + ks * 2048); ldsm_x4_t(wo[2 * ks + 1], pW1 + ks * 2048); }
  {
    unsigned v[8];
#pragma unroll
    for (int q = 0; q < 8; q++) v[q] = __ldg(reinterpret_cast<const unsigned*>(mem0) + q * 256 + t);
    sts128(sb + R_MEM + t * 32, make_uint4(__byte_perm(v[0], v[1], 0x5410), __byte_perm(v[2], v[3], 0x5410), __byte_perm(v[4], v[5], 0x5410), __byte_perm(v[6], v[7], 0x5410)));
    sts128(sb + R_MEM + t * 32 + 16, make_uint4(__byte_perm(v[0], v[1], 0x7632), __byte_perm(v[2], v[3], 0x7632), __byte_perm(v[4], v[5], 0x7632), __byte_perm(v[6], v[7], 0x7632)));
  }
  fence_proxy_async_smem();
  bar_sync(3, 384);

#pragma unroll 1
  for (int s = 0;; s++) {
    const unsigned par = s & 1;
    const unsigned slot = s & (RING_N - 1), rpar = (s / RING_N) & 1;
    const unsigned ring = sb + R_RING + slot * RING_BYTES;
    asm volatile("" : "+r"(t8), "+r"(pW0), "+r"(r1), "+r"(r2), "+r"(r4));
    RSTAMP(1);
    RSTAMP(2);
    float aq[4] = {0, 0, 0, 0}, ak[4] = {0, 0, 0, 0};
    {
      float aq1[4] = {0, 0, 0, 0}, ak1[4] = {0, 0, 0, 0};
      unsigned b[8][4];
#pragma unroll
      for (int i = 0; i < 4; i++) ldsm_x4_t(b[i], pA + i * 512);
#pragma unroll
      for (int i = 0; i < 8; i++) {
        mma16816(aq, wq[2 * i], b[i][0], b[i][1]); mma16816(ak, wk[2 * i], b[i][0], b[i][1]);
        mma16816(aq1, wq[2 * i + 1], b[i][2], b[i][3]); mma16816(ak1, wk[2 * i + 1], b[i][2], b[i][3]);
        if (i < 4) ldsm_x4_t(b[i + 4], pA + (i + 4) * 512);
      }
#pragma unroll
      for (int i = 0; i < 4; i++) { aq[i] += aq1[i]; ak[i] += ak1[i]; }
    }
    RSTAMP(3);
#define STSF4(a, v) asm volatile("st.shared.v4.f32 [%0], {%1,%2,%3,%4};" ::"r"(a), "f"(v[0]), "f"(v[1]), "f"(v[2]), "f"(v[3]) : "memory")
#define VLD(i) do { ldsm_x4_t(b[i], pA + (i) * 512); ldsm_x4_t(f0[i], pVk + ((i) >> 1) * 8192 + ((i) & 1) * 4096); ldsm_x4_t(f1[i], pVk + ((i) >> 1) * 8192 + ((i) & 1) * 4096 + 2048); } while (0)
#define VPASS() float av[4] = {0, 0, 0, 0}; { float av1[4] = {0, 0, 0, 0}; unsigned b[8][4], f1[8][4], f0[8][4]; VLD(0); if (VD > 1) VLD(1); \
      _Pragma("unroll") for (int i = 0; i < 8; i++) { if (i + VD < 8) VLD(i + VD); \
        mma16816(av, f0[i], b[i][0], b[i][1]); mma16816(av1, f1[i], b[i][2], b[i][3]); } \
      _Pragma("unroll") for (int i = 0; i < 4; i++) av[i] += av1[i]; }
    unsigned f[8][4];
#define WO_LD(i0, i1) do { _Pragma("unroll") for (int i = i0; i < i1; i++) { ldsm_x4_t(f[2 * i], pW0 + 32768 + i * 2048); ldsm_x4_t(f[2 * i + 1], pW1 + 32768 + i * 2048); } } while (0)
    if (kh) {
      STSF4(aX, aq);
      bar_sync(4 + et, 64);
      uint4 o = lds128(aX + 2048);
      stsm_x2_t(aQKst, pack_bf16(ak[0] + __uint_as_float(o.x), ak[1] + __uint_as_float(o.y)), pack_bf16(ak[2] + __uint_as_float(o.z), ak[3] + __uint_as_float(o.w)));
      bar_arrive(1, 256);
      RSTAMP(4);
      RSTAMP(5);
      if (s == NSEG - 1) {
        mbar_wait(bar + 8 * MB_V, par);
        bar_sync(8, 128);
        if (t == 128) mbar_arrive(bar + 8 * MB_KVR);
        break;
      }
      mbar_wait(bar + 8 * (MB_FULL + slot), rpar);
      unsigned vx[4][4];
      ldsm_x4_t(vx[0], ring + oVx); ldsm_x4_t(vx[1], ring + oVx + 2048); ldsm_x4_t(vx[2], ring + (oVx ^ 32)); ldsm_x4_t(vx[3], ring + (oVx ^ 32) + 2048);
      WO_LD(0, NPRE1);
      RSTAMP(6); RSTAMP(7);
      mbar_wait(bar + 8 * MB_S, par);
      RSTAMP(8);
      float sc[10];
#pragma unroll
      for (int i = 0; i < 5; i++) {
        uint2 o = lds64(aL8 + R_SOWN + i * 256), p = lds64(aL8 + R_SPEER + i * 256);
        sc[2 * i] = __uint_as_float(o.x) + __uint_as_float(p.x); sc[2 * i + 1] = __uint_as_float(o.y) + __uint_as_float(p.y);
      }
      float mx = fmaxf(fmaxf(fmaxf(sc[0], sc[1]), fmaxf(sc[2], sc[3])), fmaxf(fmaxf(fmaxf(sc[4], sc[5]), fmaxf(sc[6], sc[7])), fmaxf(sc[8], sc[9])));
      mx = fmaxf(mx, __shfl_xor_sync(~0u, mx, 1)); mx = fmaxf(mx, __shfl_xor_sync(~0u, mx, 2));
      const float nm = -mx * (SCALE_QK * LOG2E);
      unsigned p[5];
#pragma unroll
      for (int i = 0; i < 5; i++) p[i] = pack_bf16(ex2f(fmaf(sc[2 * i], SCALE_QK * LOG2E, nm)), ex2f(fmaf(sc[2 * i + 1], SCALE_QK * LOG2E, nm)));
      RSTAMP(9);
      float o0[4] = {0, 0, 0, 0}, o1[4] = {0, 0, 0, 0}, o3[4] = {0, 0, 0, 0}, o4[4] = {0, 0, 0, 0}, z0[4] = {0, 0, 0, 0}, z1[4] = {0, 0, 0, 0};
      const unsigned ones[4] = {0x3F803F80u, 0u, 0x3F803F80u, 0u};
      mma16816(z0, ones, p[0], p[1]); mma16816(ZS ? z0 : z1, ones, p[2], p[3]);
      mma16816(o0, vx[0], p[0], p[1]); mma16816(o3, vx[2], p[0], p[1]); mma16816(o1, vx[1], p[2], p[3]); mma16816(o4, vx[3], p[2], p[3]);
      mma1688(z0, 0x3F803F80u, 0u, p[4]);
      mbar_wait(bar + 8 * MB_V, par);
      uint2 vm0 = lds64(aVm), vm1 = lds64(aVm + 256);
      mma1688(o0, vm0.x, vm0.y, p[4]); mma1688(o3, vm1.x, vm1.y, p[4]);
      float i0, i1;
      asm("rcp.approx.ftz.f32 %0, %1;" : "=f"(i0) : "f"(z0[0] + z1[0])); asm("rcp.approx.ftz.f32 %0, %1;" : "=f"(i1) : "f"(z0[1] + z1[1]));
      asm volatile("stmatrix.sync.aligned.m8n8.x4.trans.shared.b16 [%0], {%1,%2,%3,%4};" ::"r"(aOst), "r"(pack_bf16((o0[0] + o1[0]) * i0, (o0[1] + o1[1]) * i1)), "r"(pack_bf16((o0[2] + o1[2]) * i0, (o0[3] + o1[3]) * i1)),
                   "r"(pack_bf16((o3[0] + o4[0]) * i0, (o3[1] + o4[1]) * i1)), "r"(pack_bf16((o3[2] + o4[2]) * i0, (o3[3] + o4[3]) * i1)) : "memory");
      RSTAMP(10);
      bar_sync(1, 256);
      WO_LD(NPRE1, 3);
    } else {
      STSF4(aX + 2048, ak);
      unsigned kb[8];
      mbar_wait(bar + 8 * (MB_FULL + slot), rpar);
      ldsm_x4(kb, ring + oKx); ldsm_x4(kb + 4, ring + (oKx ^ 64));
      bar_sync(4 + et, 64);
      uint4 o = lds128(aX);
      stsm_x2_t(aQKst, pack_bf16(aq[0] + __uint_as_float(o.x), aq[1] + __uint_as_float(o.y)), pack_bf16(aq[2] + __uint_as_float(o.z), aq[3] + __uint_as_float(o.w)));
      RSTAMP(4);
      bar_sync(1, 256);
      RSTAMP(5);
      if (s != NSEG - 1) {
        unsigned qa[8], km[8];
        ldsm_x4(qa, aQ); ldsm_x4(qa + 4, aQ + 64);
        if (w == 3) { ldsm_x4(km, aQ + 1152); ldsm_x4(km + 4, aQ + 1152 + 64); }
        float s0[4] = {0, 0, 0, 0}, s1[4] = {0, 0, 0, 0};
        unsigned af[4][4];
#pragma unroll
        for (int i = 0; i < 4; i++) { af[i][0] = qa[2 * i]; af[i][1] = 0; af[i][2] = qa[2 * i + 1]; af[i][3] = 0; }
        mma16816(s0, af[0], kb[0], kb[1]); mma16816(s1, af[1], kb[2], kb[3]);
        mma16816(s0, af[2], kb[4], kb[5]); mma16816(s1, af[3], kb[6], kb[7]);
        if (w == 3) {
          float m0[4] = {0, 0, 0, 0}, m1[4] = {0, 0, 0, 0};
          mma16816(m0, af[0], km[0], km[1]); mma16816(m1, af[1], km[2], km[3]);
          mma16816(m0, af[2], km[4], km[5]); mma16816(m1, af[3], km[6], km[7]);
          unsigned x = __float_as_uint(m0[0] + m1[0]), y = __float_as_uint(m0[1] + m1[1]);
          st_async_b64(aSr + 256, x, y, mbSr); st_async_b64(aSl + 256, x, y, mbSl);
        }
        unsigned x = __float_as_uint(s0[0] + s1[0]), y = __float_as_uint(s0[1] + s1[1]);
        st_async_b64(aSr, x, y, mbSr); st_async_b64(aSl, x, y, mbSl);
      }
      RSTAMP(6);
      RSTAMP(7); RSTAMP(8);
      if (s == NSEG - 1) break;
      WO_LD(0, 3);
      RSTAMP(9); RSTAMP(10);
      bar_sync(1, 256);
    }
    RSTAMP(11);
    float d0[4] = {0, 0, 0, 0}, d1[4] = {0, 0, 0, 0}, e0[4] = {0, 0, 0, 0}, e1[4] = {0, 0, 0, 0};
    unsigned ob[4][4];
    ldsm_x4(ob[0], aOld); ldsm_x4(ob[1], aOld + 64);
    mma16816(d0, wo[0], ob[0][0], ob[0][1]); mma16816(d1, wo[1], ob[0][0], ob[0][1]);
    mma16816(e0, wo[2], ob[0][2], ob[0][3]); mma16816(e1, wo[3], ob[0][2], ob[0][3]);
    ldsm_x4(ob[2], aOld + 128);
    mma16816(d0, wo[4], ob[1][0], ob[1][1]); mma16816(d1, wo[5], ob[1][0], ob[1][1]);
    mma16816(e0, wo[6], ob[1][2], ob[1][3]); mma16816(e1, wo[7], ob[1][2], ob[1][3]);
    ldsm_x4(ob[3], aOld + 192);
    mma16816(d0, f[0], ob[2][0], ob[2][1]); mma16816(d1, f[1], ob[2][0], ob[2][1]);
    WO_LD(3, 4);
    mma16816(e0, f[2], ob[2][2], ob[2][3]); mma16816(e1, f[3], ob[2][2], ob[2][3]);
    const unsigned mbRSr = mapa(bar + 8 * MB_RS, j * 4 + (t8 >> 9));
    mma16816(d0, f[4], ob[3][0], ob[3][1]); mma16816(d1, f[5], ob[3][0], ob[3][1]);
    mma16816(e0, f[6], ob[3][2], ob[3][3]); mma16816(e1, f[7], ob[3][2], ob[3][3]);
    st_async_b64(aRSr, __float_as_uint(d0[0] + e0[0]), __float_as_uint(d0[1] + e0[1]), mbRSr);
    st_async_b64(aRSr + 256, __float_as_uint(d0[2] + e0[2]), __float_as_uint(d0[3] + e0[3]), mbRSr);
    st_async_b64(aRSr + 512, __float_as_uint(d1[0] + e1[0]), __float_as_uint(d1[1] + e1[1]), mbRSr);
    st_async_b64(aRSr + 768, __float_as_uint(d1[2] + e1[2]), __float_as_uint(d1[3] + e1[3]), mbRSr);
    RSTAMP(12);
    if (t == 128) {
      mbar_arrive(bar + 8 * (MB_EMPTY + slot)); mbar_arrive(bar + 8 * MB_KVR);
      mbar_expect_tx(bar + 8 * MB_S, 2560); mbar_expect_tx(bar + 8 * MB_V, 2048);
    }
    const unsigned tag = ((s >> 1) & 1) ^ 1;
    const char* gp = reinterpret_cast<const char*>(g_part);
    const unsigned goff = (par * 8 + rk) * 16384 + cl * 2048 + t8;
    unsigned mbA[8];
#pragma unroll
    for (int i = 0; i < 8; i++) if (!MBL) mbA[i] = mapa(bar + 8 * MB_AG, i);
    const unsigned dlt = (R_MEM + rk * 1024) - (SM_BAR + 8 * MB_AG) + (t8 >> 1);
    mbar_wait(bar + 8 * MB_RS, par);
    RSTAMP(13);
    uint2 a[8];
    {
      uint2 x0 = lds64(sb + R_RS + t8), x1 = lds64(sb + R_RS + 2048 + t8), x2 = lds64(sb + R_RS + 4096 + t8), x3 = lds64(sb + R_RS + 6144 + t8);
      float q0 = (__uint_as_float(x0.x) + __uint_as_float(x1.x)) + (__uint_as_float(x2.x) + __uint_as_float(x3.x));
      float q1 = (__uint_as_float(x0.y) + __uint_as_float(x1.y)) + (__uint_as_float(x2.y) + __uint_as_float(x3.y));
      a[0].x = (__float_as_uint(q0) & ~1u) | tag; a[0].y = (__float_as_uint(q1) & ~1u) | tag;
      asm volatile("st.relaxed.gpu.global.v2.u32 [%0], {%1,%2};" ::"l"(gp + goff), "r"(a[0].x), "r"(a[0].y) : "memory");
    }
    RSTAMP(14);
    if (t == 128) mbar_expect_tx(bar + 8 * MB_RS, 8192);
    {
      unsigned it = 0;
#define PLOAD(a) _Pragma("unroll") for (int i = 1; i < 8; i++) a[i] = ldv2_relaxed(gp + (goff ^ (i * 2048)))
#define PAND(a) (((a[1].x & a[1].y) & (a[2].x & a[2].y) & (a[3].x & a[3].y)) & ((a[4].x & a[4].y) & (a[5].x & a[5].y)) & ((a[6].x & a[6].y) & (a[7].x & a[7].y)))
#define POR(a) (((a[1].x | a[1].y) | (a[2].x | a[2].y) | (a[3].x | a[3].y)) | ((a[4].x | a[4].y) | (a[5].x | a[5].y)) | ((a[6].x | a[6].y) | (a[7].x | a[7].y)))
#define POK(a) (((tag ? PAND(a) : ~POR(a)) & 1u) != 0)
      if (D_RED) DELAY(D_RED);
      while (true) { PLOAD(a); if (POK(a)) break; if (D_PUB) DELAY(D_PUB); spin_check(it); }
    }
    RSTAMP(15);
    {
#define AF(i, c) __uint_as_float(a[i].c)
      unsigned u = pack_bf16(((AF(0, x) + AF(1, x)) + (AF(2, x) + AF(3, x))) + ((AF(4, x) + AF(5, x)) + (AF(6, x) + AF(7, x))),
                             ((AF(0, y) + AF(1, y)) + (AF(2, y) + AF(3, y))) + ((AF(4, y) + AF(5, y)) + (AF(6, y) + AF(7, y))));
      __syncwarp();
#pragma unroll
      for (int i = 0; i < 8; i++) { if (MBL) mbA[i] = mapa(bar + 8 * MB_AG, i); st_async_b32(mbA[i] + dlt, u, mbA[i]); }
    }
    mbar_wait(bar + 8 * MB_KVF, par);
    mbar_wait(bar + 8 * MB_AG, par);
    if (t == 128) mbar_expect_tx(bar + 8 * MB_AG, 8192);
  }
}

__device__ __forceinline__ void rec_aux(const Maps& maps, unsigned sb) {
  const int c = blockIdx.x, h = c >> 1, j = c & 1;
  const unsigned bar = sb + SM_BAR;
  const int lane = threadIdx.x & 31, w = (threadIdx.x >> 5) & 3;
  if (w == 0) {
    if (lane == 0) {
      mbar_expect_tx(bar + 8 * MB_W0, 131072);
      for (int kb = 0; kb < 8; kb++) tma_load_2d(sb + R_WO + kb * 8192, &maps.wq, h * 128 + j * 64, kb * 64, bar + 8 * MB_W0);
      for (int kb = 0; kb < 8; kb++) tma_load_2d(sb + R_T1 + kb * 8192, &maps.wk, h * 128 + j * 64, kb * 64, bar + 8 * MB_W0);
      mbar_expect_tx(bar + 8 * MB_W1, 65536);
      for (int kb = 0; kb < 8; kb++) tma_load_2d(sb + R_T2 + kb * 8192, &maps.wv, h * 128 + j * 64, kb * 64, bar + 8 * MB_W1);
    }
    __syncwarp();
    bar_sync(2, 288);
    fence_proxy_async_smem();
  }
  mbar_wait(bar + 8 * MB_W1, 0);
  const unsigned aVr = mapa(sb + R_VM + (j * 4 + w) * 256 + lane * 8, (c & 7) ^ 1), mbVr = mapa(bar + 8 * MB_V, (c & 7) ^ 1), mbVl = mapa(bar + 8 * MB_V, c & 7);
  const uint64_t ad = mkdesc(sb + R_T2, 8192, 1024), bd = (uint64_t)(((sb + R_MEM) >> 4) & 0x3fff) | (8ull << 16) | (8ull << 32);
  int nf = 0;
#pragma unroll 1
  for (int s = 0; s < NSEG; s++) {
    if (s == 0) bar_sync(3, 384);
    else { mbar_wait(bar + 8 * MB_KVF, (s - 1) & 1); mbar_wait(bar + 8 * MB_AG, (s - 1) & 1); }
    if (D_V) DELAY(D_V);
    float av[4];
    asm volatile("wgmma.fence.sync.aligned;" ::: "memory");
    asm volatile("wgmma.mma_async.sync.aligned.m64n8k16.f32.bf16.bf16 {%0,%1,%2,%3}, %4, %5, 0, 1, 1, 1, 1;"
                 : "=f"(av[0]), "=f"(av[1]), "=f"(av[2]), "=f"(av[3]) : "l"(ad), "l"(bd));
#pragma unroll
    for (int i = 1; i < 32; i++)
      asm volatile("wgmma.mma_async.sync.aligned.m64n8k16.f32.bf16.bf16 {%0,%1,%2,%3}, %4, %5, 1, 1, 1, 1, 1;"
                   : "+f"(av[0]), "+f"(av[1]), "+f"(av[2]), "+f"(av[3]) : "l"(ad + i * 128), "l"(bd + i * 16));
    asm volatile("wgmma.commit_group.sync.aligned;" ::: "memory");
    asm volatile("wgmma.wait_group.sync.aligned 0;" : "+f"(av[0]), "+f"(av[1]), "+f"(av[2]), "+f"(av[3])::"memory");
    {
      unsigned x = pack_bf16(av[0], av[1]), y = pack_bf16(av[2], av[3]);
      st_async_b64(aVr, x, y, mbVr);
      st_async_b64(aVr + (mbVl - mbVr), x, y, mbVl);
    }
    if (w == 0) {
      if (lane == 0) {
        for (; nf < s + RING_N && nf < NSEG; nf++) {
          unsigned slot = nf & (RING_N - 1);
          if ((nf & 3) == 0 && !DBGMODE) {
            wait_flag_ge(&g_flags.qkv[(nf >> 2) * 48 + 16 + (h >> 1)], 1);
            wait_flag_ge(&g_flags.qkv[(nf >> 2) * 48 + 32 + (h >> 1)], 1);
            fence_proxy_async();
          }
          if (nf >= RING_N) mbar_wait(bar + 8 * (MB_EMPTY + slot), ((nf / RING_N) - 1) & 1);
          unsigned dst = sb + R_RING + slot * RING_BYTES, mb = bar + 8 * (MB_FULL + slot);
          mbar_expect_tx(mb, RING_BYTES);
          tma_load_2d(dst, &maps.qkv_ld, HD + h * 128 + j * 64, nf * SEG, mb);
          tma_load_2d(dst + 4096, &maps.qkv_ld, 2 * HD + h * 128, nf * SEG, mb);
          tma_load_2d(dst + 8192, &maps.qkv_ld, 2 * HD + h * 128 + 64, nf * SEG, mb);
        }
      }
      __syncwarp();
    } else if (w == 1) {
      mbar_wait(bar + 8 * MB_KVR, s & 1);
      uint4 k0 = lds128(sb + R_KS + (lane >> 3) * 144 + (lane & 7) * 16), k1 = lds128(sb + R_KS + (4 + (lane >> 3)) * 144 + (lane & 7) * 16);
      uint2 v[4];
#pragma unroll
      for (int i = 0; i < 4; i++) v[i] = lds64(sb + R_VM + (j * 4 + i) * 256 + lane * 8);
      __syncwarp();
      if (lane == 0) mbar_arrive(bar + 8 * MB_KVF);
      bf16* kd = g_km + ((size_t)(s * NH + h) * NMEM) * DH + j * 64;
      *reinterpret_cast<uint4*>(kd + (lane >> 3) * DH + (lane & 7) * 8) = k0;
      *reinterpret_cast<uint4*>(kd + (4 + (lane >> 3)) * DH + (lane & 7) * 8) = k1;
      unsigned* vd = reinterpret_cast<unsigned*>(g_vmt) + ((size_t)(s * NH + h) * DH + j * 64) * 4;
#pragma unroll
      for (int i = 0; i < 4; i++) { vd[(i * 16) * 4 + lane] = v[i].x; vd[(i * 16 + 8) * 4 + lane] = v[i].y; }
      __syncwarp();
      if (lane == 0) st_release(&g_flags.rec[c], s + 1);
    }
  }
}

__device__ __forceinline__ void bulk_producer(const Maps& maps, unsigned sb, int* misc) {
  const unsigned bar = sb + SM_BAR;
  const int lane = threadIdx.x & 31;
  unsigned st = 0, ph = 0, seq = 0;
  while (true) {
    int idx = 0;
    if (lane == 0) idx = (int)atomicAdd(&g_flags.ctr, 1u);
    idx = __shfl_sync(~0u, idx, 0);
    if (idx >= N_ITEMS) {
      if (lane == 0) {
        mbar_wait(bar + 8 * (MB_EMPTY + st), ph ^ 1);
        misc[seq & 3] = -1;
        mbar_arrive(bar + 8 * (MB_FULL + st));
      }
      break;
    }
    if (lane == 0) ISTAMP(idx, 0);
    Item it = decode_item(idx);
    if (it.b < 0) continue;
    const CUtensorMap* mp; int c0, c1, dc0, dc1; unsigned doff;
    const unsigned* fl = nullptr; unsigned tgt = 1; int nbox = 5, rdy = 0;
    if (it.type == T_ATT) {
      mp = &maps.qkv_ld; nbox = 12; doff = lane * 4096;
      c0 = (lane >> 2) * HD + it.c * 256 + (lane & 1) * 64; c1 = it.b * 128 + ((lane >> 1) & 1) * 32; dc0 = dc1 = 0;
      if (lane < 3) fl = &g_flags.qkv[it.b * 48 + lane * 16 + it.c];
      bool ok = true;
      if (lane >= 4 && lane < 8) ok = ld_acquire(&g_flags.rec[it.c * 4 + lane - 4]) >= (unsigned)(it.b * 4 + 4);
      rdy = __all_sync(~0u, ok) ? 65536 : 0;
    } else {
      int k0 = 0, nb0 = it.c * 256;
      if (it.type == T_QKV) { mp = lane == 0 ? &maps.xn : (it.c < 16 ? &maps.wq : (it.c < 32 ? &maps.wk : &maps.wv)); nb0 = (it.c & 15) * 256; }
      else if (it.type == T_M1) mp = lane == 0 ? &maps.y : &maps.w1;
      else if (it.type == T_M2) { mp = lane == 0 ? &maps.h1 : &maps.w2; fl = &g_flags.h1[it.b]; tgt = 7; }
      else {
        mp = lane == 0 ? &maps.o : &maps.wo;
        if (it.type == T_OUT) { k0 = it.ks * 1024; fl = &g_flags.o[it.b * 4 + it.ks]; tgt = 4; }
        else if (it.type == T_OUTL) { k0 = it.ks * 256; fl = &g_flags.o16[it.ks]; }
        else if (lane == 1) { fl = &g_flags.g[it.b]; tgt = 2; }
        else { fl = &g_flags.p[it.b]; tgt = it.type == T_RED ? 8 : 32; }
      }
      if (lane > (it.type >= T_RED ? 1 : 0)) fl = nullptr;
      if (lane == 0) { c0 = k0; c1 = it.b * 128; dc0 = 64; dc1 = 0; doff = 0; }
      else { c0 = nb0 + (lane - 1) * 64; c1 = k0; dc0 = 0; dc1 = 64; doff = 8192 + lane * 8192; }
    }
    if (fl) wait_flag_ge(fl, tgt);
    __syncwarp();
    fence_proxy_async();
    if (lane == 0) ISTAMP(idx, 1);
    const int nkb = item_nkb(it.type);
    for (int kb = 0; kb < nkb; kb++) {
      const unsigned mb = bar + 8 * (MB_FULL + st);
      mbar_wait(bar + 8 * (MB_EMPTY + st), ph ^ 1);
      if (lane == 0) {
        if (kb == 0) misc[seq & 3] = idx | rdy;
        if (it.type >= T_RED) mbar_arrive(mb); else mbar_expect_tx(mb, STAGE_BYTES);
      }
      if (it.type == T_ATT) { if (lane < 12) tma_load_2d(sb + st * STAGE_BYTES + doff, mp, c0 + (kb & 1) * 128, c1 + (kb >> 1) * 64, mb); }
      else if (lane < nbox && it.type < T_RED) tma_load_2d(sb + st * STAGE_BYTES + doff, mp, c0 + kb * dc0, c1 + kb * dc1, mb);
      __syncwarp();
      if (++st == NSTAGE) { st = 0; ph ^= 1; }
    }
    seq++;
  }
}
__device__ __forceinline__ void bulk_store(const Maps& maps, unsigned sb, volatile int* misc) {
  const unsigned bar = sb + SM_BAR;
  unsigned ph = 0;
  while (true) {
    mbar_wait(bar + 8 * MB_STGF, ph); ph ^= 1;
    int idx = misc[4];
    if (idx < 0) break;
    Item it = decode_item(idx);
    const CUtensorMap* mp = it.type == T_QKV ? &maps.qkv_st : (it.type == T_M1 ? &maps.h1 : (it.type == T_M2 ? &maps.g : &maps.o));
    unsigned* flag = it.type == T_QKV ? &g_flags.qkv[it.b * 48 + it.c] : (it.type == T_M1 ? &g_flags.h1[it.b] : (it.type == T_M2 ? &g_flags.g[it.b] : (it.b == 15 ? &g_flags.o16[it.c] : &g_flags.o[it.b * 4 + (it.c >> 2)])));
    for (int i = 0; i < 4; i++) tma_store_2d(mp, sb + B_STG + i * 16384, it.c * 256 + i * 64, it.b * 128);
    asm volatile("cp.async.bulk.commit_group;" ::: "memory");
    asm volatile("cp.async.bulk.wait_group.read 0;" ::: "memory");
    mbar_arrive(bar + 8 * MB_STGE);
    asm volatile("cp.async.bulk.wait_group 0;" ::: "memory");
    fence_proxy_async();
    red_release_add(flag, 1);
    ISTAMP(idx, 3);
  }
}
__device__ __forceinline__ float rcpf(float x) { float y; asm("rcp.approx.ftz.f32 %0, %1;" : "=f"(y) : "f"(x)); return y; }
__device__ __forceinline__ float gelu_t(float x) {
  float e = ex2f(x * fmaf(x * x, -2.0f * LOG2E * 0.7978845608028654f * 0.044715f, -2.0f * LOG2E * 0.7978845608028654f));
  return x * rcpf(1.0f + e);
}
__device__ __forceinline__ float silu_f(float x) { return x * rcpf(1.0f + ex2f(-LOG2E * x)); }
__device__ __forceinline__ unsigned badd2(unsigned a, unsigned b) { unsigned r; asm("add.rn.bf16x2 %0, %1, %2;" : "=r"(r) : "r"(a), "r"(b)); return r; }

__device__ __forceinline__ void final_out(bf16* __restrict__ out, const bf16* __restrict__ x, size_t o, float4 s) {
  uint2 gv = __ldcg(reinterpret_cast<const uint2*>(g_g + o)), xv = __ldg(reinterpret_cast<const uint2*>(x + o));
  uint2 r;
  r.x = pack_bf16(bf_lo(xv.x) + bf16r(bf16r(s.x) * bf_lo(gv.x)), bf_hi(xv.x) + bf16r(bf16r(s.y) * bf_hi(gv.x)));
  r.y = pack_bf16(bf_lo(xv.y) + bf16r(bf16r(s.z) * bf_lo(gv.y)), bf_hi(xv.y) + bf16r(bf16r(s.w) * bf_hi(gv.y)));
  *reinterpret_cast<uint2*>(out + o) = r;
}
__device__ __forceinline__ void bulk_att_load(unsigned* km, unsigned* vm, int b, int hp, int kb, int w, int lane) {
  const int g = lane >> 2, tq = lane & 3, seg = w >> 2, eh = w & 1;
  const int head = hp * 2 + (kb & 1), sg = b * 4 + (kb >> 1) * 2 + seg;
  const unsigned* kmp = reinterpret_cast<const unsigned*>(g_km + ((size_t)(sg * NH + head) * NMEM + g) * DH) + tq;
  const unsigned* vmp = reinterpret_cast<const unsigned*>(g_vmt) + ((size_t)(sg * NH + head) * DH + eh * 64) * 4 + lane;
#pragma unroll
  for (int i = 0; i < 16; i++) asm volatile("ld.global.cg.u32 %0, [%1];" : "=r"(km[i]) : "l"(kmp + i * 4) : "memory");
#pragma unroll
  for (int i = 0; i < 8; i++) asm volatile("ld.global.cg.u32 %0, [%1];" : "=r"(vm[i]) : "l"(vmp + i * 32) : "memory");
}
__device__ __forceinline__ void bulk_att_stage(unsigned sa, unsigned stg, const unsigned* km, const unsigned* vm, int kb, int w, int lane) {
  const int g = lane >> 2, tq = lane & 3, m = lane >> 3, r8 = lane & 7;
  const int seg = w >> 2, mt = (w >> 1) & 1, eh = w & 1;
  float s[5][4];
#pragma unroll
  for (int i = 0; i < 5; i++) { s[i][0] = s[i][1] = s[i][2] = s[i][3] = 0; }
  const unsigned qb = sa + (0 * 2 + seg) * 8192, kbs = sa + (1 * 2 + seg) * 8192, vb = sa + (2 * 2 + seg) * 8192 + eh * 4096;
  unsigned qa[8][4];
#pragma unroll
  for (int ks = 0; ks < 8; ks++) {
    int row = mt * 16 + (m & 1) * 8 + r8;
    ldsm_x4(qa[ks], qb + (ks >> 2) * 4096 + row * 128 + ((((ks & 3) * 2 + (m >> 1)) ^ r8) << 4));
    unsigned kf[4];
    int krow = (m >> 1) * 8 + r8;
    unsigned ka = kbs + (ks >> 2) * 4096 + krow * 128 + ((((ks & 3) * 2 + (m & 1)) ^ r8) << 4);
    ldsm_x4(kf, ka);
    mma16816(s[0], qa[ks], kf[0], kf[1]); mma16816(s[1], qa[ks], kf[2], kf[3]);
    if (mt) { ldsm_x4(kf, ka + 2048); mma16816(s[2], qa[ks], kf[0], kf[1]); mma16816(s[3], qa[ks], kf[2], kf[3]); }
  }
#pragma unroll
  for (int ks = 0; ks < 8; ks++) mma16816(s[4], qa[ks], km[2 * ks], km[2 * ks + 1]);
  float mx0 = -INFINITY, mx1 = -INFINITY;
  const int t0 = mt * 16 + g, t1 = t0 + 8;
#pragma unroll
  for (int i = 0; i < 5; i++) {
#pragma unroll
    for (int e = 0; e < 4; e++) {
      float v = s[i][e];
      if (i < 4) { int kj = i * 8 + 2 * tq + (e & 1); if (kj > (e < 2 ? t0 : t1)) v = -INFINITY; }
      s[i][e] = v;
      if (e < 2) mx0 = fmaxf(mx0, v); else mx1 = fmaxf(mx1, v);
    }
  }
  mx0 = fmaxf(mx0, __shfl_xor_sync(~0u, mx0, 1)); mx0 = fmaxf(mx0, __shfl_xor_sync(~0u, mx0, 2));
  mx1 = fmaxf(mx1, __shfl_xor_sync(~0u, mx1, 1)); mx1 = fmaxf(mx1, __shfl_xor_sync(~0u, mx1, 2));
  float sm0 = 0, sm1 = 0;
#pragma unroll
  for (int i = 0; i < 5; i++) {
    s[i][0] = ex2f((s[i][0] - mx0) * (SCALE_QK * LOG2E)); s[i][1] = ex2f((s[i][1] - mx0) * (SCALE_QK * LOG2E));
    s[i][2] = ex2f((s[i][2] - mx1) * (SCALE_QK * LOG2E)); s[i][3] = ex2f((s[i][3] - mx1) * (SCALE_QK * LOG2E));
    sm0 += s[i][0] + s[i][1]; sm1 += s[i][2] + s[i][3];
  }
  sm0 += __shfl_xor_sync(~0u, sm0, 1); sm0 += __shfl_xor_sync(~0u, sm0, 2);
  sm1 += __shfl_xor_sync(~0u, sm1, 1); sm1 += __shfl_xor_sync(~0u, sm1, 2);
  const float i0 = __fdividef(1.0f, sm0), i1 = __fdividef(1.0f, sm1);
  unsigned pa[2][4], pm0, pm1;
#pragma unroll
  for (int kk = 0; kk < 2; kk++) {
    pa[kk][0] = pack_bf16(s[2 * kk][0] * i0, s[2 * kk][1] * i0); pa[kk][1] = pack_bf16(s[2 * kk][2] * i1, s[2 * kk][3] * i1);
    pa[kk][2] = pack_bf16(s[2 * kk + 1][0] * i0, s[2 * kk + 1][1] * i0); pa[kk][3] = pack_bf16(s[2 * kk + 1][2] * i1, s[2 * kk + 1][3] * i1);
  }
  pm0 = pack_bf16(s[4][0] * i0, s[4][1] * i0); pm1 = pack_bf16(s[4][2] * i1, s[4][3] * i1);
  const int orow = (kb >> 1) * 64 + seg * 32 + mt * 16 + (m & 1) * 8 + r8;
  const unsigned ob = stg + ((kb & 1) * 2 + eh) * 16384 + orow * 128;
#pragma unroll
  for (int cp = 0; cp < 4; cp++) {
    float o0[4] = {0, 0, 0, 0}, o1[4] = {0, 0, 0, 0};
    mma1688(o0, pm0, pm1, vm[2 * cp]); mma1688(o1, pm0, pm1, vm[2 * cp + 1]);
    unsigned vf[4];
    int row = (m & 1) * 8 + r8;
    unsigned va = vb + row * 128 + (((cp * 2 + (m >> 1)) ^ r8) << 4);
    ldsm_x4_t(vf, va);
    mma16816(o0, pa[0], vf[0], vf[1]); mma16816(o1, pa[0], vf[2], vf[3]);
    if (mt) { ldsm_x4_t(vf, va + 2048); mma16816(o0, pa[1], vf[0], vf[1]); mma16816(o1, pa[1], vf[2], vf[3]); }
    stsm_x4(ob + (((cp * 2 + (m >> 1)) ^ r8) << 4), pack_bf16(o0[0], o0[1]), pack_bf16(o0[2], o0[3]), pack_bf16(o1[0], o1[1]), pack_bf16(o1[2], o1[3]));
  }
}

__device__ __forceinline__ void bulk_worker(unsigned sb, volatile int* misc, const bf16* __restrict__ x, const bf16* __restrict__ b1, const bf16* __restrict__ b2, bf16* __restrict__ out) {
  const int t = threadIdx.x, lane = t & 31, w = t >> 5, wg = w >> 2, g = lane >> 2, tq = lane & 3, m = lane >> 3, r8 = lane & 7;
  const unsigned bar = sb + SM_BAR;
  unsigned st = 0, ph = 0, seq = 0, sph = 0;
  float d[128];
  while (true) {
    mbar_wait(bar + 8 * (MB_FULL + st), ph);
    const int idr = misc[seq & 3]; seq++;
    const int idx = idr & 65535;
    if (idr < 0 || idx >= N_ITEMS) break;
    if (t == 0) ISTAMP(idx, 2);
    const Item it = decode_item(idx);
    const int nkb = item_nkb(it.type);
    if (it.type == T_ATT) {
      unsigned km[16], vm[8], kn[16], vn[8];
      const bool pref = idr >= 65536;
      if (pref) bulk_att_load(kn, vn, it.b, it.c, 0, w, lane);
      mbar_wait(bar + 8 * MB_STGE, sph ^ 1);
#pragma unroll 1
      for (int kb = 0; kb < 4; kb++) {
        if (!pref) {
          if (lane < 2) wait_flag_ge(&g_flags.rec[it.c * 4 + (kb & 1) * 2 + lane], it.b * 4 + (kb >> 1) * 2 + wg + 1);
          __syncwarp();
          bulk_att_load(kn, vn, it.b, it.c, kb, w, lane);
        }
        if (kb) mbar_wait(bar + 8 * (MB_FULL + st), ph);
#pragma unroll
        for (int i = 0; i < 16; i++) km[i] = kn[i];
#pragma unroll
        for (int i = 0; i < 8; i++) vm[i] = vn[i];
        if (pref && kb != 3) bulk_att_load(kn, vn, it.b, it.c, kb + 1, w, lane);
        bulk_att_stage(sb + st * STAGE_BYTES, sb + B_STG, km, vm, kb, w, lane);
        __syncwarp();
        if (lane == 0) mbar_arrive(bar + 8 * (MB_EMPTY + st));
        if (++st == NSTAGE) { st = 0; ph ^= 1; }
      }
      if (t == 0) misc[4] = idx;
      fence_proxy_async_smem();
      mbar_arrive(bar + 8 * MB_STGF); sph ^= 1;
      continue;
    }
    if (it.type >= T_RED) {
      __syncwarp();
      if (lane == 0) mbar_arrive(bar + 8 * (MB_EMPTY + st));
      if (++st == NSTAGE) { st = 0; ph ^= 1; }
      if (it.type == T_RED) {
#pragma unroll 2
        for (int i = 0; i < 8; i++) {
          size_t o = ((size_t)it.b * 128 + it.c * 16 + i * 2 + (t >> 7)) * DM + (t & 127) * 4;
          float4 a = __ldcg(reinterpret_cast<const float4*>(g_opart + o)), b = __ldcg(reinterpret_cast<const float4*>(g_opart + o + (size_t)S_TOK * DM));
          float4 c = __ldcg(reinterpret_cast<const float4*>(g_opart + o + (size_t)2 * S_TOK * DM)), e = __ldcg(reinterpret_cast<const float4*>(g_opart + o + (size_t)3 * S_TOK * DM));
          final_out(out, x, o, make_float4((a.x + b.x) + (c.x + e.x), (a.y + b.y) + (c.y + e.y), (a.z + b.z) + (c.z + e.z), (a.w + b.w) + (c.w + e.w)));
        }
      } else {
        size_t ol = ((size_t)it.c * 2 + (t >> 7)) * DM + (t & 127) * 4;
        float4 v[16];
#pragma unroll
        for (int i = 0; i < 16; i++) v[i] = __ldcg(reinterpret_cast<const float4*>(g_opl + ol + (size_t)i * 128 * DM));
#pragma unroll
        for (int st2 = 1; st2 < 16; st2 <<= 1)
#pragma unroll
          for (int i = 0; i < 16; i += 2 * st2) { v[i].x += v[i + st2].x; v[i].y += v[i + st2].y; v[i].z += v[i + st2].z; v[i].w += v[i + st2].w; }
        final_out(out, x, ol + (size_t)15 * 128 * DM, v[0]);
      }
      if (t == 0) ISTAMP(idx, 3);
      continue;
    }
    unsigned pst = 0, bv[32];
#pragma unroll
    for (int i = 0; i < 128; i++) d[i] = 0.0f;
    if (it.type == T_M1 || it.type == T_M2) {
      const unsigned* bp = reinterpret_cast<const unsigned*>((it.type == T_M1 ? b1 : b2) + it.c * 256) + tq;
#pragma unroll
      for (int i = 0; i < 32; i++) asm volatile("ld.global.nc.u32 %0, [%1];" : "=r"(bv[i]) : "l"(bp + i * 4));
    } else {
#pragma unroll
      for (int i = 0; i < 32; i++) bv[i] = 0;
    }
    for (int kb = 0; kb < nkb; kb++) {
      if (kb) mbar_wait(bar + 8 * (MB_FULL + st), ph);
      unsigned sa = sb + st * STAGE_BYTES;
      uint64_t ad = mkdesc(sa + wg * 8192, 16, 1024), bd = mkdesc(sa + 16384, 8192, 1024);
      asm volatile("wgmma.fence.sync.aligned;" ::: "memory");
#pragma unroll
      for (int k = 0; k < 4; k++) wgmma_n256(d, ad + k * 2, bd + k * 128, (kb | k) != 0);
      asm volatile("wgmma.commit_group.sync.aligned;" ::: "memory");
      if (kb) {
        asm volatile("wgmma.wait_group.sync.aligned 1;" ::: "memory");
        if (lane == 0) mbar_arrive(bar + 8 * (MB_EMPTY + pst));
      }
      pst = st;
      if (++st == NSTAGE) { st = 0; ph ^= 1; }
    }
    asm volatile("wgmma.wait_group.sync.aligned 0;" ::: "memory");
    if (lane == 0) mbar_arrive(bar + 8 * (MB_EMPTY + pst));
    if (it.type >= T_OUT) {
      const int col = it.c * 256 + 2 * tq;
      float* pp = it.type == T_OUT ? g_opart + ((size_t)it.ks * S_TOK + it.b * 128 + w * 16 + g) * DM + col : g_opl + ((size_t)it.ks * 128 + w * 16 + g) * DM + col;
#pragma unroll
      for (int i = 0; i < 32; i++) {
        __stcg(reinterpret_cast<float2*>(pp + i * 8), make_float2(d[4 * i], d[4 * i + 1]));
        __stcg(reinterpret_cast<float2*>(pp + 8 * DM + i * 8), make_float2(d[4 * i + 2], d[4 * i + 3]));
      }
      bar_sync(1, 256);
      if (t == 0) { red_release_add(&g_flags.p[it.b], 1); ISTAMP(idx, 3); }
      continue;
    }
#define ACT(F) _Pragma("unroll") for (int i = 0; i < 32; i++) { \
        unsigned u0 = badd2(pack_bf16(d[4 * i], d[4 * i + 1]), bv[i]), u1 = badd2(pack_bf16(d[4 * i + 2], d[4 * i + 3]), bv[i]); \
        d[4 * i] = F(bf_lo(u0)); d[4 * i + 1] = F(bf_hi(u0)); d[4 * i + 2] = F(bf_lo(u1)); d[4 * i + 3] = F(bf_hi(u1)); }
    if (it.type == T_M1) { ACT(gelu_t) } else if (it.type == T_M2) { ACT(silu_f) }
    mbar_wait(bar + 8 * MB_STGE, sph ^ 1);
    {
      const unsigned ob = sb + B_STG + (w * 16 + (m & 1) * 8 + r8) * 128;
#pragma unroll
      for (int i = 0; i < 16; i++)
        stsm_x4(ob + (i >> 2) * 16384 + ((((i & 3) * 2 + (m >> 1)) ^ r8) << 4), pack_bf16(d[8 * i], d[8 * i + 1]), pack_bf16(d[8 * i + 2], d[8 * i + 3]),
                pack_bf16(d[8 * i + 4], d[8 * i + 5]), pack_bf16(d[8 * i + 6], d[8 * i + 7]));
    }
    if (t == 0) misc[4] = idx;
    fence_proxy_async_smem();
    mbar_arrive(bar + 8 * MB_STGF); sph ^= 1;
  }
  mbar_wait(bar + 8 * MB_STGE, sph ^ 1);
  if (t == 0) misc[4] = -1;
  mbar_arrive(bar + 8 * MB_STGF);
}

__global__ void __launch_bounds__(384, 1)
k_main(const __grid_constant__ Maps maps, const bf16* __restrict__ x, const bf16* __restrict__ mem0, const bf16* __restrict__ b1, const bf16* __restrict__ b2, bf16* __restrict__ out, int helper) {
  extern __shared__ unsigned char smem_raw[];
  const unsigned sraw = smem_u32(smem_raw);
  const unsigned sb = (sraw + 1023u) & ~1023u;
  int* misc = reinterpret_cast<int*>(smem_raw + (sb - sraw) + SM_MISC);
  const int w = threadIdx.x >> 5;
  const bool rec = !helper && blockIdx.x < NREC;
  if (!helper) asm volatile("griddepcontrol.launch_dependents;");
  if (threadIdx.x == 0) {
    const unsigned bar = sb + SM_BAR;
    for (int i = 0; i < 8; i++) { mbar_init(bar + 8 * (MB_FULL + i), 1); mbar_init(bar + 8 * (MB_EMPTY + i), rec ? 1 : 8); }
    mbar_init(bar + 8 * MB_STGF, 256); mbar_init(bar + 8 * MB_STGE, 1);
    for (int i = MB_W0; i <= MB_AG; i++) mbar_init(bar + 8 * i, 1);
    if (rec) { mbar_expect_tx(bar + 8 * MB_S, 2560); mbar_expect_tx(bar + 8 * MB_V, 2048); mbar_expect_tx(bar + 8 * MB_RS, 8192); mbar_expect_tx(bar + 8 * MB_AG, 8192); }
    asm volatile("fence.mbarrier_init.release.cluster;" ::: "memory");
  }
  __syncthreads();
  asm volatile("barrier.cluster.arrive.release.aligned;\nbarrier.cluster.wait.acquire.aligned;" ::: "memory");
  if (DBGMODE && !rec) { if (helper) asm volatile("griddepcontrol.wait;" ::: "memory"); return; }
  if (w >= 8) {
    asm volatile("setmaxnreg.dec.sync.aligned.u32 24;");
    if (rec) rec_aux(maps, sb);
    else if (w == 8) bulk_producer(maps, sb, misc);
    else if ((threadIdx.x & 31) == 0) { if (w == 9) bulk_store(maps, sb, misc);
      else if (w == 10 && helper) asm volatile("griddepcontrol.wait;" ::: "memory"); }
  } else {
    if (rec) { asm volatile("setmaxnreg.inc.sync.aligned.u32 240;"); rec_worker(maps, sb, mem0); }
    else { asm volatile("setmaxnreg.inc.sync.aligned.u32 240;"); bulk_worker(sb, misc, x, b1, b2, out); }
  }
}

typedef CUresult (*EncFn)(CUtensorMap*, CUtensorMapDataType, cuuint32_t, void*, const cuuint64_t*, const cuuint64_t*, const cuuint32_t*, const cuuint32_t*,
                          CUtensorMapInterleave, CUtensorMapSwizzle, CUtensorMapL2promotion, CUtensorMapFloatOOBfill);
static void mk_map(EncFn enc, CUtensorMap* m, const void* ptr, uint64_t rows, uint64_t cols, uint32_t box_rows) {
  cuuint64_t dims[2] = {cols, rows}; cuuint64_t strides[1] = {cols * 2};
  cuuint32_t box[2] = {64, box_rows}, es[2] = {1, 1};
  enc(m, CU_TENSOR_MAP_DATA_TYPE_BFLOAT16, 2, const_cast<void*>(ptr), dims, strides, box, es, CU_TENSOR_MAP_INTERLEAVE_NONE, CU_TENSOR_MAP_SWIZZLE_128B,
      CU_TENSOR_MAP_L2_PROMOTION_L2_256B, CU_TENSOR_MAP_FLOAT_OOB_FILL_NONE);
}
extern "C" void kernel_launch(void* const* d_in, const int* in_sizes, int n_in, void* d_out, int out_size) {
  static EncFn enc = nullptr;
  static int ncl = 0, nhelp = 0;
  static void *p_xn, *p_y, *p_h1, *p_o, *p_qkv, *p_g;
  if (!enc) {
    void* fn = nullptr; cudaDriverEntryPointQueryResult qr;
    cudaGetDriverEntryPoint("cuTensorMapEncodeTiled", &fn, cudaEnableDefault, &qr);
    enc = (EncFn)fn;
    cudaGetSymbolAddress(&p_xn, g_xn); cudaGetSymbolAddress(&p_y, g_y); cudaGetSymbolAddress(&p_h1, g_h1);
    cudaGetSymbolAddress(&p_o, g_o); cudaGetSymbolAddress(&p_qkv, g_qkv); cudaGetSymbolAddress(&p_g, g_g);
    cudaFuncSetAttribute(k_main, cudaFuncAttributeMaxDynamicSharedMemorySize, SMEM_TOTAL);
    cudaLaunchConfig_t cfg = {}; cfg.gridDim = dim3(128); cfg.blockDim = dim3(384); cfg.dynamicSmemBytes = SMEM_TOTAL;
    cudaLaunchAttribute at[1]; at[0].id = cudaLaunchAttributeClusterDimension; at[0].val.clusterDim.x = CLS; at[0].val.clusterDim.y = 1; at[0].val.clusterDim.z = 1;
    cfg.attrs = at; cfg.numAttrs = 1;
    if (cudaOccupancyMaxActiveClusters(&ncl, k_main, &cfg) != cudaSuccess) { cudaGetLastError(); ncl = 14; }
    ncl = ncl > 16 ? 16 : (ncl < 9 ? 9 : ncl);
    int nsm = 0, dev = 0; cudaGetDevice(&dev); cudaDeviceGetAttribute(&nsm, cudaDevAttrMultiProcessorCount, dev);
    nhelp = nsm - ncl * CLS;
  }
  Maps maps;
  mk_map(enc, &maps.xn, p_xn, S_TOK, DM, 128); mk_map(enc, &maps.y, p_y, S_TOK, DM, 128); mk_map(enc, &maps.h1, p_h1, S_TOK, FF, 128);
  mk_map(enc, &maps.o, p_o, S_TOK, HD, 128); mk_map(enc, &maps.qkv_st, p_qkv, S_TOK, 3 * HD, 128); mk_map(enc, &maps.qkv_ld, p_qkv, S_TOK, 3 * HD, 32);
  mk_map(enc, &maps.g, p_g, S_TOK, DM, 128);
  mk_map(enc, &maps.wq, d_in[2], DM, HD, 64); mk_map(enc, &maps.wk, d_in[3], DM, HD, 64); mk_map(enc, &maps.wv, d_in[4], DM, HD, 64);
  mk_map(enc, &maps.wo, d_in[5], HD, DM, 64); mk_map(enc, &maps.w1, d_in[8], DM, FF, 64); mk_map(enc, &maps.w2, d_in[10], FF, DM, 64);
  cudaStream_t st = cudaStreamPerThread;
  k_pre<<<256, 256, 0, st>>>((const bf16*)d_in[0]);
  cudaLaunchConfig_t cfg = {}; cfg.gridDim = dim3(ncl * CLS); cfg.blockDim = dim3(384); cfg.dynamicSmemBytes = SMEM_TOTAL; cfg.stream = st;
  cudaLaunchAttribute at[1]; at[0].id = cudaLaunchAttributeClusterDimension; at[0].val.clusterDim.x = CLS; at[0].val.clusterDim.y = 1; at[0].val.clusterDim.z = 1;
  cfg.attrs = at; cfg.numAttrs = 1;
  cudaLaunchKernelEx(&cfg, k_main, maps, (const bf16*)d_in[0], (const bf16*)d_in[1], (const bf16*)d_in[9], (const bf16*)d_in[11], (bf16*)d_out, 0);
  if (nhelp > 0) {
    cfg.gridDim = dim3(nhelp);
    at[0].id = cudaLaunchAttributeProgrammaticStreamSerialization; at[0].val.programmaticStreamSerializationAllowed = 1;
    cudaLaunchKernelEx(&cfg, k_main, maps, (const bf16*)d_in[0], (const bf16*)d_in[1], (const bf16*)d_in[9], (const bf16*)d_in[11], (bf16*)d_out, 1);
  }
}
```

```cpp
#include <cuda_runtime.h>
#include <cuda_bf16.h>
#include <cuda.h>
#include <stdint.h>

typedef __nv_bfloat16 bf16;

#define S_TOK 2048
#define DM 512
#define NH 32
#define DH 128
#define HD 4096
#define NMEM 8
#define SEG 32
#define NSEG 64
#define FF 1792
#define NBLK 16
#define NREC 64
#define REPL 0
#define CLS 8

__device__ __align__(1024) bf16 g_xn[S_TOK * DM];
__device__ __align__(1024) bf16 g_y[S_TOK * DM];
__device__ __align__(1024) bf16 g_qkv[(size_t)S_TOK * 3 * HD];
__device__ __align__(1024) bf16 g_h1[S_TOK * FF];
__device__ __align__(1024) bf16 g_g[S_TOK * DM];
__device__ __align__(1024) bf16 g_o[(size_t)S_TOK * HD];
__device__ __align__(1024) bf16 g_km[NSEG * NH * NMEM * DH];
__device__ __align__(1024) bf16 g_vmt[NSEG * NH * DH * NMEM];
__device__ __align__(1024) float g_opart[(size_t)4 * S_TOK * DM];
__device__ __align__(1024) float g_opl[(size_t)16 * 128 * DM];
__device__ __align__(1024) unsigned g_part[8 * 2 * 8 * 8 * 512];
struct Flags {
  unsigned qkv[NBLK * 48];
  unsigned h1[NBLK];
  unsigned g[NBLK];
  unsigned o[NBLK * 4];
  unsigned p[NBLK];
  unsigned o16[16];
  unsigned ctr;
  unsigned rec[NREC];
  unsigned abort_;
};
__device__ __align__(1024) Flags g_flags;

#define RSTAMP(k)
#define DBGMODE 0
#define ISTAMP(i, k)
__device__ __forceinline__ unsigned smem_u32(const void* p) { return (unsigned)__cvta_generic_to_shared(p); }
__device__ __forceinline__ float bf16r(float x) { unsigned u; asm("cvt.rn.bf16x2.f32 %0, %1, %2;" : "=r"(u) : "f"(x), "f"(0.0f)); return __uint_as_float(u); }
__device__ __forceinline__ unsigned pack_bf16(float lo, float hi) {
  __nv_bfloat162 v = __floats2bfloat162_rn(lo, hi);
  return *reinterpret_cast<unsigned*>(&v);
}
__device__ __forceinline__ float bf_lo(unsigned u) { return __uint_as_float(u << 16); }
__device__ __forceinline__ float bf_hi(unsigned u) { return __uint_as_float(u & 0xffff0000u); }

#define SPIN_LIMIT (1u << 20)
#define TRAP_IF(x) if ((x) > SPIN_LIMIT) { asm volatile("st.global.u32 [%0], %1;" ::"l"(0ull), "r"(0u) : "memory"); break; }
__device__ __forceinline__ unsigned ld_acquire(const unsigned* p) {
  unsigned v; asm volatile("ld.acquire.gpu.global.u32 %0, [%1];" : "=r"(v) : "l"(p) : "memory"); return v;
}
__device__ __forceinline__ unsigned ld_relaxed(const unsigned* p) {
  unsigned v; asm volatile("ld.relaxed.gpu.global.u32 %0, [%1];" : "=r"(v) : "l"(p) : "memory"); return v;
}
__device__ __forceinline__ void red_release_add(unsigned* p, unsigned v) {
  asm volatile("red.release.gpu.global.add.u32 [%0], %1;" ::"l"(p), "r"(v) : "memory");
}
__device__ __forceinline__ void st_release(unsigned* p, unsigned v) {
  asm volatile("st.release.gpu.global.u32 [%0], %1;" ::"l"(p), "r"(v) : "memory");
}
__device__ __forceinline__ void wait_flag_ge(const unsigned* p, unsigned target) {
  unsigned it = 0;
  while (ld_acquire(p) < target) {
    __nanosleep(64);
    TRAP_IF(++it);
  }
}
__device__ __forceinline__ uint4 ldv4_relaxed(const void* p) {
  uint4 a; asm volatile("ld.relaxed.gpu.global.v4.u32 {%0,%1,%2,%3}, [%4];" : "=r"(a.x), "=r"(a.y), "=r"(a.z), "=r"(a.w) : "l"(p) : "memory"); return a;
}
__device__ __forceinline__ uint2 ldv2_relaxed(const void* p) {
  uint2 a; asm volatile("ld.relaxed.gpu.global.v2.u32 {%0,%1}, [%2];" : "=r"(a.x), "=r"(a.y) : "l"(p) : "memory"); return a;
}
__device__ __forceinline__ void mbar_init(unsigned mb, unsigned cnt) { asm volatile("mbarrier.init.shared::cta.b64 [%0], %1;" ::"r"(mb), "r"(cnt) : "memory"); }
__device__ __forceinline__ void mbar_expect_tx(unsigned mb, unsigned bytes) { asm volatile("mbarrier.arrive.expect_tx.shared::cta.b64 _, [%0], %1;" ::"r"(mb), "r"(bytes) : "memory"); }
__device__ __forceinline__ void mbar_arrive(unsigned mb) { asm volatile("mbarrier.arrive.shared::cta.b64 _, [%0];" ::"r"(mb) : "memory"); }
__device__ __forceinline__ void mbar_wait(unsigned mb, unsigned parity) {
  unsigned ok, it = 0;
  while (true) {
    asm volatile("{.reg .pred p; mbarrier.try_wait.parity.shared::cta.b64 p, [%1], %2; selp.u32 %0,1,0,p;}" : "=r"(ok) : "r"(mb), "r"(parity) : "memory");
    if (ok) break;
    TRAP_IF(++it);
  }
}
__device__ __forceinline__ void mbar_wait_sleep(unsigned mb, unsigned parity) {
  unsigned ok, it = 0;
  while (true) {
    asm volatile("{.reg .pred p; mbarrier.test_wait.parity.shared::cta.b64 p, [%1], %2; selp.u32 %0,1,0,p;}" : "=r"(ok) : "r"(mb), "r"(parity) : "memory");
    if (ok) break;
    __nanosleep(200);
    TRAP_IF(++it);
  }
}
__device__ __forceinline__ float ex2f(float x) { float y; asm("ex2.approx.ftz.f32 %0, %1;" : "=f"(y) : "f"(x)); return y; }
__device__ __forceinline__ int opaque_tid() { int t = threadIdx.x; t = __shfl_sync(~0u, t, t & 31); return t; }
#define LOG2E 1.4426950408889634f
__device__ __forceinline__ void mbar_wait_cluster(unsigned mb, unsigned parity) {
  unsigned ok, it = 0;
  while (true) {
    asm volatile("{.reg .pred p; mbarrier.try_wait.parity.acquire.cluster.shared::cta.b64 p, [%1], %2; selp.u32 %0,1,0,p;}" : "=r"(ok) : "r"(mb), "r"(parity) : "memory");
    if (ok) break;
    TRAP_IF(++it);
  }
}
__device__ __forceinline__ void bar_sync(int id, int n) { asm volatile("bar.sync %0, %1;" ::"r"(id), "r"(n) : "memory"); }
__device__ __forceinline__ void bar_arrive(int id, int n) { asm volatile("bar.arrive %0, %1;" ::"r"(id), "r"(n) : "memory"); }
__device__ __forceinline__ void tma_load_2d(unsigned dst, const CUtensorMap* map, int c0, int c1, unsigned mb) {
  asm volatile("cp.async.bulk.tensor.2d.shared::cluster.global.mbarrier::complete_tx::bytes [%0], [%1, {%3, %4}], [%2];"
               ::"r"(dst), "l"((uint64_t)map), "r"(mb), "r"(c0), "r"(c1) : "memory");
}
__device__ __forceinline__ void tma_store_2d(const CUtensorMap* map, unsigned src, int c0, int c1) {
  asm volatile("cp.async.bulk.tensor.2d.global.shared::cta.bulk_group [%0, {%2, %3}], [%1];"
               ::"l"((uint64_t)map), "r"(src), "r"(c0), "r"(c1) : "memory");
}
__device__ __forceinline__ void fence_proxy_async() { asm volatile("fence.proxy.async;" ::: "memory"); }
__device__ __forceinline__ void fence_proxy_async_smem() { asm volatile("fence.proxy.async.shared::cta;" ::: "memory"); }
__device__ __forceinline__ void ldsm_x4(unsigned* r, unsigned addr) {
  asm volatile("ldmatrix.sync.aligned.m8n8.x4.shared.b16 {%0,%1,%2,%3}, [%4];" : "=r"(r[0]), "=r"(r[1]), "=r"(r[2]), "=r"(r[3]) : "r"(addr) : "memory");
}
__device__ __forceinline__ void ldsm_x4_t(unsigned* r, unsigned addr) {
  asm volatile("ldmatrix.sync.aligned.m8n8.x4.trans.shared.b16 {%0,%1,%2,%3}, [%4];" : "=r"(r[0]), "=r"(r[1]), "=r"(r[2]), "=r"(r[3]) : "r"(addr) : "memory");
}
__device__ __forceinline__ void stsm_x2_t(unsigned addr, unsigned r0, unsigned r1) {
  asm volatile("stmatrix.sync.aligned.m8n8.x2.trans.shared.b16 [%0], {%1,%2};" ::"r"(addr), "r"(r0), "r"(r1) : "memory");
}
__device__ __forceinline__ void stsm_x4(unsigned addr, unsigned r0, unsigned r1, unsigned r2, unsigned r3) {
  asm volatile("stmatrix.sync.aligned.m8n8.x4.shared.b16 [%0], {%1,%2,%3,%4};" ::"r"(addr), "r"(r0), "r"(r1), "r"(r2), "r"(r3) : "memory");
}
__device__ __forceinline__ void mma16816(float* d, const unsigned* a, unsigned b0, unsigned b1) {
  asm volatile("mma.sync.aligned.m16n8k16.row.col.f32.bf16.bf16.f32 {%0,%1,%2,%3}, {%4,%5,%6,%7}, {%8,%9}, {%0,%1,%2,%3};"
               : "+f"(d[0]), "+f"(d[1]), "+f"(d[2]), "+f"(d[3]) : "r"(a[0]), "r"(a[1]), "r"(a[2]), "r"(a[3]), "r"(b0), "r"(b1));
}
__device__ __forceinline__ void mma1688(float* d, unsigned a0, unsigned a1, unsigned b0) {
  asm volatile("mma.sync.aligned.m16n8k8.row.col.f32.bf16.bf16.f32 {%0,%1,%2,%3}, {%4,%5}, {%6}, {%0,%1,%2,%3};"
               : "+f"(d[0]), "+f"(d[1]), "+f"(d[2]), "+f"(d[3]) : "r"(a0), "r"(a1), "r"(b0));
}
__device__ __forceinline__ uint64_t mkdesc(unsigned addr, unsigned lbo, unsigned sbo) {
  return (uint64_t)((addr >> 4) & 0x3fff) | ((uint64_t)(lbo >> 4) << 16) | ((uint64_t)(sbo >> 4) << 32) | (1ull << 62);
}
#define R8(b) "+f"(d[b]), "+f"(d[b + 1]), "+f"(d[b + 2]), "+f"(d[b + 3]), "+f"(d[b + 4]), "+f"(d[b + 5]), "+f"(d[b + 6]), "+f"(d[b + 7])
#define R32(b) R8(b), R8(b + 8), R8(b + 16), R8(b + 24)
__device__ __forceinline__ void wgmma_n256(float* d, uint64_t ad, uint64_t bd, int acc) {
  asm volatile(
      "{.reg .pred p; setp.ne.b32 p, %130, 0;\n"
      "wgmma.mma_async.sync.aligned.m64n256k16.f32.bf16.bf16 "
      "{%0,%1,%2,%3,%4,%5,%6,%7,%8,%9,%10,%11,%12,%13,%14,%15,%16,%17,%18,%19,%20,%21,%22,%23,%24,%25,%26,%27,%28,%29,%30,%31,"
      "%32,%33,%34,%35,%36,%37,%38,%39,%40,%41,%42,%43,%44,%45,%46,%47,%48,%49,%50,%51,%52,%53,%54,%55,%56,%57,%58,%59,%60,%61,%62,%63,"
      "%64,%65,%66,%67,%68,%69,%70,%71,%72,%73,%74,%75,%76,%77,%78,%79,%80,%81,%82,%83,%84,%85,%86,%87,%88,%89,%90,%91,%92,%93,%94,%95,"
      "%96,%97,%98,%99,%100,%101,%102,%103,%104,%105,%106,%107,%108,%109,%110,%111,%112,%113,%114,%115,%116,%117,%118,%119,%120,%121,%122,%123,%124,%125,%126,%127},"
      "%128, %129, p, 1, 1, 0, 1;}\n"
      : R32(0), R32(32), R32(64), R32(96)
      : "l"(ad), "l"(bd), "r"(acc));
}

__device__ __forceinline__ void ln16(const float* x, float* o) {
  float s = 0;
#pragma unroll
  for (int i = 0; i < 16; i++) s += x[i];
#pragma unroll
  for (int of = 16; of > 0; of >>= 1) s += __shfl_xor_sync(~0u, s, of);
  float mean = s * (1.0f / DM);
  float v = 0;
#pragma unroll
  for (int i = 0; i < 16; i++) { float dd = x[i] - mean; v += dd * dd; }
#pragma unroll
  for (int of = 16; of > 0; of >>= 1) v += __shfl_xor_sync(~0u, v, of);
  float mb = bf16r(mean);
  float vb = bf16r(v * (1.0f / DM));
  float den = bf16r(sqrtf(bf16r(vb + 1e-5f)));
#pragma unroll
  for (int i = 0; i < 16; i++) o[i] = bf16r(__fdiv_rn(bf16r(x[i] - mb), den));
}
__global__ void __launch_bounds__(256) k_pre(const bf16* __restrict__ x) {
  int t = threadIdx.x, lane = t & 31, w = t >> 5;
  int row = blockIdx.x * 8 + w;
  const uint4* src = reinterpret_cast<const uint4*>(x + (size_t)row * DM);
  uint4 a = src[lane], b = src[lane + 32];
  unsigned u[8] = {a.x, a.y, a.z, a.w, b.x, b.y, b.z, b.w};
  float f[16], o[16], o2[16];
#pragma unroll
  for (int i = 0; i < 8; i++) { f[2 * i] = bf_lo(u[i]); f[2 * i + 1] = bf_hi(u[i]); }
  ln16(f, o);
  ln16(o, o2);
  uint4* d1 = reinterpret_cast<uint4*>(g_xn + (size_t)row * DM);
  uint4* d2 = reinterpret_cast<uint4*>(g_y + (size_t)row * DM);
  d1[lane] = make_uint4(pack_bf16(o[0], o[1]), pack_bf16(o[2], o[3]), pack_bf16(o[4], o[5]), pack_bf16(o[6], o[7]));
  d1[lane + 32] = make_uint4(pack_bf16(o[8], o[9]), pack_bf16(o[10], o[11]), pack_bf16(o[12], o[13]), pack_bf16(o[14], o[15]));
  d2[lane] = make_uint4(pack_bf16(o2[0], o2[1]), pack_bf16(o2[2], o2[3]), pack_bf16(o2[4], o2[5]), pack_bf16(o2[6], o2[7]));
  d2[lane + 32] = make_uint4(pack_bf16(o2[8], o2[9]), pack_bf16(o2[10], o2[11]), pack_bf16(o2[12], o2[13]), pack_bf16(o2[14], o2[15]));
  int gt = blockIdx.x * 256 + t;
  uint4 z = make_uint4(0, 0, 0, 0);
  if (gt < 16384) reinterpret_cast<uint4*>(g_part)[gt] = z;
  if (gt < (int)(sizeof(Flags) / 4)) reinterpret_cast<unsigned*>(&g_flags)[gt] = 0;
}

struct Maps { CUtensorMap xn, y, h1, o, qkv_st, qkv_ld, g, wq, wk, wv, wo, w1, w2; };

#define NSTAGE 3
#define STAGE_BYTES 49152
#define B_STG (NSTAGE * STAGE_BYTES)
#define R_WO 0
#define R_T1 65536
#define R_T2 131072
#define R_RING 65536
#define RING_N 4
#define RING_BYTES 12288
#define R_MEM 196608
#define R_QS (R_MEM + 8448)
#define R_KS (R_QS + 1152)
#define R_OS (R_KS + 1152)
#define R_SOWN (R_OS + 2176)
#define R_SPEER (R_SOWN + 1280)
#define R_VM (R_SPEER + 1280)
#define R_VRED (R_VM + 2048)
#define R_RS (R_VRED + 6144)
#define SM_BAR (R_RS + 8192)
#define SMEM_TOTAL (SM_BAR + 256 + 1024)
#define MB_FULL 0
#define MB_EMPTY 8
#define MB_STGF 16
#define MB_STGE 17
#define MB_W0 18
#define MB_W1 19
#define MB_WO 20
#define MB_S 21
#define MB_V 22
#define MB_KVR 23
#define MB_KVF 24
#define MB_RS 25
#define MB_AG 26
#define SM_MISC (SM_BAR + 224)

#define N_KV 512
#define I_M1 512
#define I_Q 624
#define I_M2 880
#define I_POST 912
#define I_TAIL (I_POST + 16 * 32)
#define N_ITEMS (I_TAIL + 5 * 8 + 32 + 8 + 64)
enum { T_QKV = 0, T_M1 = 1, T_M2 = 2, T_ATT = 3, T_OUT = 4, T_OUTL = 5, T_RED = 6, T_REDL = 7 };
struct Item { int type, b, c, ks; };
__device__ __forceinline__ Item decode_item(int i) {
  Item it; it.ks = 0;
  if (i < N_KV) { it.type = T_QKV; it.b = i >> 5; it.c = 16 + (i & 31); }
  else if (i < I_Q) { it.type = T_M1; it.b = (i - I_M1) / 7; it.c = (i - I_M1) % 7; }
  else if (i < I_M2) { it.type = T_QKV; it.b = (i - I_Q) >> 4; it.c = (i - I_Q) & 15; }
  else if (i < I_POST) { it.type = T_M2; it.b = (i - I_M2) >> 1; it.c = (i - I_M2) & 1; }
  else if (i < I_TAIL) {
    int x = i - I_POST, p = x >> 5, r = x & 31;
    if (r < 16) { it.type = T_ATT; it.b = p; it.c = r; }
    else if (r < 24) { it.type = T_OUT; it.b = p - 3; it.c = r & 1; it.ks = (r - 16) >> 1; }
    else { it.type = T_RED; it.b = p - 5; it.c = r - 24; }
  } else {
    int x = i - I_TAIL, r = x & 7;
    if (x < 40) {
      int q = x >> 3;
      if (q == 0 || q == 2) { it.type = T_OUT; it.b = 13 + (q >> 1); it.c = r & 1; it.ks = r >> 1; }
      else { it.type = T_RED; it.b = q == 1 ? 11 : 9 + q; it.c = r; }
    }
    else if (x < 72) { it.type = T_OUTL; it.b = 15; it.c = x & 1; it.ks = (x - 40) >> 1; }
    else if (x < 80) { it.type = T_RED; it.b = 14; it.c = r; }
    else { it.type = T_REDL; it.b = 15; it.c = x - 80; }
  }
  return it;
}
__device__ __forceinline__ int item_nkb(int type) { return type == T_M2 ? 28 : (type == T_OUT ? 16 : (type >= T_RED ? 1 : (type >= T_ATT ? 4 : 8))); }

__device__ __forceinline__ void st_async_b64(unsigned raddr, unsigned lo, unsigned hi, unsigned rmb) {
  asm volatile("st.async.weak.shared::cluster.mbarrier::complete_tx::bytes.v2.b32 [%0], {%1,%2}, [%3];" ::"r"(raddr), "r"(lo), "r"(hi), "r"(rmb) : "memory");
}
__device__ __forceinline__ void st_async_b32(unsigned raddr, unsigned v, unsigned rmb) {
  asm volatile("st.async.weak.shared::cluster.mbarrier::complete_tx::bytes.b32 [%0], %1, [%2];" ::"r"(raddr), "r"(v), "r"(rmb) : "memory");
}
__device__ __forceinline__ unsigned mapa(unsigned a, unsigned rank) {
  unsigned r; asm volatile("mapa.shared::cluster.u32 %0, %1, %2;" : "=r"(r) : "r"(a), "r"(rank)); return r;
}
__device__ __forceinline__ void sts64(unsigned a, unsigned x, unsigned y) { asm volatile("st.shared.v2.b32 [%0], {%1,%2};" ::"r"(a), "r"(x), "r"(y) : "memory"); }
__device__ __forceinline__ void sts128(unsigned a, uint4 v) { asm volatile("st.shared.v4.b32 [%0], {%1,%2,%3,%4};" ::"r"(a), "r"(v.x), "r"(v.y), "r"(v.z), "r"(v.w) : "memory"); }
__device__ __forceinline__ uint2 lds64(unsigned a) { uint2 v; asm volatile("ld.shared.v2.b32 {%0,%1}, [%2];" : "=r"(v.x), "=r"(v.y) : "r"(a) : "memory"); return v; }
__device__ __forceinline__ uint4 lds128(unsigned a) { uint4 v; asm volatile("ld.shared.v4.b32 {%0,%1,%2,%3}, [%4];" : "=r"(v.x), "=r"(v.y), "=r"(v.z), "=r"(v.w) : "r"(a) : "memory"); return v; }
__device__ __forceinline__ float lds32f(unsigned a) { float v; asm volatile("ld.shared.f32 %0, [%1];" : "=f"(v) : "r"(a) : "memory"); return v; }
#define spin_check(it) TRAP_IF(++it)
#define POLLV 0
#define BAR8 0
#define D_STAG 150
#define D_RED 480
#define D_PUB 0
#define DELAY(n) do { unsigned c0_, c1_; asm volatile("mov.u32 %0, %%clock;" : "=r"(c0_)); do { asm volatile("mov.u32 %0, %%clock;" : "=r"(c1_)); } while (c1_ - c0_ < (n)); } while (0)
#define NPRE1 0
#define VD 2
#define ZS 0
#define MBL 1
#define D_V 0
#define SCALE_QK 0.08838834764831845f

__device__ __forceinline__ void rec_worker(const Maps& maps, unsigned sb, const bf16* __restrict__ mem0) {
  const int c = blockIdx.x, h = c >> 1, j = c & 1;
  const int t = opaque_tid(), lane = t & 31, w = t >> 5, g = lane >> 2, tq = lane & 3;
  const int m = lane >> 3, r8 = lane & 7, kh = w >> 2, et = w & 3;
  const unsigned bar = sb + SM_BAR;
  unsigned wq[16][4], wk[16][4], wo[8][4];
  const unsigned woff = (kh * 4) * 8192 + ((m >> 1) * 8 + r8) * 128 + (((et * 2 + (m & 1)) ^ r8) << 4);
  mbar_wait(bar + 8 * MB_W0, 0);
#pragma unroll
  for (int i = 0; i < 16; i++) {
    ldsm_x4_t(wq[i], sb + R_WO + woff + (i >> 2) * 8192 + (i & 3) * 2048);
    ldsm_x4_t(wk[i], sb + R_T1 + woff + (i >> 2) * 8192 + (i & 3) * 2048);
  }
  bar_sync(2, 288);
  if (t == 0) {
    fence_proxy_async_smem();
    mbar_expect_tx(bar + 8 * MB_WO, 65536);
    for (int kb = 0; kb < 2; kb++)
      for (int cb = 0; cb < 4; cb++) tma_load_2d(sb + R_WO + (kb * 4 + cb) * 8192, &maps.wo, j * 256 + cb * 64, h * 128 + kb * 64, bar + 8 * MB_WO);
  }
  const unsigned rk = c & 7, peer = rk ^ 1, cl = c >> 3;
#define KEEP(x) x = __shfl_sync(~0u, x, lane)
  unsigned pA = sb + R_MEM + kh * 4096 + lane * 16;
  unsigned pW0 = sb + R_WO + (w >> 1) * 8192 + ((m >> 1) * 8 + r8) * 128 + ((((w & 1) * 4 + (m & 1)) ^ r8) << 4);
#define pW1 (pW0 ^ 32)
  unsigned aX = sb + R_VRED + et * 512 + lane * 16;
  unsigned aQKst = sb + (kh ? R_KS : R_QS) + r8 * 144 + (et * 16 + (m & 1) * 8) * 2;
  unsigned aL8_ = sb + lane * 8;
  unsigned aSl_ = mapa(sb + R_SOWN + w * 256 + lane * 8, rk), aSr_ = mapa(sb + R_SPEER + w * 256 + lane * 8, peer);
  const unsigned mbSl = mapa(bar + 8 * MB_S, rk), mbSr = mapa(bar + 8 * MB_S, peer), mbVl = mbSl + 8, mbVr = mbSr + 8;
  unsigned aQ_ = sb + R_QS + r8 * 144 + m * 16;
  unsigned oKx_ = (et * 8 + r8) * 128 + ((m ^ r8) << 4);
  unsigned oVx_ = 4096 + (et >> 1) * 4096 + ((m >> 1) * 8 + r8) * 128 + ((((et & 1) * 4 + (m & 1)) ^ r8) << 4);
  unsigned aOst_ = sb + R_OS + r8 * 272 + (et * 32 + m * 8) * 2;
  unsigned aOld = sb + R_OS + r8 * 272 + m * 16;
  unsigned aVm_ = sb + R_VM + et * 512 + lane * 8;
  unsigned aRSr = mapa(sb + R_RS + (h & 3) * 2048 + (w & 1) * 1024 + lane * 8, j * 4 + (w >> 1));
  unsigned t8 = t * 8;
  unsigned r1 = kh ? aL8_ : aSl_, r2 = kh ? oVx_ : aSr_, r3 = kh ? aOst_ : aQ_, r4 = kh ? aVm_ : oKx_;
#define aL8 r1
#define aSl r1
#define oVx r2
#define aSr r2
#define aOst r3
#define aQ r3
#define aVm r4
#define oKx r4
  KEEP(pA); KEEP(pW0); KEEP(aX); KEEP(aQKst); KEEP(r1); KEEP(r2); KEEP(r3); KEEP(r4);
  KEEP(aOld); KEEP(aRSr); KEEP(t8);
  mbar_wait(bar + 8 * MB_WO, 0);
#pragma unroll
  for (int ks = 0; ks < 3; ks++) { ldsm_x4_t(wo[2 * ks], pW0 + ks * 2048); ldsm_x4_t(wo[2 * ks + 1], pW1 + ks * 2048); }
  {
    unsigned v[8];
#pragma unroll
    for (int q = 0; q < 8; q++) v[q] = __ldg(reinterpret_cast<const unsigned*>(mem0) + q * 256 + t);
    sts128(sb + R_MEM + t * 32, make_uint4(__byte_perm(v[0], v[1], 0x5410), __byte_perm(v[2], v[3], 0x5410), __byte_perm(v[4], v[5], 0x5410), __byte_perm(v[6], v[7], 0x5410)));
    sts128(sb + R_MEM + t * 32 + 16, make_uint4(__byte_perm(v[0], v[1], 0x7632), __byte_perm(v[2], v[3], 0x7632), __byte_perm(v[4], v[5], 0x7632), __byte_perm(v[6], v[7], 0x7632)));
  }
  fence_proxy_async_smem();
  bar_sync(3, 384);

#pragma unroll 1
  for (int s = 0;; s++) {
    const unsigned par = s & 1;
    const unsigned slot = s & (RING_N - 1), rpar = (s / RING_N) & 1;
    const unsigned ring = sb + R_RING + slot * RING_BYTES;
    asm volatile("" : "+r"(t8), "+r"(pW0), "+r"(r1), "+r"(r2), "+r"(r4));
    RSTAMP(1);
    RSTAMP(2);
    float aq[4] = {0, 0, 0, 0}, ak[4] = {0, 0, 0, 0};
    {
      float aq1[4] = {0, 0, 0, 0}, ak1[4] = {0, 0, 0, 0};
      unsigned b[8][4];
#pragma unroll
      for (int i = 0; i < 4; i++) ldsm_x4_t(b[i], pA + i * 512);
#pragma unroll
      for (int i = 0; i < 8; i++) {
        mma16816(aq, wq[2 * i], b[i][0], b[i][1]); mma16816(ak, wk[2 * i], b[i][0], b[i][1]);
        mma16816(aq1, wq[2 * i + 1], b[i][2], b[i][3]); mma16816(ak1, wk[2 * i + 1], b[i][2], b[i][3]);
        if (i < 4) ldsm_x4_t(b[i + 4], pA + (i + 4) * 512);
      }
#pragma unroll
      for (int i = 0; i < 4; i++) { aq[i] += aq1[i]; ak[i] += ak1[i]; }
    }
    RSTAMP(3);
#define STSF4(a, v) asm volatile("st.shared.v4.f32 [%0], {%1,%2,%3,%4};" ::"r"(a), "f"(v[0]), "f"(v[1]), "f"(v[2]), "f"(v[3]) : "memory")
#define VLD(i) do { ldsm_x4_t(b[i], pA + (i) * 512); ldsm_x4_t(f0[i], pVk + ((i) >> 1) * 8192 + ((i) & 1) * 4096); ldsm_x4_t(f1[i], pVk + ((i) >> 1) * 8192 + ((i) & 1) * 4096 + 2048); } while (0)
#define VPASS() float av[4] = {0, 0, 0, 0}; { float av1[4] = {0, 0, 0, 0}; unsigned b[8][4], f1[8][4], f0[8][4]; VLD(0); if (VD > 1) VLD(1); \
      _Pragma("unroll") for (int i = 0; i < 8; i++) { if (i + VD < 8) VLD(i + VD); \
        mma16816(av, f0[i], b[i][0], b[i][1]); mma16816(av1, f1[i], b[i][2], b[i][3]); } \
      _Pragma("unroll") for (int i = 0; i < 4; i++) av[i] += av1[i]; }
    unsigned f[8][4];
#define WO_LD(i0, i1) do { _Pragma("unroll") for (int i = i0; i < i1; i++) { ldsm_x4_t(f[2 * i], pW0 + 32768 + i * 2048); ldsm_x4_t(f[2 * i + 1], pW1 + 32768 + i * 2048); } } while (0)
    if (kh) {
      STSF4(aX, aq);
      bar_sync(4 + et, 64);
      uint4 o = lds128(aX + 2048);
      stsm_x2_t(aQKst, pack_bf16(ak[0] + __uint_as_float(o.x), ak[1] + __uint_as_float(o.y)), pack_bf16(ak[2] + __uint_as_float(o.z), ak[3] + __uint_as_float(o.w)));
      bar_arrive(1, 256);
      RSTAMP(4);
      RSTAMP(5);
      if (s == NSEG - 1) {
        mbar_wait(bar + 8 * MB_V, par);
        bar_sync(8, 128);
        if (t == 128) mbar_arrive(bar + 8 * MB_KVR);
        break;
      }
      mbar_wait(bar + 8 * (MB_FULL + slot), rpar);
      unsigned vx[4][4];
      ldsm_x4_t(vx[0], ring + oVx); ldsm_x4_t(vx[1], ring + oVx + 2048); ldsm_x4_t(vx[2], ring + (oVx ^ 32)); ldsm_x4_t(vx[3], ring + (oVx ^ 32) + 2048);
      WO_LD(0, NPRE1);
      RSTAMP(6); RSTAMP(7);
      mbar_wait(bar + 8 * MB_S, par);
      RSTAMP(8);
      float sc[10];
#pragma unroll
      for (int i = 0; i < 5; i++) {
        uint2 o = lds64(aL8 + R_SOWN + i * 256), p = lds64(aL8 + R_SPEER + i * 256);
        sc[2 * i] = __uint_as_float(o.x) + __uint_as_float(p.x); sc[2 * i + 1] = __uint_as_float(o.y) + __uint_as_float(p.y);
      }
      float mx = fmaxf(fmaxf(fmaxf(sc[0], sc[1]), fmaxf(sc[2], sc[3])), fmaxf(fmaxf(fmaxf(sc[4], sc[5]), fmaxf(sc[6], sc[7])), fmaxf(sc[8], sc[9])));
      mx = fmaxf(mx, __shfl_xor_sync(~0u, mx, 1)); mx = fmaxf(mx, __shfl_xor_sync(~0u, mx, 2));
      const float nm = -mx * (SCALE_QK * LOG2E);
      unsigned p[5];
#pragma unroll
      for (int i = 0; i < 5; i++) p[i] = pack_bf16(ex2f(fmaf(sc[2 * i], SCALE_QK * LOG2E, nm)), ex2f(fmaf(sc[2 * i + 1], SCALE_QK * LOG2E, nm)));
      RSTAMP(9);
      float o0[4] = {0, 0, 0, 0}, o1[4] = {0, 0, 0, 0}, o3[4] = {0, 0, 0, 0}, o4[4] = {0, 0, 0, 0}, z0[4] = {0, 0, 0, 0}, z1[4] = {0, 0, 0, 0};
      const unsigned ones[4] = {0x3F803F80u, 0u, 0x3F803F80u, 0u};
      mma16816(z0, ones, p[0], p[1]); mma16816(ZS ? z0 : z1, ones, p[2], p[3]);
      mma16816(o0, vx[0], p[0], p[1]); mma16816(o3, vx[2], p[0], p[1]); mma16816(o1, vx[1], p[2], p[3]); mma16816(o4, vx[3], p[2], p[3]);
      mma1688(z0, 0x3F803F80u, 0u, p[4]);
      mbar_wait(bar + 8 * MB_V, par);
      uint2 vm0 = lds64(aVm), vm1 = lds64(aVm + 256);
      mma1688(o0, vm0.x, vm0.y, p[4]); mma1688(o3, vm1.x, vm1.y, p[4]);
      float i0, i1;
      asm("rcp.approx.ftz.f32 %0, %1;" : "=f"(i0) : "f"(z0[0] + z1[0])); asm("rcp.approx.ftz.f32 %0, %1;" : "=f"(i1) : "f"(z0[1] + z1[1]));
      asm volatile("stmatrix.sync.aligned.m8n8.x4.trans.shared.b16 [%0], {%1,%2,%3,%4};" ::"r"(aOst), "r"(pack_bf16((o0[0] + o1[0]) * i0, (o0[1] + o1[1]) * i1)), "r"(pack_bf16((o0[2] + o1[2]) * i0, (o0[3] + o1[3]) * i1)),
                   "r"(pack_bf16((o3[0] + o4[0]) * i0, (o3[1] + o4[1]) * i1)), "r"(pack_bf16((o3[2] + o4[2]) * i0, (o3[3] + o4[3]) * i1)) : "memory");
      RSTAMP(10);
      bar_sync(1, 256);
      WO_LD(NPRE1, 3);
    } else {
      STSF4(aX + 2048, ak);
      unsigned kb[8];
      mbar_wait(bar + 8 * (MB_FULL + slot), rpar);
      ldsm_x4(kb, ring + oKx); ldsm_x4(kb + 4, ring + (oKx ^ 64));
      bar_sync(4 + et, 64);
      uint4 o = lds128(aX);
      stsm_x2_t(aQKst, pack_bf16(aq[0] + __uint_as_float(o.x), aq[1] + __uint_as_float(o.y)), pack_bf16(aq[2] + __uint_as_float(o.z), aq[3] + __uint_as_float(o.w)));
      RSTAMP(4);
      bar_sync(1, 256);
      RSTAMP(5);
      if (s != NSEG - 1) {
        unsigned qa[8], km[8];
        ldsm_x4(qa, aQ); ldsm_x4(qa + 4, aQ + 64);
        if (w == 3) { ldsm_x4(km, aQ + 1152); ldsm_x4(km + 4, aQ + 1152 + 64); }
        float s0[4] = {0, 0, 0, 0}, s1[4] = {0, 0, 0, 0};
        unsigned af[4][4];
#pragma unroll
        for (int i = 0; i < 4; i++) { af[i][0] = qa[2 * i]; af[i][1] = 0; af[i][2] = qa[2 * i + 1]; af[i][3] = 0; }
        mma16816(s0, af[0], kb[0], kb[1]); mma16816(s1, af[1], kb[2], kb[3]);
        mma16816(s0, af[2], kb[4], kb[5]); mma16816(s1, af[3], kb[6], kb[7]);
        if (w == 3) {
          float m0[4] = {0, 0, 0, 0}, m1[4] = {0, 0, 0, 0};
          mma16816(m0, af[0], km[0], km[1]); mma16816(m1, af[1], km[2], km[3]);
          mma16816(m0, af[2], km[4], km[5]); mma16816(m1, af[3], km[6], km[7]);
          unsigned x = __float_as_uint(m0[0] + m1[0]), y = __float_as_uint(m0[1] + m1[1]);
          st_async_b64(aSr + 256, x, y, mbSr); st_async_b64(aSl + 256, x, y, mbSl);
        }
        unsigned x = __float_as_uint(s0[0] + s1[0]), y = __float_as_uint(s0[1] + s1[1]);
        st_async_b64(aSr, x, y, mbSr); st_async_b64(aSl, x, y, mbSl);
      }
      RSTAMP(6);
      RSTAMP(7); RSTAMP(8);
      if (s == NSEG - 1) break;
      WO_LD(0, 3);
      RSTAMP(9); RSTAMP(10);
      bar_sync(1, 256);
    }
    RSTAMP(11);
    float d0[4] = {0, 0, 0, 0}, d1[4] = {0, 0, 0, 0}, e0[4] = {0, 0, 0, 0}, e1[4] = {0, 0, 0, 0};
    unsigned ob[4][4];
    ldsm_x4(ob[0], aOld); ldsm_x4(ob[2], aOld + 128);
    mma16816(d0, wo[0], ob[0][0], ob[0][1]); mma16816(d1, wo[1], ob[0][0], ob[0][1]);
    mma16816(e0, wo[2], ob[0][2], ob[0][3]); mma16816(e1, wo[3], ob[0][2], ob[0][3]);
    ldsm_x4(ob[1], aOld + 64);
    mma16816(d0, f[0], ob[2][0], ob[2][1]); mma16816(d1, f[1], ob[2][0], ob[2][1]);
    ldsm_x4_t(wo[6], pW0 + 3 * 2048); ldsm_x4_t(wo[7], pW1 + 3 * 2048);
    mma16816(e0, f[2], ob[2][2], ob[2][3]); mma16816(e1, f[3], ob[2][2], ob[2][3]);
    ldsm_x4(ob[3], aOld + 192);
    WO_LD(3, 4);
    mma16816(d0, wo[4], ob[1][0], ob[1][1]); mma16816(d1, wo[5], ob[1][0], ob[1][1]);
    mma16816(e0, wo[6], ob[1][2], ob[1][3]); mma16816(e1, wo[7], ob[1][2], ob[1][3]);
    const unsigned mbRSr = mapa(bar + 8 * MB_RS, j * 4 + (t8 >> 9));
    mma16816(d0, f[4], ob[3][0], ob[3][1]); mma16816(d1, f[5], ob[3][0], ob[3][1]);
    mma16816(e0, f[6], ob[3][2], ob[3][3]); mma16816(e1, f[7], ob[3][2], ob[3][3]);
    st_async_b64(aRSr, __float_as_uint(d0[0] + e0[0]), __float_as_uint(d0[1] + e0[1]), mbRSr);
    st_async_b64(aRSr + 256, __float_as_uint(d0[2] + e0[2]), __float_as_uint(d0[3] + e0[3]), mbRSr);
    st_async_b64(aRSr + 512, __float_as_uint(d1[0] + e1[0]), __float_as_uint(d1[1] + e1[1]), mbRSr);
    st_async_b64(aRSr + 768, __float_as_uint(d1[2] + e1[2]), __float_as_uint(d1[3] + e1[3]), mbRSr);
    RSTAMP(12);
    if (t == 128) {
      mbar_arrive(bar + 8 * (MB_EMPTY + slot)); mbar_arrive(bar + 8 * MB_KVR);
      mbar_expect_tx(bar + 8 * MB_S, 2560); mbar_expect_tx(bar + 8 * MB_V, 2048);
    }
    const unsigned tag = ((s >> 1) & 1) ^ 1;
    const char* gp = reinterpret_cast<const char*>(g_part);
    const unsigned goff = (par * 8 + rk) * 16384 + cl * 2048 + t8;
    unsigned mbA[8];
#pragma unroll
    for (int i = 0; i < 8; i++) if (!MBL) mbA[i] = mapa(bar + 8 * MB_AG, i);
    const unsigned dlt = (R_MEM + rk * 1024) - (SM_BAR + 8 * MB_AG) + (t8 >> 1);
    mbar_wait(bar + 8 * MB_RS, par);
    RSTAMP(13);
    uint2 a[8];
    {
      uint2 x0 = lds64(sb + R_RS + t8), x1 = lds64(sb + R_RS + 2048 + t8), x2 = lds64(sb + R_RS + 4096 + t8), x3 = lds64(sb + R_RS + 6144 + t8);
      float q0 = (__uint_as_float(x0.x) + __uint_as_float(x1.x)) + (__uint_as_float(x2.x) + __uint_as_float(x3.x));
      float q1 = (__uint_as_float(x0.y) + __uint_as_float(x1.y)) + (__uint_as_float(x2.y) + __uint_as_float(x3.y));
      a[0].x = (__float_as_uint(q0) & ~1u) | tag; a[0].y = (__float_as_uint(q1) & ~1u) | tag;
      asm volatile("st.relaxed.gpu.global.v2.u32 [%0], {%1,%2};" ::"l"(gp + goff), "r"(a[0].x), "r"(a[0].y) : "memory");
    }
    RSTAMP(14);
    if (t == 128) mbar_expect_tx(bar + 8 * MB_RS, 8192);
    {
      unsigned it = 0;
#define PLOAD(a) _Pragma("unroll") for (int i = 1; i < 8; i++) a[i] = ldv2_relaxed(gp + (goff ^ (i * 2048)))
#define PAND(a) (((a[1].x & a[1].y) & (a[2].x & a[2].y) & (a[3].x & a[3].y)) & ((a[4].x & a[4].y) & (a[5].x & a[5].y)) & ((a[6].x & a[6].y) & (a[7].x & a[7].y)))
#define POR(a) (((a[1].x | a[1].y) | (a[2].x | a[2].y) | (a[3].x | a[3].y)) | ((a[4].x | a[4].y) | (a[5].x | a[5].y)) | ((a[6].x | a[6].y) | (a[7].x | a[7].y)))
#define POK(a) (((tag ? PAND(a) : ~POR(a)) & 1u) != 0)
      if (D_RED) DELAY(D_RED);
      while (true) { PLOAD(a); if (POK(a)) break; if (D_PUB) DELAY(D_PUB); spin_check(it); }
    }
    RSTAMP(15);
    {
#define AF(i, c) __uint_as_float(a[i].c)
      unsigned u = pack_bf16(((AF(0, x) + AF(1, x)) + (AF(2, x) + AF(3, x))) + ((AF(4, x) + AF(5, x)) + (AF(6, x) + AF(7, x))),
                             ((AF(0, y) + AF(1, y)) + (AF(2, y) + AF(3, y))) + ((AF(4, y) + AF(5, y)) + (AF(6, y) + AF(7, y))));
      __syncwarp();
#pragma unroll
      for (int i = 0; i < 8; i++) { if (MBL) mbA[i] = mapa(bar + 8 * MB_AG, i); st_async_b32(mbA[i] + dlt, u, mbA[i]); }
    }
    mbar_wait(bar + 8 * MB_KVF, par);
    mbar_wait(bar + 8 * MB_AG, par);
    if (t == 128) mbar_expect_tx(bar + 8 * MB_AG, 8192);
  }
}

__device__ __forceinline__ void rec_aux(const Maps& maps, unsigned sb) {
  const int c = blockIdx.x, h = c >> 1, j = c & 1;
  const unsigned bar = sb + SM_BAR;
  const int lane = threadIdx.x & 31, w = (threadIdx.x >> 5) & 3;
  if (w == 0) {
    if (lane == 0) {
      mbar_expect_tx(bar + 8 * MB_W0, 131072);
      for (int kb = 0; kb < 8; kb++) tma_load_2d(sb + R_WO + kb * 8192, &maps.wq, h * 128 + j * 64, kb * 64, bar + 8 * MB_W0);
      for (int kb = 0; kb < 8; kb++) tma_load_2d(sb + R_T1 + kb * 8192, &maps.wk, h * 128 + j * 64, kb * 64, bar + 8 * MB_W0);
      mbar_expect_tx(bar + 8 * MB_W1, 65536);
      for (int kb = 0; kb < 8; kb++) tma_load_2d(sb + R_T2 + kb * 8192, &maps.wv, h * 128 + j * 64, kb * 64, bar + 8 * MB_W1);
    }
    __syncwarp();
    bar_sync(2, 288);
    fence_proxy_async_smem();
  }
  mbar_wait(bar + 8 * MB_W1, 0);
  const unsigned aVr = mapa(sb + R_VM + (j * 4 + w) * 256 + lane * 8, (c & 7) ^ 1), mbVr = mapa(bar + 8 * MB_V, (c & 7) ^ 1), mbVl = mapa(bar + 8 * MB_V, c & 7);
  const uint64_t ad = mkdesc(sb + R_T2, 8192, 1024), bd = (uint64_t)(((sb + R_MEM) >> 4) & 0x3fff) | (8ull << 16) | (8ull << 32);
  int nf = 0;
#pragma unroll 1
  for (int s = 0; s < NSEG; s++) {
    if (s == 0) bar_sync(3, 384);
    else { mbar_wait(bar + 8 * MB_KVF, (s - 1) & 1); mbar_wait(bar + 8 * MB_AG, (s - 1) & 1); }
    if (D_V) DELAY(D_V);
    float av[4];
    asm volatile("wgmma.fence.sync.aligned;" ::: "memory");
    asm volatile("wgmma.mma_async.sync.aligned.m64n8k16.f32.bf16.bf16 {%0,%1,%2,%3}, %4, %5, 0, 1, 1, 1, 1;"
                 : "=f"(av[0]), "=f"(av[1]), "=f"(av[2]), "=f"(av[3]) : "l"(ad), "l"(bd));
#pragma unroll
    for (int i = 1; i < 32; i++)
      asm volatile("wgmma.mma_async.sync.aligned.m64n8k16.f32.bf16.bf16 {%0,%1,%2,%3}, %4, %5, 1, 1, 1, 1, 1;"
                   : "+f"(av[0]), "+f"(av[1]), "+f"(av[2]), "+f"(av[3]) : "l"(ad + i * 128), "l"(bd + i * 16));
    asm volatile("wgmma.commit_group.sync.aligned;" ::: "memory");
    asm volatile("wgmma.wait_group.sync.aligned 0;" : "+f"(av[0]), "+f"(av[1]), "+f"(av[2]), "+f"(av[3])::"memory");
    {
      unsigned x = pack_bf16(av[0], av[1]), y = pack_bf16(av[2], av[3]);
      st_async_b64(aVr, x, y, mbVr);
      st_async_b64(aVr + (mbVl - mbVr), x, y, mbVl);
    }
    if (w == 0) {
      if (lane == 0) {
        for (; nf < s + RING_N && nf < NSEG; nf++) {
          unsigned slot = nf & (RING_N - 1);
          if ((nf & 3) == 0 && !DBGMODE) {
            wait_flag_ge(&g_flags.qkv[(nf >> 2) * 48 + 16 + (h >> 1)], 1);
            wait_flag_ge(&g_flags.qkv[(nf >> 2) * 48 + 32 + (h >> 1)], 1);
            fence_proxy_async();
          }
          if (nf >= RING_N) mbar_wait(bar + 8 * (MB_EMPTY + slot), ((nf / RING_N) - 1) & 1);
          unsigned dst = sb + R_RING + slot * RING_BYTES, mb = bar + 8 * (MB_FULL + slot);
          mbar_expect_tx(mb, RING_BYTES);
          tma_load_2d(dst, &maps.qkv_ld, HD + h * 128 + j * 64, nf * SEG, mb);
          tma_load_2d(dst + 4096, &maps.qkv_ld, 2 * HD + h * 128, nf * SEG, mb);
          tma_load_2d(dst + 8192, &maps.qkv_ld, 2 * HD + h * 128 + 64, nf * SEG, mb);
        }
      }
      __syncwarp();
    } else if (w == 1) {
      mbar_wait(bar + 8 * MB_KVR, s & 1);
      uint4 k0 = lds128(sb + R_KS + (lane >> 3) * 144 + (lane & 7) * 16), k1 = lds128(sb + R_KS + (4 + (lane >> 3)) * 144 + (lane & 7) * 16);
      uint2 v[4];
#pragma unroll
      for (int i = 0; i < 4; i++) v[i] = lds64(sb + R_VM + (j * 4 + i) * 256 + lane * 8);
      __syncwarp();
      if (lane == 0) mbar_arrive(bar + 8 * MB_KVF);
      bf16* kd = g_km + ((size_t)(s * NH + h) * NMEM) * DH + j * 64;
      *reinterpret_cast<uint4*>(kd + (lane >> 3) * DH + (lane & 7) * 8) = k0;
      *reinterpret_cast<uint4*>(kd + (4 + (lane >> 3)) * DH + (lane & 7) * 8) = k1;
      unsigned* vd = reinterpret_cast<unsigned*>(g_vmt) + ((size_t)(s * NH + h) * DH + j * 64) * 4;
#pragma unroll
      for (int i = 0; i < 4; i++) { vd[(i * 16) * 4 + lane] = v[i].x; vd[(i * 16 + 8) * 4 + lane] = v[i].y; }
      __syncwarp();
      if (lane == 0) st_release(&g_flags.rec[c], s + 1);
    }
  }
}

__device__ __forceinline__ void bulk_producer(const Maps& maps, unsigned sb, int* misc) {
  const unsigned bar = sb + SM_BAR;
  const int lane = threadIdx.x & 31;
  unsigned st = 0, ph = 0, seq = 0;
  while (true) {
    int idx = 0;
    if (lane == 0) idx = (int)atomicAdd(&g_flags.ctr, 1u);
    idx = __shfl_sync(~0u, idx, 0);
    if (idx >= N_ITEMS) {
      if (lane == 0) {
        mbar_wait(bar + 8 * (MB_EMPTY + st), ph ^ 1);
        misc[seq & 3] = -1;
        mbar_arrive(bar + 8 * (MB_FULL + st));
      }
      break;
    }
    if (lane == 0) ISTAMP(idx, 0);
    Item it = decode_item(idx);
    if (it.b < 0) continue;
    const CUtensorMap* mp; int c0, c1, dc0, dc1; unsigned doff;
    const unsigned* fl = nullptr; unsigned tgt = 1; int nbox = 5, rdy = 0;
    if (it.type == T_ATT) {
      mp = &maps.qkv_ld; nbox = 12; doff = lane * 4096;
      c0 = (lane >> 2) * HD + it.c * 256 + (lane & 1) * 64; c1 = it.b * 128 + ((lane >> 1) & 1) * 32; dc0 = dc1 = 0;
      if (lane < 3) fl = &g_flags.qkv[it.b * 48 + lane * 16 + it.c];
      bool ok = true;
      if (lane >= 4 && lane < 8) ok = ld_acquire(&g_flags.rec[it.c * 4 + lane - 4]) >= (unsigned)(it.b * 4 + 4);
      rdy = __all_sync(~0u, ok) ? 65536 : 0;
    } else {
      int k0 = 0, nb0 = it.c * 256;
      if (it.type == T_QKV) { mp = lane == 0 ? &maps.xn : (it.c < 16 ? &maps.wq : (it.c < 32 ? &maps.wk : &maps.wv)); nb0 = (it.c & 15) * 256; }
      else if (it.type == T_M1) mp = lane == 0 ? &maps.y : &maps.w1;
      else if (it.type == T_M2) { mp = lane == 0 ? &maps.h1 : &maps.w2; fl = &g_flags.h1[it.b]; tgt = 7; }
      else {
        mp = lane == 0 ? &maps.o : &maps.wo;
        if (it.type == T_OUT) { k0 = it.ks * 1024; fl = &g_flags.o[it.b * 4 + it.ks]; tgt = 4; }
        else if (it.type == T_OUTL) { k0 = it.ks * 256; fl = &g_flags.o16[it.ks]; }
        else if (lane == 1) { fl = &g_flags.g[it.b]; tgt = 2; }
        else { fl = &g_flags.p[it.b]; tgt = it.type == T_RED ? 8 : 32; }
      }
      if (lane > (it.type >= T_RED ? 1 : 0)) fl = nullptr;
      if (lane == 0) { c0 = k0; c1 = it.b * 128; dc0 = 64; dc1 = 0; doff = 0; }
      else { c0 = nb0 + (lane - 1) * 64; c1 = k0; dc0 = 0; dc1 = 64; doff = 8192 + lane * 8192; }
    }
    if (fl) wait_flag_ge(fl, tgt);
    __syncwarp();
    fence_proxy_async();
    if (lane == 0) ISTAMP(idx, 1);
    const int nkb = item_nkb(it.type);
    for (int kb = 0; kb < nkb; kb++) {
      const unsigned mb = bar + 8 * (MB_FULL + st);
      mbar_wait(bar + 8 * (MB_EMPTY + st), ph ^ 1);
      if (lane == 0) {
        if (kb == 0) misc[seq & 3] = idx | rdy;
        if (it.type >= T_RED) mbar_arrive(mb); else mbar_expect_tx(mb, STAGE_BYTES);
      }
      if (it.type == T_ATT) { if (lane < 12) tma_load_2d(sb + st * STAGE_BYTES + doff, mp, c0 + (kb & 1) * 128, c1 + (kb >> 1) * 64, mb); }
      else if (lane < nbox && it.type < T_RED) tma_load_2d(sb + st * STAGE_BYTES + doff, mp, c0 + kb * dc0, c1 + kb * dc1, mb);
      __syncwarp();
      if (++st == NSTAGE) { st = 0; ph ^= 1; }
    }
    seq++;
  }
}
__device__ __forceinline__ void bulk_store(const Maps& maps, unsigned sb, volatile int* misc) {
  const unsigned bar = sb + SM_BAR;
  unsigned ph = 0;
  while (true) {
    mbar_wait(bar + 8 * MB_STGF, ph); ph ^= 1;
    int idx = misc[4];
    if (idx < 0) break;
    Item it = decode_item(idx);
    const CUtensorMap* mp = it.type == T_QKV ? &maps.qkv_st : (it.type == T_M1 ? &maps.h1 : (it.type == T_M2 ? &maps.g : &maps.o));
    unsigned* flag = it.type == T_QKV ? &g_flags.qkv[it.b * 48 + it.c] : (it.type == T_M1 ? &g_flags.h1[it.b] : (it.type == T_M2 ? &g_flags.g[it.b] : (it.b == 15 ? &g_flags.o16[it.c] : &g_flags.o[it.b * 4 + (it.c >> 2)])));
    for (int i = 0; i < 4; i++) tma_store_2d(mp, sb + B_STG + i * 16384, it.c * 256 + i * 64, it.b * 128);
    asm volatile("cp.async.bulk.commit_group;" ::: "memory");
    asm volatile("cp.async.bulk.wait_group.read 0;" ::: "memory");
    mbar_arrive(bar + 8 * MB_STGE);
    asm volatile("cp.async.bulk.wait_group 0;" ::: "memory");
    fence_proxy_async();
    red_release_add(flag, 1);
    ISTAMP(idx, 3);
  }
}
__device__ __forceinline__ float rcpf(float x) { float y; asm("rcp.approx.ftz.f32 %0, %1;" : "=f"(y) : "f"(x)); return y; }
__device__ __forceinline__ float gelu_t(float x) {
  float e = ex2f(x * fmaf(x * x, -2.0f * LOG2E * 0.7978845608028654f * 0.044715f, -2.0f * LOG2E * 0.7978845608028654f));
  return x * rcpf(1.0f + e);
}
__device__ __forceinline__ float silu_f(float x) { return x * rcpf(1.0f + ex2f(-LOG2E * x)); }
__device__ __forceinline__ unsigned badd2(unsigned a, unsigned b) { unsigned r; asm("add.rn.bf16x2 %0, %1, %2;" : "=r"(r) : "r"(a), "r"(b)); return r; }

__device__ __forceinline__ void final_out(bf16* __restrict__ out, const bf16* __restrict__ x, size_t o, float4 s) {
  uint2 gv = __ldcg(reinterpret_cast<const uint2*>(g_g + o)), xv = __ldg(reinterpret_cast<const uint2*>(x + o));
  uint2 r;
  r.x = pack_bf16(bf_lo(xv.x) + bf16r(bf16r(s.x) * bf_lo(gv.x)), bf_hi(xv.x) + bf16r(bf16r(s.y) * bf_hi(gv.x)));
  r.y = pack_bf16(bf_lo(xv.y) + bf16r(bf16r(s.z) * bf_lo(gv.y)), bf_hi(xv.y) + bf16r(bf16r(s.w) * bf_hi(gv.y)));
  *reinterpret_cast<uint2*>(out + o) = r;
}
__device__ __forceinline__ void bulk_att_load(unsigned* km, unsigned* vm, int b, int hp, int kb, int w, int lane) {
  const int g = lane >> 2, tq = lane & 3, seg = w >> 2, eh = w & 1;
  const int head = hp * 2 + (kb & 1), sg = b * 4 + (kb >> 1) * 2 + seg;
  const unsigned* kmp = reinterpret_cast<const unsigned*>(g_km + ((size_t)(sg * NH + head) * NMEM + g) * DH) + tq;
  const unsigned* vmp = reinterpret_cast<const unsigned*>(g_vmt) + ((size_t)(sg * NH + head) * DH + eh * 64) * 4 + lane;
#pragma unroll
  for (int i = 0; i < 16; i++) asm volatile("ld.global.cg.u32 %0, [%1];" : "=r"(km[i]) : "l"(kmp + i * 4) : "memory");
#pragma unroll
  for (int i = 0; i < 8; i++) asm volatile("ld.global.cg.u32 %0, [%1];" : "=r"(vm[i]) : "l"(vmp + i * 32) : "memory");
}
__device__ __forceinline__ void bulk_att_stage(unsigned sa, unsigned stg, const unsigned* km, const unsigned* vm, int kb, int w, int lane) {
  const int g = lane >> 2, tq = lane & 3, m = lane >> 3, r8 = lane & 7;
  const int seg = w >> 2, mt = (w >> 1) & 1, eh = w & 1;
  float s[5][4];
#pragma unroll
  for (int i = 0; i < 5; i++) { s[i][0] = s[i][1] = s[i][2] = s[i][3] = 0; }
  const unsigned qb = sa + (0 * 2 + seg) * 8192, kbs = sa + (1 * 2 + seg) * 8192, vb = sa + (2 * 2 + seg) * 8192 + eh * 4096;
  unsigned qa[8][4];
#pragma unroll
  for (int ks = 0; ks < 8; ks++) {
    int row = mt * 16 + (m & 1) * 8 + r8;
    ldsm_x4(qa[ks], qb + (ks >> 2) * 4096 + row * 128 + ((((ks & 3) * 2 + (m >> 1)) ^ r8) << 4));
    unsigned kf[4];
    int krow = (m >> 1) * 8 + r8;
    unsigned ka = kbs + (ks >> 2) * 4096 + krow * 128 + ((((ks & 3) * 2 + (m & 1)) ^ r8) << 4);
    ldsm_x4(kf, ka);
    mma16816(s[0], qa[ks], kf[0], kf[1]); mma16816(s[1], qa[ks], kf[2], kf[3]);
    if (mt) { ldsm_x4(kf, ka + 2048); mma16816(s[2], qa[ks], kf[0], kf[1]); mma16816(s[3], qa[ks], kf[2], kf[3]); }
  }
#pragma unroll
  for (int ks = 0; ks < 8; ks++) mma16816(s[4], qa[ks], km[2 * ks], km[2 * ks + 1]);
  float mx0 = -INFINITY, mx1 = -INFINITY;
  const int t0 = mt * 16 + g, t1 = t0 + 8;
#pragma unroll
  for (int i = 0; i < 5; i++) {
#pragma unroll
    for (int e = 0; e < 4; e++) {
      float v = s[i][e];
      if (i < 4) { int kj = i * 8 + 2 * tq + (e & 1); if (kj > (e < 2 ? t0 : t1)) v = -INFINITY; }
      s[i][e] = v;
      if (e < 2) mx0 = fmaxf(mx0, v); else mx1 = fmaxf(mx1, v);
    }
  }
  mx0 = fmaxf(mx0, __shfl_xor_sync(~0u, mx0, 1)); mx0 = fmaxf(mx0, __shfl_xor_sync(~0u, mx0, 2));
  mx1 = fmaxf(mx1, __shfl_xor_sync(~0u, mx1, 1)); mx1 = fmaxf(mx1, __shfl_xor_sync(~0u, mx1, 2));
  float sm0 = 0, sm1 = 0;
#pragma unroll
  for (int i = 0; i < 5; i++) {
    s[i][0] = ex2f((s[i][0] - mx0) * (SCALE_QK * LOG2E)); s[i][1] = ex2f((s[i][1] - mx0) * (SCALE_QK * LOG2E));
    s[i][2] = ex2f((s[i][2] - mx1) * (SCALE_QK * LOG2E)); s[i][3] = ex2f((s[i][3] - mx1) * (SCALE_QK * LOG2E));
    sm0 += s[i][0] + s[i][1]; sm1 += s[i][2] + s[i][3];
  }
  sm0 += __shfl_xor_sync(~0u, sm0, 1); sm0 += __shfl_xor_sync(~0u, sm0, 2);
  sm1 += __shfl_xor_sync(~0u, sm1, 1); sm1 += __shfl_xor_sync(~0u, sm1, 2);
  const float i0 = __fdividef(1.0f, sm0), i1 = __fdividef(1.0f, sm1);
  unsigned pa[2][4], pm0, pm1;
#pragma unroll
  for (int kk = 0; kk < 2; kk++) {
    pa[kk][0] = pack_bf16(s[2 * kk][0] * i0, s[2 * kk][1] * i0); pa[kk][1] = pack_bf16(s[2 * kk][2] * i1, s[2 * kk][3] * i1);
    pa[kk][2] = pack_bf16(s[2 * kk + 1][0] * i0, s[2 * kk + 1][1] * i0); pa[kk][3] = pack_bf16(s[2 * kk + 1][2] * i1, s[2 * kk + 1][3] * i1);
  }
  pm0 = pack_bf16(s[4][0] * i0, s[4][1] * i0); pm1 = pack_bf16(s[4][2] * i1, s[4][3] * i1);
  const int orow = (kb >> 1) * 64 + seg * 32 + mt * 16 + (m & 1) * 8 + r8;
  const unsigned ob = stg + ((kb & 1) * 2 + eh) * 16384 + orow * 128;
#pragma unroll
  for (int cp = 0; cp < 4; cp++) {
    float o0[4] = {0, 0, 0, 0}, o1[4] = {0, 0, 0, 0};
    mma1688(o0, pm0, pm1, vm[2 * cp]); mma1688(o1, pm0, pm1, vm[2 * cp + 1]);
    unsigned vf[4];
    int row = (m & 1) * 8 + r8;
    unsigned va = vb + row * 128 + (((cp * 2 + (m >> 1)) ^ r8) << 4);
    ldsm_x4_t(vf, va);
    mma16816(o0, pa[0], vf[0], vf[1]); mma16816(o1, pa[0], vf[2], vf[3]);
    if (mt) { ldsm_x4_t(vf, va + 2048); mma16816(o0, pa[1], vf[0], vf[1]); mma16816(o1, pa[1], vf[2], vf[3]); }
    stsm_x4(ob + (((cp * 2 + (m >> 1)) ^ r8) << 4), pack_bf16(o0[0], o0[1]), pack_bf16(o0[2], o0[3]), pack_bf16(o1[0], o1[1]), pack_bf16(o1[2], o1[3]));
  }
}

__device__ __forceinline__ void bulk_worker(unsigned sb, volatile int* misc, const bf16* __restrict__ x, const bf16* __restrict__ b1, const bf16* __restrict__ b2, bf16* __restrict__ out) {
  const int t = threadIdx.x, lane = t & 31, w = t >> 5, wg = w >> 2, g = lane >> 2, tq = lane & 3, m = lane >> 3, r8 = lane & 7;
  const unsigned bar = sb + SM_BAR;
  unsigned st = 0, ph = 0, seq = 0, sph = 0;
  float d[128];
  while (true) {
    mbar_wait(bar + 8 * (MB_FULL + st), ph);
    const int idr = misc[seq & 3]; seq++;
    const int idx = idr & 65535;
    if (idr < 0 || idx >= N_ITEMS) break;
    if (t == 0) ISTAMP(idx, 2);
    const Item it = decode_item(idx);
    const int nkb = item_nkb(it.type);
    if (it.type == T_ATT) {
      unsigned km[16], vm[8], kn[16], vn[8];
      const bool pref = idr >= 65536;
      if (pref) bulk_att_load(kn, vn, it.b, it.c, 0, w, lane);
      mbar_wait(bar + 8 * MB_STGE, sph ^ 1);
#pragma unroll 1
      for (int kb = 0; kb < 4; kb++) {
        if (!pref) {
          if (lane < 2) wait_flag_ge(&g_flags.rec[it.c * 4 + (kb & 1) * 2 + lane], it.b * 4 + (kb >> 1) * 2 + wg + 1);
          __syncwarp();
          bulk_att_load(kn, vn, it.b, it.c, kb, w, lane);
        }
        if (kb) mbar_wait(bar + 8 * (MB_FULL + st), ph);
#pragma unroll
        for (int i = 0; i < 16; i++) km[i] = kn[i];
#pragma unroll
        for (int i = 0; i < 8; i++) vm[i] = vn[i];
        if (pref && kb != 3) bulk_att_load(kn, vn, it.b, it.c, kb + 1, w, lane);
        bulk_att_stage(sb + st * STAGE_BYTES, sb + B_STG, km, vm, kb, w, lane);
        __syncwarp();
        if (lane == 0) mbar_arrive(bar + 8 * (MB_EMPTY + st));
        if (++st == NSTAGE) { st = 0; ph ^= 1; }
      }
      if (t == 0) misc[4] = idx;
      fence_proxy_async_smem();
      mbar_arrive(bar + 8 * MB_STGF); sph ^= 1;
      continue;
    }
    if (it.type >= T_RED) {
      __syncwarp();
      if (lane == 0) mbar_arrive(bar + 8 * (MB_EMPTY + st));
      if (++st == NSTAGE) { st = 0; ph ^= 1; }
      if (it.type == T_RED) {
#pragma unroll 2
        for (int i = 0; i < 8; i++) {
          size_t o = ((size_t)it.b * 128 + it.c * 16 + i * 2 + (t >> 7)) * DM + (t & 127) * 4;
          float4 a = __ldcg(reinterpret_cast<const float4*>(g_opart + o)), b = __ldcg(reinterpret_cast<const float4*>(g_opart + o + (size_t)S_TOK * DM));
          float4 c = __ldcg(reinterpret_cast<const float4*>(g_opart + o + (size_t)2 * S_TOK * DM)), e = __ldcg(reinterpret_cast<const float4*>(g_opart + o + (size_t)3 * S_TOK * DM));
          final_out(out, x, o, make_float4((a.x + b.x) + (c.x + e.x), (a.y + b.y) + (c.y + e.y), (a.z + b.z) + (c.z + e.z), (a.w + b.w) + (c.w + e.w)));
        }
      } else {
        size_t ol = ((size_t)it.c * 2 + (t >> 7)) * DM + (t & 127) * 4;
        float4 v[16];
#pragma unroll
        for (int i = 0; i < 16; i++) v[i] = __ldcg(reinterpret_cast<const float4*>(g_opl + ol + (size_t)i * 128 * DM));
#pragma unroll
        for (int st2 = 1; st2 < 16; st2 <<= 1)
#pragma unroll
          for (int i = 0; i < 16; i += 2 * st2) { v[i].x += v[i + st2].x; v[i].y += v[i + st2].y; v[i].z += v[i + st2].z; v[i].w += v[i + st2].w; }
        final_out(out, x, ol + (size_t)15 * 128 * DM, v[0]);
      }
      if (t == 0) ISTAMP(idx, 3);
      continue;
    }
    unsigned pst = 0, bv[32];
#pragma unroll
    for (int i = 0; i < 128; i++) d[i] = 0.0f;
    if (it.type == T_M1 || it.type == T_M2) {
      const unsigned* bp = reinterpret_cast<const unsigned*>((it.type == T_M1 ? b1 : b2) + it.c * 256) + tq;
#pragma unroll
      for (int i = 0; i < 32; i++) asm volatile("ld.global.nc.u32 %0, [%1];" : "=r"(bv[i]) : "l"(bp + i * 4));
    } else {
#pragma unroll
      for (int i = 0; i < 32; i++) bv[i] = 0;
    }
    for (int kb = 0; kb < nkb; kb++) {
      if (kb) mbar_wait(bar + 8 * (MB_FULL + st), ph);
      unsigned sa = sb + st * STAGE_BYTES;
      uint64_t ad = mkdesc(sa + wg * 8192, 16, 1024), bd = mkdesc(sa + 16384, 8192, 1024);
      asm volatile("wgmma.fence.sync.aligned;" ::: "memory");
#pragma unroll
      for (int k = 0; k < 4; k++) wgmma_n256(d, ad + k * 2, bd + k * 128, (kb | k) != 0);
      asm volatile("wgmma.commit_group.sync.aligned;" ::: "memory");
      if (kb) {
        asm volatile("wgmma.wait_group.sync.aligned 1;" ::: "memory");
        if (lane == 0) mbar_arrive(bar + 8 * (MB_EMPTY + pst));
      }
      pst = st;
      if (++st == NSTAGE) { st = 0; ph ^= 1; }
    }
    asm volatile("wgmma.wait_group.sync.aligned 0;" ::: "memory");
    if (lane == 0) mbar_arrive(bar + 8 * (MB_EMPTY + pst));
    if (it.type >= T_OUT) {
      const int col = it.c * 256 + 2 * tq;
      float* pp = it.type == T_OUT ? g_opart + ((size_t)it.ks * S_TOK + it.b * 128 + w * 16 + g) * DM + col : g_opl + ((size_t)it.ks * 128 + w * 16 + g) * DM + col;
#pragma unroll
      for (int i = 0; i < 32; i++) {
        __stcg(reinterpret_cast<float2*>(pp + i * 8), make_float2(d[4 * i], d[4 * i + 1]));
        __stcg(reinterpret_cast<float2*>(pp + 8 * DM + i * 8), make_float2(d[4 * i + 2], d[4 * i + 3]));
      }
      bar_sync(1, 256);
      if (t == 0) { red_release_add(&g_flags.p[it.b], 1); ISTAMP(idx, 3); }
      continue;
    }
#define ACT(F) _Pragma("unroll") for (int i = 0; i < 32; i++) { \
        unsigned u0 = badd2(pack_bf16(d[4 * i], d[4 * i + 1]), bv[i]), u1 = badd2(pack_bf16(d[4 * i + 2], d[4 * i + 3]), bv[i]); \
        d[4 * i] = F(bf_lo(u0)); d[4 * i + 1] = F(bf_hi(u0)); d[4 * i + 2] = F(bf_lo(u1)); d[4 * i + 3] = F(bf_hi(u1)); }
    if (it.type == T_M1) { ACT(gelu_t) } else if (it.type == T_M2) { ACT(silu_f) }
    mbar_wait(bar + 8 * MB_STGE, sph ^ 1);
    {
      const unsigned ob = sb + B_STG + (w * 16 + (m & 1) * 8 + r8) * 128;
#pragma unroll
      for (int i = 0; i < 16; i++)
        stsm_x4(ob + (i >> 2) * 16384 + ((((i & 3) * 2 + (m >> 1)) ^ r8) << 4), pack_bf16(d[8 * i], d[8 * i + 1]), pack_bf16(d[8 * i + 2], d[8 * i + 3]),
                pack_bf16(d[8 * i + 4], d[8 * i + 5]), pack_bf16(d[8 * i + 6], d[8 * i + 7]));
    }
    if (t == 0) misc[4] = idx;
    fence_proxy_async_smem();
    mbar_arrive(bar + 8 * MB_STGF); sph ^= 1;
  }
  mbar_wait(bar + 8 * MB_STGE, sph ^ 1);
  if (t == 0) misc[4] = -1;
  mbar_arrive(bar + 8 * MB_STGF);
}

__global__ void __launch_bounds__(384, 1)
k_main(const __grid_constant__ Maps maps, const bf16* __restrict__ x, const bf16* __restrict__ mem0, const bf16* __restrict__ b1, const bf16* __restrict__ b2, bf16* __restrict__ out, int helper) {
  extern __shared__ unsigned char smem_raw[];
  const unsigned sraw = smem_u32(smem_raw);
  const unsigned sb = (sraw + 1023u) & ~1023u;
  int* misc = reinterpret_cast<int*>(smem_raw + (sb - sraw) + SM_MISC);
  const int w = threadIdx.x >> 5;
  const bool rec = !helper && blockIdx.x < NREC;
  if (!helper) asm volatile("griddepcontrol.launch_dependents;");
  if (threadIdx.x == 0) {
    const unsigned bar = sb + SM_BAR;
    for (int i = 0; i < 8; i++) { mbar_init(bar + 8 * (MB_FULL + i), 1); mbar_init(bar + 8 * (MB_EMPTY + i), rec ? 1 : 8); }
    mbar_init(bar + 8 * MB_STGF, 256); mbar_init(bar + 8 * MB_STGE, 1);
    for (int i = MB_W0; i <= MB_AG; i++) mbar_init(bar + 8 * i, 1);
    if (rec) { mbar_expect_tx(bar + 8 * MB_S, 2560); mbar_expect_tx(bar + 8 * MB_V, 2048); mbar_expect_tx(bar + 8 * MB_RS, 8192); mbar_expect_tx(bar + 8 * MB_AG, 8192); }
    asm volatile("fence.mbarrier_init.release.cluster;" ::: "memory");
  }
  __syncthreads();
  asm volatile("barrier.cluster.arrive.release.aligned;\nbarrier.cluster.wait.acquire.aligned;" ::: "memory");
  if (DBGMODE && !rec) { if (helper) asm volatile("griddepcontrol.wait;" ::: "memory"); return; }
  if (w >= 8) {
    asm volatile("setmaxnreg.dec.sync.aligned.u32 40;");
    if (rec) rec_aux(maps, sb);
    else if (w == 8) bulk_producer(maps, sb, misc);
    else if ((threadIdx.x & 31) == 0) { if (w == 9) bulk_store(maps, sb, misc);
      else if (w == 10 && helper) asm volatile("griddepcontrol.wait;" ::: "memory"); }
  } else {
    if (rec) { asm volatile("setmaxnreg.inc.sync.aligned.u32 232;"); rec_worker(maps, sb, mem0); }
    else { asm volatile("setmaxnreg.inc.sync.aligned.u32 232;"); bulk_worker(sb, misc, x, b1, b2, out); }
  }
}

typedef CUresult (*EncFn)(CUtensorMap*, CUtensorMapDataType, cuuint32_t, void*, const cuuint64_t*, const cuuint64_t*, const cuuint32_t*, const cuuint32_t*,
                          CUtensorMapInterleave, CUtensorMapSwizzle, CUtensorMapL2promotion, CUtensorMapFloatOOBfill);
static void mk_map(EncFn enc, CUtensorMap* m, const void* ptr, uint64_t rows, uint64_t cols, uint32_t box_rows) {
  cuuint64_t dims[2] = {cols, rows}; cuuint64_t strides[1] = {cols * 2};
  cuuint32_t box[2] = {64, box_rows}, es[2] = {1, 1};
  enc(m, CU_TENSOR_MAP_DATA_TYPE_BFLOAT16, 2, const_cast<void*>(ptr), dims, strides, box, es, CU_TENSOR_MAP_INTERLEAVE_NONE, CU_TENSOR_MAP_SWIZZLE_128B,
      CU_TENSOR_MAP_L2_PROMOTION_L2_256B, CU_TENSOR_MAP_FLOAT_OOB_FILL_NONE);
}
extern "C" void kernel_launch(void* const* d_in, const int* in_sizes, int n_in, void* d_out, int out_size) {
  static EncFn enc = nullptr;
  static int ncl = 0, nhelp = 0;
  static void *p_xn, *p_y, *p_h1, *p_o, *p_qkv, *p_g;
  if (!enc) {
    void* fn = nullptr; cudaDriverEntryPointQueryResult qr;
    cudaGetDriverEntryPoint("cuTensorMapEncodeTiled", &fn, cudaEnableDefault, &qr);
    enc = (EncFn)fn;
    cudaGetSymbolAddress(&p_xn, g_xn); cudaGetSymbolAddress(&p_y, g_y); cudaGetSymbolAddress(&p_h1, g_h1);
    cudaGetSymbolAddress(&p_o, g_o); cudaGetSymbolAddress(&p_qkv, g_qkv); cudaGetSymbolAddress(&p_g, g_g);
    cudaFuncSetAttribute(k_main, cudaFuncAttributeMaxDynamicSharedMemorySize, SMEM_TOTAL);
    cudaLaunchConfig_t cfg = {}; cfg.gridDim = dim3(128); cfg.blockDim = dim3(384); cfg.dynamicSmemBytes = SMEM_TOTAL;
    cudaLaunchAttribute at[1]; at[0].id = cudaLaunchAttributeClusterDimension; at[0].val.clusterDim.x = CLS; at[0].val.clusterDim.y = 1; at[0].val.clusterDim.z = 1;
    cfg.attrs = at; cfg.numAttrs = 1;
    if (cudaOccupancyMaxActiveClusters(&ncl, k_main, &cfg) != cudaSuccess) { cudaGetLastError(); ncl = 14; }
    ncl = ncl > 16 ? 16 : (ncl < 9 ? 9 : ncl);
    int nsm = 0, dev = 0; cudaGetDevice(&dev); cudaDeviceGetAttribute(&nsm, cudaDevAttrMultiProcessorCount, dev);
    nhelp = nsm - ncl * CLS;
  }
  Maps maps;
  mk_map(enc, &maps.xn, p_xn, S_TOK, DM, 128); mk_map(enc, &maps.y, p_y, S_TOK, DM, 128); mk_map(enc, &maps.h1, p_h1, S_TOK, FF, 128);
  mk_map(enc, &maps.o, p_o, S_TOK, HD, 128); mk_map(enc, &maps.qkv_st, p_qkv, S_TOK, 3 * HD, 128); mk_map(enc, &maps.qkv_ld, p_qkv, S_TOK, 3 * HD, 32);
  mk_map(enc, &maps.g, p_g, S_TOK, DM, 128);
  mk_map(enc, &maps.wq, d_in[2], DM, HD, 64); mk_map(enc, &maps.wk, d_in[3], DM, HD, 64); mk_map(enc, &maps.wv, d_in[4], DM, HD, 64);
  mk_map(enc, &maps.wo, d_in[5], HD, DM, 64); mk_map(enc, &maps.w1, d_in[8], DM, FF, 64); mk_map(enc, &maps.w2, d_in[10], FF, DM, 64);
  cudaStream_t st = cudaStreamPerThread;
  k_pre<<<256, 256, 0, st>>>((const bf16*)d_in[0]);
  cudaLaunchConfig_t cfg = {}; cfg.gridDim = dim3(ncl * CLS); cfg.blockDim = dim3(384); cfg.dynamicSmemBytes = SMEM_TOTAL; cfg.stream = st;
  cudaLaunchAttribute at[1]; at[0].id = cudaLaunchAttributeClusterDimension; at[0].val.clusterDim.x = CLS; at[0].val.clusterDim.y = 1; at[0].val.clusterDim.z = 1;
  cfg.attrs = at; cfg.numAttrs = 1;
  cudaLaunchKernelEx(&cfg, k_main, maps, (const bf16*)d_in[0], (const bf16*)d_in[1], (const bf16*)d_in[9], (const bf16*)d_in[11], (bf16*)d_out, 0);
  if (nhelp > 0) {
    cfg.gridDim = dim3(nhelp);
    at[0].id = cudaLaunchAttributeProgrammaticStreamSerialization; at[0].val.programmaticStreamSerializationAllowed = 1;
    cudaLaunchKernelEx(&cfg, k_main, maps, (const bf16*)d_in[0], (const bf16*)d_in[1], (const bf16*)d_in[9], (const bf16*)d_in[11], (bf16*)d_out, 1);
  }
}
```

```cpp
#include <cuda_runtime.h>
#include <cuda_bf16.h>
#include <cuda.h>
#include <stdint.h>

typedef __nv_bfloat16 bf16;

#define S_TOK 2048
#define DM 512
#define NH 32
#define DH 128
#define HD 4096
#define NMEM 8
#define SEG 32
#define NSEG 64
#define FF 1792
#define NBLK 16
#define NREC 64
#define REPL 0
#define CLS 8

__device__ __align__(1024) bf16 g_xn[S_TOK * DM];
__device__ __align__(1024) bf16 g_y[S_TOK * DM];
__device__ __align__(1024) bf16 g_qkv[(size_t)S_TOK * 3 * HD];
__device__ __align__(1024) bf16 g_h1[S_TOK * FF];
__device__ __align__(1024) bf16 g_g[S_TOK * DM];
__device__ __align__(1024) bf16 g_o[(size_t)S_TOK * HD];
__device__ __align__(1024) bf16 g_km[NSEG * NH * NMEM * DH];
__device__ __align__(1024) bf16 g_vmt[NSEG * NH * DH * NMEM];
__device__ __align__(1024) float g_opart[(size_t)4 * S_TOK * DM];
__device__ __align__(1024) float g_opl[(size_t)16 * 128 * DM];
__device__ __align__(1024) unsigned g_part[8 * 2 * 8 * 8 * 512];
struct Flags {
  unsigned qkv[NBLK * 48];
  unsigned h1[NBLK];
  unsigned g[NBLK];
  unsigned o[NBLK * 4];
  unsigned p[NBLK];
  unsigned o16[16];
  unsigned ctr;
  unsigned rec[NREC];
  unsigned abort_;
};
__device__ __align__(1024) Flags g_flags;

#define RSTAMP(k)
#define DBGMODE 0
#define ISTAMP(i, k)
__device__ __forceinline__ unsigned smem_u32(const void* p) { return (unsigned)__cvta_generic_to_shared(p); }
__device__ __forceinline__ float bf16r(float x) { unsigned u; asm("cvt.rn.bf16x2.f32 %0, %1, %2;" : "=r"(u) : "f"(x), "f"(0.0f)); return __uint_as_float(u); }
__device__ __forceinline__ unsigned pack_bf16(float lo, float hi) {
  __nv_bfloat162 v = __floats2bfloat162_rn(lo, hi);
  return *reinterpret_cast<unsigned*>(&v);
}
__device__ __forceinline__ float bf_lo(unsigned u) { return __uint_as_float(u << 16); }
__device__ __forceinline__ float bf_hi(unsigned u) { return __uint_as_float(u & 0xffff0000u); }

#define SPIN_LIMIT (1u << 20)
#define TRAP_IF(x) if ((x) > SPIN_LIMIT) { asm volatile("st.global.u32 [%0], %1;" ::"l"(0ull), "r"(0u) : "memory"); break; }
__device__ __forceinline__ unsigned ld_acquire(const unsigned* p) {
  unsigned v; asm volatile("ld.acquire.gpu.global.u32 %0, [%1];" : "=r"(v) : "l"(p) : "memory"); return v;
}
__device__ __forceinline__ unsigned ld_relaxed(const unsigned* p) {
  unsigned v; asm volatile("ld.relaxed.gpu.global.u32 %0, [%1];" : "=r"(v) : "l"(p) : "memory"); return v;
}
__device__ __forceinline__ void red_release_add(unsigned* p, unsigned v) {
  asm volatile("red.release.gpu.global.add.u32 [%0], %1;" ::"l"(p), "r"(v) : "memory");
}
__device__ __forceinline__ void st_release(unsigned* p, unsigned v) {
  asm volatile("st.release.gpu.global.u32 [%0], %1;" ::"l"(p), "r"(v) : "memory");
}
__device__ __forceinline__ void wait_flag_ge(const unsigned* p, unsigned target) {
  unsigned it = 0;
  while (ld_acquire(p) < target) {
    __nanosleep(64);
    TRAP_IF(++it);
  }
}
__device__ __forceinline__ uint4 ldv4_relaxed(const void* p) {
  uint4 a; asm volatile("ld.relaxed.gpu.global.v4.u32 {%0,%1,%2,%3}, [%4];" : "=r"(a.x), "=r"(a.y), "=r"(a.z), "=r"(a.w) : "l"(p) : "memory"); return a;
}
__device__ __forceinline__ uint2 ldv2_relaxed(const void* p) {
  uint2 a; asm volatile("ld.relaxed.gpu.global.v2.u32 {%0,%1}, [%2];" : "=r"(a.x), "=r"(a.y) : "l"(p) : "memory"); return a;
}
__device__ __forceinline__ void mbar_init(unsigned mb, unsigned cnt) { asm volatile("mbarrier.init.shared::cta.b64 [%0], %1;" ::"r"(mb), "r"(cnt) : "memory"); }
__device__ __forceinline__ void mbar_expect_tx(unsigned mb, unsigned bytes) { asm volatile("mbarrier.arrive.expect_tx.shared::cta.b64 _, [%0], %1;" ::"r"(mb), "r"(bytes) : "memory"); }
__device__ __forceinline__ void mbar_arrive(unsigned mb) { asm volatile("mbarrier.arrive.shared::cta.b64 _, [%0];" ::"r"(mb) : "memory"); }
__device__ __forceinline__ void mbar_wait(unsigned mb, unsigned parity) {
  unsigned ok, it = 0;
  while (true) {
    asm volatile("{.reg .pred p; mbarrier.try_wait.parity.shared::cta.b64 p, [%1], %2; selp.u32 %0,1,0,p;}" : "=r"(ok) : "r"(mb), "r"(parity) : "memory");
    if (ok) break;
    TRAP_IF(++it);
  }
}
__device__ __forceinline__ void mbar_wait_sleep(unsigned mb, unsigned parity) {
  unsigned ok, it = 0;
  while (true) {
    asm volatile("{.reg .pred p; mbarrier.test_wait.parity.shared::cta.b64 p, [%1], %2; selp.u32 %0,1,0,p;}" : "=r"(ok) : "r"(mb), "r"(parity) : "memory");
    if (ok) break;
    __nanosleep(200);
    TRAP_IF(++it);
  }
}
__device__ __forceinline__ float ex2f(float x) { float y; asm("ex2.approx.ftz.f32 %0, %1;" : "=f"(y) : "f"(x)); return y; }
__device__ __forceinline__ int opaque_tid() { int t = threadIdx.x; t = __shfl_sync(~0u, t, t & 31); return t; }
#define LOG2E 1.4426950408889634f
__device__ __forceinline__ void mbar_wait_cluster(unsigned mb, unsigned parity) {
  unsigned ok, it = 0;
  while (true) {
    asm volatile("{.reg .pred p; mbarrier.try_wait.parity.acquire.cluster.shared::cta.b64 p, [%1], %2; selp.u32 %0,1,0,p;}" : "=r"(ok) : "r"(mb), "r"(parity) : "memory");
    if (ok) break;
    TRAP_IF(++it);
  }
}
__device__ __forceinline__ void bar_sync(int id, int n) { asm volatile("bar.sync %0, %1;" ::"r"(id), "r"(n) : "memory"); }
__device__ __forceinline__ void bar_arrive(int id, int n) { asm volatile("bar.arrive %0, %1;" ::"r"(id), "r"(n) : "memory"); }
__device__ __forceinline__ void tma_load_2d(unsigned dst, const CUtensorMap* map, int c0, int c1, unsigned mb) {
  asm volatile("cp.async.bulk.tensor.2d.shared::cluster.global.mbarrier::complete_tx::bytes [%0], [%1, {%3, %4}], [%2];"
               ::"r"(dst), "l"((uint64_t)map), "r"(mb), "r"(c0), "r"(c1) : "memory");
}
__device__ __forceinline__ void tma_store_2d(const CUtensorMap* map, unsigned src, int c0, int c1) {
  asm volatile("cp.async.bulk.tensor.2d.global.shared::cta.bulk_group [%0, {%2, %3}], [%1];"
               ::"l"((uint64_t)map), "r"(src), "r"(c0), "r"(c1) : "memory");
}
__device__ __forceinline__ void fence_proxy_async() { asm volatile("fence.proxy.async;" ::: "memory"); }
__device__ __forceinline__ void fence_proxy_async_smem() { asm volatile("fence.proxy.async.shared::cta;" ::: "memory"); }
__device__ __forceinline__ void ldsm_x4(unsigned* r, unsigned addr) {
  asm volatile("ldmatrix.sync.aligned.m8n8.x4.shared.b16 {%0,%1,%2,%3}, [%4];" : "=r"(r[0]), "=r"(r[1]), "=r"(r[2]), "=r"(r[3]) : "r"(addr) : "memory");
}
__device__ __forceinline__ void ldsm_x4_t(unsigned* r, unsigned addr) {
  asm volatile("ldmatrix.sync.aligned.m8n8.x4.trans.shared.b16 {%0,%1,%2,%3}, [%4];" : "=r"(r[0]), "=r"(r[1]), "=r"(r[2]), "=r"(r[3]) : "r"(addr) : "memory");
}
__device__ __forceinline__ void stsm_x2_t(unsigned addr, unsigned r0, unsigned r1) {
  asm volatile("stmatrix.sync.aligned.m8n8.x2.trans.shared.b16 [%0], {%1,%2};" ::"r"(addr), "r"(r0), "r"(r1) : "memory");
}
__device__ __forceinline__ void stsm_x4(unsigned addr, unsigned r0, unsigned r1, unsigned r2, unsigned r3) {
  asm volatile("stmatrix.sync.aligned.m8n8.x4.shared.b16 [%0], {%1,%2,%3,%4};" ::"r"(addr), "r"(r0), "r"(r1), "r"(r2), "r"(r3) : "memory");
}
__device__ __forceinline__ void mma16816(float* d, const unsigned* a, unsigned b0, unsigned b1) {
  asm volatile("mma.sync.aligned.m16n8k16.row.col.f32.bf16.bf16.f32 {%0,%1,%2,%3}, {%4,%5,%6,%7}, {%8,%9}, {%0,%1,%2,%3};"
               : "+f"(d[0]), "+f"(d[1]), "+f"(d[2]), "+f"(d[3]) : "r"(a[0]), "r"(a[1]), "r"(a[2]), "r"(a[3]), "r"(b0), "r"(b1));
}
__device__ __forceinline__ void mma1688(float* d, unsigned a0, unsigned a1, unsigned b0) {
  asm volatile("mma.sync.aligned.m16n8k8.row.col.f32.bf16.bf16.f32 {%0,%1,%2,%3}, {%4,%5}, {%6}, {%0,%1,%2,%3};"
               : "+f"(d[0]), "+f"(d[1]), "+f"(d[2]), "+f"(d[3]) : "r"(a0), "r"(a1), "r"(b0));
}
__device__ __forceinline__ uint64_t mkdesc(unsigned addr, unsigned lbo, unsigned sbo) {
  return (uint64_t)((addr >> 4) & 0x3fff) | ((uint64_t)(lbo >> 4) << 16) | ((uint64_t)(sbo >> 4) << 32) | (1ull << 62);
}
#define R8(b) "+f"(d[b]), "+f"(d[b + 1]), "+f"(d[b + 2]), "+f"(d[b + 3]), "+f"(d[b + 4]), "+f"(d[b + 5]), "+f"(d[b + 6]), "+f"(d[b + 7])
#define R32(b) R8(b), R8(b + 8), R8(b + 16), R8(b + 24)
__device__ __forceinline__ void wgmma_n256(float* d, uint64_t ad, uint64_t bd, int acc) {
  asm volatile(
      "{.reg .pred p; setp.ne.b32 p, %130, 0;\n"
      "wgmma.mma_async.sync.aligned.m64n256k16.f32.bf16.bf16 "
      "{%0,%1,%2,%3,%4,%5,%6,%7,%8,%9,%10,%11,%12,%13,%14,%15,%16,%17,%18,%19,%20,%21,%22,%23,%24,%25,%26,%27,%28,%29,%30,%31,"
      "%32,%33,%34,%35,%36,%37,%38,%39,%40,%41,%42,%43,%44,%45,%46,%47,%48,%49,%50,%51,%52,%53,%54,%55,%56,%57,%58,%59,%60,%61,%62,%63,"
      "%64,%65,%66,%67,%68,%69,%70,%71,%72,%73,%74,%75,%76,%77,%78,%79,%80,%81,%82,%83,%84,%85,%86,%87,%88,%89,%90,%91,%92,%93,%94,%95,"
      "%96,%97,%98,%99,%100,%101,%102,%103,%104,%105,%106,%107,%108,%109,%110,%111,%112,%113,%114,%115,%116,%117,%118,%119,%120,%121,%122,%123,%124,%125,%126,%127},"
      "%128, %129, p, 1, 1, 0, 1;}\n"
      : R32(0), R32(32), R32(64), R32(96)
      : "l"(ad), "l"(bd), "r"(acc));
}

__device__ __forceinline__ void ln16(const float* x, float* o) {
  float s = 0;
#pragma unroll
  for (int i = 0; i < 16; i++) s += x[i];
#pragma unroll
  for (int of = 16; of > 0; of >>= 1) s += __shfl_xor_sync(~0u, s, of);
  float mean = s * (1.0f / DM);
  float v = 0;
#pragma unroll
  for (int i = 0; i < 16; i++) { float dd = x[i] - mean; v += dd * dd; }
#pragma unroll
  for (int of = 16; of > 0; of >>= 1) v += __shfl_xor_sync(~0u, v, of);
  float mb = bf16r(mean);
  float vb = bf16r(v * (1.0f / DM));
  float den = bf16r(sqrtf(bf16r(vb + 1e-5f)));
#pragma unroll
  for (int i = 0; i < 16; i++) o[i] = bf16r(__fdiv_rn(bf16r(x[i] - mb), den));
}
__global__ void __launch_bounds__(256) k_pre(const bf16* __restrict__ x) {
  int t = threadIdx.x, lane = t & 31, w = t >> 5;
  int row = blockIdx.x * 8 + w;
  const uint4* src = reinterpret_cast<const uint4*>(x + (size_t)row * DM);
  uint4 a = src[lane], b = src[lane + 32];
  unsigned u[8] = {a.x, a.y, a.z, a.w, b.x, b.y, b.z, b.w};
  float f[16], o[16], o2[16];
#pragma unroll
  for (int i = 0; i < 8; i++) { f[2 * i] = bf_lo(u[i]); f[2 * i + 1] = bf_hi(u[i]); }
  ln16(f, o);
  ln16(o, o2);
  uint4* d1 = reinterpret_cast<uint4*>(g_xn + (size_t)row * DM);
  uint4* d2 = reinterpret_cast<uint4*>(g_y + (size_t)row * DM);
  d1[lane] = make_uint4(pack_bf16(o[0], o[1]), pack_bf16(o[2], o[3]), pack_bf16(o[4], o[5]), pack_bf16(o[6], o[7]));
  d1[lane + 32] = make_uint4(pack_bf16(o[8], o[9]), pack_bf16(o[10], o[11]), pack_bf16(o[12], o[13]), pack_bf16(o[14], o[15]));
  d2[lane] = make_uint4(pack_bf16(o2[0], o2[1]), pack_bf16(o2[2], o2[3]), pack_bf16(o2[4], o2[5]), pack_bf16(o2[6], o2[7]));
  d2[lane + 32] = make_uint4(pack_bf16(o2[8], o2[9]), pack_bf16(o2[10], o2[11]), pack_bf16(o2[12], o2[13]), pack_bf16(o2[14], o2[15]));
  int gt = blockIdx.x * 256 + t;
  uint4 z = make_uint4(0, 0, 0, 0);
  if (gt < 16384) reinterpret_cast<uint4*>(g_part)[gt] = z;
  if (gt < (int)(sizeof(Flags) / 4)) reinterpret_cast<unsigned*>(&g_flags)[gt] = 0;
}

struct Maps { CUtensorMap xn, y, h1, o, qkv_st, qkv_ld, g, wq, wk, wv, wo, w1, w2; };

#define NSTAGE 3
#define STAGE_BYTES 49152
#define B_STG (NSTAGE * STAGE_BYTES)
#define R_WO 0
#define R_T1 65536
#define R_T2 131072
#define R_RING 65536
#define RING_N 4
#define RING_BYTES 12288
#define R_MEM 196608
#define R_QS (R_MEM + 8448)
#define R_KS (R_QS + 1152)
#define R_OS (R_KS + 1152)
#define R_SOWN (R_OS + 2176)
#define R_SPEER (R_SOWN + 1280)
#define R_VM (R_SPEER + 1280)
#define R_VRED (R_VM + 2048)
#define R_RS (R_VRED + 6144)
#define SM_BAR (R_RS + 8192)
#define SMEM_TOTAL (SM_BAR + 256 + 1024)
#define MB_FULL 0
#define MB_EMPTY 8
#define MB_STGF 16
#define MB_STGE 17
#define MB_W0 18
#define MB_W1 19
#define MB_WO 20
#define MB_S 21
#define MB_V 22
#define MB_KVR 23
#define MB_KVF 24
#define MB_RS 25
#define MB_AG 26
#define SM_MISC (SM_BAR + 224)

#define N_KV 512
#define I_M1 512
#define I_Q 624
#define I_M2 880
#define I_POST 912
#define I_TAIL (I_POST + 16 * 32)
#define N_ITEMS (I_TAIL + 5 * 8 + 32 + 8 + 64)
enum { T_QKV = 0, T_M1 = 1, T_M2 = 2, T_ATT = 3, T_OUT = 4, T_OUTL = 5, T_RED = 6, T_REDL = 7 };
struct Item { int type, b, c, ks; };
__device__ __forceinline__ Item decode_item(int i) {
  Item it; it.ks = 0;
  if (i < N_KV) { it.type = T_QKV; it.b = i >> 5; it.c = 16 + (i & 31); }
  else if (i < I_Q) { it.type = T_M1; it.b = (i - I_M1) / 7; it.c = (i - I_M1) % 7; }
  else if (i < I_M2) { it.type = T_QKV; it.b = (i - I_Q) >> 4; it.c = (i - I_Q) & 15; }
  else if (i < I_POST) { it.type = T_M2; it.b = (i - I_M2) >> 1; it.c = (i - I_M2) & 1; }
  else if (i < I_TAIL) {
    int x = i - I_POST, p = x >> 5, r = x & 31;
    if (r < 16) { it.type = T_ATT; it.b = p; it.c = r; }
    else if (r < 24) { it.type = T_OUT; it.b = p - 3; it.c = r & 1; it.ks = (r - 16) >> 1; }
    else { it.type = T_RED; it.b = p - 5; it.c = r - 24; }
  } else {
    int x = i - I_TAIL, r = x & 7;
    if (x < 40) {
      int q = x >> 3;
      if (q == 0 || q == 2) { it.type = T_OUT; it.b = 13 + (q >> 1); it.c = r & 1; it.ks = r >> 1; }
      else { it.type = T_RED; it.b = q == 1 ? 11 : 9 + q; it.c = r; }
    }
    else if (x < 72) { it.type = T_OUTL; it.b = 15; it.c = x & 1; it.ks = (x - 40) >> 1; }
    else if (x < 80) { it.type = T_RED; it.b = 14; it.c = r; }
    else { it.type = T_REDL; it.b = 15; it.c = x - 80; }
  }
  return it;
}
__device__ __forceinline__ int item_nkb(int type) { return type == T_M2 ? 28 : (type == T_OUT ? 16 : (type >= T_RED ? 1 : (type >= T_ATT ? 4 : 8))); }

__device__ __forceinline__ void st_async_b64(unsigned raddr, unsigned lo, unsigned hi, unsigned rmb) {
  asm volatile("st.async.weak.shared::cluster.mbarrier::complete_tx::bytes.v2.b32 [%0], {%1,%2}, [%3];" ::"r"(raddr), "r"(lo), "r"(hi), "r"(rmb) : "memory");
}
__device__ __forceinline__ void st_async_b32(unsigned raddr, unsigned v, unsigned rmb) {
  asm volatile("st.async.weak.shared::cluster.mbarrier::complete_tx::bytes.b32 [%0], %1, [%2];" ::"r"(raddr), "r"(v), "r"(rmb) : "memory");
}
__device__ __forceinline__ unsigned mapa(unsigned a, unsigned rank) {
  unsigned r; asm volatile("mapa.shared::cluster.u32 %0, %1, %2;" : "=r"(r) : "r"(a), "r"(rank)); return r;
}
__device__ __forceinline__ void sts64(unsigned a, unsigned x, unsigned y) { asm volatile("st.shared.v2.b32 [%0], {%1,%2};" ::"r"(a), "r"(x), "r"(y) : "memory"); }
__device__ __forceinline__ void sts128(unsigned a, uint4 v) { asm volatile("st.shared.v4.b32 [%0], {%1,%2,%3,%4};" ::"r"(a), "r"(v.x), "r"(v.y), "r"(v.z), "r"(v.w) : "memory"); }
__device__ __forceinline__ uint2 lds64(unsigned a) { uint2 v; asm volatile("ld.shared.v2.b32 {%0,%1}, [%2];" : "=r"(v.x), "=r"(v.y) : "r"(a) : "memory"); return v; }
__device__ __forceinline__ uint4 lds128(unsigned a) { uint4 v; asm volatile("ld.shared.v4.b32 {%0,%1,%2,%3}, [%4];" : "=r"(v.x), "=r"(v.y), "=r"(v.z), "=r"(v.w) : "r"(a) : "memory"); return v; }
__device__ __forceinline__ float lds32f(unsigned a) { float v; asm volatile("ld.shared.f32 %0, [%1];" : "=f"(v) : "r"(a) : "memory"); return v; }
#define spin_check(it) TRAP_IF(++it)
#define POLLV 0
#define BAR8 0
#define D_STAG 150
#define D_RED 480
#define D_PUB 0
#define DELAY(n) do { unsigned c0_, c1_; asm volatile("mov.u32 %0, %%clock;" : "=r"(c0_)); do { asm volatile("mov.u32 %0, %%clock;" : "=r"(c1_)); } while (c1_ - c0_ < (n)); } while (0)
#define VD 1
#define NPRE 2
#define SCALE_QK 0.08838834764831845f

__device__ __forceinline__ void rec_worker(const Maps& maps, unsigned sb, const bf16* __restrict__ mem0) {
  const int c = blockIdx.x, h = c >> 1, j = c & 1;
  const int t = opaque_tid(), lane = t & 31, w = t >> 5, g = lane >> 2, tq = lane & 3;
  const int m = lane >> 3, r8 = lane & 7, kh = w >> 2, et = w & 3;
  const unsigned bar = sb + SM_BAR;
  unsigned wq[16][4], wk[16][4], wo[8][4];
  const unsigned woff = (kh * 4) * 8192 + ((m >> 1) * 8 + r8) * 128 + (((et * 2 + (m & 1)) ^ r8) << 4);
  mbar_wait(bar + 8 * MB_W0, 0);
#pragma unroll
  for (int i = 0; i < 16; i++) {
    ldsm_x4_t(wq[i], sb + R_WO + woff + (i >> 2) * 8192 + (i & 3) * 2048);
    ldsm_x4_t(wk[i], sb + R_T1 + woff + (i >> 2) * 8192 + (i & 3) * 2048);
  }
  bar_sync(2, 288);
  if (t == 0) {
    fence_proxy_async_smem();
    mbar_expect_tx(bar + 8 * MB_WO, 65536);
    for (int kb = 0; kb < 2; kb++)
      for (int cb = 0; cb < 4; cb++) tma_load_2d(sb + R_WO + (kb * 4 + cb) * 8192, &maps.wo, j * 256 + cb * 64, h * 128 + kb * 64, bar + 8 * MB_WO);
  }
  mbar_wait(bar + 8 * MB_W1, 0);
  const unsigned pV = sb + R_T2 + woff;
  const unsigned rk = c & 7, peer = rk ^ 1, cl = c >> 3;
#define KEEP(x) x = __shfl_sync(~0u, x, lane)
  unsigned pA = sb + R_MEM + kh * 4096 + lane * 16;
  unsigned pW0 = sb + R_WO + (w >> 1) * 8192 + ((m >> 1) * 8 + r8) * 128 + ((((w & 1) * 4 + (m & 1)) ^ r8) << 4);
  unsigned pW1 = pW0 ^ 32;
  unsigned pVk = pV;
  unsigned aX = sb + R_VRED + et * 512 + lane * 16;
  unsigned aQKst = sb + (kh ? R_KS : R_QS) + r8 * 144 + (et * 16 + (m & 1) * 8) * 2;
  unsigned aL8 = sb + lane * 8;
  unsigned aSl = mapa(sb + R_SOWN + w * 256 + lane * 8, rk), aSr = mapa(sb + R_SPEER + w * 256 + lane * 8, peer);
  unsigned aVl = mapa(sb + R_VM + (j * 4 + et) * 256 + lane * 8, rk), aVr = mapa(sb + R_VM + (j * 4 + et) * 256 + lane * 8, peer);
  const unsigned mbSl = mapa(bar + 8 * MB_S, rk), mbSr = mapa(bar + 8 * MB_S, peer), mbVl = mbSl + 8, mbVr = mbSr + 8;
  unsigned aQ = sb + R_QS + r8 * 144 + m * 16;
  unsigned oKx = (et * 8 + r8) * 128 + ((m ^ r8) << 4);
  unsigned oVx = 4096 + (et >> 1) * 4096 + ((m >> 1) * 8 + r8) * 128 + ((((et & 1) * 4 + (m & 1)) ^ r8) << 4);
  unsigned aOst = sb + R_OS + r8 * 272 + (et * 32 + m * 8) * 2;
  unsigned aOld = sb + R_OS + r8 * 272 + m * 16;
  unsigned aVm = sb + R_VM + et * 512 + lane * 8;
  unsigned aRSr = mapa(sb + R_RS + (h & 3) * 2048 + (w & 1) * 1024 + lane * 8, j * 4 + (w >> 1));
  unsigned mbRSr = mapa(bar + 8 * MB_RS, j * 4 + (w >> 1));
  unsigned t8 = t * 8;
  KEEP(pA); KEEP(pW0); KEEP(pW1); KEEP(pVk); KEEP(aX); KEEP(aQKst); KEEP(aL8); KEEP(aSl); KEEP(aSr); KEEP(aVl); KEEP(aVr); KEEP(aQ); KEEP(oKx); KEEP(oVx);
  KEEP(aOst); KEEP(aOld); KEEP(aVm); KEEP(aRSr); KEEP(mbRSr); KEEP(t8);
  mbar_wait(bar + 8 * MB_WO, 0);
#pragma unroll
  for (int ks = 0; ks < 4; ks++) { ldsm_x4_t(wo[2 * ks], pW0 + ks * 2048); ldsm_x4_t(wo[2 * ks + 1], pW1 + ks * 2048); }
  {
    unsigned v[8];
#pragma unroll
    for (int q = 0; q < 8; q++) v[q] = __ldg(reinterpret_cast<const unsigned*>(mem0) + q * 256 + t);
    sts128(sb + R_MEM + t * 32, make_uint4(__byte_perm(v[0], v[1], 0x5410), __byte_perm(v[2], v[3], 0x5410), __byte_perm(v[4], v[5], 0x5410), __byte_perm(v[6], v[7], 0x5410)));
    sts128(sb + R_MEM + t * 32 + 16, make_uint4(__byte_perm(v[0], v[1], 0x7632), __byte_perm(v[2], v[3], 0x7632), __byte_perm(v[4], v[5], 0x7632), __byte_perm(v[6], v[7], 0x7632)));
  }
  bar_sync(1, 256);

#pragma unroll 1
  for (int s = 0;; s++) {
    const unsigned par = s & 1;
    const unsigned slot = s & (RING_N - 1), rpar = (s / RING_N) & 1;
    const unsigned ring = sb + R_RING + slot * RING_BYTES;
    asm volatile("" : "+r"(t8));
    RSTAMP(1);
    RSTAMP(2);
    float aq[4] = {0, 0, 0, 0}, ak[4] = {0, 0, 0, 0}, av[4] = {0, 0, 0, 0};
    {
      unsigned b[8][4], f1[8][4], f0[8][4];
#define VLD(i) do { ldsm_x4_t(b[i], pA + (i) * 512); ldsm_x4_t(f0[i], pVk + ((i) >> 1) * 8192 + ((i) & 1) * 4096); ldsm_x4_t(f1[i], pVk + ((i) >> 1) * 8192 + ((i) & 1) * 4096 + 2048); } while (0)
      VLD(0);
      if (VD > 1) VLD(1);
#pragma unroll
      for (int i = 0; i < 8; i++) {
        if (i + VD < 8) VLD(i + VD);
        mma16816(aq, wq[2 * i], b[i][0], b[i][1]); mma16816(ak, wk[2 * i], b[i][0], b[i][1]); mma16816(av, f0[i], b[i][0], b[i][1]);
        mma16816(aq, wq[2 * i + 1], b[i][2], b[i][3]); mma16816(ak, wk[2 * i + 1], b[i][2], b[i][3]); mma16816(av, f1[i], b[i][2], b[i][3]);
      }
    }
    RSTAMP(3);
#define STSF4(a, v) asm volatile("st.shared.v4.f32 [%0], {%1,%2,%3,%4};" ::"r"(a), "f"(v[0]), "f"(v[1]), "f"(v[2]), "f"(v[3]) : "memory")
    unsigned f[8][4];
#define WO_PREFETCH() do { _Pragma("unroll") for (int i = 0; i < NPRE; i++) { ldsm_x4_t(f[2 * i], pW0 + 32768 + i * 2048); ldsm_x4_t(f[2 * i + 1], pW1 + 32768 + i * 2048); } } while (0)
    if (kh) {
      STSF4(aX, aq);
      bar_sync(4 + et, 64);
      uint4 o = lds128(aX + 2048), o2 = lds128(aX + 4096);
      stsm_x2_t(aQKst, pack_bf16(ak[0] + __uint_as_float(o.x), ak[1] + __uint_as_float(o.y)), pack_bf16(ak[2] + __uint_as_float(o.z), ak[3] + __uint_as_float(o.w)));
      bar_arrive(1, 256);
      unsigned x = pack_bf16(av[0] + __uint_as_float(o2.x), av[1] + __uint_as_float(o2.y)), y = pack_bf16(av[2] + __uint_as_float(o2.z), av[3] + __uint_as_float(o2.w));
      st_async_b64(aVr, x, y, mbVr);
      st_async_b64(aVl, x, y, mbVl);
      if (s == NSEG - 1) {
        mbar_wait(bar + 8 * MB_V, par);
        if (t == 128) mbar_arrive(bar + 8 * MB_KVR);
        break;
      }
      mbar_wait(bar + 8 * (MB_FULL + slot), rpar);
      unsigned vx[4][4];
      ldsm_x4_t(vx[0], ring + oVx); ldsm_x4_t(vx[1], ring + oVx + 2048); ldsm_x4_t(vx[2], ring + (oVx ^ 32)); ldsm_x4_t(vx[3], ring + (oVx ^ 32) + 2048);
      RSTAMP(4); RSTAMP(5); RSTAMP(6); RSTAMP(7);
      mbar_wait(bar + 8 * MB_S, par);
      RSTAMP(8);
      float sc[10];
#pragma unroll
      for (int i = 0; i < 5; i++) {
        uint2 o = lds64(aL8 + R_SOWN + i * 256), p = lds64(aL8 + R_SPEER + i * 256);
        sc[2 * i] = __uint_as_float(o.x) + __uint_as_float(p.x); sc[2 * i + 1] = __uint_as_float(o.y) + __uint_as_float(p.y);
      }
      mbar_wait(bar + 8 * MB_V, par);
      uint2 vm0 = lds64(aVm), vm1 = lds64(aVm + 256);
      float mx = fmaxf(fmaxf(fmaxf(sc[0], sc[1]), fmaxf(sc[2], sc[3])), fmaxf(fmaxf(fmaxf(sc[4], sc[5]), fmaxf(sc[6], sc[7])), fmaxf(sc[8], sc[9])));
      mx = fmaxf(mx, __shfl_xor_sync(~0u, mx, 1)); mx = fmaxf(mx, __shfl_xor_sync(~0u, mx, 2));
      const float nm = -mx * (SCALE_QK * LOG2E);
      unsigned p[5];
#pragma unroll
      for (int i = 0; i < 5; i++) p[i] = pack_bf16(ex2f(fmaf(sc[2 * i], SCALE_QK * LOG2E, nm)), ex2f(fmaf(sc[2 * i + 1], SCALE_QK * LOG2E, nm)));
      RSTAMP(9);
      float o0[4] = {0, 0, 0, 0}, o1[4] = {0, 0, 0, 0}, o3[4] = {0, 0, 0, 0}, o4[4] = {0, 0, 0, 0}, z0[4] = {0, 0, 0, 0}, z1[4] = {0, 0, 0, 0};
      const unsigned ones[4] = {0x3F803F80u, 0u, 0x3F803F80u, 0u};
      mma16816(z0, ones, p[0], p[1]); mma16816(z1, ones, p[2], p[3]);
      mma16816(o0, vx[0], p[0], p[1]); mma16816(o3, vx[2], p[0], p[1]);
      mma1688(z0, 0x3F803F80u, 0u, p[4]);
      mma16816(o1, vx[1], p[2], p[3]); mma16816(o4, vx[3], p[2], p[3]);
      mma1688(o0, vm0.x, vm0.y, p[4]); mma1688(o3, vm1.x, vm1.y, p[4]);
      float i0, i1;
      asm("rcp.approx.ftz.f32 %0, %1;" : "=f"(i0) : "f"(z0[0] + z1[0])); asm("rcp.approx.ftz.f32 %0, %1;" : "=f"(i1) : "f"(z0[1] + z1[1]));
      asm volatile("stmatrix.sync.aligned.m8n8.x4.trans.shared.b16 [%0], {%1,%2,%3,%4};" ::"r"(aOst), "r"(pack_bf16((o0[0] + o1[0]) * i0, (o0[1] + o1[1]) * i1)), "r"(pack_bf16((o0[2] + o1[2]) * i0, (o0[3] + o1[3]) * i1)),
                   "r"(pack_bf16((o3[0] + o4[0]) * i0, (o3[1] + o4[1]) * i1)), "r"(pack_bf16((o3[2] + o4[2]) * i0, (o3[3] + o4[3]) * i1)) : "memory");
      RSTAMP(10);
      bar_sync(1, 256);
      WO_PREFETCH();
    } else {
      STSF4(aX + 2048, ak); STSF4(aX + 4096, av);
      unsigned kb[8];
      mbar_wait(bar + 8 * (MB_FULL + slot), rpar);
      ldsm_x4(kb, ring + oKx); ldsm_x4(kb + 4, ring + (oKx ^ 64));
      bar_sync(4 + et, 64);
      uint4 o = lds128(aX);
      stsm_x2_t(aQKst, pack_bf16(aq[0] + __uint_as_float(o.x), aq[1] + __uint_as_float(o.y)), pack_bf16(aq[2] + __uint_as_float(o.z), aq[3] + __uint_as_float(o.w)));
      RSTAMP(4);
      bar_sync(1, 256);
      RSTAMP(5);
      if (s == NSEG - 1) break;
      unsigned qa[8], km[8];
      ldsm_x4(qa, aQ); ldsm_x4(qa + 4, aQ + 64);
      if (w == 3) { ldsm_x4(km, aQ + 1152); ldsm_x4(km + 4, aQ + 1152 + 64); }
      float s0[4] = {0, 0, 0, 0}, s1[4] = {0, 0, 0, 0};
      unsigned af[4][4];
#pragma unroll
      for (int i = 0; i < 4; i++) { af[i][0] = qa[2 * i]; af[i][1] = 0; af[i][2] = qa[2 * i + 1]; af[i][3] = 0; }
      mma16816(s0, af[0], kb[0], kb[1]); mma16816(s1, af[1], kb[2], kb[3]);
      mma16816(s0, af[2], kb[4], kb[5]); mma16816(s1, af[3], kb[6], kb[7]);
      if (w == 3) {
        float m0[4] = {0, 0, 0, 0}, m1[4] = {0, 0, 0, 0};
        mma16816(m0, af[0], km[0], km[1]); mma16816(m1, af[1], km[2], km[3]);
        mma16816(m0, af[2], km[4], km[5]); mma16816(m1, af[3], km[6], km[7]);
        unsigned x = __float_as_uint(m0[0] + m1[0]), y = __float_as_uint(m0[1] + m1[1]);
        st_async_b64(aSr + 256, x, y, mbSr); st_async_b64(aSl + 256, x, y, mbSl);
      }
      unsigned x = __float_as_uint(s0[0] + s1[0]), y = __float_as_uint(s0[1] + s1[1]);
      st_async_b64(aSr, x, y, mbSr); st_async_b64(aSl, x, y, mbSl);
      RSTAMP(6);
      WO_PREFETCH();
      RSTAMP(7); RSTAMP(8); RSTAMP(9); RSTAMP(10);
      bar_sync(1, 256);
    }
    RSTAMP(11);
    float d0[4] = {0, 0, 0, 0}, d1[4] = {0, 0, 0, 0}, e0[4] = {0, 0, 0, 0}, e1[4] = {0, 0, 0, 0};
    unsigned ob[4][4];
#pragma unroll
    for (int k2 = 0; k2 < 4; k2++) ldsm_x4(ob[k2], aOld + k2 * 64);
#pragma unroll
    for (int i = NPRE; i < 4; i++) { ldsm_x4_t(f[2 * i], pW0 + 32768 + i * 2048); ldsm_x4_t(f[2 * i + 1], pW1 + 32768 + i * 2048); }
    mma16816(d0, wo[0], ob[0][0], ob[0][1]); mma16816(d1, wo[1], ob[0][0], ob[0][1]);
    mma16816(e0, wo[2], ob[0][2], ob[0][3]); mma16816(e1, wo[3], ob[0][2], ob[0][3]);
    mma16816(d0, wo[4], ob[1][0], ob[1][1]); mma16816(d1, wo[5], ob[1][0], ob[1][1]);
    mma16816(e0, wo[6], ob[1][2], ob[1][3]); mma16816(e1, wo[7], ob[1][2], ob[1][3]);
    mma16816(d0, f[0], ob[2][0], ob[2][1]); mma16816(d1, f[1], ob[2][0], ob[2][1]);
    mma16816(e0, f[2], ob[2][2], ob[2][3]); mma16816(e1, f[3], ob[2][2], ob[2][3]);
    mma16816(d0, f[4], ob[3][0], ob[3][1]); mma16816(d1, f[5], ob[3][0], ob[3][1]);
    mma16816(e0, f[6], ob[3][2], ob[3][3]); mma16816(e1, f[7], ob[3][2], ob[3][3]);
    st_async_b64(aRSr, __float_as_uint(d0[0] + e0[0]), __float_as_uint(d0[1] + e0[1]), mbRSr);
    st_async_b64(aRSr + 256, __float_as_uint(d0[2] + e0[2]), __float_as_uint(d0[3] + e0[3]), mbRSr);
    st_async_b64(aRSr + 512, __float_as_uint(d1[0] + e1[0]), __float_as_uint(d1[1] + e1[1]), mbRSr);
    st_async_b64(aRSr + 768, __float_as_uint(d1[2] + e1[2]), __float_as_uint(d1[3] + e1[3]), mbRSr);
    RSTAMP(12);
    if (t == 128) {
      mbar_arrive(bar + 8 * (MB_EMPTY + slot)); mbar_arrive(bar + 8 * MB_KVR);
      mbar_expect_tx(bar + 8 * MB_S, 2560); mbar_expect_tx(bar + 8 * MB_V, 2048);
    }
    const unsigned tag = ((s >> 1) & 1) ^ 1;
    const char* gp = reinterpret_cast<const char*>(g_part);
    const unsigned goff = (par * 8 + rk) * 16384 + cl * 2048 + t8;
    unsigned mbA[8];
#pragma unroll
    for (int i = 0; i < 8; i++) mbA[i] = mapa(bar + 8 * MB_AG, i);
    const unsigned dlt = (R_MEM + rk * 1024) - (SM_BAR + 8 * MB_AG) + (t8 >> 1);
    mbar_wait(bar + 8 * MB_RS, par);
    RSTAMP(13);
    uint2 a[8];
    {
      uint2 x0 = lds64(sb + R_RS + t8), x1 = lds64(sb + R_RS + 2048 + t8), x2 = lds64(sb + R_RS + 4096 + t8), x3 = lds64(sb + R_RS + 6144 + t8);
      float r0 = (__uint_as_float(x0.x) + __uint_as_float(x1.x)) + (__uint_as_float(x2.x) + __uint_as_float(x3.x));
      float r1 = (__uint_as_float(x0.y) + __uint_as_float(x1.y)) + (__uint_as_float(x2.y) + __uint_as_float(x3.y));
      a[0].x = (__float_as_uint(r0) & ~1u) | tag; a[0].y = (__float_as_uint(r1) & ~1u) | tag;
      asm volatile("st.relaxed.gpu.global.v2.u32 [%0], {%1,%2};" ::"l"(gp + goff), "r"(a[0].x), "r"(a[0].y) : "memory");
    }
    RSTAMP(14);
    if (t == 128) mbar_expect_tx(bar + 8 * MB_RS, 8192);
    {
      unsigned it = 0;
#define PLOAD(a) _Pragma("unroll") for (int i = 1; i < 8; i++) a[i] = ldv2_relaxed(gp + (goff ^ (i * 2048)))
#define PAND(a) (((a[1].x & a[1].y) & (a[2].x & a[2].y) & (a[3].x & a[3].y)) & ((a[4].x & a[4].y) & (a[5].x & a[5].y)) & ((a[6].x & a[6].y) & (a[7].x & a[7].y)))
#define POR(a) (((a[1].x | a[1].y) | (a[2].x | a[2].y) | (a[3].x | a[3].y)) | ((a[4].x | a[4].y) | (a[5].x | a[5].y)) | ((a[6].x | a[6].y) | (a[7].x | a[7].y)))
#define POK(a) (((tag ? PAND(a) : ~POR(a)) & 1u) != 0)
      if (D_RED) DELAY(D_RED);
      while (true) { PLOAD(a); if (POK(a)) break; if (D_PUB) DELAY(D_PUB); spin_check(it); }
    }
    RSTAMP(15);
    {
#define AF(i, c) __uint_as_float(a[i].c)
      unsigned u = pack_bf16(((AF(0, x) + AF(1, x)) + (AF(2, x) + AF(3, x))) + ((AF(4, x) + AF(5, x)) + (AF(6, x) + AF(7, x))),
                             ((AF(0, y) + AF(1, y)) + (AF(2, y) + AF(3, y))) + ((AF(4, y) + AF(5, y)) + (AF(6, y) + AF(7, y))));
      __syncwarp();
#pragma unroll
      for (int i = 0; i < 8; i++) st_async_b32(mbA[i] + dlt, u, mbA[i]);
    }
    mbar_wait(bar + 8 * MB_KVF, par);
    mbar_wait(bar + 8 * MB_AG, par);
    if (t == 128) mbar_expect_tx(bar + 8 * MB_AG, 8192);
  }
}

__device__ __forceinline__ void rec_ring(const Maps& maps, unsigned sb) {
  const int c = blockIdx.x, h = c >> 1, j = c & 1;
  const unsigned bar = sb + SM_BAR;
  const int lane = threadIdx.x & 31;
  if (lane == 0) {
    mbar_expect_tx(bar + 8 * MB_W0, 131072);
    for (int kb = 0; kb < 8; kb++) tma_load_2d(sb + R_WO + kb * 8192, &maps.wq, h * 128 + j * 64, kb * 64, bar + 8 * MB_W0);
    for (int kb = 0; kb < 8; kb++) tma_load_2d(sb + R_T1 + kb * 8192, &maps.wk, h * 128 + j * 64, kb * 64, bar + 8 * MB_W0);
    mbar_expect_tx(bar + 8 * MB_W1, 65536);
    for (int kb = 0; kb < 8; kb++) tma_load_2d(sb + R_T2 + kb * 8192, &maps.wv, h * 128 + j * 64, kb * 64, bar + 8 * MB_W1);
  }
  __syncwarp();
  bar_sync(2, 288);
  if (lane == 0) {
    fence_proxy_async_smem();
    for (int s = 0; s < NSEG; s++) {
      unsigned slot = s & (RING_N - 1);
      if ((s & 3) == 0 && !DBGMODE) {
        wait_flag_ge(&g_flags.qkv[(s >> 2) * 48 + 16 + (h >> 1)], 1);
        wait_flag_ge(&g_flags.qkv[(s >> 2) * 48 + 32 + (h >> 1)], 1);
        fence_proxy_async();
      }
      if (s >= RING_N) mbar_wait_sleep(bar + 8 * (MB_EMPTY + slot), ((s / RING_N) - 1) & 1);
      unsigned dst = sb + R_RING + slot * RING_BYTES, mb = bar + 8 * (MB_FULL + slot);
      mbar_expect_tx(mb, RING_BYTES);
      tma_load_2d(dst, &maps.qkv_ld, HD + h * 128 + j * 64, s * SEG, mb);
      tma_load_2d(dst + 4096, &maps.qkv_ld, 2 * HD + h * 128, s * SEG, mb);
      tma_load_2d(dst + 8192, &maps.qkv_ld, 2 * HD + h * 128 + 64, s * SEG, mb);
    }
  }
}
__device__ __forceinline__ void rec_copy(unsigned sb) {
  const int c = blockIdx.x, h = c >> 1, j = c & 1;
  const unsigned bar = sb + SM_BAR;
  const int lane = threadIdx.x & 31;
  for (int s = 0; s < NSEG; s++) {
    if (s < NSEG - 1) mbar_wait_sleep(bar + 8 * MB_KVR, s & 1); else mbar_wait(bar + 8 * MB_KVR, s & 1);
    uint4 k0 = lds128(sb + R_KS + (lane >> 3) * 144 + (lane & 7) * 16), k1 = lds128(sb + R_KS + (4 + (lane >> 3)) * 144 + (lane & 7) * 16);
    uint2 v[4];
#pragma unroll
    for (int i = 0; i < 4; i++) v[i] = lds64(sb + R_VM + (j * 4 + i) * 256 + lane * 8);
    __syncwarp();
    if (lane == 0) mbar_arrive(bar + 8 * MB_KVF);
    bf16* kd = g_km + ((size_t)(s * NH + h) * NMEM) * DH + j * 64;
    *reinterpret_cast<uint4*>(kd + (lane >> 3) * DH + (lane & 7) * 8) = k0;
    *reinterpret_cast<uint4*>(kd + (4 + (lane >> 3)) * DH + (lane & 7) * 8) = k1;
    unsigned* vd = reinterpret_cast<unsigned*>(g_vmt) + ((size_t)(s * NH + h) * DH + j * 64) * 4;
#pragma unroll
    for (int i = 0; i < 4; i++) { vd[(i * 16) * 4 + lane] = v[i].x; vd[(i * 16 + 8) * 4 + lane] = v[i].y; }
    __syncwarp();
    if (lane == 0) st_release(&g_flags.rec[c], s + 1);
  }
}

__device__ __forceinline__ void bulk_producer(const Maps& maps, unsigned sb, int* misc) {
  const unsigned bar = sb + SM_BAR;
  const int lane = threadIdx.x & 31;
  unsigned st = 0, ph = 0, seq = 0;
  while (true) {
    int idx = 0;
    if (lane == 0) idx = (int)atomicAdd(&g_flags.ctr, 1u);
    idx = __shfl_sync(~0u, idx, 0);
    if (idx >= N_ITEMS) {
      if (lane == 0) {
        mbar_wait(bar + 8 * (MB_EMPTY + st), ph ^ 1);
        misc[seq & 3] = -1;
        mbar_arrive(bar + 8 * (MB_FULL + st));
      }
      break;
    }
    if (lane == 0) ISTAMP(idx, 0);
    Item it = decode_item(idx);
    if (it.b < 0) continue;
    const CUtensorMap* mp; int c0, c1, dc0, dc1; unsigned doff;
    const unsigned* fl = nullptr; unsigned tgt = 1; int nbox = 5, rdy = 0;
    if (it.type == T_ATT) {
      mp = &maps.qkv_ld; nbox = 12; doff = lane * 4096;
      c0 = (lane >> 2) * HD + it.c * 256 + (lane & 1) * 64; c1 = it.b * 128 + ((lane >> 1) & 1) * 32; dc0 = dc1 = 0;
      if (lane < 3) fl = &g_flags.qkv[it.b * 48 + lane * 16 + it.c];
      bool ok = true;
      if (lane >= 4 && lane < 8) ok = ld_acquire(&g_flags.rec[it.c * 4 + lane - 4]) >= (unsigned)(it.b * 4 + 4);
      rdy = __all_sync(~0u, ok) ? 65536 : 0;
    } else {
      int k0 = 0, nb0 = it.c * 256;
      if (it.type == T_QKV) { mp = lane == 0 ? &maps.xn : (it.c < 16 ? &maps.wq : (it.c < 32 ? &maps.wk : &maps.wv)); nb0 = (it.c & 15) * 256; }
      else if (it.type == T_M1) mp = lane == 0 ? &maps.y : &maps.w1;
      else if (it.type == T_M2) { mp = lane == 0 ? &maps.h1 : &maps.w2; fl = &g_flags.h1[it.b]; tgt = 7; }
      else {
        mp = lane == 0 ? &maps.o : &maps.wo;
        if (it.type == T_OUT) { k0 = it.ks * 1024; fl = &g_flags.o[it.b * 4 + it.ks]; tgt = 4; }
        else if (it.type == T_OUTL) { k0 = it.ks * 256; fl = &g_flags.o16[it.ks]; }
        else if (lane == 1) { fl = &g_flags.g[it.b]; tgt = 2; }
        else { fl = &g_flags.p[it.b]; tgt = it.type == T_RED ? 8 : 32; }
      }
      if (lane > (it.type >= T_RED ? 1 : 0)) fl = nullptr;
      if (lane == 0) { c0 = k0; c1 = it.b * 128; dc0 = 64; dc1 = 0; doff = 0; }
      else { c0 = nb0 + (lane - 1) * 64; c1 = k0; dc0 = 0; dc1 = 64; doff = 8192 + lane * 8192; }
    }
    if (fl) wait_flag_ge(fl, tgt);
    __syncwarp();
    fence_proxy_async();
    if (lane == 0) ISTAMP(idx, 1);
    const int nkb = item_nkb(it.type);
    for (int kb = 0; kb < nkb; kb++) {
      const unsigned mb = bar + 8 * (MB_FULL + st);
      mbar_wait(bar + 8 * (MB_EMPTY + st), ph ^ 1);
      if (lane == 0) {
        if (kb == 0) misc[seq & 3] = idx | rdy;
        if (it.type >= T_RED) mbar_arrive(mb); else mbar_expect_tx(mb, STAGE_BYTES);
      }
      if (it.type == T_ATT) { if (lane < 12) tma_load_2d(sb + st * STAGE_BYTES + doff, mp, c0 + (kb & 1) * 128, c1 + (kb >> 1) * 64, mb); }
      else if (lane < nbox && it.type < T_RED) tma_load_2d(sb + st * STAGE_BYTES + doff, mp, c0 + kb * dc0, c1 + kb * dc1, mb);
      __syncwarp();
      if (++st == NSTAGE) { st = 0; ph ^= 1; }
    }
    seq++;
  }
}
__device__ __forceinline__ void bulk_store(const Maps& maps, unsigned sb, volatile int* misc) {
  const unsigned bar = sb + SM_BAR;
  unsigned ph = 0;
  while (true) {
    mbar_wait(bar + 8 * MB_STGF, ph); ph ^= 1;
    int idx = misc[4];
    if (idx < 0) break;
    Item it = decode_item(idx);
    const CUtensorMap* mp = it.type == T_QKV ? &maps.qkv_st : (it.type == T_M1 ? &maps.h1 : (it.type == T_M2 ? &maps.g : &maps.o));
    unsigned* flag = it.type == T_QKV ? &g_flags.qkv[it.b * 48 + it.c] : (it.type == T_M1 ? &g_flags.h1[it.b] : (it.type == T_M2 ? &g_flags.g[it.b] : (it.b == 15 ? &g_flags.o16[it.c] : &g_flags.o[it.b * 4 + (it.c >> 2)])));
    for (int i = 0; i < 4; i++) tma_store_2d(mp, sb + B_STG + i * 16384, it.c * 256 + i * 64, it.b * 128);
    asm volatile("cp.async.bulk.commit_group;" ::: "memory");
    asm volatile("cp.async.bulk.wait_group.read 0;" ::: "memory");
    mbar_arrive(bar + 8 * MB_STGE);
    asm volatile("cp.async.bulk.wait_group 0;" ::: "memory");
    fence_proxy_async();
    red_release_add(flag, 1);
    ISTAMP(idx, 3);
  }
}
__device__ __forceinline__ float rcpf(float x) { float y; asm("rcp.approx.ftz.f32 %0, %1;" : "=f"(y) : "f"(x)); return y; }
__device__ __forceinline__ float gelu_t(float x) {
  float e = ex2f(x * fmaf(x * x, -2.0f * LOG2E * 0.7978845608028654f * 0.044715f, -2.0f * LOG2E * 0.7978845608028654f));
  return x * rcpf(1.0f + e);
}
__device__ __forceinline__ float silu_f(float x) { return x * rcpf(1.0f + ex2f(-LOG2E * x)); }
__device__ __forceinline__ unsigned badd2(unsigned a, unsigned b) { unsigned r; asm("add.rn.bf16x2 %0, %1, %2;" : "=r"(r) : "r"(a), "r"(b)); return r; }

__device__ __forceinline__ void final_out(bf16* __restrict__ out, const bf16* __restrict__ x, size_t o, float4 s) {
  uint2 gv = __ldcg(reinterpret_cast<const uint2*>(g_g + o)), xv = __ldg(reinterpret_cast<const uint2*>(x + o));
  uint2 r;
  r.x = pack_bf16(bf_lo(xv.x) + bf16r(bf16r(s.x) * bf_lo(gv.x)), bf_hi(xv.x) + bf16r(bf16r(s.y) * bf_hi(gv.x)));
  r.y = pack_bf16(bf_lo(xv.y) + bf16r(bf16r(s.z) * bf_lo(gv.y)), bf_hi(xv.y) + bf16r(bf16r(s.w) * bf_hi(gv.y)));
  *reinterpret_cast<uint2*>(out + o) = r;
}
__device__ __forceinline__ void bulk_att_load(unsigned* km, unsigned* vm, int b, int hp, int kb, int w, int lane) {
  const int g = lane >> 2, tq = lane & 3, seg = w >> 2, eh = w & 1;
  const int head = hp * 2 + (kb & 1), sg = b * 4 + (kb >> 1) * 2 + seg;
  const unsigned* kmp = reinterpret_cast<const unsigned*>(g_km + ((size_t)(sg * NH + head) * NMEM + g) * DH) + tq;
  const unsigned* vmp = reinterpret_cast<const unsigned*>(g_vmt) + ((size_t)(sg * NH + head) * DH + eh * 64) * 4 + lane;
#pragma unroll
  for (int i = 0; i < 16; i++) asm volatile("ld.global.cg.u32 %0, [%1];" : "=r"(km[i]) : "l"(kmp + i * 4) : "memory");
#pragma unroll
  for (int i = 0; i < 8; i++) asm volatile("ld.global.cg.u32 %0, [%1];" : "=r"(vm[i]) : "l"(vmp + i * 32) : "memory");
}
__device__ __forceinline__ void bulk_att_stage(unsigned sa, unsigned stg, const unsigned* km, const unsigned* vm, int kb, int w, int lane) {
  const int g = lane >> 2, tq = lane & 3, m = lane >> 3, r8 = lane & 7;
  const int seg = w >> 2, mt = (w >> 1) & 1, eh = w & 1;
  float s[5][4];
#pragma unroll
  for (int i = 0; i < 5; i++) { s[i][0] = s[i][1] = s[i][2] = s[i][3] = 0; }
  const unsigned qb = sa + (0 * 2 + seg) * 8192, kbs = sa + (1 * 2 + seg) * 8192, vb = sa + (2 * 2 + seg) * 8192 + eh * 4096;
  unsigned qa[8][4];
#pragma unroll
  for (int ks = 0; ks < 8; ks++) {
    int row = mt * 16 + (m & 1) * 8 + r8;
    ldsm_x4(qa[ks], qb + (ks >> 2) * 4096 + row * 128 + ((((ks & 3) * 2 + (m >> 1)) ^ r8) << 4));
    unsigned kf[4];
    int krow = (m >> 1) * 8 + r8;
    unsigned ka = kbs + (ks >> 2) * 4096 + krow * 128 + ((((ks & 3) * 2 + (m & 1)) ^ r8) << 4);
    ldsm_x4(kf, ka);
    mma16816(s[0], qa[ks], kf[0], kf[1]); mma16816(s[1], qa[ks], kf[2], kf[3]);
    if (mt) { ldsm_x4(kf, ka + 2048); mma16816(s[2], qa[ks], kf[0], kf[1]); mma16816(s[3], qa[ks], kf[2], kf[3]); }
  }
#pragma unroll
  for (int ks = 0; ks < 8; ks++) mma16816(s[4], qa[ks], km[2 * ks], km[2 * ks + 1]);
  float mx0 = -INFINITY, mx1 = -INFINITY;
  const int t0 = mt * 16 + g, t1 = t0 + 8;
#pragma unroll
  for (int i = 0; i < 5; i++) {
#pragma unroll
    for (int e = 0; e < 4; e++) {
      float v = s[i][e];
      if (i < 4) { int kj = i * 8 + 2 * tq + (e & 1); if (kj > (e < 2 ? t0 : t1)) v = -INFINITY; }
      s[i][e] = v;
      if (e < 2) mx0 = fmaxf(mx0, v); else mx1 = fmaxf(mx1, v);
    }
  }
  mx0 = fmaxf(mx0, __shfl_xor_sync(~0u, mx0, 1)); mx0 = fmaxf(mx0, __shfl_xor_sync(~0u, mx0, 2));
  mx1 = fmaxf(mx1, __shfl_xor_sync(~0u, mx1, 1)); mx1 = fmaxf(mx1, __shfl_xor_sync(~0u, mx1, 2));
  float sm0 = 0, sm1 = 0;
#pragma unroll
  for (int i = 0; i < 5; i++) {
    s[i][0] = ex2f((s[i][0] - mx0) * (SCALE_QK * LOG2E)); s[i][1] = ex2f((s[i][1] - mx0) * (SCALE_QK * LOG2E));
    s[i][2] = ex2f((s[i][2] - mx1) * (SCALE_QK * LOG2E)); s[i][3] = ex2f((s[i][3] - mx1) * (SCALE_QK * LOG2E));
    sm0 += s[i][0] + s[i][1]; sm1 += s[i][2] + s[i][3];
  }
  sm0 += __shfl_xor_sync(~0u, sm0, 1); sm0 += __shfl_xor_sync(~0u, sm0, 2);
  sm1 += __shfl_xor_sync(~0u, sm1, 1); sm1 += __shfl_xor_sync(~0u, sm1, 2);
  const float i0 = __fdividef(1.0f, sm0), i1 = __fdividef(1.0f, sm1);
  unsigned pa[2][4], pm0, pm1;
#pragma unroll
  for (int kk = 0; kk < 2; kk++) {
    pa[kk][0] = pack_bf16(s[2 * kk][0] * i0, s[2 * kk][1] * i0); pa[kk][1] = pack_bf16(s[2 * kk][2] * i1, s[2 * kk][3] * i1);
    pa[kk][2] = pack_bf16(s[2 * kk + 1][0] * i0, s[2 * kk + 1][1] * i0); pa[kk][3] = pack_bf16(s[2 * kk + 1][2] * i1, s[2 * kk + 1][3] * i1);
  }
  pm0 = pack_bf16(s[4][0] * i0, s[4][1] * i0); pm1 = pack_bf16(s[4][2] * i1, s[4][3] * i1);
  const int orow = (kb >> 1) * 64 + seg * 32 + mt * 16 + (m & 1) * 8 + r8;
  const unsigned ob = stg + ((kb & 1) * 2 + eh) * 16384 + orow * 128;
#pragma unroll
  for (int cp = 0; cp < 4; cp++) {
    float o0[4] = {0, 0, 0, 0}, o1[4] = {0, 0, 0, 0};
    mma1688(o0, pm0, pm1, vm[2 * cp]); mma1688(o1, pm0, pm1, vm[2 * cp + 1]);
    unsigned vf[4];
    int row = (m & 1) * 8 + r8;
    unsigned va = vb + row * 128 + (((cp * 2 + (m >> 1)) ^ r8) << 4);
    ldsm_x4_t(vf, va);
    mma16816(o0, pa[0], vf[0], vf[1]); mma16816(o1, pa[0], vf[2], vf[3]);
    if (mt) { ldsm_x4_t(vf, va + 2048); mma16816(o0, pa[1], vf[0], vf[1]); mma16816(o1, pa[1], vf[2], vf[3]); }
    stsm_x4(ob + (((cp * 2 + (m >> 1)) ^ r8) << 4), pack_bf16(o0[0], o0[1]), pack_bf16(o0[2], o0[3]), pack_bf16(o1[0], o1[1]), pack_bf16(o1[2], o1[3]));
  }
}

__device__ __forceinline__ void bulk_worker(unsigned sb, volatile int* misc, const bf16* __restrict__ x, const bf16* __restrict__ b1, const bf16* __restrict__ b2, bf16* __restrict__ out) {
  const int t = threadIdx.x, lane = t & 31, w = t >> 5, wg = w >> 2, g = lane >> 2, tq = lane & 3, m = lane >> 3, r8 = lane & 7;
  const unsigned bar = sb + SM_BAR;
  unsigned st = 0, ph = 0, seq = 0, sph = 0;
  float d[128];
  while (true) {
    mbar_wait(bar + 8 * (MB_FULL + st), ph);
    const int idr = misc[seq & 3]; seq++;
    const int idx = idr & 65535;
    if (idr < 0 || idx >= N_ITEMS) break;
    if (t == 0) ISTAMP(idx, 2);
    const Item it = decode_item(idx);
    const int nkb = item_nkb(it.type);
    if (it.type == T_ATT) {
      unsigned km[16], vm[8], kn[16], vn[8];
      const bool pref = idr >= 65536;
      if (pref) bulk_att_load(kn, vn, it.b, it.c, 0, w, lane);
      mbar_wait(bar + 8 * MB_STGE, sph ^ 1);
#pragma unroll 1
      for (int kb = 0; kb < 4; kb++) {
        if (!pref) {
          if (lane < 2) wait_flag_ge(&g_flags.rec[it.c * 4 + (kb & 1) * 2 + lane], it.b * 4 + (kb >> 1) * 2 + wg + 1);
          __syncwarp();
          bulk_att_load(kn, vn, it.b, it.c, kb, w, lane);
        }
        if (kb) mbar_wait(bar + 8 * (MB_FULL + st), ph);
#pragma unroll
        for (int i = 0; i < 16; i++) km[i] = kn[i];
#pragma unroll
        for (int i = 0; i < 8; i++) vm[i] = vn[i];
        if (pref && kb != 3) bulk_att_load(kn, vn, it.b, it.c, kb + 1, w, lane);
        bulk_att_stage(sb + st * STAGE_BYTES, sb + B_STG, km, vm, kb, w, lane);
        __syncwarp();
        if (lane == 0) mbar_arrive(bar + 8 * (MB_EMPTY + st));
        if (++st == NSTAGE) { st = 0; ph ^= 1; }
      }
      if (t == 0) misc[4] = idx;
      fence_proxy_async_smem();
      mbar_arrive(bar + 8 * MB_STGF); sph ^= 1;
      continue;
    }
    if (it.type >= T_RED) {
      __syncwarp();
      if (lane == 0) mbar_arrive(bar + 8 * (MB_EMPTY + st));
      if (++st == NSTAGE) { st = 0; ph ^= 1; }
      if (it.type == T_RED) {
#pragma unroll 2
        for (int i = 0; i < 8; i++) {
          size_t o = ((size_t)it.b * 128 + it.c * 16 + i * 2 + (t >> 7)) * DM + (t & 127) * 4;
          float4 a = __ldcg(reinterpret_cast<const float4*>(g_opart + o)), b = __ldcg(reinterpret_cast<const float4*>(g_opart + o + (size_t)S_TOK * DM));
          float4 c = __ldcg(reinterpret_cast<const float4*>(g_opart + o + (size_t)2 * S_TOK * DM)), e = __ldcg(reinterpret_cast<const float4*>(g_opart + o + (size_t)3 * S_TOK * DM));
          final_out(out, x, o, make_float4((a.x + b.x) + (c.x + e.x), (a.y + b.y) + (c.y + e.y), (a.z + b.z) + (c.z + e.z), (a.w + b.w) + (c.w + e.w)));
        }
      } else {
        size_t ol = ((size_t)it.c * 2 + (t >> 7)) * DM + (t & 127) * 4;
        float4 v[16];
#pragma unroll
        for (int i = 0; i < 16; i++) v[i] = __ldcg(reinterpret_cast<const float4*>(g_opl + ol + (size_t)i * 128 * DM));
#pragma unroll
        for (int st2 = 1; st2 < 16; st2 <<= 1)
#pragma unroll
          for (int i = 0; i < 16; i += 2 * st2) { v[i].x += v[i + st2].x; v[i].y += v[i + st2].y; v[i].z += v[i + st2].z; v[i].w += v[i + st2].w; }
        final_out(out, x, ol + (size_t)15 * 128 * DM, v[0]);
      }
      if (t == 0) ISTAMP(idx, 3);
      continue;
    }
    unsigned pst = 0, bv[32];
#pragma unroll
    for (int i = 0; i < 128; i++) d[i] = 0.0f;
    if (it.type == T_M1 || it.type == T_M2) {
      const unsigned* bp = reinterpret_cast<const unsigned*>((it.type == T_M1 ? b1 : b2) + it.c * 256) + tq;
#pragma unroll
      for (int i = 0; i < 32; i++) asm volatile("ld.global.nc.u32 %0, [%1];" : "=r"(bv[i]) : "l"(bp + i * 4));
    } else {
#pragma unroll
      for (int i = 0; i < 32; i++) bv[i] = 0;
    }
    for (int kb = 0; kb < nkb; kb++) {
      if (kb) mbar_wait(bar + 8 * (MB_FULL + st), ph);
      unsigned sa = sb + st * STAGE_BYTES;
      uint64_t ad = mkdesc(sa + wg * 8192, 16, 1024), bd = mkdesc(sa + 16384, 8192, 1024);
      asm volatile("wgmma.fence.sync.aligned;" ::: "memory");
#pragma unroll
      for (int k = 0; k < 4; k++) wgmma_n256(d, ad + k * 2, bd + k * 128, (kb | k) != 0);
      asm volatile("wgmma.commit_group.sync.aligned;" ::: "memory");
      if (kb) {
        asm volatile("wgmma.wait_group.sync.aligned 1;" ::: "memory");
        if (lane == 0) mbar_arrive(bar + 8 * (MB_EMPTY + pst));
      }
      pst = st;
      if (++st == NSTAGE) { st = 0; ph ^= 1; }
    }
    asm volatile("wgmma.wait_group.sync.aligned 0;" ::: "memory");
    if (lane == 0) mbar_arrive(bar + 8 * (MB_EMPTY + pst));
    if (it.type >= T_OUT) {
      const int col = it.c * 256 + 2 * tq;
      float* pp = it.type == T_OUT ? g_opart + ((size_t)it.ks * S_TOK + it.b * 128 + w * 16 + g) * DM + col : g_opl + ((size_t)it.ks * 128 + w * 16 + g) * DM + col;
#pragma unroll
      for (int i = 0; i < 32; i++) {
        __stcg(reinterpret_cast<float2*>(pp + i * 8), make_float2(d[4 * i], d[4 * i + 1]));
        __stcg(reinterpret_cast<float2*>(pp + 8 * DM + i * 8), make_float2(d[4 * i + 2], d[4 * i + 3]));
      }
      bar_sync(1, 256);
      if (t == 0) { red_release_add(&g_flags.p[it.b], 1); ISTAMP(idx, 3); }
      continue;
    }
#define ACT(F) _Pragma("unroll") for (int i = 0; i < 32; i++) { \
        unsigned u0 = badd2(pack_bf16(d[4 * i], d[4 * i + 1]), bv[i]), u1 = badd2(pack_bf16(d[4 * i + 2], d[4 * i + 3]), bv[i]); \
        d[4 * i] = F(bf_lo(u0)); d[4 * i + 1] = F(bf_hi(u0)); d[4 * i + 2] = F(bf_lo(u1)); d[4 * i + 3] = F(bf_hi(u1)); }
    if (it.type == T_M1) { ACT(gelu_t) } else if (it.type == T_M2) { ACT(silu_f) }
    mbar_wait(bar + 8 * MB_STGE, sph ^ 1);
    {
      const unsigned ob = sb + B_STG + (w * 16 + (m & 1) * 8 + r8) * 128;
#pragma unroll
      for (int i = 0; i < 16; i++)
        stsm_x4(ob + (i >> 2) * 16384 + ((((i & 3) * 2 + (m >> 1)) ^ r8) << 4), pack_bf16(d[8 * i], d[8 * i + 1]), pack_bf16(d[8 * i + 2], d[8 * i + 3]),
                pack_bf16(d[8 * i + 4], d[8 * i + 5]), pack_bf16(d[8 * i + 6], d[8 * i + 7]));
    }
    if (t == 0) misc[4] = idx;
    fence_proxy_async_smem();
    mbar_arrive(bar + 8 * MB_STGF); sph ^= 1;
  }
  mbar_wait(bar + 8 * MB_STGE, sph ^ 1);
  if (t == 0) misc[4] = -1;
  mbar_arrive(bar + 8 * MB_STGF);
}

__global__ void __launch_bounds__(384, 1)
k_main(const __grid_constant__ Maps maps, const bf16* __restrict__ x, const bf16* __restrict__ mem0, const bf16* __restrict__ b1, const bf16* __restrict__ b2, bf16* __restrict__ out, int helper) {
  extern __shared__ unsigned char smem_raw[];
  const unsigned sraw = smem_u32(smem_raw);
  const unsigned sb = (sraw + 1023u) & ~1023u;
  int* misc = reinterpret_cast<int*>(smem_raw + (sb - sraw) + SM_MISC);
  const int w = threadIdx.x >> 5;
  const bool rec = !helper && blockIdx.x < NREC;
  if (!helper) asm volatile("griddepcontrol.launch_dependents;");
  if (threadIdx.x == 0) {
    const unsigned bar = sb + SM_BAR;
    for (int i = 0; i < 8; i++) { mbar_init(bar + 8 * (MB_FULL + i), 1); mbar_init(bar + 8 * (MB_EMPTY + i), rec ? 1 : 8); }
    mbar_init(bar + 8 * MB_STGF, 256); mbar_init(bar + 8 * MB_STGE, 1);
    for (int i = MB_W0; i <= MB_AG; i++) mbar_init(bar + 8 * i, 1);
    if (rec) { mbar_expect_tx(bar + 8 * MB_S, 2560); mbar_expect_tx(bar + 8 * MB_V, 2048); mbar_expect_tx(bar + 8 * MB_RS, 8192); mbar_expect_tx(bar + 8 * MB_AG, 8192); }
    asm volatile("fence.mbarrier_init.release.cluster;" ::: "memory");
  }
  __syncthreads();
  asm volatile("barrier.cluster.arrive.release.aligned;\nbarrier.cluster.wait.acquire.aligned;" ::: "memory");
  if (DBGMODE && !rec) { if (helper) asm volatile("griddepcontrol.wait;" ::: "memory"); return; }
  if (w >= 8) {
    asm volatile("setmaxnreg.dec.sync.aligned.u32 24;");
    if (rec) { if (w == 8) rec_ring(maps, sb); else if (w == 9) rec_copy(sb); }
    else if (w == 8) bulk_producer(maps, sb, misc);
    else if ((threadIdx.x & 31) == 0) { if (w == 9) bulk_store(maps, sb, misc);
      else if (w == 10 && helper) asm volatile("griddepcontrol.wait;" ::: "memory"); }
  } else {
    if (rec) { asm volatile("setmaxnreg.inc.sync.aligned.u32 240;"); rec_worker(maps, sb, mem0); }
    else { asm volatile("setmaxnreg.inc.sync.aligned.u32 240;"); bulk_worker(sb, misc, x, b1, b2, out); }
  }
}

typedef CUresult (*EncFn)(CUtensorMap*, CUtensorMapDataType, cuuint32_t, void*, const cuuint64_t*, const cuuint64_t*, const cuuint32_t*, const cuuint32_t*,
                          CUtensorMapInterleave, CUtensorMapSwizzle, CUtensorMapL2promotion, CUtensorMapFloatOOBfill);
static void mk_map(EncFn enc, CUtensorMap* m, const void* ptr, uint64_t rows, uint64_t cols, uint32_t box_rows) {
  cuuint64_t dims[2] = {cols, rows}; cuuint64_t strides[1] = {cols * 2};
  cuuint32_t box[2] = {64, box_rows}, es[2] = {1, 1};
  enc(m, CU_TENSOR_MAP_DATA_TYPE_BFLOAT16, 2, const_cast<void*>(ptr), dims, strides, box, es, CU_TENSOR_MAP_INTERLEAVE_NONE, CU_TENSOR_MAP_SWIZZLE_128B,
      CU_TENSOR_MAP_L2_PROMOTION_L2_256B, CU_TENSOR_MAP_FLOAT_OOB_FILL_NONE);
}
extern "C" void kernel_launch(void* const* d_in, const int* in_sizes, int n_in, void* d_out, int out_size) {
  static EncFn enc = nullptr;
  static int ncl = 0, nhelp = 0;
  static void *p_xn, *p_y, *p_h1, *p_o, *p_qkv, *p_g;
  if (!enc) {
    void* fn = nullptr; cudaDriverEntryPointQueryResult qr;
    cudaGetDriverEntryPoint("cuTensorMapEncodeTiled", &fn, cudaEnableDefault, &qr);
    enc = (EncFn)fn;
    cudaGetSymbolAddress(&p_xn, g_xn); cudaGetSymbolAddress(&p_y, g_y); cudaGetSymbolAddress(&p_h1, g_h1);
    cudaGetSymbolAddress(&p_o, g_o); cudaGetSymbolAddress(&p_qkv, g_qkv); cudaGetSymbolAddress(&p_g, g_g);
    cudaFuncSetAttribute(k_main, cudaFuncAttributeMaxDynamicSharedMemorySize, SMEM_TOTAL);
    cudaLaunchConfig_t cfg = {}; cfg.gridDim = dim3(128); cfg.blockDim = dim3(384); cfg.dynamicSmemBytes = SMEM_TOTAL;
    cudaLaunchAttribute at[1]; at[0].id = cudaLaunchAttributeClusterDimension; at[0].val.clusterDim.x = CLS; at[0].val.clusterDim.y = 1; at[0].val.clusterDim.z = 1;
    cfg.attrs = at; cfg.numAttrs = 1;
    if (cudaOccupancyMaxActiveClusters(&ncl, k_main, &cfg) != cudaSuccess) { cudaGetLastError(); ncl = 14; }
    ncl = ncl > 16 ? 16 : (ncl < 9 ? 9 : ncl);
    int nsm = 0, dev = 0; cudaGetDevice(&dev); cudaDeviceGetAttribute(&nsm, cudaDevAttrMultiProcessorCount, dev);
    nhelp = nsm - ncl * CLS;
  }
  Maps maps;
  mk_map(enc, &maps.xn, p_xn, S_TOK, DM, 128); mk_map(enc, &maps.y, p_y, S_TOK, DM, 128); mk_map(enc, &maps.h1, p_h1, S_TOK, FF, 128);
  mk_map(enc, &maps.o, p_o, S_TOK, HD, 128); mk_map(enc, &maps.qkv_st, p_qkv, S_TOK, 3 * HD, 128); mk_map(enc, &maps.qkv_ld, p_qkv, S_TOK, 3 * HD, 32);
  mk_map(enc, &maps.g, p_g, S_TOK, DM, 128);
  mk_map(enc, &maps.wq, d_in[2], DM, HD, 64); mk_map(enc, &maps.wk, d_in[3], DM, HD, 64); mk_map(enc, &maps.wv, d_in[4], DM, HD, 64);
  mk_map(enc, &maps.wo, d_in[5], HD, DM, 64); mk_map(enc, &maps.w1, d_in[8], DM, FF, 64); mk_map(enc, &maps.w2, d_in[10], FF, DM, 64);
  cudaStream_t st = cudaStreamPerThread;
  k_pre<<<256, 256, 0, st>>>((const bf16*)d_in[0]);
  cudaLaunchConfig_t cfg = {}; cfg.gridDim = dim3(ncl * CLS); cfg.blockDim = dim3(384); cfg.dynamicSmemBytes = SMEM_TOTAL; cfg.stream = st;
  cudaLaunchAttribute at[1]; at[0].id = cudaLaunchAttributeClusterDimension; at[0].val.clusterDim.x = CLS; at[0].val.clusterDim.y = 1; at[0].val.clusterDim.z = 1;
  cfg.attrs = at; cfg.numAttrs = 1;
  cudaLaunchKernelEx(&cfg, k_main, maps, (const bf16*)d_in[0], (const bf16*)d_in[1], (const bf16*)d_in[9], (const bf16*)d_in[11], (bf16*)d_out, 0);
  if (nhelp > 0) {
    cfg.gridDim = dim3(nhelp);
    at[0].id = cudaLaunchAttributeProgrammaticStreamSerialization; at[0].val.programmaticStreamSerializationAllowed = 1;
    cudaLaunchKernelEx(&cfg, k_main, maps, (const bf16*)d_in[0], (const bf16*)d_in[1], (const bf16*)d_in[9], (const bf16*)d_in[11], (bf16*)d_out, 1);
  }
}
```

```cpp
#include <cuda_runtime.h>
#include <cuda_bf16.h>
#include <cuda.h>
#include <stdint.h>

typedef __nv_bfloat16 bf16;

#define S_TOK 2048
#define DM 512
#define NH 32
#define DH 128
#define HD 4096
#define NMEM 8
#define SEG 32
#define NSEG 64
#define FF 1792
#define NBLK 16
#define NREC 64
#define REPL 0
#define CLS 8

__device__ __align__(1024) bf16 g_xn[S_TOK * DM];
__device__ __align__(1024) bf16 g_y[S_TOK * DM];
__device__ __align__(1024) bf16 g_qkv[(size_t)S_TOK * 3 * HD];
__device__ __align__(1024) bf16 g_h1[S_TOK * FF];
__device__ __align__(1024) bf16 g_g[S_TOK * DM];
__device__ __align__(1024) bf16 g_o[(size_t)S_TOK * HD];
__device__ __align__(1024) bf16 g_km[NSEG * NH * NMEM * DH];
__device__ __align__(1024) bf16 g_vmt[NSEG * NH * DH * NMEM];
__device__ __align__(1024) float g_opart[(size_t)4 * S_TOK * DM];
__device__ __align__(1024) float g_opl[(size_t)16 * 128 * DM];
__device__ __align__(1024) unsigned g_part[8 * 2 * 8 * 8 * 512];
struct Flags {
  unsigned qkv[NBLK * 48];
  unsigned h1[NBLK];
  unsigned g[NBLK];
  unsigned o[NBLK * 4];
  unsigned p[NBLK];
  unsigned o16[16];
  unsigned ctr;
  unsigned rec[NREC];
  unsigned abort_;
};
__device__ __align__(1024) Flags g_flags;

#define RSTAMP(k)
#define DBGMODE 0
#define ISTAMP(i, k)
__device__ __forceinline__ unsigned smem_u32(const void* p) { return (unsigned)__cvta_generic_to_shared(p); }
__device__ __forceinline__ float bf16r(float x) { unsigned u; asm("cvt.rn.bf16x2.f32 %0, %1, %2;" : "=r"(u) : "f"(x), "f"(0.0f)); return __uint_as_float(u); }
__device__ __forceinline__ unsigned pack_bf16(float lo, float hi) {
  __nv_bfloat162 v = __floats2bfloat162_rn(lo, hi);
  return *reinterpret_cast<unsigned*>(&v);
}
__device__ __forceinline__ float bf_lo(unsigned u) { return __uint_as_float(u << 16); }
__device__ __forceinline__ float bf_hi(unsigned u) { return __uint_as_float(u & 0xffff0000u); }

#define SPIN_LIMIT (1u << 20)
#define TRAP_IF(x) if ((x) > SPIN_LIMIT) { asm volatile("st.global.u32 [%0], %1;" ::"l"(0ull), "r"(0u) : "memory"); break; }
__device__ __forceinline__ unsigned ld_acquire(const unsigned* p) {
  unsigned v; asm volatile("ld.acquire.gpu.global.u32 %0, [%1];" : "=r"(v) : "l"(p) : "memory"); return v;
}
__device__ __forceinline__ unsigned ld_relaxed(const unsigned* p) {
  unsigned v; asm volatile("ld.relaxed.gpu.global.u32 %0, [%1];" : "=r"(v) : "l"(p) : "memory"); return v;
}
__device__ __forceinline__ void red_release_add(unsigned* p, unsigned v) {
  asm volatile("red.release.gpu.global.add.u32 [%0], %1;" ::"l"(p), "r"(v) : "memory");
}
__device__ __forceinline__ void st_release(unsigned* p, unsigned v) {
  asm volatile("st.release.gpu.global.u32 [%0], %1;" ::"l"(p), "r"(v) : "memory");
}
__device__ __forceinline__ void wait_flag_ge(const unsigned* p, unsigned target) {
  unsigned it = 0;
  while (ld_acquire(p) < target) {
    __nanosleep(64);
    TRAP_IF(++it);
  }
}
__device__ __forceinline__ uint4 ldv4_relaxed(const void* p) {
  uint4 a; asm volatile("ld.relaxed.gpu.global.v4.u32 {%0,%1,%2,%3}, [%4];" : "=r"(a.x), "=r"(a.y), "=r"(a.z), "=r"(a.w) : "l"(p) : "memory"); return a;
}
__device__ __forceinline__ uint2 ldv2_relaxed(const void* p) {
  uint2 a; asm volatile("ld.relaxed.gpu.global.v2.u32 {%0,%1}, [%2];" : "=r"(a.x), "=r"(a.y) : "l"(p) : "memory"); return a;
}
__device__ __forceinline__ void mbar_init(unsigned mb, unsigned cnt) { asm volatile("mbarrier.init.shared::cta.b64 [%0], %1;" ::"r"(mb), "r"(cnt) : "memory"); }
__device__ __forceinline__ void mbar_expect_tx(unsigned mb, unsigned bytes) { asm volatile("mbarrier.arrive.expect_tx.shared::cta.b64 _, [%0], %1;" ::"r"(mb), "r"(bytes) : "memory"); }
__device__ __forceinline__ void mbar_arrive(unsigned mb) { asm volatile("mbarrier.arrive.shared::cta.b64 _, [%0];" ::"r"(mb) : "memory"); }
__device__ __forceinline__ void mbar_wait(unsigned mb, unsigned parity) {
  unsigned ok, it = 0;
  while (true) {
    asm volatile("{.reg .pred p; mbarrier.try_wait.parity.shared::cta.b64 p, [%1], %2; selp.u32 %0,1,0,p;}" : "=r"(ok) : "r"(mb), "r"(parity) : "memory");
    if (ok) break;
    TRAP_IF(++it);
  }
}
__device__ __forceinline__ void mbar_wait_sleep(unsigned mb, unsigned parity) {
  unsigned ok, it = 0;
  while (true) {
    asm volatile("{.reg .pred p; mbarrier.test_wait.parity.shared::cta.b64 p, [%1], %2; selp.u32 %0,1,0,p;}" : "=r"(ok) : "r"(mb), "r"(parity) : "memory");
    if (ok) break;
    __nanosleep(200);
    TRAP_IF(++it);
  }
}
__device__ __forceinline__ float ex2f(float x) { float y; asm("ex2.approx.ftz.f32 %0, %1;" : "=f"(y) : "f"(x)); return y; }
__device__ __forceinline__ int opaque_tid() { int t = threadIdx.x; t = __shfl_sync(~0u, t, t & 31); return t; }
#define LOG2E 1.4426950408889634f
__device__ __forceinline__ void mbar_wait_cluster(unsigned mb, unsigned parity) {
  unsigned ok, it = 0;
  while (true) {
    asm volatile("{.reg .pred p; mbarrier.try_wait.parity.acquire.cluster.shared::cta.b64 p, [%1], %2; selp.u32 %0,1,0,p;}" : "=r"(ok) : "r"(mb), "r"(parity) : "memory");
    if (ok) break;
    TRAP_IF(++it);
  }
}
__device__ __forceinline__ void bar_sync(int id, int n) { asm volatile("bar.sync %0, %1;" ::"r"(id), "r"(n) : "memory"); }
__device__ __forceinline__ void bar_arrive(int id, int n) { asm volatile("bar.arrive %0, %1;" ::"r"(id), "r"(n) : "memory"); }
__device__ __forceinline__ void tma_load_2d(unsigned dst, const CUtensorMap* map, int c0, int c1, unsigned mb) {
  asm volatile("cp.async.bulk.tensor.2d.shared::cluster.global.mbarrier::complete_tx::bytes [%0], [%1, {%3, %4}], [%2];"
               ::"r"(dst), "l"((uint64_t)map), "r"(mb), "r"(c0), "r"(c1) : "memory");
}
__device__ __forceinline__ void tma_store_2d(const CUtensorMap* map, unsigned src, int c0, int c1) {
  asm volatile("cp.async.bulk.tensor.2d.global.shared::cta.bulk_group [%0, {%2, %3}], [%1];"
               ::"l"((uint64_t)map), "r"(src), "r"(c0), "r"(c1) : "memory");
}
__device__ __forceinline__ void fence_proxy_async() { asm volatile("fence.proxy.async;" ::: "memory"); }
__device__ __forceinline__ void fence_proxy_async_smem() { asm volatile("fence.proxy.async.shared::cta;" ::: "memory"); }
__device__ __forceinline__ void ldsm_x4(unsigned* r, unsigned addr) {
  asm volatile("ldmatrix.sync.aligned.m8n8.x4.shared.b16 {%0,%1,%2,%3}, [%4];" : "=r"(r[0]), "=r"(r[1]), "=r"(r[2]), "=r"(r[3]) : "r"(addr) : "memory");
}
__device__ __forceinline__ void ldsm_x4_t(unsigned* r, unsigned addr) {
  asm volatile("ldmatrix.sync.aligned.m8n8.x4.trans.shared.b16 {%0,%1,%2,%3}, [%4];" : "=r"(r[0]), "=r"(r[1]), "=r"(r[2]), "=r"(r[3]) : "r"(addr) : "memory");
}
__device__ __forceinline__ void stsm_x2_t(unsigned addr, unsigned r0, unsigned r1) {
  asm volatile("stmatrix.sync.aligned.m8n8.x2.trans.shared.b16 [%0], {%1,%2};" ::"r"(addr), "r"(r0), "r"(r1) : "memory");
}
__device__ __forceinline__ void stsm_x4(unsigned addr, unsigned r0, unsigned r1, unsigned r2, unsigned r3) {
  asm volatile("stmatrix.sync.aligned.m8n8.x4.shared.b16 [%0], {%1,%2,%3,%4};" ::"r"(addr), "r"(r0), "r"(r1), "r"(r2), "r"(r3) : "memory");
}
__device__ __forceinline__ void mma16816(float* d, const unsigned* a, unsigned b0, unsigned b1) {
  asm volatile("mma.sync.aligned.m16n8k16.row.col.f32.bf16.bf16.f32 {%0,%1,%2,%3}, {%4,%5,%6,%7}, {%8,%9}, {%0,%1,%2,%3};"
               : "+f"(d[0]), "+f"(d[1]), "+f"(d[2]), "+f"(d[3]) : "r"(a[0]), "r"(a[1]), "r"(a[2]), "r"(a[3]), "r"(b0), "r"(b1));
}
__device__ __forceinline__ void mma1688(float* d, unsigned a0, unsigned a1, unsigned b0) {
  asm volatile("mma.sync.aligned.m16n8k8.row.col.f32.bf16.bf16.f32 {%0,%1,%2,%3}, {%4,%5}, {%6}, {%0,%1,%2,%3};"
               : "+f"(d[0]), "+f"(d[1]), "+f"(d[2]), "+f"(d[3]) : "r"(a0), "r"(a1), "r"(b0));
}
__device__ __forceinline__ uint64_t mkdesc(unsigned addr, unsigned lbo, unsigned sbo) {
  return (uint64_t)((addr >> 4) & 0x3fff) | ((uint64_t)(lbo >> 4) << 16) | ((uint64_t)(sbo >> 4) << 32) | (1ull << 62);
}
#define R8(b) "+f"(d[b]), "+f"(d[b + 1]), "+f"(d[b + 2]), "+f"(d[b + 3]), "+f"(d[b + 4]), "+f"(d[b + 5]), "+f"(d[b + 6]), "+f"(d[b + 7])
#define R32(b) R8(b), R8(b + 8), R8(b + 16), R8(b + 24)
__device__ __forceinline__ void wgmma_n256(float* d, uint64_t ad, uint64_t bd, int acc) {
  asm volatile(
      "{.reg .pred p; setp.ne.b32 p, %130, 0;\n"
      "wgmma.mma_async.sync.aligned.m64n256k16.f32.bf16.bf16 "
      "{%0,%1,%2,%3,%4,%5,%6,%7,%8,%9,%10,%11,%12,%13,%14,%15,%16,%17,%18,%19,%20,%21,%22,%23,%24,%25,%26,%27,%28,%29,%30,%31,"
      "%32,%33,%34,%35,%36,%37,%38,%39,%40,%41,%42,%43,%44,%45,%46,%47,%48,%49,%50,%51,%52,%53,%54,%55,%56,%57,%58,%59,%60,%61,%62,%63,"
      "%64,%65,%66,%67,%68,%69,%70,%71,%72,%73,%74,%75,%76,%77,%78,%79,%80,%81,%82,%83,%84,%85,%86,%87,%88,%89,%90,%91,%92,%93,%94,%95,"
      "%96,%97,%98,%99,%100,%101,%102,%103,%104,%105,%106,%107,%108,%109,%110,%111,%112,%113,%114,%115,%116,%117,%118,%119,%120,%121,%122,%123,%124,%125,%126,%127},"
      "%128, %129, p, 1, 1, 0, 1;}\n"
      : R32(0), R32(32), R32(64), R32(96)
      : "l"(ad), "l"(bd), "r"(acc));
}

__device__ __forceinline__ void ln16(const float* x, float* o) {
  float s = 0;
#pragma unroll
  for (int i = 0; i < 16; i++) s += x[i];
#pragma unroll
  for (int of = 16; of > 0; of >>= 1) s += __shfl_xor_sync(~0u, s, of);
  float mean = s * (1.0f / DM);
  float v = 0;
#pragma unroll
  for (int i = 0; i < 16; i++) { float dd = x[i] - mean; v += dd * dd; }
#pragma unroll
  for (int of = 16; of > 0; of >>= 1) v += __shfl_xor_sync(~0u, v, of);
  float mb = bf16r(mean);
  float vb = bf16r(v * (1.0f / DM));
  float den = bf16r(sqrtf(bf16r(vb + 1e-5f)));
#pragma unroll
  for (int i = 0; i < 16; i++) o[i] = bf16r(__fdiv_rn(bf16r(x[i] - mb), den));
}
__global__ void __launch_bounds__(256) k_pre(const bf16* __restrict__ x, const char* wq, const char* wk, const char* wv, const char* wo) {
  int t = threadIdx.x, lane = t & 31, w = t >> 5;
  asm volatile("griddepcontrol.launch_dependents;");
  {
    int g2 = blockIdx.x * 256 + t, o = (g2 & 32767) * 128;
    asm volatile("prefetch.global.L2 [%0];" ::"l"((g2 < 32768 ? wk : wv) + o));
    asm volatile("prefetch.global.L2 [%0];" ::"l"((g2 < 32768 ? wq : wo) + o));
  }
  int row = blockIdx.x * 8 + w;
  const uint4* src = reinterpret_cast<const uint4*>(x + (size_t)row * DM);
  uint4 a = src[lane], b = src[lane + 32];
  unsigned u[8] = {a.x, a.y, a.z, a.w, b.x, b.y, b.z, b.w};
  float f[16], o[16], o2[16];
#pragma unroll
  for (int i = 0; i < 8; i++) { f[2 * i] = bf_lo(u[i]); f[2 * i + 1] = bf_hi(u[i]); }
  ln16(f, o);
  ln16(o, o2);
  uint4* d1 = reinterpret_cast<uint4*>(g_xn + (size_t)row * DM);
  uint4* d2 = reinterpret_cast<uint4*>(g_y + (size_t)row * DM);
  d1[lane] = make_uint4(pack_bf16(o[0], o[1]), pack_bf16(o[2], o[3]), pack_bf16(o[4], o[5]), pack_bf16(o[6], o[7]));
  d1[lane + 32] = make_uint4(pack_bf16(o[8], o[9]), pack_bf16(o[10], o[11]), pack_bf16(o[12], o[13]), pack_bf16(o[14], o[15]));
  d2[lane] = make_uint4(pack_bf16(o2[0], o2[1]), pack_bf16(o2[2], o2[3]), pack_bf16(o2[4], o2[5]), pack_bf16(o2[6], o2[7]));
  d2[lane + 32] = make_uint4(pack_bf16(o2[8], o2[9]), pack_bf16(o2[10], o2[11]), pack_bf16(o2[12], o2[13]), pack_bf16(o2[14], o2[15]));
  int gt = blockIdx.x * 256 + t;
  uint4 z = make_uint4(0, 0, 0, 0);
  if (gt < 16384) reinterpret_cast<uint4*>(g_part)[gt] = z;
  if (gt < (int)(sizeof(Flags) / 4)) reinterpret_cast<unsigned*>(&g_flags)[gt] = 0;
}

struct Maps { CUtensorMap xn, y, h1, o, qkv_st, qkv_ld, g, wq, wk, wv, wo, w1, w2; };

#define NSTAGE 3
#define STAGE_BYTES 49152
#define B_STG (NSTAGE * STAGE_BYTES)
#define R_WO 0
#define R_T1 65536
#define R_T2 131072
#define R_RING 65536
#define RING_N 4
#define RING_BYTES 12288
#define R_MEM 196608
#define R_QS (R_MEM + 8448)
#define R_KS (R_QS + 1152)
#define R_OS (R_KS + 1152)
#define R_SOWN (R_OS + 2176)
#define R_SPEER (R_SOWN + 1280)
#define R_VM (R_SPEER + 1280)
#define R_VRED (R_VM + 2048)
#define R_RS (R_VRED + 6144)
#define SM_BAR (R_RS + 8192)
#define SMEM_TOTAL (SM_BAR + 256 + 1024)
#define MB_FULL 0
#define MB_EMPTY 8
#define MB_STGF 16
#define MB_STGE 17
#define MB_W0 18
#define MB_W1 19
#define MB_WO 20
#define MB_S 21
#define MB_V 22
#define MB_KVR 23
#define MB_KVF 24
#define MB_RS 25
#define MB_AG 26
#define SM_MISC (SM_BAR + 224)

#define N_KV 512
#define I_M1 512
#define I_Q 624
#define I_M2 880
#define I_POST 912
#define I_TAIL (I_POST + 16 * 32)
#define N_ITEMS (I_TAIL + 5 * 8 + 32 + 8 + 64)
enum { T_QKV = 0, T_M1 = 1, T_M2 = 2, T_ATT = 3, T_OUT = 4, T_OUTL = 5, T_RED = 6, T_REDL = 7 };
struct Item { int type, b, c, ks; };
__device__ __forceinline__ Item decode_item(int i) {
  Item it; it.ks = 0;
  if (i < N_KV) { it.type = T_QKV; it.b = i >> 5; it.c = 16 + (i & 31); }
  else if (i < I_Q) { it.type = T_M1; it.b = (i - I_M1) / 7; it.c = (i - I_M1) % 7; }
  else if (i < I_M2) { it.type = T_QKV; it.b = (i - I_Q) >> 4; it.c = (i - I_Q) & 15; }
  else if (i < I_POST) { it.type = T_M2; it.b = (i - I_M2) >> 1; it.c = (i - I_M2) & 1; }
  else if (i < I_TAIL) {
    int x = i - I_POST, p = x >> 5, r = x & 31;
    if (r < 16) { it.type = T_ATT; it.b = p; it.c = r; }
    else if (r < 24) { it.type = T_OUT; it.b = p - 3; it.c = r & 1; it.ks = (r - 16) >> 1; }
    else { it.type = T_RED; it.b = p - 5; it.c = r - 24; }
  } else {
    int x = i - I_TAIL, r = x & 7;
    if (x < 40) {
      int q = x >> 3;
      if (q == 0 || q == 2) { it.type = T_OUT; it.b = 13 + (q >> 1); it.c = r & 1; it.ks = r >> 1; }
      else { it.type = T_RED; it.b = q == 1 ? 11 : 9 + q; it.c = r; }
    }
    else if (x < 72) { it.type = T_OUTL; it.b = 15; it.c = x & 1; it.ks = (x - 40) >> 1; }
    else if (x < 80) { it.type = T_RED; it.b = 14; it.c = r; }
    else { it.type = T_REDL; it.b = 15; it.c = x - 80; }
  }
  return it;
}
__device__ __forceinline__ int item_nkb(int type) { return type == T_M2 ? 28 : (type == T_OUT ? 16 : (type >= T_RED ? 1 : (type >= T_ATT ? 4 : 8))); }

__device__ __forceinline__ void st_async_b64(unsigned raddr, unsigned lo, unsigned hi, unsigned rmb) {
  asm volatile("st.async.weak.shared::cluster.mbarrier::complete_tx::bytes.v2.b32 [%0], {%1,%2}, [%3];" ::"r"(raddr), "r"(lo), "r"(hi), "r"(rmb) : "memory");
}
__device__ __forceinline__ void st_async_b32(unsigned raddr, unsigned v, unsigned rmb) {
  asm volatile("st.async.weak.shared::cluster.mbarrier::complete_tx::bytes.b32 [%0], %1, [%2];" ::"r"(raddr), "r"(v), "r"(rmb) : "memory");
}
__device__ __forceinline__ unsigned mapa(unsigned a, unsigned rank) {
  unsigned r; asm volatile("mapa.shared::cluster.u32 %0, %1, %2;" : "=r"(r) : "r"(a), "r"(rank)); return r;
}
__device__ __forceinline__ void sts64(unsigned a, unsigned x, unsigned y) { asm volatile("st.shared.v2.b32 [%0], {%1,%2};" ::"r"(a), "r"(x), "r"(y) : "memory"); }
__device__ __forceinline__ void sts128(unsigned a, uint4 v) { asm volatile("st.shared.v4.b32 [%0], {%1,%2,%3,%4};" ::"r"(a), "r"(v.x), "r"(v.y), "r"(v.z), "r"(v.w) : "memory"); }
__device__ __forceinline__ uint2 lds64(unsigned a) { uint2 v; asm volatile("ld.shared.v2.b32 {%0,%1}, [%2];" : "=r"(v.x), "=r"(v.y) : "r"(a) : "memory"); return v; }
__device__ __forceinline__ uint4 lds128(unsigned a) { uint4 v; asm volatile("ld.shared.v4.b32 {%0,%1,%2,%3}, [%4];" : "=r"(v.x), "=r"(v.y), "=r"(v.z), "=r"(v.w) : "r"(a) : "memory"); return v; }
__device__ __forceinline__ float lds32f(unsigned a) { float v; asm volatile("ld.shared.f32 %0, [%1];" : "=f"(v) : "r"(a) : "memory"); return v; }
#define spin_check(it) TRAP_IF(++it)
#define POLLV 0
#define BAR8 0
#define D_STAG 150
#define D_RED 480
#define D_PUB 0
#define DELAY(n) do { unsigned c0_, c1_; asm volatile("mov.u32 %0, %%clock;" : "=r"(c0_)); do { asm volatile("mov.u32 %0, %%clock;" : "=r"(c1_)); } while (c1_ - c0_ < (n)); } while (0)
#define VD 2
#define NPRE 3
#define SCALE_QK 0.08838834764831845f

__device__ __forceinline__ void rec_worker(const Maps& maps, unsigned sb, const bf16* __restrict__ mem0) {
  const int c = blockIdx.x, h = c >> 1, j = c & 1;
  const int t = opaque_tid(), lane = t & 31, w = t >> 5, g = lane >> 2, tq = lane & 3;
  const int m = lane >> 3, r8 = lane & 7, kh = w >> 2, et = w & 3;
  const unsigned bar = sb + SM_BAR;
  unsigned wq[16][4], wk[16][4], wo[8][4];
  const unsigned woff = (kh * 4) * 8192 + ((m >> 1) * 8 + r8) * 128 + (((et * 2 + (m & 1)) ^ r8) << 4);
  mbar_wait(bar + 8 * MB_W0, 0);
#pragma unroll
  for (int i = 0; i < 16; i++) {
    ldsm_x4_t(wq[i], sb + R_WO + woff + (i >> 2) * 8192 + (i & 3) * 2048);
    ldsm_x4_t(wk[i], sb + R_T1 + woff + (i >> 2) * 8192 + (i & 3) * 2048);
  }
  bar_sync(2, 288);
  if (t == 0) {
    fence_proxy_async_smem();
    mbar_expect_tx(bar + 8 * MB_WO, 65536);
    for (int kb = 0; kb < 2; kb++)
      for (int cb = 0; cb < 4; cb++) tma_load_2d(sb + R_WO + (kb * 4 + cb) * 8192, &maps.wo, j * 256 + cb * 64, h * 128 + kb * 64, bar + 8 * MB_WO);
  }
  mbar_wait(bar + 8 * MB_W1, 0);
  const unsigned pV = sb + R_T2 + woff;
  const unsigned rk = c & 7, peer = rk ^ 1, cl = c >> 3;
#define KEEP(x) x = __shfl_sync(~0u, x, lane)
  unsigned pA = sb + R_MEM + kh * 4096 + lane * 16;
  unsigned pW0 = sb + R_WO + (w >> 1) * 8192 + ((m >> 1) * 8 + r8) * 128 + ((((w & 1) * 4 + (m & 1)) ^ r8) << 4);
  unsigned pW1 = pW0 ^ 32;
  unsigned pVk = pV;
  unsigned aX = sb + R_VRED + et * 512 + lane * 16;
  unsigned aQKst = sb + (kh ? R_KS : R_QS) + r8 * 144 + (et * 16 + (m & 1) * 8) * 2;
  unsigned aL8 = sb + lane * 8;
  unsigned aSl = mapa(sb + R_SOWN + w * 256 + lane * 8, rk), aSr = mapa(sb + R_SPEER + w * 256 + lane * 8, peer);
  unsigned aVl = mapa(sb + R_VM + (j * 4 + et) * 256 + lane * 8, rk), aVr = mapa(sb + R_VM + (j * 4 + et) * 256 + lane * 8, peer);
  const unsigned mbSl = mapa(bar + 8 * MB_S, rk), mbSr = mapa(bar + 8 * MB_S, peer), mbVl = mbSl + 8, mbVr = mbSr + 8;
  unsigned aQ = sb + R_QS + r8 * 144 + m * 16;
  unsigned oKx = (et * 8 + r8) * 128 + ((m ^ r8) << 4);
  unsigned oVx = 4096 + (et >> 1) * 4096 + ((m >> 1) * 8 + r8) * 128 + ((((et & 1) * 4 + (m & 1)) ^ r8) << 4);
  unsigned aOst = sb + R_OS + r8 * 272 + (et * 32 + m * 8) * 2;
  unsigned aOld = sb + R_OS + r8 * 272 + m * 16;
  unsigned aVm = sb + R_VM + et * 512 + lane * 8;
  unsigned aRSr = mapa(sb + R_RS + (h & 3) * 2048 + (w & 1) * 1024 + lane * 8, j * 4 + (w >> 1));
  unsigned mbRSr = mapa(bar + 8 * MB_RS, j * 4 + (w >> 1));
  unsigned t8 = t * 8;
  KEEP(pA); KEEP(pW0); KEEP(pW1); KEEP(pVk); KEEP(aX); KEEP(aQKst); KEEP(aL8); KEEP(aSl); KEEP(aSr); KEEP(aVl); KEEP(aVr); KEEP(aQ); KEEP(oKx); KEEP(oVx);
  KEEP(aOst); KEEP(aOld); KEEP(aVm); KEEP(aRSr); KEEP(mbRSr); KEEP(t8);
  mbar_wait(bar + 8 * MB_WO, 0);
#pragma unroll
  for (int ks = 0; ks < 4; ks++) { ldsm_x4_t(wo[2 * ks], pW0 + ks * 2048); ldsm_x4_t(wo[2 * ks + 1], pW1 + ks * 2048); }
  {
    unsigned v[8];
#pragma unroll
    for (int q = 0; q < 8; q++) v[q] = __ldg(reinterpret_cast<const unsigned*>(mem0) + q * 256 + t);
    sts128(sb + R_MEM + t * 32, make_uint4(__byte_perm(v[0], v[1], 0x5410), __byte_perm(v[2], v[3], 0x5410), __byte_perm(v[4], v[5], 0x5410), __byte_perm(v[6], v[7], 0x5410)));
    sts128(sb + R_MEM + t * 32 + 16, make_uint4(__byte_perm(v[0], v[1], 0x7632), __byte_perm(v[2], v[3], 0x7632), __byte_perm(v[4], v[5], 0x7632), __byte_perm(v[6], v[7], 0x7632)));
  }
  bar_sync(1, 256);

#pragma unroll 1
  for (int s = 0;; s++) {
    const unsigned par = s & 1;
    const unsigned slot = s & (RING_N - 1), rpar = (s / RING_N) & 1;
    const unsigned ring = sb + R_RING + slot * RING_BYTES;
    asm volatile("" : "+r"(t8));
    RSTAMP(1);
    RSTAMP(2);
    float aq[4] = {0, 0, 0, 0}, ak[4] = {0, 0, 0, 0}, av[4] = {0, 0, 0, 0};
    {
      unsigned b[8][4], f1[8][4], f0[8][4];
#define VLD(i) do { ldsm_x4_t(b[i], pA + (i) * 512); ldsm_x4_t(f0[i], pVk + ((i) >> 1) * 8192 + ((i) & 1) * 4096); ldsm_x4_t(f1[i], pVk + ((i) >> 1) * 8192 + ((i) & 1) * 4096 + 2048); } while (0)
      VLD(0);
      if (VD > 1) VLD(1);
#pragma unroll
      for (int i = 0; i < 8; i++) {
        if (i + VD < 8) VLD(i + VD);
        mma16816(aq, wq[2 * i], b[i][0], b[i][1]); mma16816(ak, wk[2 * i], b[i][0], b[i][1]); mma16816(av, f0[i], b[i][0], b[i][1]);
        mma16816(aq, wq[2 * i + 1], b[i][2], b[i][3]); mma16816(ak, wk[2 * i + 1], b[i][2], b[i][3]); mma16816(av, f1[i], b[i][2], b[i][3]);
      }
    }
    RSTAMP(3);
#define STSF4(a, v) asm volatile("st.shared.v4.f32 [%0], {%1,%2,%3,%4};" ::"r"(a), "f"(v[0]), "f"(v[1]), "f"(v[2]), "f"(v[3]) : "memory")
    unsigned f[8][4];
#define WO_PREFETCH() do { _Pragma("unroll") for (int i = 0; i < NPRE; i++) { ldsm_x4_t(f[2 * i], pW0 + 32768 + i * 2048); ldsm_x4_t(f[2 * i + 1], pW1 + 32768 + i * 2048); } } while (0)
    if (kh) {
      STSF4(aX, aq);
      bar_sync(4 + et, 64);
      uint4 o = lds128(aX + 2048), o2 = lds128(aX + 4096);
      stsm_x2_t(aQKst, pack_bf16(ak[0] + __uint_as_float(o.x), ak[1] + __uint_as_float(o.y)), pack_bf16(ak[2] + __uint_as_float(o.z), ak[3] + __uint_as_float(o.w)));
      bar_arrive(1, 256);
      unsigned x = pack_bf16(av[0] + __uint_as_float(o2.x), av[1] + __uint_as_float(o2.y)), y = pack_bf16(av[2] + __uint_as_float(o2.z), av[3] + __uint_as_float(o2.w));
      st_async_b64(aVr, x, y, mbVr);
      st_async_b64(aVl, x, y, mbVl);
      if (s == NSEG - 1) {
        mbar_wait(bar + 8 * MB_V, par);
        if (t == 128) mbar_arrive(bar + 8 * MB_KVR);
        break;
      }
      mbar_wait(bar + 8 * (MB_FULL + slot), rpar);
      unsigned vx[4][4];
      ldsm_x4_t(vx[0], ring + oVx); ldsm_x4_t(vx[1], ring + oVx + 2048); ldsm_x4_t(vx[2], ring + (oVx ^ 32)); ldsm_x4_t(vx[3], ring + (oVx ^ 32) + 2048);
      RSTAMP(4); RSTAMP(5); RSTAMP(6); RSTAMP(7);
      mbar_wait(bar + 8 * MB_S, par);
      RSTAMP(8);
      float sc[10];
#pragma unroll
      for (int i = 0; i < 5; i++) {
        uint2 o = lds64(aL8 + R_SOWN + i * 256), p = lds64(aL8 + R_SPEER + i * 256);
        sc[2 * i] = __uint_as_float(o.x) + __uint_as_float(p.x); sc[2 * i + 1] = __uint_as_float(o.y) + __uint_as_float(p.y);
      }
      mbar_wait(bar + 8 * MB_V, par);
      uint2 vm0 = lds64(aVm), vm1 = lds64(aVm + 256);
      float mx = fmaxf(fmaxf(fmaxf(sc[0], sc[1]), fmaxf(sc[2], sc[3])), fmaxf(fmaxf(fmaxf(sc[4], sc[5]), fmaxf(sc[6], sc[7])), fmaxf(sc[8], sc[9])));
      mx = fmaxf(mx, __shfl_xor_sync(~0u, mx, 1)); mx = fmaxf(mx, __shfl_xor_sync(~0u, mx, 2));
      const float nm = -mx * (SCALE_QK * LOG2E);
      unsigned p[5];
#pragma unroll
      for (int i = 0; i < 5; i++) p[i] = pack_bf16(ex2f(fmaf(sc[2 * i], SCALE_QK * LOG2E, nm)), ex2f(fmaf(sc[2 * i + 1], SCALE_QK * LOG2E, nm)));
      RSTAMP(9);
      float o0[4] = {0, 0, 0, 0}, o1[4] = {0, 0, 0, 0}, o3[4] = {0, 0, 0, 0}, o4[4] = {0, 0, 0, 0}, z0[4] = {0, 0, 0, 0}, z1[4] = {0, 0, 0, 0};
      const unsigned ones[4] = {0x3F803F80u, 0u, 0x3F803F80u, 0u};
      mma16816(z0, ones, p[0], p[1]); mma16816(z1, ones, p[2], p[3]);
      mma16816(o0, vx[0], p[0], p[1]); mma16816(o3, vx[2], p[0], p[1]);
      mma1688(z0, 0x3F803F80u, 0u, p[4]);
      mma16816(o1, vx[1], p[2], p[3]); mma16816(o4, vx[3], p[2], p[3]);
      mma1688(o0, vm0.x, vm0.y, p[4]); mma1688(o3, vm1.x, vm1.y, p[4]);
      float i0, i1;
      asm("rcp.approx.ftz.f32 %0, %1;" : "=f"(i0) : "f"(z0[0] + z1[0])); asm("rcp.approx.ftz.f32 %0, %1;" : "=f"(i1) : "f"(z0[1] + z1[1]));
      asm volatile("stmatrix.sync.aligned.m8n8.x4.trans.shared.b16 [%0], {%1,%2,%3,%4};" ::"r"(aOst), "r"(pack_bf16((o0[0] + o1[0]) * i0, (o0[1] + o1[1]) * i1)), "r"(pack_bf16((o0[2] + o1[2]) * i0, (o0[3] + o1[3]) * i1)),
                   "r"(pack_bf16((o3[0] + o4[0]) * i0, (o3[1] + o4[1]) * i1)), "r"(pack_bf16((o3[2] + o4[2]) * i0, (o3[3] + o4[3]) * i1)) : "memory");
      RSTAMP(10);
      bar_sync(1, 256);
      WO_PREFETCH();
    } else {
      STSF4(aX + 2048, ak); STSF4(aX + 4096, av);
      unsigned kb[8];
      mbar_wait(bar + 8 * (MB_FULL + slot), rpar);
      ldsm_x4(kb, ring + oKx); ldsm_x4(kb + 4, ring + (oKx ^ 64));
      bar_sync(4 + et, 64);
      uint4 o = lds128(aX);
      stsm_x2_t(aQKst, pack_bf16(aq[0] + __uint_as_float(o.x), aq[1] + __uint_as_float(o.y)), pack_bf16(aq[2] + __uint_as_float(o.z), aq[3] + __uint_as_float(o.w)));
      RSTAMP(4);
      bar_sync(1, 256);
      RSTAMP(5);
      if (s == NSEG - 1) break;
      unsigned qa[8], km[8];
      ldsm_x4(qa, aQ); ldsm_x4(qa + 4, aQ + 64);
      if (w == 3) { ldsm_x4(km, aQ + 1152); ldsm_x4(km + 4, aQ + 1152 + 64); }
      float s0[4] = {0, 0, 0, 0}, s1[4] = {0, 0, 0, 0};
      unsigned af[4][4];
#pragma unroll
      for (int i = 0; i < 4; i++) { af[i][0] = qa[2 * i]; af[i][1] = 0; af[i][2] = qa[2 * i + 1]; af[i][3] = 0; }
      mma16816(s0, af[0], kb[0], kb[1]); mma16816(s1, af[1], kb[2], kb[3]);
      mma16816(s0, af[2], kb[4], kb[5]); mma16816(s1, af[3], kb[6], kb[7]);
      if (w == 3) {
        float m0[4] = {0, 0, 0, 0}, m1[4] = {0, 0, 0, 0};
        mma16816(m0, af[0], km[0], km[1]); mma16816(m1, af[1], km[2], km[3]);
        mma16816(m0, af[2], km[4], km[5]); mma16816(m1, af[3], km[6], km[7]);
        unsigned x = __float_as_uint(m0[0] + m1[0]), y = __float_as_uint(m0[1] + m1[1]);
        st_async_b64(aSr + 256, x, y, mbSr); st_async_b64(aSl + 256, x, y, mbSl);
      }
      unsigned x = __float_as_uint(s0[0] + s1[0]), y = __float_as_uint(s0[1] + s1[1]);
      st_async_b64(aSr, x, y, mbSr); st_async_b64(aSl, x, y, mbSl);
      RSTAMP(6);
      WO_PREFETCH();
      RSTAMP(7); RSTAMP(8); RSTAMP(9); RSTAMP(10);
      bar_sync(1, 256);
    }
    RSTAMP(11);
    float d0[4] = {0, 0, 0, 0}, d1[4] = {0, 0, 0, 0}, e0[4] = {0, 0, 0, 0}, e1[4] = {0, 0, 0, 0};
    unsigned ob[4][4];
#pragma unroll
    for (int k2 = 0; k2 < 4; k2++) ldsm_x4(ob[k2], aOld + k2 * 64);
#pragma unroll
    for (int i = NPRE; i < 4; i++) { ldsm_x4_t(f[2 * i], pW0 + 32768 + i * 2048); ldsm_x4_t(f[2 * i + 1], pW1 + 32768 + i * 2048); }
    mma16816(d0, wo[0], ob[0][0], ob[0][1]); mma16816(d1, wo[1], ob[0][0], ob[0][1]);
    mma16816(e0, wo[2], ob[0][2], ob[0][3]); mma16816(e1, wo[3], ob[0][2], ob[0][3]);
    mma16816(d0, wo[4], ob[1][0], ob[1][1]); mma16816(d1, wo[5], ob[1][0], ob[1][1]);
    mma16816(e0, wo[6], ob[1][2], ob[1][3]); mma16816(e1, wo[7], ob[1][2], ob[1][3]);
    mma16816(d0, f[0], ob[2][0], ob[2][1]); mma16816(d1, f[1], ob[2][0], ob[2][1]);
    mma16816(e0, f[2], ob[2][2], ob[2][3]); mma16816(e1, f[3], ob[2][2], ob[2][3]);
    mma16816(d0, f[4], ob[3][0], ob[3][1]); mma16816(d1, f[5], ob[3][0], ob[3][1]);
    mma16816(e0, f[6], ob[3][2], ob[3][3]); mma16816(e1, f[7], ob[3][2], ob[3][3]);
    st_async_b64(aRSr, __float_as_uint(d0[0] + e0[0]), __float_as_uint(d0[1] + e0[1]), mbRSr);
    st_async_b64(aRSr + 256, __float_as_uint(d0[2] + e0[2]), __float_as_uint(d0[3] + e0[3]), mbRSr);
    st_async_b64(aRSr + 512, __float_as_uint(d1[0] + e1[0]), __float_as_uint(d1[1] + e1[1]), mbRSr);
    st_async_b64(aRSr + 768, __float_as_uint(d1[2] + e1[2]), __float_as_uint(d1[3] + e1[3]), mbRSr);
    RSTAMP(12);
    if (t == 128) {
      mbar_arrive(bar + 8 * (MB_EMPTY + slot)); mbar_arrive(bar + 8 * MB_KVR);
      mbar_expect_tx(bar + 8 * MB_S, 2560); mbar_expect_tx(bar + 8 * MB_V, 2048);
    }
    const unsigned tag = ((s >> 1) & 1) ^ 1;
    const char* gp = reinterpret_cast<const char*>(g_part);
    const unsigned goff = (par * 8 + rk) * 16384 + cl * 2048 + t8;
    unsigned mbA[8];
#pragma unroll
    for (int i = 0; i < 8; i++) mbA[i] = mapa(bar + 8 * MB_AG, i);
    const unsigned dlt = (R_MEM + rk * 1024) - (SM_BAR + 8 * MB_AG) + (t8 >> 1);
    mbar_wait(bar + 8 * MB_RS, par);
    RSTAMP(13);
    uint2 a[8];
    {
      uint2 x0 = lds64(sb + R_RS + t8), x1 = lds64(sb + R_RS + 2048 + t8), x2 = lds64(sb + R_RS + 4096 + t8), x3 = lds64(sb + R_RS + 6144 + t8);
      float r0 = (__uint_as_float(x0.x) + __uint_as_float(x1.x)) + (__uint_as_float(x2.x) + __uint_as_float(x3.x));
      float r1 = (__uint_as_float(x0.y) + __uint_as_float(x1.y)) + (__uint_as_float(x2.y) + __uint_as_float(x3.y));
      a[0].x = (__float_as_uint(r0) & ~1u) | tag; a[0].y = (__float_as_uint(r1) & ~1u) | tag;
      asm volatile("st.relaxed.gpu.global.v2.u32 [%0], {%1,%2};" ::"l"(gp + goff), "r"(a[0].x), "r"(a[0].y) : "memory");
    }
    RSTAMP(14);
    if (t == 128) mbar_expect_tx(bar + 8 * MB_RS, 8192);
    {
      unsigned it = 0;
#define PLOAD(a) _Pragma("unroll") for (int i = 1; i < 8; i++) a[i] = ldv2_relaxed(gp + (goff ^ (i * 2048)))
#define PAND(a) (((a[1].x & a[1].y) & (a[2].x & a[2].y) & (a[3].x & a[3].y)) & ((a[4].x & a[4].y) & (a[5].x & a[5].y)) & ((a[6].x & a[6].y) & (a[7].x & a[7].y)))
#define POR(a) (((a[1].x | a[1].y) | (a[2].x | a[2].y) | (a[3].x | a[3].y)) | ((a[4].x | a[4].y) | (a[5].x | a[5].y)) | ((a[6].x | a[6].y) | (a[7].x | a[7].y)))
#define POK(a) (((tag ? PAND(a) : ~POR(a)) & 1u) != 0)
      if (D_RED) DELAY(D_RED);
      while (true) { PLOAD(a); if (POK(a)) break; if (D_PUB) DELAY(D_PUB); spin_check(it); }
    }
    RSTAMP(15);
    {
#define AF(i, c) __uint_as_float(a[i].c)
      unsigned u = pack_bf16(((AF(0, x) + AF(1, x)) + (AF(2, x) + AF(3, x))) + ((AF(4, x) + AF(5, x)) + (AF(6, x) + AF(7, x))),
                             ((AF(0, y) + AF(1, y)) + (AF(2, y) + AF(3, y))) + ((AF(4, y) + AF(5, y)) + (AF(6, y) + AF(7, y))));
      __syncwarp();
#pragma unroll
      for (int i = 0; i < 8; i++) st_async_b32(mbA[i] + dlt, u, mbA[i]);
    }
    mbar_wait(bar + 8 * MB_KVF, par);
    mbar_wait(bar + 8 * MB_AG, par);
    if (t == 128) mbar_expect_tx(bar + 8 * MB_AG, 8192);
  }
}

__device__ __forceinline__ void rec_ring(const Maps& maps, unsigned sb) {
  const int c = blockIdx.x, h = c >> 1, j = c & 1;
  const unsigned bar = sb + SM_BAR;
  const int lane = threadIdx.x & 31;
  __syncwarp();
  bar_sync(2, 288);
  if (lane == 0) {
    fence_proxy_async_smem();
    for (int s = 0; s < NSEG; s++) {
      unsigned slot = s & (RING_N - 1);
      if ((s & 3) == 0 && !DBGMODE) {
        wait_flag_ge(&g_flags.qkv[(s >> 2) * 48 + 16 + (h >> 1)], 1);
        wait_flag_ge(&g_flags.qkv[(s >> 2) * 48 + 32 + (h >> 1)], 1);
        fence_proxy_async();
      }
      if (s >= RING_N) mbar_wait_sleep(bar + 8 * (MB_EMPTY + slot), ((s / RING_N) - 1) & 1);
      unsigned dst = sb + R_RING + slot * RING_BYTES, mb = bar + 8 * (MB_FULL + slot);
      mbar_expect_tx(mb, RING_BYTES);
      tma_load_2d(dst, &maps.qkv_ld, HD + h * 128 + j * 64, s * SEG, mb);
      tma_load_2d(dst + 4096, &maps.qkv_ld, 2 * HD + h * 128, s * SEG, mb);
      tma_load_2d(dst + 8192, &maps.qkv_ld, 2 * HD + h * 128 + 64, s * SEG, mb);
    }
  }
}
__device__ __forceinline__ void rec_copy(unsigned sb) {
  const int c = blockIdx.x, h = c >> 1, j = c & 1;
  const unsigned bar = sb + SM_BAR;
  const int lane = threadIdx.x & 31;
  for (int s = 0; s < NSEG; s++) {
    if (s < NSEG - 1) mbar_wait_sleep(bar + 8 * MB_KVR, s & 1); else mbar_wait(bar + 8 * MB_KVR, s & 1);
    uint4 k0 = lds128(sb + R_KS + (lane >> 3) * 144 + (lane & 7) * 16), k1 = lds128(sb + R_KS + (4 + (lane >> 3)) * 144 + (lane & 7) * 16);
    uint2 v[4];
#pragma unroll
    for (int i = 0; i < 4; i++) v[i] = lds64(sb + R_VM + (j * 4 + i) * 256 + lane * 8);
    __syncwarp();
    if (lane == 0) mbar_arrive(bar + 8 * MB_KVF);
    bf16* kd = g_km + ((size_t)(s * NH + h) * NMEM) * DH + j * 64;
    *reinterpret_cast<uint4*>(kd + (lane >> 3) * DH + (lane & 7) * 8) = k0;
    *reinterpret_cast<uint4*>(kd + (4 + (lane >> 3)) * DH + (lane & 7) * 8) = k1;
    unsigned* vd = reinterpret_cast<unsigned*>(g_vmt) + ((size_t)(s * NH + h) * DH + j * 64) * 4;
#pragma unroll
    for (int i = 0; i < 4; i++) { vd[(i * 16) * 4 + lane] = v[i].x; vd[(i * 16 + 8) * 4 + lane] = v[i].y; }
    __syncwarp();
    if (lane == 0) st_release(&g_flags.rec[c], s + 1);
  }
}

__device__ __forceinline__ void bulk_producer(const Maps& maps, unsigned sb, int* misc) {
  const unsigned bar = sb + SM_BAR;
  const int lane = threadIdx.x & 31;
  unsigned st = 0, ph = 0, seq = 0;
  while (true) {
    int idx = 0;
    if (lane == 0) idx = (int)atomicAdd(&g_flags.ctr, 1u);
    idx = __shfl_sync(~0u, idx, 0);
    if (idx >= N_ITEMS) {
      if (lane == 0) {
        mbar_wait(bar + 8 * (MB_EMPTY + st), ph ^ 1);
        misc[seq & 3] = -1;
        mbar_arrive(bar + 8 * (MB_FULL + st));
      }
      break;
    }
    if (lane == 0) ISTAMP(idx, 0);
    Item it = decode_item(idx);
    if (it.b < 0) continue;
    const CUtensorMap* mp; int c0, c1, dc0, dc1; unsigned doff;
    const unsigned* fl = nullptr; unsigned tgt = 1; int nbox = 5, rdy = 0;
    if (it.type == T_ATT) {
      mp = &maps.qkv_ld; nbox = 12; doff = lane * 4096;
      c0 = (lane >> 2) * HD + it.c * 256 + (lane & 1) * 64; c1 = it.b * 128 + ((lane >> 1) & 1) * 32; dc0 = dc1 = 0;
      if (lane < 3) fl = &g_flags.qkv[it.b * 48 + lane * 16 + it.c];
      bool ok = true;
      if (lane >= 4 && lane < 8) ok = ld_acquire(&g_flags.rec[it.c * 4 + lane - 4]) >= (unsigned)(it.b * 4 + 4);
      rdy = __all_sync(~0u, ok) ? 65536 : 0;
    } else {
      int k0 = 0, nb0 = it.c * 256;
      if (it.type == T_QKV) { mp = lane == 0 ? &maps.xn : (it.c < 16 ? &maps.wq : (it.c < 32 ? &maps.wk : &maps.wv)); nb0 = (it.c & 15) * 256; }
      else if (it.type == T_M1) mp = lane == 0 ? &maps.y : &maps.w1;
      else if (it.type == T_M2) { mp = lane == 0 ? &maps.h1 : &maps.w2; fl = &g_flags.h1[it.b]; tgt = 7; }
      else {
        mp = lane == 0 ? &maps.o : &maps.wo;
        if (it.type == T_OUT) { k0 = it.ks * 1024; fl = &g_flags.o[it.b * 4 + it.ks]; tgt = 4; }
        else if (it.type == T_OUTL) { k0 = it.ks * 256; fl = &g_flags.o16[it.ks]; }
        else if (lane == 1) { fl = &g_flags.g[it.b]; tgt = 2; }
        else { fl = &g_flags.p[it.b]; tgt = it.type == T_RED ? 8 : 32; }
      }
      if (lane > (it.type >= T_RED ? 1 : 0)) fl = nullptr;
      if (lane == 0) { c0 = k0; c1 = it.b * 128; dc0 = 64; dc1 = 0; doff = 0; }
      else { c0 = nb0 + (lane - 1) * 64; c1 = k0; dc0 = 0; dc1 = 64; doff = 8192 + lane * 8192; }
    }
    if (fl) wait_flag_ge(fl, tgt);
    __syncwarp();
    fence_proxy_async();
    if (lane == 0) ISTAMP(idx, 1);
    const int nkb = item_nkb(it.type);
    for (int kb = 0; kb < nkb; kb++) {
      const unsigned mb = bar + 8 * (MB_FULL + st);
      mbar_wait(bar + 8 * (MB_EMPTY + st), ph ^ 1);
      if (lane == 0) {
        if (kb == 0) misc[seq & 3] = idx | rdy;
        if (it.type >= T_RED) mbar_arrive(mb); else mbar_expect_tx(mb, STAGE_BYTES);
      }
      if (it.type == T_ATT) { if (lane < 12) tma_load_2d(sb + st * STAGE_BYTES + doff, mp, c0 + (kb & 1) * 128, c1 + (kb >> 1) * 64, mb); }
      else if (lane < nbox && it.type < T_RED) tma_load_2d(sb + st * STAGE_BYTES + doff, mp, c0 + kb * dc0, c1 + kb * dc1, mb);
      __syncwarp();
      if (++st == NSTAGE) { st = 0; ph ^= 1; }
    }
    seq++;
  }
}
__device__ __forceinline__ void bulk_store(const Maps& maps, unsigned sb, volatile int* misc) {
  const unsigned bar = sb + SM_BAR;
  unsigned ph = 0;
  while (true) {
    mbar_wait(bar + 8 * MB_STGF, ph); ph ^= 1;
    int idx = misc[4];
    if (idx < 0) break;
    Item it = decode_item(idx);
    const CUtensorMap* mp = it.type == T_QKV ? &maps.qkv_st : (it.type == T_M1 ? &maps.h1 : (it.type == T_M2 ? &maps.g : &maps.o));
    unsigned* flag = it.type == T_QKV ? &g_flags.qkv[it.b * 48 + it.c] : (it.type == T_M1 ? &g_flags.h1[it.b] : (it.type == T_M2 ? &g_flags.g[it.b] : (it.b == 15 ? &g_flags.o16[it.c] : &g_flags.o[it.b * 4 + (it.c >> 2)])));
    for (int i = 0; i < 4; i++) tma_store_2d(mp, sb + B_STG + i * 16384, it.c * 256 + i * 64, it.b * 128);
    asm volatile("cp.async.bulk.commit_group;" ::: "memory");
    asm volatile("cp.async.bulk.wait_group.read 0;" ::: "memory");
    mbar_arrive(bar + 8 * MB_STGE);
    asm volatile("cp.async.bulk.wait_group 0;" ::: "memory");
    fence_proxy_async();
    red_release_add(flag, 1);
    ISTAMP(idx, 3);
  }
}
__device__ __forceinline__ float rcpf(float x) { float y; asm("rcp.approx.ftz.f32 %0, %1;" : "=f"(y) : "f"(x)); return y; }
__device__ __forceinline__ float gelu_t(float x) {
  float e = ex2f(x * fmaf(x * x, -2.0f * LOG2E * 0.7978845608028654f * 0.044715f, -2.0f * LOG2E * 0.7978845608028654f));
  return x * rcpf(1.0f + e);
}
__device__ __forceinline__ float silu_f(float x) { return x * rcpf(1.0f + ex2f(-LOG2E * x)); }
__device__ __forceinline__ unsigned badd2(unsigned a, unsigned b) { unsigned r; asm("add.rn.bf16x2 %0, %1, %2;" : "=r"(r) : "r"(a), "r"(b)); return r; }

__device__ __forceinline__ void final_out(bf16* __restrict__ out, const bf16* __restrict__ x, size_t o, float4 s) {
  uint2 gv = __ldcg(reinterpret_cast<const uint2*>(g_g + o)), xv = __ldg(reinterpret_cast<const uint2*>(x + o));
  uint2 r;
  r.x = pack_bf16(bf_lo(xv.x) + bf16r(bf16r(s.x) * bf_lo(gv.x)), bf_hi(xv.x) + bf16r(bf16r(s.y) * bf_hi(gv.x)));
  r.y = pack_bf16(bf_lo(xv.y) + bf16r(bf16r(s.z) * bf_lo(gv.y)), bf_hi(xv.y) + bf16r(bf16r(s.w) * bf_hi(gv.y)));
  *reinterpret_cast<uint2*>(out + o) = r;
}
__device__ __forceinline__ void bulk_att_load(unsigned* km, unsigned* vm, int b, int hp, int kb, int w, int lane) {
  const int g = lane >> 2, tq = lane & 3, seg = w >> 2, eh = w & 1;
  const int head = hp * 2 + (kb & 1), sg = b * 4 + (kb >> 1) * 2 + seg;
  const unsigned* kmp = reinterpret_cast<const unsigned*>(g_km + ((size_t)(sg * NH + head) * NMEM + g) * DH) + tq;
  const unsigned* vmp = reinterpret_cast<const unsigned*>(g_vmt) + ((size_t)(sg * NH + head) * DH + eh * 64) * 4 + lane;
#pragma unroll
  for (int i = 0; i < 16; i++) asm volatile("ld.global.cg.u32 %0, [%1];" : "=r"(km[i]) : "l"(kmp + i * 4) : "memory");
#pragma unroll
  for (int i = 0; i < 8; i++) asm volatile("ld.global.cg.u32 %0, [%1];" : "=r"(vm[i]) : "l"(vmp + i * 32) : "memory");
}
__device__ __forceinline__ void bulk_att_stage(unsigned sa, unsigned stg, const unsigned* km, const unsigned* vm, int kb, int w, int lane) {
  const int g = lane >> 2, tq = lane & 3, m = lane >> 3, r8 = lane & 7;
  const int seg = w >> 2, mt = (w >> 1) & 1, eh = w & 1;
  float s[5][4];
#pragma unroll
  for (int i = 0; i < 5; i++) { s[i][0] = s[i][1] = s[i][2] = s[i][3] = 0; }
  const unsigned qb = sa + (0 * 2 + seg) * 8192, kbs = sa + (1 * 2 + seg) * 8192, vb = sa + (2 * 2 + seg) * 8192 + eh * 4096;
  unsigned qa[8][4];
#pragma unroll
  for (int ks = 0; ks < 8; ks++) {
    int row = mt * 16 + (m & 1) * 8 + r8;
    ldsm_x4(qa[ks], qb + (ks >> 2) * 4096 + row * 128 + ((((ks & 3) * 2 + (m >> 1)) ^ r8) << 4));
    unsigned kf[4];
    int krow = (m >> 1) * 8 + r8;
    unsigned ka = kbs + (ks >> 2) * 4096 + krow * 128 + ((((ks & 3) * 2 + (m & 1)) ^ r8) << 4);
    ldsm_x4(kf, ka);
    mma16816(s[0], qa[ks], kf[0], kf[1]); mma16816(s[1], qa[ks], kf[2], kf[3]);
    if (mt) { ldsm_x4(kf, ka + 2048); mma16816(s[2], qa[ks], kf[0], kf[1]); mma16816(s[3], qa[ks], kf[2], kf[3]); }
  }
#pragma unroll
  for (int ks = 0; ks < 8; ks++) mma16816(s[4], qa[ks], km[2 * ks], km[2 * ks + 1]);
  float mx0 = -INFINITY, mx1 = -INFINITY;
  const int t0 = mt * 16 + g, t1 = t0 + 8;
#pragma unroll
  for (int i = 0; i < 5; i++) {
#pragma unroll
    for (int e = 0; e < 4; e++) {
      float v = s[i][e];
      if (i < 4) { int kj = i * 8 + 2 * tq + (e & 1); if (kj > (e < 2 ? t0 : t1)) v = -INFINITY; }
      s[i][e] = v;
      if (e < 2) mx0 = fmaxf(mx0, v); else mx1 = fmaxf(mx1, v);
    }
  }
  mx0 = fmaxf(mx0, __shfl_xor_sync(~0u, mx0, 1)); mx0 = fmaxf(mx0, __shfl_xor_sync(~0u, mx0, 2));
  mx1 = fmaxf(mx1, __shfl_xor_sync(~0u, mx1, 1)); mx1 = fmaxf(mx1, __shfl_xor_sync(~0u, mx1, 2));
  float sm0 = 0, sm1 = 0;
#pragma unroll
  for (int i = 0; i < 5; i++) {
    s[i][0] = ex2f((s[i][0] - mx0) * (SCALE_QK * LOG2E)); s[i][1] = ex2f((s[i][1] - mx0) * (SCALE_QK * LOG2E));
    s[i][2] = ex2f((s[i][2] - mx1) * (SCALE_QK * LOG2E)); s[i][3] = ex2f((s[i][3] - mx1) * (SCALE_QK * LOG2E));
    sm0 += s[i][0] + s[i][1]; sm1 += s[i][2] + s[i][3];
  }
  sm0 += __shfl_xor_sync(~0u, sm0, 1); sm0 += __shfl_xor_sync(~0u, sm0, 2);
  sm1 += __shfl_xor_sync(~0u, sm1, 1); sm1 += __shfl_xor_sync(~0u, sm1, 2);
  const float i0 = __fdividef(1.0f, sm0), i1 = __fdividef(1.0f, sm1);
  unsigned pa[2][4], pm0, pm1;
#pragma unroll
  for (int kk = 0; kk < 2; kk++) {
    pa[kk][0] = pack_bf16(s[2 * kk][0] * i0, s[2 * kk][1] * i0); pa[kk][1] = pack_bf16(s[2 * kk][2] * i1, s[2 * kk][3] * i1);
    pa[kk][2] = pack_bf16(s[2 * kk + 1][0] * i0, s[2 * kk + 1][1] * i0); pa[kk][3] = pack_bf16(s[2 * kk + 1][2] * i1, s[2 * kk + 1][3] * i1);
  }
  pm0 = pack_bf16(s[4][0] * i0, s[4][1] * i0); pm1 = pack_bf16(s[4][2] * i1, s[4][3] * i1);
  const int orow = (kb >> 1) * 64 + seg * 32 + mt * 16 + (m & 1) * 8 + r8;
  const unsigned ob = stg + ((kb & 1) * 2 + eh) * 16384 + orow * 128;
#pragma unroll
  for (int cp = 0; cp < 4; cp++) {
    float o0[4] = {0, 0, 0, 0}, o1[4] = {0, 0, 0, 0};
    mma1688(o0, pm0, pm1, vm[2 * cp]); mma1688(o1, pm0, pm1, vm[2 * cp + 1]);
    unsigned vf[4];
    int row = (m & 1) * 8 + r8;
    unsigned va = vb + row * 128 + (((cp * 2 + (m >> 1)) ^ r8) << 4);
    ldsm_x4_t(vf, va);
    mma16816(o0, pa[0], vf[0], vf[1]); mma16816(o1, pa[0], vf[2], vf[3]);
    if (mt) { ldsm_x4_t(vf, va + 2048); mma16816(o0, pa[1], vf[0], vf[1]); mma16816(o1, pa[1], vf[2], vf[3]); }
    stsm_x4(ob + (((cp * 2 + (m >> 1)) ^ r8) << 4), pack_bf16(o0[0], o0[1]), pack_bf16(o0[2], o0[3]), pack_bf16(o1[0], o1[1]), pack_bf16(o1[2], o1[3]));
  }
}

__device__ __forceinline__ void bulk_worker(unsigned sb, volatile int* misc, const bf16* __restrict__ x, const bf16* __restrict__ b1, const bf16* __restrict__ b2, bf16* __restrict__ out) {
  const int t = threadIdx.x, lane = t & 31, w = t >> 5, wg = w >> 2, g = lane >> 2, tq = lane & 3, m = lane >> 3, r8 = lane & 7;
  const unsigned bar = sb + SM_BAR;
  unsigned st = 0, ph = 0, seq = 0, sph = 0;
  float d[128];
  while (true) {
    mbar_wait(bar + 8 * (MB_FULL + st), ph);
    const int idr = misc[seq & 3]; seq++;
    const int idx = idr & 65535;
    if (idr < 0 || idx >= N_ITEMS) break;
    if (t == 0) ISTAMP(idx, 2);
    const Item it = decode_item(idx);
    const int nkb = item_nkb(it.type);
    if (it.type == T_ATT) {
      unsigned km[16], vm[8], kn[16], vn[8];
      const bool pref = idr >= 65536;
      if (pref) bulk_att_load(kn, vn, it.b, it.c, 0, w, lane);
      mbar_wait(bar + 8 * MB_STGE, sph ^ 1);
#pragma unroll 1
      for (int kb = 0; kb < 4; kb++) {
        if (!pref && !(kb & 1)) {
          if (lane < 4) wait_flag_ge(&g_flags.rec[it.c * 4 + lane], it.b * 4 + (kb >> 1) * 2 + wg + 1);
          __syncwarp();
          bulk_att_load(kn, vn, it.b, it.c, kb, w, lane);
        }
        if (kb) mbar_wait(bar + 8 * (MB_FULL + st), ph);
#pragma unroll
        for (int i = 0; i < 16; i++) km[i] = kn[i];
#pragma unroll
        for (int i = 0; i < 8; i++) vm[i] = vn[i];
        if (pref ? kb != 3 : !(kb & 1)) bulk_att_load(kn, vn, it.b, it.c, kb + 1, w, lane);
        bulk_att_stage(sb + st * STAGE_BYTES, sb + B_STG, km, vm, kb, w, lane);
        __syncwarp();
        if (lane == 0) mbar_arrive(bar + 8 * (MB_EMPTY + st));
        if (++st == NSTAGE) { st = 0; ph ^= 1; }
      }
      if (t == 0) misc[4] = idx;
      fence_proxy_async_smem();
      mbar_arrive(bar + 8 * MB_STGF); sph ^= 1;
      continue;
    }
    if (it.type >= T_RED) {
      __syncwarp();
      if (lane == 0) mbar_arrive(bar + 8 * (MB_EMPTY + st));
      if (++st == NSTAGE) { st = 0; ph ^= 1; }
      if (it.type == T_RED) {
#pragma unroll 2
        for (int i = 0; i < 8; i++) {
          size_t o = ((size_t)it.b * 128 + it.c * 16 + i * 2 + (t >> 7)) * DM + (t & 127) * 4;
          float4 a = __ldcg(reinterpret_cast<const float4*>(g_opart + o)), b = __ldcg(reinterpret_cast<const float4*>(g_opart + o + (size_t)S_TOK * DM));
          float4 c = __ldcg(reinterpret_cast<const float4*>(g_opart + o + (size_t)2 * S_TOK * DM)), e = __ldcg(reinterpret_cast<const float4*>(g_opart + o + (size_t)3 * S_TOK * DM));
          final_out(out, x, o, make_float4((a.x + b.x) + (c.x + e.x), (a.y + b.y) + (c.y + e.y), (a.z + b.z) + (c.z + e.z), (a.w + b.w) + (c.w + e.w)));
        }
      } else {
        size_t ol = ((size_t)it.c * 2 + (t >> 7)) * DM + (t & 127) * 4;
        float4 v[16];
#pragma unroll
        for (int i = 0; i < 16; i++) v[i] = __ldcg(reinterpret_cast<const float4*>(g_opl + ol + (size_t)i * 128 * DM));
#pragma unroll
        for (int st2 = 1; st2 < 16; st2 <<= 1)
#pragma unroll
          for (int i = 0; i < 16; i += 2 * st2) { v[i].x += v[i + st2].x; v[i].y += v[i + st2].y; v[i].z += v[i + st2].z; v[i].w += v[i + st2].w; }
        final_out(out, x, ol + (size_t)15 * 128 * DM, v[0]);
      }
      if (t == 0) ISTAMP(idx, 3);
      continue;
    }
    unsigned pst = 0, bv[32];
#pragma unroll
    for (int i = 0; i < 128; i++) d[i] = 0.0f;
    if (it.type == T_M1 || it.type == T_M2) {
      const unsigned* bp = reinterpret_cast<const unsigned*>((it.type == T_M1 ? b1 : b2) + it.c * 256) + tq;
#pragma unroll
      for (int i = 0; i < 32; i++) asm volatile("ld.global.nc.u32 %0, [%1];" : "=r"(bv[i]) : "l"(bp + i * 4));
    } else {
#pragma unroll
      for (int i = 0; i < 32; i++) bv[i] = 0;
    }
    for (int kb = 0; kb < nkb; kb++) {
      if (kb) mbar_wait(bar + 8 * (MB_FULL + st), ph);
      unsigned sa = sb + st * STAGE_BYTES;
      uint64_t ad = mkdesc(sa + wg * 8192, 16, 1024), bd = mkdesc(sa + 16384, 8192, 1024);
      asm volatile("wgmma.fence.sync.aligned;" ::: "memory");
#pragma unroll
      for (int k = 0; k < 4; k++) wgmma_n256(d, ad + k * 2, bd + k * 128, (kb | k) != 0);
      asm volatile("wgmma.commit_group.sync.aligned;" ::: "memory");
      if (kb) {
        asm volatile("wgmma.wait_group.sync.aligned 1;" ::: "memory");
        if (lane == 0) mbar_arrive(bar + 8 * (MB_EMPTY + pst));
      }
      pst = st;
      if (++st == NSTAGE) { st = 0; ph ^= 1; }
    }
    asm volatile("wgmma.wait_group.sync.aligned 0;" ::: "memory");
    if (lane == 0) mbar_arrive(bar + 8 * (MB_EMPTY + pst));
    if (it.type >= T_OUT) {
      const int col = it.c * 256 + 2 * tq;
      float* pp = it.type == T_OUT ? g_opart + ((size_t)it.ks * S_TOK + it.b * 128 + w * 16 + g) * DM + col : g_opl + ((size_t)it.ks * 128 + w * 16 + g) * DM + col;
#pragma unroll
      for (int i = 0; i < 32; i++) {
        __stcg(reinterpret_cast<float2*>(pp + i * 8), make_float2(d[4 * i], d[4 * i + 1]));
        __stcg(reinterpret_cast<float2*>(pp + 8 * DM + i * 8), make_float2(d[4 * i + 2], d[4 * i + 3]));
      }
      bar_sync(1, 256);
      if (t == 0) { red_release_add(&g_flags.p[it.b], 1); ISTAMP(idx, 3); }
      continue;
    }
#define ACT(F) _Pragma("unroll") for (int i = 0; i < 32; i++) { \
        unsigned u0 = badd2(pack_bf16(d[4 * i], d[4 * i + 1]), bv[i]), u1 = badd2(pack_bf16(d[4 * i + 2], d[4 * i + 3]), bv[i]); \
        d[4 * i] = F(bf_lo(u0)); d[4 * i + 1] = F(bf_hi(u0)); d[4 * i + 2] = F(bf_lo(u1)); d[4 * i + 3] = F(bf_hi(u1)); }
    if (it.type == T_M1) { ACT(gelu_t) } else if (it.type == T_M2) { ACT(silu_f) }
    mbar_wait(bar + 8 * MB_STGE, sph ^ 1);
    {
      const unsigned ob = sb + B_STG + (w * 16 + (m & 1) * 8 + r8) * 128;
#pragma unroll
      for (int i = 0; i < 16; i++)
        stsm_x4(ob + (i >> 2) * 16384 + ((((i & 3) * 2 + (m >> 1)) ^ r8) << 4), pack_bf16(d[8 * i], d[8 * i + 1]), pack_bf16(d[8 * i + 2], d[8 * i + 3]),
                pack_bf16(d[8 * i + 4], d[8 * i + 5]), pack_bf16(d[8 * i + 6], d[8 * i + 7]));
    }
    if (t == 0) misc[4] = idx;
    fence_proxy_async_smem();
    mbar_arrive(bar + 8 * MB_STGF); sph ^= 1;
  }
  mbar_wait(bar + 8 * MB_STGE, sph ^ 1);
  if (t == 0) misc[4] = -1;
  mbar_arrive(bar + 8 * MB_STGF);
}

__global__ void __launch_bounds__(384, 1)
k_main(const __grid_constant__ Maps maps, const bf16* __restrict__ x, const bf16* __restrict__ mem0, const bf16* __restrict__ b1, const bf16* __restrict__ b2, bf16* __restrict__ out, int helper) {
  extern __shared__ unsigned char smem_raw[];
  const unsigned sraw = smem_u32(smem_raw);
  const unsigned sb = (sraw + 1023u) & ~1023u;
  int* misc = reinterpret_cast<int*>(smem_raw + (sb - sraw) + SM_MISC);
  const int w = threadIdx.x >> 5;
  const bool rec = !helper && blockIdx.x < NREC;
  if (threadIdx.x == 0) {
    const unsigned bar = sb + SM_BAR;
    for (int i = 0; i < 8; i++) { mbar_init(bar + 8 * (MB_FULL + i), 1); mbar_init(bar + 8 * (MB_EMPTY + i), rec ? 1 : 8); }
    mbar_init(bar + 8 * MB_STGF, 256); mbar_init(bar + 8 * MB_STGE, 1);
    for (int i = MB_W0; i <= MB_AG; i++) mbar_init(bar + 8 * i, 1);
    if (rec) { mbar_expect_tx(bar + 8 * MB_S, 2560); mbar_expect_tx(bar + 8 * MB_V, 2048); mbar_expect_tx(bar + 8 * MB_RS, 8192); mbar_expect_tx(bar + 8 * MB_AG, 8192); }
    asm volatile("fence.mbarrier_init.release.cluster;" ::: "memory");
  }
  __syncthreads();
  asm volatile("barrier.cluster.arrive.release.aligned;\nbarrier.cluster.wait.acquire.aligned;" ::: "memory");
  if (rec && threadIdx.x == 256) {
    const unsigned bar = sb + SM_BAR; const int col = blockIdx.x * 64;
    mbar_expect_tx(bar + 8 * MB_W0, 131072);
    for (int kb = 0; kb < 8; kb++) tma_load_2d(sb + R_WO + kb * 8192, &maps.wq, col, kb * 64, bar + 8 * MB_W0);
    for (int kb = 0; kb < 8; kb++) tma_load_2d(sb + R_T1 + kb * 8192, &maps.wk, col, kb * 64, bar + 8 * MB_W0);
    mbar_expect_tx(bar + 8 * MB_W1, 65536);
    for (int kb = 0; kb < 8; kb++) tma_load_2d(sb + R_T2 + kb * 8192, &maps.wv, col, kb * 64, bar + 8 * MB_W1);
  }
  if (!helper) {
    asm volatile("griddepcontrol.wait;" ::: "memory");
    asm volatile("griddepcontrol.launch_dependents;");
  }
  if (DBGMODE && !rec) { if (helper) asm volatile("griddepcontrol.wait;" ::: "memory"); return; }
  if (w >= 8) {
    asm volatile("setmaxnreg.dec.sync.aligned.u32 24;");
    if (rec) { if (w == 8) rec_ring(maps, sb); else if (w == 9) rec_copy(sb); }
    else if (w == 8) bulk_producer(maps, sb, misc);
    else if ((threadIdx.x & 31) == 0) { if (w == 9) bulk_store(maps, sb, misc);
      else if (w == 10 && helper) asm volatile("griddepcontrol.wait;" ::: "memory"); }
  } else {
    if (rec) { asm volatile("setmaxnreg.inc.sync.aligned.u32 240;"); rec_worker(maps, sb, mem0); }
    else { asm volatile("setmaxnreg.inc.sync.aligned.u32 240;"); bulk_worker(sb, misc, x, b1, b2, out); }
  }
}

typedef CUresult (*EncFn)(CUtensorMap*, CUtensorMapDataType, cuuint32_t, void*, const cuuint64_t*, const cuuint64_t*, const cuuint32_t*, const cuuint32_t*,
                          CUtensorMapInterleave, CUtensorMapSwizzle, CUtensorMapL2promotion, CUtensorMapFloatOOBfill);
static void mk_map(EncFn enc, CUtensorMap* m, const void* ptr, uint64_t rows, uint64_t cols, uint32_t box_rows) {
  cuuint64_t dims[2] = {cols, rows}; cuuint64_t strides[1] = {cols * 2};
  cuuint32_t box[2] = {64, box_rows}, es[2] = {1, 1};
  enc(m, CU_TENSOR_MAP_DATA_TYPE_BFLOAT16, 2, const_cast<void*>(ptr), dims, strides, box, es, CU_TENSOR_MAP_INTERLEAVE_NONE, CU_TENSOR_MAP_SWIZZLE_128B,
      CU_TENSOR_MAP_L2_PROMOTION_L2_256B, CU_TENSOR_MAP_FLOAT_OOB_FILL_NONE);
}
extern "C" void kernel_launch(void* const* d_in, const int* in_sizes, int n_in, void* d_out, int out_size) {
  static EncFn enc = nullptr;
  static int ncl = 0, nhelp = 0;
  static void *p_xn, *p_y, *p_h1, *p_o, *p_qkv, *p_g;
  if (!enc) {
    void* fn = nullptr; cudaDriverEntryPointQueryResult qr;
    cudaGetDriverEntryPoint("cuTensorMapEncodeTiled", &fn, cudaEnableDefault, &qr);
    enc = (EncFn)fn;
    cudaGetSymbolAddress(&p_xn, g_xn); cudaGetSymbolAddress(&p_y, g_y); cudaGetSymbolAddress(&p_h1, g_h1);
    cudaGetSymbolAddress(&p_o, g_o); cudaGetSymbolAddress(&p_qkv, g_qkv); cudaGetSymbolAddress(&p_g, g_g);
    cudaFuncSetAttribute(k_main, cudaFuncAttributeMaxDynamicSharedMemorySize, SMEM_TOTAL);
    cudaLaunchConfig_t cfg = {}; cfg.gridDim = dim3(128); cfg.blockDim = dim3(384); cfg.dynamicSmemBytes = SMEM_TOTAL;
    cudaLaunchAttribute at[1]; at[0].id = cudaLaunchAttributeClusterDimension; at[0].val.clusterDim.x = CLS; at[0].val.clusterDim.y = 1; at[0].val.clusterDim.z = 1;
    cfg.attrs = at; cfg.numAttrs = 1;
    if (cudaOccupancyMaxActiveClusters(&ncl, k_main, &cfg) != cudaSuccess) { cudaGetLastError(); ncl = 14; }
    ncl = ncl > 16 ? 16 : (ncl < 9 ? 9 : ncl);
    int nsm = 0, dev = 0; cudaGetDevice(&dev); cudaDeviceGetAttribute(&nsm, cudaDevAttrMultiProcessorCount, dev);
    nhelp = nsm - ncl * CLS;
  }
  Maps maps;
  mk_map(enc, &maps.xn, p_xn, S_TOK, DM, 128); mk_map(enc, &maps.y, p_y, S_TOK, DM, 128); mk_map(enc, &maps.h1, p_h1, S_TOK, FF, 128);
  mk_map(enc, &maps.o, p_o, S_TOK, HD, 128); mk_map(enc, &maps.qkv_st, p_qkv, S_TOK, 3 * HD, 128); mk_map(enc, &maps.qkv_ld, p_qkv, S_TOK, 3 * HD, 32);
  mk_map(enc, &maps.g, p_g, S_TOK, DM, 128);
  mk_map(enc, &maps.wq, d_in[2], DM, HD, 64); mk_map(enc, &maps.wk, d_in[3], DM, HD, 64); mk_map(enc, &maps.wv, d_in[4], DM, HD, 64);
  mk_map(enc, &maps.wo, d_in[5], HD, DM, 64); mk_map(enc, &maps.w1, d_in[8], DM, FF, 64); mk_map(enc, &maps.w2, d_in[10], FF, DM, 64);
  cudaStream_t st = cudaStreamPerThread;
  k_pre<<<256, 256, 0, st>>>((const bf16*)d_in[0], (const char*)d_in[2], (const char*)d_in[3], (const char*)d_in[4], (const char*)d_in[5]);
  cudaLaunchConfig_t cfg = {}; cfg.gridDim = dim3(ncl * CLS); cfg.blockDim = dim3(384); cfg.dynamicSmemBytes = SMEM_TOTAL; cfg.stream = st;
  cudaLaunchAttribute at[2]; at[1].id = cudaLaunchAttributeClusterDimension; at[1].val.clusterDim.x = CLS; at[1].val.clusterDim.y = 1; at[1].val.clusterDim.z = 1;
  at[0].id = cudaLaunchAttributeProgrammaticStreamSerialization; at[0].val.programmaticStreamSerializationAllowed = 1;
#define PDL1 0
  cfg.attrs = at + (PDL1 ? 0 : 1); cfg.numAttrs = PDL1 ? 2 : 1;
  cudaLaunchKernelEx(&cfg, k_main, maps, (const bf16*)d_in[0], (const bf16*)d_in[1], (const bf16*)d_in[9], (const bf16*)d_in[11], (bf16*)d_out, 0);
  if (nhelp > 0) {
    cfg.gridDim = dim3(nhelp);
    cfg.attrs = at; cfg.numAttrs = 1;
    cudaLaunchKernelEx(&cfg, k_main, maps, (const bf16*)d_in[0], (const bf16*)d_in[1], (const bf16*)d_in[9], (const bf16*)d_in[11], (bf16*)d_out, 1);
  }
}
```

```cpp
#include <cuda_runtime.h>
#include <cuda_bf16.h>
#include <cuda.h>
#include <stdint.h>

typedef __nv_bfloat16 bf16;

#define S_TOK 2048
#define DM 512
#define NH 32
#define DH 128
#define HD 4096
#define NMEM 8
#define SEG 32
#define NSEG 64
#define FF 1792
#define NBLK 16
#define NREC 64
#define REPL 0
#define CLS 8

__device__ __align__(1024) bf16 g_xn[S_TOK * DM];
__device__ __align__(1024) bf16 g_y[S_TOK * DM];
__device__ __align__(1024) bf16 g_qkv[(size_t)S_TOK * 3 * HD];
__device__ __align__(1024) bf16 g_h1[S_TOK * FF];
__device__ __align__(1024) bf16 g_g[S_TOK * DM];
__device__ __align__(1024) bf16 g_o[(size_t)S_TOK * HD];
__device__ __align__(1024) bf16 g_km[NSEG * NH * NMEM * DH];
__device__ __align__(1024) bf16 g_vmt[NSEG * NH * DH * NMEM];
__device__ __align__(1024) float g_opart[(size_t)4 * S_TOK * DM];
__device__ __align__(1024) float g_opl[(size_t)16 * 128 * DM];
__device__ __align__(1024) unsigned g_part[8 * 2 * 8 * 8 * 512];
struct Flags {
  unsigned qkv[NBLK * 48];
  unsigned h1[NBLK];
  unsigned g[NBLK];
  unsigned o[NBLK * 4];
  unsigned p[NBLK];
  unsigned o16[16];
  unsigned ctr;
  unsigned rec[NREC];
  unsigned abort_;
};
__device__ __align__(1024) Flags g_flags;

#define RSTAMP(k)
#define DBGMODE 0
#define ISTAMP(i, k)
__device__ __forceinline__ unsigned smem_u32(const void* p) { return (unsigned)__cvta_generic_to_shared(p); }
__device__ __forceinline__ float bf16r(float x) { unsigned u; asm("cvt.rn.bf16x2.f32 %0, %1, %2;" : "=r"(u) : "f"(x), "f"(0.0f)); return __uint_as_float(u); }
__device__ __forceinline__ unsigned pack_bf16(float lo, float hi) {
  __nv_bfloat162 v = __floats2bfloat162_rn(lo, hi);
  return *reinterpret_cast<unsigned*>(&v);
}
__device__ __forceinline__ float bf_lo(unsigned u) { return __uint_as_float(u << 16); }
__device__ __forceinline__ float bf_hi(unsigned u) { return __uint_as_float(u & 0xffff0000u); }

#define SPIN_LIMIT (1u << 20)
#define TRAP_IF(x) if ((x) > SPIN_LIMIT) { asm volatile("st.global.u32 [%0], %1;" ::"l"(0ull), "r"(0u) : "memory"); break; }
__device__ __forceinline__ unsigned ld_acquire(const unsigned* p) {
  unsigned v; asm volatile("ld.acquire.gpu.global.u32 %0, [%1];" : "=r"(v) : "l"(p) : "memory"); return v;
}
__device__ __forceinline__ unsigned ld_relaxed(const unsigned* p) {
  unsigned v; asm volatile("ld.relaxed.gpu.global.u32 %0, [%1];" : "=r"(v) : "l"(p) : "memory"); return v;
}
__device__ __forceinline__ void red_release_add(unsigned* p, unsigned v) {
  asm volatile("red.release.gpu.global.add.u32 [%0], %1;" ::"l"(p), "r"(v) : "memory");
}
__device__ __forceinline__ void st_release(unsigned* p, unsigned v) {
  asm volatile("st.release.gpu.global.u32 [%0], %1;" ::"l"(p), "r"(v) : "memory");
}
__device__ __forceinline__ void wait_flag_ge(const unsigned* p, unsigned target) {
  unsigned it = 0;
  while (ld_acquire(p) < target) {
    __nanosleep(64);
    TRAP_IF(++it);
  }
}
__device__ __forceinline__ uint4 ldv4_relaxed(const void* p) {
  uint4 a; asm volatile("ld.relaxed.gpu.global.v4.u32 {%0,%1,%2,%3}, [%4];" : "=r"(a.x), "=r"(a.y), "=r"(a.z), "=r"(a.w) : "l"(p) : "memory"); return a;
}
__device__ __forceinline__ uint2 ldv2_relaxed(const void* p) {
  uint2 a; asm volatile("ld.relaxed.gpu.global.v2.u32 {%0,%1}, [%2];" : "=r"(a.x), "=r"(a.y) : "l"(p) : "memory"); return a;
}
__device__ __forceinline__ void mbar_init(unsigned mb, unsigned cnt) { asm volatile("mbarrier.init.shared::cta.b64 [%0], %1;" ::"r"(mb), "r"(cnt) : "memory"); }
__device__ __forceinline__ void mbar_expect_tx(unsigned mb, unsigned bytes) { asm volatile("mbarrier.arrive.expect_tx.shared::cta.b64 _, [%0], %1;" ::"r"(mb), "r"(bytes) : "memory"); }
__device__ __forceinline__ void mbar_arrive(unsigned mb) { asm volatile("mbarrier.arrive.shared::cta.b64 _, [%0];" ::"r"(mb) : "memory"); }
__device__ __forceinline__ void mbar_wait(unsigned mb, unsigned parity) {
  unsigned ok, it = 0;
  while (true) {
    asm volatile("{.reg .pred p; mbarrier.try_wait.parity.shared::cta.b64 p, [%1], %2; selp.u32 %0,1,0,p;}" : "=r"(ok) : "r"(mb), "r"(parity) : "memory");
    if (ok) break;
    TRAP_IF(++it);
  }
}
__device__ __forceinline__ void mbar_wait_sleep(unsigned mb, unsigned parity) {
  unsigned ok, it = 0;
  while (true) {
    asm volatile("{.reg .pred p; mbarrier.test_wait.parity.shared::cta.b64 p, [%1], %2; selp.u32 %0,1,0,p;}" : "=r"(ok) : "r"(mb), "r"(parity) : "memory");
    if (ok) break;
    __nanosleep(200);
    TRAP_IF(++it);
  }
}
__device__ __forceinline__ float ex2f(float x) { float y; asm("ex2.approx.ftz.f32 %0, %1;" : "=f"(y) : "f"(x)); return y; }
__device__ __forceinline__ int opaque_tid() { int t = threadIdx.x; t = __shfl_sync(~0u, t, t & 31); return t; }
#define LOG2E 1.4426950408889634f
__device__ __forceinline__ void mbar_wait_cluster(unsigned mb, unsigned parity) {
  unsigned ok, it = 0;
  while (true) {
    asm volatile("{.reg .pred p; mbarrier.try_wait.parity.acquire.cluster.shared::cta.b64 p, [%1], %2; selp.u32 %0,1,0,p;}" : "=r"(ok) : "r"(mb), "r"(parity) : "memory");
    if (ok) break;
    TRAP_IF(++it);
  }
}
__device__ __forceinline__ void bar_sync(int id, int n) { asm volatile("bar.sync %0, %1;" ::"r"(id), "r"(n) : "memory"); }
__device__ __forceinline__ void bar_arrive(int id, int n) { asm volatile("bar.arrive %0, %1;" ::"r"(id), "r"(n) : "memory"); }
__device__ __forceinline__ void tma_load_2d(unsigned dst, const CUtensorMap* map, int c0, int c1, unsigned mb) {
  asm volatile("cp.async.bulk.tensor.2d.shared::cluster.global.mbarrier::complete_tx::bytes [%0], [%1, {%3, %4}], [%2];"
               ::"r"(dst), "l"((uint64_t)map), "r"(mb), "r"(c0), "r"(c1) : "memory");
}
__device__ __forceinline__ void tma_store_2d(const CUtensorMap* map, unsigned src, int c0, int c1) {
  asm volatile("cp.async.bulk.tensor.2d.global.shared::cta.bulk_group [%0, {%2, %3}], [%1];"
               ::"l"((uint64_t)map), "r"(src), "r"(c0), "r"(c1) : "memory");
}
__device__ __forceinline__ void fence_proxy_async() { asm volatile("fence.proxy.async;" ::: "memory"); }
__device__ __forceinline__ void fence_proxy_async_smem() { asm volatile("fence.proxy.async.shared::cta;" ::: "memory"); }
__device__ __forceinline__ void ldsm_x4(unsigned* r, unsigned addr) {
  asm volatile("ldmatrix.sync.aligned.m8n8.x4.shared.b16 {%0,%1,%2,%3}, [%4];" : "=r"(r[0]), "=r"(r[1]), "=r"(r[2]), "=r"(r[3]) : "r"(addr) : "memory");
}
__device__ __forceinline__ void ldsm_x4_t(unsigned* r, unsigned addr) {
  asm volatile("ldmatrix.sync.aligned.m8n8.x4.trans.shared.b16 {%0,%1,%2,%3}, [%4];" : "=r"(r[0]), "=r"(r[1]), "=r"(r[2]), "=r"(r[3]) : "r"(addr) : "memory");
}
__device__ __forceinline__ void stsm_x2_t(unsigned addr, unsigned r0, unsigned r1) {
  asm volatile("stmatrix.sync.aligned.m8n8.x2.trans.shared.b16 [%0], {%1,%2};" ::"r"(addr), "r"(r0), "r"(r1) : "memory");
}
__device__ __forceinline__ void stsm_x4(unsigned addr, unsigned r0, unsigned r1, unsigned r2, unsigned r3) {
  asm volatile("stmatrix.sync.aligned.m8n8.x4.shared.b16 [%0], {%1,%2,%3,%4};" ::"r"(addr), "r"(r0), "r"(r1), "r"(r2), "r"(r3) : "memory");
}
__device__ __forceinline__ void mma16816(float* d, const unsigned* a, unsigned b0, unsigned b1) {
  asm volatile("mma.sync.aligned.m16n8k16.row.col.f32.bf16.bf16.f32 {%0,%1,%2,%3}, {%4,%5,%6,%7}, {%8,%9}, {%0,%1,%2,%3};"
               : "+f"(d[0]), "+f"(d[1]), "+f"(d[2]), "+f"(d[3]) : "r"(a[0]), "r"(a[1]), "r"(a[2]), "r"(a[3]), "r"(b0), "r"(b1));
}
__device__ __forceinline__ void mma1688(float* d, unsigned a0, unsigned a1, unsigned b0) {
  asm volatile("mma.sync.aligned.m16n8k8.row.col.f32.bf16.bf16.f32 {%0,%1,%2,%3}, {%4,%5}, {%6}, {%0,%1,%2,%3};"
               : "+f"(d[0]), "+f"(d[1]), "+f"(d[2]), "+f"(d[3]) : "r"(a0), "r"(a1), "r"(b0));
}
__device__ __forceinline__ uint64_t mkdesc(unsigned addr, unsigned lbo, unsigned sbo) {
  return (uint64_t)((addr >> 4) & 0x3fff) | ((uint64_t)(lbo >> 4) << 16) | ((uint64_t)(sbo >> 4) << 32) | (1ull << 62);
}
#define R8(b) "+f"(d[b]), "+f"(d[b + 1]), "+f"(d[b + 2]), "+f"(d[b + 3]), "+f"(d[b + 4]), "+f"(d[b + 5]), "+f"(d[b + 6]), "+f"(d[b + 7])
#define R32(b) R8(b), R8(b + 8), R8(b + 16), R8(b + 24)
__device__ __forceinline__ void wgmma_n256(float* d, uint64_t ad, uint64_t bd, int acc) {
  asm volatile(
      "{.reg .pred p; setp.ne.b32 p, %130, 0;\n"
      "wgmma.mma_async.sync.aligned.m64n256k16.f32.bf16.bf16 "
      "{%0,%1,%2,%3,%4,%5,%6,%7,%8,%9,%10,%11,%12,%13,%14,%15,%16,%17,%18,%19,%20,%21,%22,%23,%24,%25,%26,%27,%28,%29,%30,%31,"
      "%32,%33,%34,%35,%36,%37,%38,%39,%40,%41,%42,%43,%44,%45,%46,%47,%48,%49,%50,%51,%52,%53,%54,%55,%56,%57,%58,%59,%60,%61,%62,%63,"
      "%64,%65,%66,%67,%68,%69,%70,%71,%72,%73,%74,%75,%76,%77,%78,%79,%80,%81,%82,%83,%84,%85,%86,%87,%88,%89,%90,%91,%92,%93,%94,%95,"
      "%96,%97,%98,%99,%100,%101,%102,%103,%104,%105,%106,%107,%108,%109,%110,%111,%112,%113,%114,%115,%116,%117,%118,%119,%120,%121,%122,%123,%124,%125,%126,%127},"
      "%128, %129, p, 1, 1, 0, 1;}\n"
      : R32(0), R32(32), R32(64), R32(96)
      : "l"(ad), "l"(bd), "r"(acc));
}

__device__ __forceinline__ void ln16(const float* x, float* o) {
  float s = 0;
#pragma unroll
  for (int i = 0; i < 16; i++) s += x[i];
#pragma unroll
  for (int of = 16; of > 0; of >>= 1) s += __shfl_xor_sync(~0u, s, of);
  float mean = s * (1.0f / DM);
  float v = 0;
#pragma unroll
  for (int i = 0; i < 16; i++) { float dd = x[i] - mean; v += dd * dd; }
#pragma unroll
  for (int of = 16; of > 0; of >>= 1) v += __shfl_xor_sync(~0u, v, of);
  float mb = bf16r(mean);
  float vb = bf16r(v * (1.0f / DM));
  float den = bf16r(sqrtf(bf16r(vb + 1e-5f)));
#pragma unroll
  for (int i = 0; i < 16; i++) o[i] = bf16r(__fdiv_rn(bf16r(x[i] - mb), den));
}
__global__ void __launch_bounds__(256) k_pre(const bf16* __restrict__ x, const char* wq, const char* wk, const char* wv, const char* wo) {
  int t = threadIdx.x, lane = t & 31, w = t >> 5;
  asm volatile("griddepcontrol.launch_dependents;");
  {
    int g2 = blockIdx.x * 256 + t, o = (g2 & 32767) * 128;
    asm volatile("prefetch.global.L2 [%0];" ::"l"((g2 < 32768 ? wk : wv) + o));
    asm volatile("prefetch.global.L2 [%0];" ::"l"((g2 < 32768 ? wq : wo) + o));
  }
  int row = blockIdx.x * 8 + w;
  const uint4* src = reinterpret_cast<const uint4*>(x + (size_t)row * DM);
  uint4 a = src[lane], b = src[lane + 32];
  unsigned u[8] = {a.x, a.y, a.z, a.w, b.x, b.y, b.z, b.w};
  float f[16], o[16], o2[16];
#pragma unroll
  for (int i = 0; i < 8; i++) { f[2 * i] = bf_lo(u[i]); f[2 * i + 1] = bf_hi(u[i]); }
  ln16(f, o);
  ln16(o, o2);
  uint4* d1 = reinterpret_cast<uint4*>(g_xn + (size_t)row * DM);
  uint4* d2 = reinterpret_cast<uint4*>(g_y + (size_t)row * DM);
  d1[lane] = make_uint4(pack_bf16(o[0], o[1]), pack_bf16(o[2], o[3]), pack_bf16(o[4], o[5]), pack_bf16(o[6], o[7]));
  d1[lane + 32] = make_uint4(pack_bf16(o[8], o[9]), pack_bf16(o[10], o[11]), pack_bf16(o[12], o[13]), pack_bf16(o[14], o[15]));
  d2[lane] = make_uint4(pack_bf16(o2[0], o2[1]), pack_bf16(o2[2], o2[3]), pack_bf16(o2[4], o2[5]), pack_bf16(o2[6], o2[7]));
  d2[lane + 32] = make_uint4(pack_bf16(o2[8], o2[9]), pack_bf16(o2[10], o2[11]), pack_bf16(o2[12], o2[13]), pack_bf16(o2[14], o2[15]));
  int gt = blockIdx.x * 256 + t;
  uint4 z = make_uint4(0, 0, 0, 0);
  if (gt < 16384) reinterpret_cast<uint4*>(g_part)[gt] = z;
  if (gt < (int)(sizeof(Flags) / 4)) reinterpret_cast<unsigned*>(&g_flags)[gt] = 0;
}

struct Maps { CUtensorMap xn, y, h1, o, qkv_st, qkv_ld, g, wq, wk, wv, wo, w1, w2; };

#define NSTAGE 3
#define STAGE_BYTES 49152
#define B_STG (NSTAGE * STAGE_BYTES)
#define R_WO 0
#define R_T1 65536
#define R_T2 131072
#define R_RING 65536
#define RING_N 4
#define RING_BYTES 12288
#define R_MEM 196608
#define R_QS (R_MEM + 8448)
#define R_KS (R_QS + 1152)
#define R_OS (R_KS + 1152)
#define R_SOWN (R_OS + 2176)
#define R_SPEER (R_SOWN + 1280)
#define R_VM (R_SPEER + 1280)
#define R_VRED (R_VM + 2048)
#define R_RS (R_VRED + 6144)
#define SM_BAR (R_RS + 8192)
#define SMEM_TOTAL (SM_BAR + 256 + 1024)
#define MB_FULL 0
#define MB_EMPTY 8
#define MB_STGF 16
#define MB_STGE 17
#define MB_W0 18
#define MB_W1 19
#define MB_WO 20
#define MB_S 21
#define MB_V 22
#define MB_KVR 23
#define MB_KVF 24
#define MB_RS 25
#define MB_AG 26
#define SM_MISC (SM_BAR + 224)

#define N_KV 512
#define I_M1 512
#define I_Q 624
#define I_M2 880
#define I_POST 912
#define I_TAIL (I_POST + 16 * 32)
#define N_ITEMS (I_TAIL + 5 * 8 + 32 + 8 + 64)
enum { T_QKV = 0, T_M1 = 1, T_M2 = 2, T_ATT = 3, T_OUT = 4, T_OUTL = 5, T_RED = 6, T_REDL = 7 };
struct Item { int type, b, c, ks; };
__device__ __forceinline__ Item decode_item(int i) {
  Item it; it.ks = 0;
  if (i < N_KV) { it.type = T_QKV; it.b = i >> 5; it.c = 16 + (i & 31); }
  else if (i < I_Q) { it.type = T_M1; it.b = (i - I_M1) / 7; it.c = (i - I_M1) % 7; }
  else if (i < I_M2) { it.type = T_QKV; it.b = (i - I_Q) >> 4; it.c = (i - I_Q) & 15; }
  else if (i < I_POST) { it.type = T_M2; it.b = (i - I_M2) >> 1; it.c = (i - I_M2) & 1; }
  else if (i < I_TAIL) {
    int x = i - I_POST, p = x >> 5, r = x & 31;
    if (r < 16) { it.type = T_ATT; it.b = p; it.c = r; }
    else if (r < 24) { it.type = T_OUT; it.b = p - 3; it.c = r & 1; it.ks = (r - 16) >> 1; }
    else { it.type = T_RED; it.b = p - 5; it.c = r - 24; }
  } else {
    int x = i - I_TAIL, r = x & 7;
    if (x < 40) {
      int q = x >> 3;
      if (q == 0 || q == 2) { it.type = T_OUT; it.b = 13 + (q >> 1); it.c = r & 1; it.ks = r >> 1; }
      else { it.type = T_RED; it.b = q == 1 ? 11 : 9 + q; it.c = r; }
    }
    else if (x < 72) { it.type = T_OUTL; it.b = 15; it.c = x & 1; it.ks = (x - 40) >> 1; }
    else if (x < 80) { it.type = T_RED; it.b = 14; it.c = r; }
    else { it.type = T_REDL; it.b = 15; it.c = x - 80; }
  }
  return it;
}
__device__ __forceinline__ int item_nkb(int type) { return type == T_M2 ? 28 : (type == T_OUT ? 16 : (type >= T_RED ? 1 : (type >= T_ATT ? 4 : 8))); }

__device__ __forceinline__ void st_async_b64(unsigned raddr, unsigned lo, unsigned hi, unsigned rmb) {
  asm volatile("st.async.weak.shared::cluster.mbarrier::complete_tx::bytes.v2.b32 [%0], {%1,%2}, [%3];" ::"r"(raddr), "r"(lo), "r"(hi), "r"(rmb) : "memory");
}
__device__ __forceinline__ void st_async_b32(unsigned raddr, unsigned v, unsigned rmb) {
  asm volatile("st.async.weak.shared::cluster.mbarrier::complete_tx::bytes.b32 [%0], %1, [%2];" ::"r"(raddr), "r"(v), "r"(rmb) : "memory");
}
__device__ __forceinline__ unsigned mapa(unsigned a, unsigned rank) {
  unsigned r; asm volatile("mapa.shared::cluster.u32 %0, %1, %2;" : "=r"(r) : "r"(a), "r"(rank)); return r;
}
__device__ __forceinline__ void sts64(unsigned a, unsigned x, unsigned y) { asm volatile("st.shared.v2.b32 [%0], {%1,%2};" ::"r"(a), "r"(x), "r"(y) : "memory"); }
__device__ __forceinline__ void sts128(unsigned a, uint4 v) { asm volatile("st.shared.v4.b32 [%0], {%1,%2,%3,%4};" ::"r"(a), "r"(v.x), "r"(v.y), "r"(v.z), "r"(v.w) : "memory"); }
__device__ __forceinline__ uint2 lds64(unsigned a) { uint2 v; asm volatile("ld.shared.v2.b32 {%0,%1}, [%2];" : "=r"(v.x), "=r"(v.y) : "r"(a) : "memory"); return v; }
__device__ __forceinline__ uint4 lds128(unsigned a) { uint4 v; asm volatile("ld.shared.v4.b32 {%0,%1,%2,%3}, [%4];" : "=r"(v.x), "=r"(v.y), "=r"(v.z), "=r"(v.w) : "r"(a) : "memory"); return v; }
__device__ __forceinline__ float lds32f(unsigned a) { float v; asm volatile("ld.shared.f32 %0, [%1];" : "=f"(v) : "r"(a) : "memory"); return v; }
#define spin_check(it) TRAP_IF(++it)
#define POLLV 0
#define BAR8 0
#define D_STAG 150
#define D_RED 540
#define D_PUB 0
#define DELAY(n) do { unsigned c0_, c1_; asm volatile("mov.u32 %0, %%clock;" : "=r"(c0_)); do { asm volatile("mov.u32 %0, %%clock;" : "=r"(c1_)); } while (c1_ - c0_ < (n)); } while (0)
#define VD 2
#define NPRE 3
#define SELP 1
#define SCALE_QK 0.08838834764831845f

__device__ __forceinline__ void rec_worker(const Maps& maps, unsigned sb, const bf16* __restrict__ mem0, const int c) {
  const int h = c >> 1, j = c & 1;
  const int t = opaque_tid(), lane = t & 31, w = t >> 5, g = lane >> 2, tq = lane & 3;
  const int m = lane >> 3, r8 = lane & 7, kh = w >> 2, et = w & 3;
  const unsigned bar = sb + SM_BAR;
  unsigned wq[16][4], wk[16][4], wo[8][4];
  const unsigned woff = (kh * 4) * 8192 + ((m >> 1) * 8 + r8) * 128 + (((et * 2 + (m & 1)) ^ r8) << 4);
  mbar_wait(bar + 8 * MB_W0, 0);
#pragma unroll
  for (int i = 0; i < 16; i++) {
    ldsm_x4_t(wq[i], sb + R_WO + woff + (i >> 2) * 8192 + (i & 3) * 2048);
    ldsm_x4_t(wk[i], sb + R_T1 + woff + (i >> 2) * 8192 + (i & 3) * 2048);
  }
  bar_sync(2, 288);
  if (t == 0) {
    fence_proxy_async_smem();
    mbar_expect_tx(bar + 8 * MB_WO, 65536);
    for (int kb = 0; kb < 2; kb++)
      for (int cb = 0; cb < 4; cb++) tma_load_2d(sb + R_WO + (kb * 4 + cb) * 8192, &maps.wo, j * 256 + cb * 64, h * 128 + kb * 64, bar + 8 * MB_WO);
  }
  mbar_wait(bar + 8 * MB_W1, 0);
  const unsigned pV = sb + R_T2 + woff;
  const unsigned rk = c & 7, peer = rk ^ 1, cl = c >> 3;
#define KEEP(x) x = __shfl_sync(~0u, x, lane)
  unsigned pA = sb + R_MEM + kh * 4096 + lane * 16;
  unsigned pW0 = sb + R_WO + (w >> 1) * 8192 + ((m >> 1) * 8 + r8) * 128 + ((((w & 1) * 4 + (m & 1)) ^ r8) << 4);
  unsigned pW1 = pW0 ^ 32;
  unsigned pVk = pV;
  unsigned aX = sb + R_VRED + et * 512 + lane * 16;
  unsigned aQKst = sb + (kh ? R_KS : R_QS) + r8 * 144 + (et * 16 + (m & 1) * 8) * 2;
  unsigned aL8 = sb + lane * 8;
  unsigned aSl = mapa(sb + R_SOWN + w * 256 + lane * 8, rk), aSr = mapa(sb + R_SPEER + w * 256 + lane * 8, peer);
  unsigned aVl = mapa(sb + R_VM + (j * 4 + et) * 256 + lane * 8, rk), aVr = mapa(sb + R_VM + (j * 4 + et) * 256 + lane * 8, peer);
  const unsigned mbSl = mapa(bar + 8 * MB_S, rk), mbSr = mapa(bar + 8 * MB_S, peer), mbVl = mbSl + 8, mbVr = mbSr + 8;
  unsigned aQ = sb + R_QS + r8 * 144 + m * 16;
  unsigned oKx = (et * 8 + r8) * 128 + ((m ^ r8) << 4);
  unsigned oVx = 4096 + (et >> 1) * 4096 + ((m >> 1) * 8 + r8) * 128 + ((((et & 1) * 4 + (m & 1)) ^ r8) << 4);
  unsigned aOst = sb + R_OS + r8 * 272 + (et * 32 + m * 8) * 2;
  unsigned aOld = sb + R_OS + r8 * 272 + m * 16;
  unsigned aVm = sb + R_VM + et * 512 + lane * 8;
  unsigned aRSr = mapa(sb + R_RS + (h & 3) * 2048 + (w & 1) * 1024 + lane * 8, j * 4 + (w >> 1));
  unsigned mbRSr = mapa(bar + 8 * MB_RS, j * 4 + (w >> 1));
  unsigned t8 = t * 8;
  KEEP(pA); KEEP(pW0); KEEP(pW1); KEEP(pVk); KEEP(aX); KEEP(aQKst); KEEP(aL8); KEEP(aSl); KEEP(aSr); KEEP(aVl); KEEP(aVr); KEEP(aQ); KEEP(oKx); KEEP(oVx);
  KEEP(aOst); KEEP(aOld); KEEP(aVm); KEEP(aRSr); KEEP(mbRSr); KEEP(t8);
  mbar_wait(bar + 8 * MB_WO, 0);
#pragma unroll
  for (int ks = 0; ks < 4; ks++) { ldsm_x4_t(wo[2 * ks], pW0 + ks * 2048); ldsm_x4_t(wo[2 * ks + 1], pW1 + ks * 2048); }
  {
    unsigned v[8];
#pragma unroll
    for (int q = 0; q < 8; q++) v[q] = __ldg(reinterpret_cast<const unsigned*>(mem0) + q * 256 + t);
    sts128(sb + R_MEM + t * 32, make_uint4(__byte_perm(v[0], v[1], 0x5410), __byte_perm(v[2], v[3], 0x5410), __byte_perm(v[4], v[5], 0x5410), __byte_perm(v[6], v[7], 0x5410)));
    sts128(sb + R_MEM + t * 32 + 16, make_uint4(__byte_perm(v[0], v[1], 0x7632), __byte_perm(v[2], v[3], 0x7632), __byte_perm(v[4], v[5], 0x7632), __byte_perm(v[6], v[7], 0x7632)));
  }
  bar_sync(1, 256);

#pragma unroll 1
  for (int s = 0;; s++) {
    const unsigned par = s & 1;
    const unsigned slot = s & (RING_N - 1), rpar = (s / RING_N) & 1;
    const unsigned ring = sb + R_RING + slot * RING_BYTES;
    asm volatile("" : "+r"(t8));
    RSTAMP(1);
    RSTAMP(2);
    float aq[4] = {0, 0, 0, 0}, ak[4] = {0, 0, 0, 0}, av[4] = {0, 0, 0, 0};
    {
      unsigned b[8][4], f1[8][4], f0[8][4];
#define VLD(i) do { ldsm_x4_t(b[i], pA + (i) * 512); ldsm_x4_t(f0[i], pVk + ((i) >> 1) * 8192 + ((i) & 1) * 4096); ldsm_x4_t(f1[i], pVk + ((i) >> 1) * 8192 + ((i) & 1) * 4096 + 2048); } while (0)
      VLD(0);
      if (VD > 1) VLD(1);
#pragma unroll
      for (int i = 0; i < 8; i++) {
        if (i + VD < 8) VLD(i + VD);
        mma16816(aq, wq[2 * i], b[i][0], b[i][1]); mma16816(ak, wk[2 * i], b[i][0], b[i][1]); mma16816(av, f0[i], b[i][0], b[i][1]);
        mma16816(aq, wq[2 * i + 1], b[i][2], b[i][3]); mma16816(ak, wk[2 * i + 1], b[i][2], b[i][3]); mma16816(av, f1[i], b[i][2], b[i][3]);
      }
    }
    RSTAMP(3);
#define STSF4(a, v) asm volatile("st.shared.v4.f32 [%0], {%1,%2,%3,%4};" ::"r"(a), "f"(v[0]), "f"(v[1]), "f"(v[2]), "f"(v[3]) : "memory")
    unsigned f[8][4];
#define WO_PREFETCH() do { _Pragma("unroll") for (int i = 0; i < NPRE; i++) { ldsm_x4_t(f[2 * i], pW0 + 32768 + i * 2048); ldsm_x4_t(f[2 * i + 1], pW1 + 32768 + i * 2048); } } while (0)
    if (kh) {
      STSF4(aX, aq);
      bar_sync(4 + et, 64);
      uint4 o = lds128(aX + 2048), o2 = lds128(aX + 4096);
      stsm_x2_t(aQKst, pack_bf16(ak[0] + __uint_as_float(o.x), ak[1] + __uint_as_float(o.y)), pack_bf16(ak[2] + __uint_as_float(o.z), ak[3] + __uint_as_float(o.w)));
      bar_arrive(1, 256);
      unsigned x = pack_bf16(av[0] + __uint_as_float(o2.x), av[1] + __uint_as_float(o2.y)), y = pack_bf16(av[2] + __uint_as_float(o2.z), av[3] + __uint_as_float(o2.w));
      st_async_b64(aVr, x, y, mbVr);
      st_async_b64(aVl, x, y, mbVl);
      if (s == NSEG - 1) {
        mbar_wait(bar + 8 * MB_V, par);
        if (t == 128) mbar_arrive(bar + 8 * MB_KVR);
        break;
      }
      mbar_wait(bar + 8 * (MB_FULL + slot), rpar);
      unsigned vx[4][4];
      ldsm_x4_t(vx[0], ring + oVx); ldsm_x4_t(vx[1], ring + oVx + 2048); ldsm_x4_t(vx[2], ring + (oVx ^ 32)); ldsm_x4_t(vx[3], ring + (oVx ^ 32) + 2048);
      RSTAMP(4); RSTAMP(5); RSTAMP(6); RSTAMP(7);
      mbar_wait(bar + 8 * MB_S, par);
      RSTAMP(8);
      float sc[10];
#pragma unroll
      for (int i = 0; i < 5; i++) {
        uint2 o = lds64(aL8 + R_SOWN + i * 256), p = lds64(aL8 + R_SPEER + i * 256);
        sc[2 * i] = __uint_as_float(o.x) + __uint_as_float(p.x); sc[2 * i + 1] = __uint_as_float(o.y) + __uint_as_float(p.y);
      }
      mbar_wait(bar + 8 * MB_V, par);
      uint2 vm0 = lds64(aVm), vm1 = lds64(aVm + 256);
      float mx = fmaxf(fmaxf(fmaxf(sc[0], sc[1]), fmaxf(sc[2], sc[3])), fmaxf(fmaxf(fmaxf(sc[4], sc[5]), fmaxf(sc[6], sc[7])), fmaxf(sc[8], sc[9])));
      mx = fmaxf(mx, __shfl_xor_sync(~0u, mx, 1)); mx = fmaxf(mx, __shfl_xor_sync(~0u, mx, 2));
      const float nm = -mx * (SCALE_QK * LOG2E);
      unsigned p[5];
#pragma unroll
      for (int i = 0; i < 5; i++) p[i] = pack_bf16(ex2f(fmaf(sc[2 * i], SCALE_QK * LOG2E, nm)), ex2f(fmaf(sc[2 * i + 1], SCALE_QK * LOG2E, nm)));
      RSTAMP(9);
      float o0[4] = {0, 0, 0, 0}, o1[4] = {0, 0, 0, 0}, o3[4] = {0, 0, 0, 0}, o4[4] = {0, 0, 0, 0}, z0[4] = {0, 0, 0, 0}, z1[4] = {0, 0, 0, 0};
      const unsigned ones[4] = {0x3F803F80u, 0u, 0x3F803F80u, 0u};
      mma16816(z0, ones, p[0], p[1]); mma16816(z1, ones, p[2], p[3]);
      mma16816(o0, vx[0], p[0], p[1]); mma16816(o3, vx[2], p[0], p[1]);
      mma1688(z0, 0x3F803F80u, 0u, p[4]);
      mma16816(o1, vx[1], p[2], p[3]); mma16816(o4, vx[3], p[2], p[3]);
      mma1688(o0, vm0.x, vm0.y, p[4]); mma1688(o3, vm1.x, vm1.y, p[4]);
      float i0, i1;
      asm("rcp.approx.ftz.f32 %0, %1;" : "=f"(i0) : "f"(z0[0] + z1[0])); asm("rcp.approx.ftz.f32 %0, %1;" : "=f"(i1) : "f"(z0[1] + z1[1]));
      asm volatile("stmatrix.sync.aligned.m8n8.x4.trans.shared.b16 [%0], {%1,%2,%3,%4};" ::"r"(aOst), "r"(pack_bf16((o0[0] + o1[0]) * i0, (o0[1] + o1[1]) * i1)), "r"(pack_bf16((o0[2] + o1[2]) * i0, (o0[3] + o1[3]) * i1)),
                   "r"(pack_bf16((o3[0] + o4[0]) * i0, (o3[1] + o4[1]) * i1)), "r"(pack_bf16((o3[2] + o4[2]) * i0, (o3[3] + o4[3]) * i1)) : "memory");
      RSTAMP(10);
      bar_sync(1, 256);
      WO_PREFETCH();
    } else {
      STSF4(aX + 2048, ak); STSF4(aX + 4096, av);
      unsigned kb[8];
      mbar_wait(bar + 8 * (MB_FULL + slot), rpar);
      ldsm_x4(kb, ring + oKx); ldsm_x4(kb + 4, ring + (oKx ^ 64));
      bar_sync(4 + et, 64);
      uint4 o = lds128(aX);
      stsm_x2_t(aQKst, pack_bf16(aq[0] + __uint_as_float(o.x), aq[1] + __uint_as_float(o.y)), pack_bf16(aq[2] + __uint_as_float(o.z), aq[3] + __uint_as_float(o.w)));
      RSTAMP(4);
      bar_sync(1, 256);
      RSTAMP(5);
      if (s == NSEG - 1) break;
      unsigned qa[8], km[8];
      ldsm_x4(qa, aQ); ldsm_x4(qa + 4, aQ + 64);
      if (w == 3) { ldsm_x4(km, aQ + 1152); ldsm_x4(km + 4, aQ + 1152 + 64); }
      float s0[4] = {0, 0, 0, 0}, s1[4] = {0, 0, 0, 0};
      unsigned af[4][4];
#pragma unroll
      for (int i = 0; i < 4; i++) { af[i][0] = qa[2 * i]; af[i][1] = 0; af[i][2] = qa[2 * i + 1]; af[i][3] = 0; }
      mma16816(s0, af[0], kb[0], kb[1]); mma16816(s1, af[1], kb[2], kb[3]);
      mma16816(s0, af[2], kb[4], kb[5]); mma16816(s1, af[3], kb[6], kb[7]);
      if (w == 3) {
        float m0[4] = {0, 0, 0, 0}, m1[4] = {0, 0, 0, 0};
        mma16816(m0, af[0], km[0], km[1]); mma16816(m1, af[1], km[2], km[3]);
        mma16816(m0, af[2], km[4], km[5]); mma16816(m1, af[3], km[6], km[7]);
        unsigned x = __float_as_uint(m0[0] + m1[0]), y = __float_as_uint(m0[1] + m1[1]);
        st_async_b64(aSr + 256, x, y, mbSr); st_async_b64(aSl + 256, x, y, mbSl);
      }
      unsigned x = __float_as_uint(s0[0] + s1[0]), y = __float_as_uint(s0[1] + s1[1]);
      st_async_b64(aSr, x, y, mbSr); st_async_b64(aSl, x, y, mbSl);
      RSTAMP(6);
      WO_PREFETCH();
      RSTAMP(7); RSTAMP(8); RSTAMP(9); RSTAMP(10);
      bar_sync(1, 256);
    }
    RSTAMP(11);
    float d0[4] = {0, 0, 0, 0}, d1[4] = {0, 0, 0, 0}, e0[4] = {0, 0, 0, 0}, e1[4] = {0, 0, 0, 0};
    unsigned ob[4][4];
#pragma unroll
    for (int k2 = 0; k2 < 4; k2++) ldsm_x4(ob[k2], aOld + k2 * 64);
#pragma unroll
    for (int i = NPRE; i < 4; i++) { ldsm_x4_t(f[2 * i], pW0 + 32768 + i * 2048); ldsm_x4_t(f[2 * i + 1], pW1 + 32768 + i * 2048); }
    mma16816(d0, wo[0], ob[0][0], ob[0][1]); mma16816(d1, wo[1], ob[0][0], ob[0][1]);
    mma16816(e0, wo[2], ob[0][2], ob[0][3]); mma16816(e1, wo[3], ob[0][2], ob[0][3]);
    mma16816(d0, wo[4], ob[1][0], ob[1][1]); mma16816(d1, wo[5], ob[1][0], ob[1][1]);
    mma16816(e0, wo[6], ob[1][2], ob[1][3]); mma16816(e1, wo[7], ob[1][2], ob[1][3]);
    mma16816(d0, f[0], ob[2][0], ob[2][1]); mma16816(d1, f[1], ob[2][0], ob[2][1]);
    mma16816(e0, f[2], ob[2][2], ob[2][3]); mma16816(e1, f[3], ob[2][2], ob[2][3]);
    mma16816(d0, f[4], ob[3][0], ob[3][1]); mma16816(d1, f[5], ob[3][0], ob[3][1]);
    mma16816(e0, f[6], ob[3][2], ob[3][3]); mma16816(e1, f[7], ob[3][2], ob[3][3]);
    st_async_b64(aRSr, __float_as_uint(d0[0] + e0[0]), __float_as_uint(d0[1] + e0[1]), mbRSr);
    st_async_b64(aRSr + 256, __float_as_uint(d0[2] + e0[2]), __float_as_uint(d0[3] + e0[3]), mbRSr);
    st_async_b64(aRSr + 512, __float_as_uint(d1[0] + e1[0]), __float_as_uint(d1[1] + e1[1]), mbRSr);
    st_async_b64(aRSr + 768, __float_as_uint(d1[2] + e1[2]), __float_as_uint(d1[3] + e1[3]), mbRSr);
    RSTAMP(12);
    if (t == 128) {
      mbar_arrive(bar + 8 * (MB_EMPTY + slot)); mbar_arrive(bar + 8 * MB_KVR);
      mbar_expect_tx(bar + 8 * MB_S, 2560); mbar_expect_tx(bar + 8 * MB_V, 2048);
    }
    const unsigned tag = ((s >> 1) & 1) ^ 1;
    const char* gp = reinterpret_cast<const char*>(g_part);
    const unsigned goff = (par * 8 + rk) * 16384 + cl * 2048 + t8;
    unsigned mbA[8];
#pragma unroll
    for (int i = 0; i < 8; i++) mbA[i] = mapa(bar + 8 * MB_AG, i);
    const unsigned dlt = (R_MEM + rk * 1024) - (SM_BAR + 8 * MB_AG) + (t8 >> 1);
    mbar_wait(bar + 8 * MB_RS, par);
    RSTAMP(13);
    uint2 a[8];
    {
      uint2 x0 = lds64(sb + R_RS + t8), x1 = lds64(sb + R_RS + 2048 + t8), x2 = lds64(sb + R_RS + 4096 + t8), x3 = lds64(sb + R_RS + 6144 + t8);
      float r0 = (__uint_as_float(x0.x) + __uint_as_float(x1.x)) + (__uint_as_float(x2.x) + __uint_as_float(x3.x));
      float r1 = (__uint_as_float(x0.y) + __uint_as_float(x1.y)) + (__uint_as_float(x2.y) + __uint_as_float(x3.y));
      a[0].x = (__float_as_uint(r0) & ~1u) | tag; a[0].y = (__float_as_uint(r1) & ~1u) | tag;
      asm volatile("st.relaxed.gpu.global.v2.u32 [%0], {%1,%2};" ::"l"(gp + goff), "r"(a[0].x), "r"(a[0].y) : "memory");
    }
    RSTAMP(14);
    if (t == 128) mbar_expect_tx(bar + 8 * MB_RS, 8192);
    {
      unsigned it = 0;
#define PLOAD(a) _Pragma("unroll") for (int i = 1; i < 8; i++) a[i] = ldv2_relaxed(gp + (goff ^ (i * 2048)))
#define PAND(a) (((a[1].x & a[1].y) & (a[2].x & a[2].y) & (a[3].x & a[3].y)) & ((a[4].x & a[4].y) & (a[5].x & a[5].y)) & ((a[6].x & a[6].y) & (a[7].x & a[7].y)))
#define POR(a) (((a[1].x | a[1].y) | (a[2].x | a[2].y) | (a[3].x | a[3].y)) | ((a[4].x | a[4].y) | (a[5].x | a[5].y)) | ((a[6].x | a[6].y) | (a[7].x | a[7].y)))
#define POK(a) (((tag ? PAND(a) : ~POR(a)) & 1u) != 0)
      if (D_RED) DELAY(D_RED);
      PLOAD(a);
      while (!POK(a)) {
#pragma unroll
        for (int i = 1; i < 8; i++) if (((a[i].x ^ tag) | (a[i].y ^ tag)) & 1u) a[i] = ldv2_relaxed(gp + (goff ^ (i * 2048)));
        spin_check(it);
      }
    }
    RSTAMP(15);
    {
#define AF(i, c) __uint_as_float(a[i].c)
      unsigned u = pack_bf16(((AF(0, x) + AF(1, x)) + (AF(2, x) + AF(3, x))) + ((AF(4, x) + AF(5, x)) + (AF(6, x) + AF(7, x))),
                             ((AF(0, y) + AF(1, y)) + (AF(2, y) + AF(3, y))) + ((AF(4, y) + AF(5, y)) + (AF(6, y) + AF(7, y))));
      __syncwarp();
#pragma unroll
      for (int i = 0; i < 8; i++) st_async_b32(mbA[i] + dlt, u, mbA[i]);
    }
    mbar_wait(bar + 8 * MB_KVF, par);
    mbar_wait(bar + 8 * MB_AG, par);
    if (t == 128) mbar_expect_tx(bar + 8 * MB_AG, 8192);
  }
}

__device__ __forceinline__ void rec_ring(const Maps& maps, unsigned sb, const int c) {
  const int h = c >> 1, j = c & 1;
  const unsigned bar = sb + SM_BAR;
  const int lane = threadIdx.x & 31;
  __syncwarp();
  bar_sync(2, 288);
  if (lane == 0) {
    fence_proxy_async_smem();
    for (int s = 0; s < NSEG; s++) {
      unsigned slot = s & (RING_N - 1);
      if ((s & 3) == 0 && !DBGMODE) {
        wait_flag_ge(&g_flags.qkv[(s >> 2) * 48 + 16 + (h >> 1)], 1);
        wait_flag_ge(&g_flags.qkv[(s >> 2) * 48 + 32 + (h >> 1)], 1);
        fence_proxy_async();
      }
      if (s >= RING_N) mbar_wait_sleep(bar + 8 * (MB_EMPTY + slot), ((s / RING_N) - 1) & 1);
      unsigned dst = sb + R_RING + slot * RING_BYTES, mb = bar + 8 * (MB_FULL + slot);
      mbar_expect_tx(mb, RING_BYTES);
      tma_load_2d(dst, &maps.qkv_ld, HD + h * 128 + j * 64, s * SEG, mb);
      tma_load_2d(dst + 4096, &maps.qkv_ld, 2 * HD + h * 128, s * SEG, mb);
      tma_load_2d(dst + 8192, &maps.qkv_ld, 2 * HD + h * 128 + 64, s * SEG, mb);
    }
  }
}
__device__ __forceinline__ void rec_copy(unsigned sb, const int c) {
  const int h = c >> 1, j = c & 1;
  const unsigned bar = sb + SM_BAR;
  const int lane = threadIdx.x & 31;
  for (int s = 0; s < NSEG; s++) {
    if (s < NSEG - 1) mbar_wait_sleep(bar + 8 * MB_KVR, s & 1); else mbar_wait(bar + 8 * MB_KVR, s & 1);
    uint4 k0 = lds128(sb + R_KS + (lane >> 3) * 144 + (lane & 7) * 16), k1 = lds128(sb + R_KS + (4 + (lane >> 3)) * 144 + (lane & 7) * 16);
    uint2 v[4];
#pragma unroll
    for (int i = 0; i < 4; i++) v[i] = lds64(sb + R_VM + (j * 4 + i) * 256 + lane * 8);
    __syncwarp();
    if (lane == 0) mbar_arrive(bar + 8 * MB_KVF);
    bf16* kd = g_km + ((size_t)(s * NH + h) * NMEM) * DH + j * 64;
    *reinterpret_cast<uint4*>(kd + (lane >> 3) * DH + (lane & 7) * 8) = k0;
    *reinterpret_cast<uint4*>(kd + (4 + (lane >> 3)) * DH + (lane & 7) * 8) = k1;
    unsigned* vd = reinterpret_cast<unsigned*>(g_vmt) + ((size_t)(s * NH + h) * DH + j * 64) * 4;
#pragma unroll
    for (int i = 0; i < 4; i++) { vd[(i * 16) * 4 + lane] = v[i].x; vd[(i * 16 + 8) * 4 + lane] = v[i].y; }
    __syncwarp();
    if (lane == 0) st_release(&g_flags.rec[c], s + 1);
  }
}

__device__ __forceinline__ void bulk_producer(const Maps& maps, unsigned sb, int* misc) {
  const unsigned bar = sb + SM_BAR;
  const int lane = threadIdx.x & 31;
  unsigned st = 0, ph = 0, seq = 0;
  while (true) {
    int idx = 0;
    if (lane == 0) idx = (int)atomicAdd(&g_flags.ctr, 1u);
    idx = __shfl_sync(~0u, idx, 0);
    if (idx >= N_ITEMS) {
      if (lane == 0) {
        mbar_wait(bar + 8 * (MB_EMPTY + st), ph ^ 1);
        misc[seq & 3] = -1;
        mbar_arrive(bar + 8 * (MB_FULL + st));
      }
      break;
    }
    if (lane == 0) ISTAMP(idx, 0);
    Item it = decode_item(idx);
    if (it.b < 0) continue;
    const CUtensorMap* mp; int c0, c1, dc0, dc1; unsigned doff;
    const unsigned* fl = nullptr; unsigned tgt = 1; int nbox = 5, rdy = 0;
    if (it.type == T_ATT) {
      mp = &maps.qkv_ld; nbox = 12; doff = lane * 4096;
      c0 = (lane >> 2) * HD + it.c * 256 + (lane & 1) * 64; c1 = it.b * 128 + ((lane >> 1) & 1) * 32; dc0 = dc1 = 0;
      if (lane < 3) fl = &g_flags.qkv[it.b * 48 + lane * 16 + it.c];
      bool ok = true;
      if (lane >= 4 && lane < 8) ok = ld_acquire(&g_flags.rec[it.c * 4 + lane - 4]) >= (unsigned)(it.b * 4 + 4);
      rdy = __all_sync(~0u, ok) ? 65536 : 0;
    } else {
      int k0 = 0, nb0 = it.c * 256;
      if (it.type == T_QKV) { mp = lane == 0 ? &maps.xn : (it.c < 16 ? &maps.wq : (it.c < 32 ? &maps.wk : &maps.wv)); nb0 = (it.c & 15) * 256; }
      else if (it.type == T_M1) mp = lane == 0 ? &maps.y : &maps.w1;
      else if (it.type == T_M2) { mp = lane == 0 ? &maps.h1 : &maps.w2; fl = &g_flags.h1[it.b]; tgt = 7; }
      else {
        mp = lane == 0 ? &maps.o : &maps.wo;
        if (it.type == T_OUT) { k0 = it.ks * 1024; fl = &g_flags.o[it.b * 4 + it.ks]; tgt = 4; }
        else if (it.type == T_OUTL) { k0 = it.ks * 256; fl = &g_flags.o16[it.ks]; }
        else if (lane == 1) { fl = &g_flags.g[it.b]; tgt = 2; }
        else { fl = &g_flags.p[it.b]; tgt = it.type == T_RED ? 8 : 32; }
      }
      if (lane > (it.type >= T_RED ? 1 : 0)) fl = nullptr;
      if (lane == 0) { c0 = k0; c1 = it.b * 128; dc0 = 64; dc1 = 0; doff = 0; }
      else { c0 = nb0 + (lane - 1) * 64; c1 = k0; dc0 = 0; dc1 = 64; doff = 8192 + lane * 8192; }
    }
    if (fl) wait_flag_ge(fl, tgt);
    __syncwarp();
    fence_proxy_async();
    if (lane == 0) ISTAMP(idx, 1);
    const int nkb = item_nkb(it.type);
    for (int kb = 0; kb < nkb; kb++) {
      const unsigned mb = bar + 8 * (MB_FULL + st);
      mbar_wait(bar + 8 * (MB_EMPTY + st), ph ^ 1);
      if (lane == 0) {
        if (kb == 0) misc[seq & 3] = idx | rdy;
        if (it.type >= T_RED) mbar_arrive(mb); else mbar_expect_tx(mb, STAGE_BYTES);
      }
      if (it.type == T_ATT) { if (lane < 12) tma_load_2d(sb + st * STAGE_BYTES + doff, mp, c0 + (kb & 1) * 128, c1 + (kb >> 1) * 64, mb); }
      else if (lane < nbox && it.type < T_RED) tma_load_2d(sb + st * STAGE_BYTES + doff, mp, c0 + kb * dc0, c1 + kb * dc1, mb);
      __syncwarp();
      if (++st == NSTAGE) { st = 0; ph ^= 1; }
    }
    seq++;
  }
}
__device__ __forceinline__ void bulk_store(const Maps& maps, unsigned sb, volatile int* misc) {
  const unsigned bar = sb + SM_BAR;
  unsigned ph = 0;
  while (true) {
    mbar_wait(bar + 8 * MB_STGF, ph); ph ^= 1;
    int idx = misc[4];
    if (idx < 0) break;
    Item it = decode_item(idx);
    const CUtensorMap* mp = it.type == T_QKV ? &maps.qkv_st : (it.type == T_M1 ? &maps.h1 : (it.type == T_M2 ? &maps.g : &maps.o));
    unsigned* flag = it.type == T_QKV ? &g_flags.qkv[it.b * 48 + it.c] : (it.type == T_M1 ? &g_flags.h1[it.b] : (it.type == T_M2 ? &g_flags.g[it.b] : (it.b == 15 ? &g_flags.o16[it.c] : &g_flags.o[it.b * 4 + (it.c >> 2)])));
    for (int i = 0; i < 4; i++) tma_store_2d(mp, sb + B_STG + i * 16384, it.c * 256 + i * 64, it.b * 128);
    asm volatile("cp.async.bulk.commit_group;" ::: "memory");
    asm volatile("cp.async.bulk.wait_group.read 0;" ::: "memory");
    mbar_arrive(bar + 8 * MB_STGE);
    asm volatile("cp.async.bulk.wait_group 0;" ::: "memory");
    fence_proxy_async();
    red_release_add(flag, 1);
    ISTAMP(idx, 3);
  }
}
__device__ __forceinline__ float rcpf(float x) { float y; asm("rcp.approx.ftz.f32 %0, %1;" : "=f"(y) : "f"(x)); return y; }
__device__ __forceinline__ float gelu_t(float x) {
  float e = ex2f(x * fmaf(x * x, -2.0f * LOG2E * 0.7978845608028654f * 0.044715f, -2.0f * LOG2E * 0.7978845608028654f));
  return x * rcpf(1.0f + e);
}
__device__ __forceinline__ float silu_f(float x) { return x * rcpf(1.0f + ex2f(-LOG2E * x)); }
__device__ __forceinline__ unsigned badd2(unsigned a, unsigned b) { unsigned r; asm("add.rn.bf16x2 %0, %1, %2;" : "=r"(r) : "r"(a), "r"(b)); return r; }

__device__ __forceinline__ void final_out(bf16* __restrict__ out, const bf16* __restrict__ x, size_t o, float4 s) {
  uint2 gv = __ldcg(reinterpret_cast<const uint2*>(g_g + o)), xv = __ldg(reinterpret_cast<const uint2*>(x + o));
  uint2 r;
  r.x = pack_bf16(bf_lo(xv.x) + bf16r(bf16r(s.x) * bf_lo(gv.x)), bf_hi(xv.x) + bf16r(bf16r(s.y) * bf_hi(gv.x)));
  r.y = pack_bf16(bf_lo(xv.y) + bf16r(bf16r(s.z) * bf_lo(gv.y)), bf_hi(xv.y) + bf16r(bf16r(s.w) * bf_hi(gv.y)));
  *reinterpret_cast<uint2*>(out + o) = r;
}
__device__ __forceinline__ void bulk_att_load(unsigned* km, unsigned* vm, int b, int hp, int kb, int w, int lane) {
  const int g = lane >> 2, tq = lane & 3, seg = w >> 2, eh = w & 1;
  const int head = hp * 2 + (kb & 1), sg = b * 4 + (kb >> 1) * 2 + seg;
  const unsigned* kmp = reinterpret_cast<const unsigned*>(g_km + ((size_t)(sg * NH + head) * NMEM + g) * DH) + tq;
  const unsigned* vmp = reinterpret_cast<const unsigned*>(g_vmt) + ((size_t)(sg * NH + head) * DH + eh * 64) * 4 + lane;
#pragma unroll
  for (int i = 0; i < 16; i++) asm volatile("ld.global.cg.u32 %0, [%1];" : "=r"(km[i]) : "l"(kmp + i * 4) : "memory");
#pragma unroll
  for (int i = 0; i < 8; i++) asm volatile("ld.global.cg.u32 %0, [%1];" : "=r"(vm[i]) : "l"(vmp + i * 32) : "memory");
}
__device__ __forceinline__ void bulk_att_stage(unsigned sa, unsigned stg, const unsigned* km, const unsigned* vm, int kb, int w, int lane) {
  const int g = lane >> 2, tq = lane & 3, m = lane >> 3, r8 = lane & 7;
  const int seg = w >> 2, mt = (w >> 1) & 1, eh = w & 1;
  float s[5][4];
#pragma unroll
  for (int i = 0; i < 5; i++) { s[i][0] = s[i][1] = s[i][2] = s[i][3] = 0; }
  const unsigned qb = sa + (0 * 2 + seg) * 8192, kbs = sa + (1 * 2 + seg) * 8192, vb = sa + (2 * 2 + seg) * 8192 + eh * 4096;
  unsigned qa[8][4];
#pragma unroll
  for (int ks = 0; ks < 8; ks++) {
    int row = mt * 16 + (m & 1) * 8 + r8;
    ldsm_x4(qa[ks], qb + (ks >> 2) * 4096 + row * 128 + ((((ks & 3) * 2 + (m >> 1)) ^ r8) << 4));
    unsigned kf[4];
    int krow = (m >> 1) * 8 + r8;
    unsigned ka = kbs + (ks >> 2) * 4096 + krow * 128 + ((((ks & 3) * 2 + (m & 1)) ^ r8) << 4);
    ldsm_x4(kf, ka);
    mma16816(s[0], qa[ks], kf[0], kf[1]); mma16816(s[1], qa[ks], kf[2], kf[3]);
    if (mt) { ldsm_x4(kf, ka + 2048); mma16816(s[2], qa[ks], kf[0], kf[1]); mma16816(s[3], qa[ks], kf[2], kf[3]); }
  }
#pragma unroll
  for (int ks = 0; ks < 8; ks++) mma16816(s[4], qa[ks], km[2 * ks], km[2 * ks + 1]);
  float mx0 = -INFINITY, mx1 = -INFINITY;
  const int t0 = mt * 16 + g, t1 = t0 + 8;
#pragma unroll
  for (int i = 0; i < 5; i++) {
#pragma unroll
    for (int e = 0; e < 4; e++) {
      float v = s[i][e];
      if (i < 4) { int kj = i * 8 + 2 * tq + (e & 1); if (kj > (e < 2 ? t0 : t1)) v = -INFINITY; }
      s[i][e] = v;
      if (e < 2) mx0 = fmaxf(mx0, v); else mx1 = fmaxf(mx1, v);
    }
  }
  mx0 = fmaxf(mx0, __shfl_xor_sync(~0u, mx0, 1)); mx0 = fmaxf(mx0, __shfl_xor_sync(~0u, mx0, 2));
  mx1 = fmaxf(mx1, __shfl_xor_sync(~0u, mx1, 1)); mx1 = fmaxf(mx1, __shfl_xor_sync(~0u, mx1, 2));
  float sm0 = 0, sm1 = 0;
#pragma unroll
  for (int i = 0; i < 5; i++) {
    s[i][0] = ex2f((s[i][0] - mx0) * (SCALE_QK * LOG2E)); s[i][1] = ex2f((s[i][1] - mx0) * (SCALE_QK * LOG2E));
    s[i][2] = ex2f((s[i][2] - mx1) * (SCALE_QK * LOG2E)); s[i][3] = ex2f((s[i][3] - mx1) * (SCALE_QK * LOG2E));
    sm0 += s[i][0] + s[i][1]; sm1 += s[i][2] + s[i][3];
  }
  sm0 += __shfl_xor_sync(~0u, sm0, 1); sm0 += __shfl_xor_sync(~0u, sm0, 2);
  sm1 += __shfl_xor_sync(~0u, sm1, 1); sm1 += __shfl_xor_sync(~0u, sm1, 2);
  const float i0 = __fdividef(1.0f, sm0), i1 = __fdividef(1.0f, sm1);
  unsigned pa[2][4], pm0, pm1;
#pragma unroll
  for (int kk = 0; kk < 2; kk++) {
    pa[kk][0] = pack_bf16(s[2 * kk][0] * i0, s[2 * kk][1] * i0); pa[kk][1] = pack_bf16(s[2 * kk][2] * i1, s[2 * kk][3] * i1);
    pa[kk][2] = pack_bf16(s[2 * kk + 1][0] * i0, s[2 * kk + 1][1] * i0); pa[kk][3] = pack_bf16(s[2 * kk + 1][2] * i1, s[2 * kk + 1][3] * i1);
  }
  pm0 = pack_bf16(s[4][0] * i0, s[4][1] * i0); pm1 = pack_bf16(s[4][2] * i1, s[4][3] * i1);
  const int orow = (kb >> 1) * 64 + seg * 32 + mt * 16 + (m & 1) * 8 + r8;
  const unsigned ob = stg + ((kb & 1) * 2 + eh) * 16384 + orow * 128;
#pragma unroll
  for (int cp = 0; cp < 4; cp++) {
    float o0[4] = {0, 0, 0, 0}, o1[4] = {0, 0, 0, 0};
    mma1688(o0, pm0, pm1, vm[2 * cp]); mma1688(o1, pm0, pm1, vm[2 * cp + 1]);
    unsigned vf[4];
    int row = (m & 1) * 8 + r8;
    unsigned va = vb + row * 128 + (((cp * 2 + (m >> 1)) ^ r8) << 4);
    ldsm_x4_t(vf, va);
    mma16816(o0, pa[0], vf[0], vf[1]); mma16816(o1, pa[0], vf[2], vf[3]);
    if (mt) { ldsm_x4_t(vf, va + 2048); mma16816(o0, pa[1], vf[0], vf[1]); mma16816(o1, pa[1], vf[2], vf[3]); }
    stsm_x4(ob + (((cp * 2 + (m >> 1)) ^ r8) << 4), pack_bf16(o0[0], o0[1]), pack_bf16(o0[2], o0[3]), pack_bf16(o1[0], o1[1]), pack_bf16(o1[2], o1[3]));
  }
}

__device__ __forceinline__ void bulk_worker(unsigned sb, volatile int* misc, const bf16* __restrict__ x, const bf16* __restrict__ b1, const bf16* __restrict__ b2, bf16* __restrict__ out) {
  const int t = threadIdx.x, lane = t & 31, w = t >> 5, wg = w >> 2, g = lane >> 2, tq = lane & 3, m = lane >> 3, r8 = lane & 7;
  const unsigned bar = sb + SM_BAR;
  unsigned st = 0, ph = 0, seq = 0, sph = 0;
  float d[128];
  while (true) {
    mbar_wait(bar + 8 * (MB_FULL + st), ph);
    const int idr = misc[seq & 3]; seq++;
    const int idx = idr & 65535;
    if (idr < 0 || idx >= N_ITEMS) break;
    if (t == 0) ISTAMP(idx, 2);
    const Item it = decode_item(idx);
    const int nkb = item_nkb(it.type);
    if (it.type == T_ATT) {
      unsigned km[16], vm[8], kn[16], vn[8];
      const bool pref = idr >= 65536;
      if (pref) bulk_att_load(kn, vn, it.b, it.c, 0, w, lane);
      mbar_wait(bar + 8 * MB_STGE, sph ^ 1);
#pragma unroll 1
      for (int kb = 0; kb < 4; kb++) {
        if (!pref && !(kb & 1)) {
          if (lane < 4) wait_flag_ge(&g_flags.rec[it.c * 4 + lane], it.b * 4 + (kb >> 1) * 2 + wg + 1);
          __syncwarp();
          bulk_att_load(kn, vn, it.b, it.c, kb, w, lane);
        }
        if (kb) mbar_wait(bar + 8 * (MB_FULL + st), ph);
#pragma unroll
        for (int i = 0; i < 16; i++) km[i] = kn[i];
#pragma unroll
        for (int i = 0; i < 8; i++) vm[i] = vn[i];
        if (pref ? kb != 3 : !(kb & 1)) bulk_att_load(kn, vn, it.b, it.c, kb + 1, w, lane);
        bulk_att_stage(sb + st * STAGE_BYTES, sb + B_STG, km, vm, kb, w, lane);
        __syncwarp();
        if (lane == 0) mbar_arrive(bar + 8 * (MB_EMPTY + st));
        if (++st == NSTAGE) { st = 0; ph ^= 1; }
      }
      if (t == 0) misc[4] = idx;
      fence_proxy_async_smem();
      mbar_arrive(bar + 8 * MB_STGF); sph ^= 1;
      continue;
    }
    if (it.type >= T_RED) {
      __syncwarp();
      if (lane == 0) mbar_arrive(bar + 8 * (MB_EMPTY + st));
      if (++st == NSTAGE) { st = 0; ph ^= 1; }
      if (it.type == T_RED) {
#pragma unroll 2
        for (int i = 0; i < 8; i++) {
          size_t o = ((size_t)it.b * 128 + it.c * 16 + i * 2 + (t >> 7)) * DM + (t & 127) * 4;
          float4 a = __ldcg(reinterpret_cast<const float4*>(g_opart + o)), b = __ldcg(reinterpret_cast<const float4*>(g_opart + o + (size_t)S_TOK * DM));
          float4 c = __ldcg(reinterpret_cast<const float4*>(g_opart + o + (size_t)2 * S_TOK * DM)), e = __ldcg(reinterpret_cast<const float4*>(g_opart + o + (size_t)3 * S_TOK * DM));
          final_out(out, x, o, make_float4((a.x + b.x) + (c.x + e.x), (a.y + b.y) + (c.y + e.y), (a.z + b.z) + (c.z + e.z), (a.w + b.w) + (c.w + e.w)));
        }
      } else {
        size_t ol = ((size_t)it.c * 2 + (t >> 7)) * DM + (t & 127) * 4;
        float4 v[16];
#pragma unroll
        for (int i = 0; i < 16; i++) v[i] = __ldcg(reinterpret_cast<const float4*>(g_opl + ol + (size_t)i * 128 * DM));
#pragma unroll
        for (int st2 = 1; st2 < 16; st2 <<= 1)
#pragma unroll
          for (int i = 0; i < 16; i += 2 * st2) { v[i].x += v[i + st2].x; v[i].y += v[i + st2].y; v[i].z += v[i + st2].z; v[i].w += v[i + st2].w; }
        final_out(out, x, ol + (size_t)15 * 128 * DM, v[0]);
      }
      if (t == 0) ISTAMP(idx, 3);
      continue;
    }
    unsigned pst = 0, bv[32];
#pragma unroll
    for (int i = 0; i < 128; i++) d[i] = 0.0f;
    if (it.type == T_M1 || it.type == T_M2) {
      const unsigned* bp = reinterpret_cast<const unsigned*>((it.type == T_M1 ? b1 : b2) + it.c * 256) + tq;
#pragma unroll
      for (int i = 0; i < 32; i++) asm volatile("ld.global.nc.u32 %0, [%1];" : "=r"(bv[i]) : "l"(bp + i * 4));
    } else {
#pragma unroll
      for (int i = 0; i < 32; i++) bv[i] = 0;
    }
    for (int kb = 0; kb < nkb; kb++) {
      if (kb) mbar_wait(bar + 8 * (MB_FULL + st), ph);
      unsigned sa = sb + st * STAGE_BYTES;
      uint64_t ad = mkdesc(sa + wg * 8192, 16, 1024), bd = mkdesc(sa + 16384, 8192, 1024);
      asm volatile("wgmma.fence.sync.aligned;" ::: "memory");
#pragma unroll
      for (int k = 0; k < 4; k++) wgmma_n256(d, ad + k * 2, bd + k * 128, (kb | k) != 0);
      asm volatile("wgmma.commit_group.sync.aligned;" ::: "memory");
      if (kb) {
        asm volatile("wgmma.wait_group.sync.aligned 1;" ::: "memory");
        if (lane == 0) mbar_arrive(bar + 8 * (MB_EMPTY + pst));
      }
      pst = st;
      if (++st == NSTAGE) { st = 0; ph ^= 1; }
    }
    asm volatile("wgmma.wait_group.sync.aligned 0;" ::: "memory");
    if (lane == 0) mbar_arrive(bar + 8 * (MB_EMPTY + pst));
    if (it.type >= T_OUT) {
      const int col = it.c * 256 + 2 * tq;
      float* pp = it.type == T_OUT ? g_opart + ((size_t)it.ks * S_TOK + it.b * 128 + w * 16 + g) * DM + col : g_opl + ((size_t)it.ks * 128 + w * 16 + g) * DM + col;
#pragma unroll
      for (int i = 0; i < 32; i++) {
        __stcg(reinterpret_cast<float2*>(pp + i * 8), make_float2(d[4 * i], d[4 * i + 1]));
        __stcg(reinterpret_cast<float2*>(pp + 8 * DM + i * 8), make_float2(d[4 * i + 2], d[4 * i + 3]));
      }
      bar_sync(1, 256);
      if (t == 0) { red_release_add(&g_flags.p[it.b], 1); ISTAMP(idx, 3); }
      continue;
    }
#define ACT(F) _Pragma("unroll") for (int i = 0; i < 32; i++) { \
        unsigned u0 = badd2(pack_bf16(d[4 * i], d[4 * i + 1]), bv[i]), u1 = badd2(pack_bf16(d[4 * i + 2], d[4 * i + 3]), bv[i]); \
        d[4 * i] = F(bf_lo(u0)); d[4 * i + 1] = F(bf_hi(u0)); d[4 * i + 2] = F(bf_lo(u1)); d[4 * i + 3] = F(bf_hi(u1)); }
    if (it.type == T_M1) { ACT(gelu_t) } else if (it.type == T_M2) { ACT(silu_f) }
    mbar_wait(bar + 8 * MB_STGE, sph ^ 1);
    {
      const unsigned ob = sb + B_STG + (w * 16 + (m & 1) * 8 + r8) * 128;
#pragma unroll
      for (int i = 0; i < 16; i++)
        stsm_x4(ob + (i >> 2) * 16384 + ((((i & 3) * 2 + (m >> 1)) ^ r8) << 4), pack_bf16(d[8 * i], d[8 * i + 1]), pack_bf16(d[8 * i + 2], d[8 * i + 3]),
                pack_bf16(d[8 * i + 4], d[8 * i + 5]), pack_bf16(d[8 * i + 6], d[8 * i + 7]));
    }
    if (t == 0) misc[4] = idx;
    fence_proxy_async_smem();
    mbar_arrive(bar + 8 * MB_STGF); sph ^= 1;
  }
  mbar_wait(bar + 8 * MB_STGE, sph ^ 1);
  if (t == 0) misc[4] = -1;
  mbar_arrive(bar + 8 * MB_STGF);
}

__global__ void __launch_bounds__(384, 1)
k_main(const __grid_constant__ Maps maps, const bf16* __restrict__ x, const bf16* __restrict__ mem0, const bf16* __restrict__ b1, const bf16* __restrict__ b2, bf16* __restrict__ out, unsigned recmask) {
  extern __shared__ unsigned char smem_raw[];
  const unsigned sraw = smem_u32(smem_raw);
  const unsigned sb = (sraw + 1023u) & ~1023u;
  int* misc = reinterpret_cast<int*>(smem_raw + (sb - sraw) + SM_MISC);
  const int w = threadIdx.x >> 5;
  const bool helper = recmask == 0;
  const unsigned kc = blockIdx.x / CLS;
  const bool rec = kc < 32 && ((recmask >> kc) & 1);
  const int c = __popc(recmask & ((1u << (kc & 31)) - 1)) * CLS + (blockIdx.x & (CLS - 1));
  if (threadIdx.x == 0) {
    const unsigned bar = sb + SM_BAR;
    for (int i = 0; i < 8; i++) { mbar_init(bar + 8 * (MB_FULL + i), 1); mbar_init(bar + 8 * (MB_EMPTY + i), rec ? 1 : 8); }
    mbar_init(bar + 8 * MB_STGF, 256); mbar_init(bar + 8 * MB_STGE, 1);
    for (int i = MB_W0; i <= MB_AG; i++) mbar_init(bar + 8 * i, 1);
    if (rec) { mbar_expect_tx(bar + 8 * MB_S, 2560); mbar_expect_tx(bar + 8 * MB_V, 2048); mbar_expect_tx(bar + 8 * MB_RS, 8192); mbar_expect_tx(bar + 8 * MB_AG, 8192); }
    asm volatile("fence.mbarrier_init.release.cluster;" ::: "memory");
  }
  __syncthreads();
  asm volatile("barrier.cluster.arrive.release.aligned;\nbarrier.cluster.wait.acquire.aligned;" ::: "memory");
  if (rec && threadIdx.x == 256) {
    const unsigned bar = sb + SM_BAR; const int col = c * 64;
    mbar_expect_tx(bar + 8 * MB_W0, 131072);
    for (int kb = 0; kb < 8; kb++) tma_load_2d(sb + R_WO + kb * 8192, &maps.wq, col, kb * 64, bar + 8 * MB_W0);
    for (int kb = 0; kb < 8; kb++) tma_load_2d(sb + R_T1 + kb * 8192, &maps.wk, col, kb * 64, bar + 8 * MB_W0);
    mbar_expect_tx(bar + 8 * MB_W1, 65536);
    for (int kb = 0; kb < 8; kb++) tma_load_2d(sb + R_T2 + kb * 8192, &maps.wv, col, kb * 64, bar + 8 * MB_W1);
  }
  if (!helper) {
    asm volatile("griddepcontrol.wait;" ::: "memory");
    asm volatile("griddepcontrol.launch_dependents;");
  }
  if (DBGMODE && !rec) { if (helper) asm volatile("griddepcontrol.wait;" ::: "memory"); return; }
  if (w >= 8) {
    asm volatile("setmaxnreg.dec.sync.aligned.u32 24;");
    if (rec) { if (w == 8) rec_ring(maps, sb, c); else if (w == 9) rec_copy(sb, c); }
    else if (w == 8) bulk_producer(maps, sb, misc);
    else if ((threadIdx.x & 31) == 0) { if (w == 9) bulk_store(maps, sb, misc);
      else if (w == 10 && helper) asm volatile("griddepcontrol.wait;" ::: "memory"); }
  } else {
    if (rec) { asm volatile("setmaxnreg.inc.sync.aligned.u32 240;"); rec_worker(maps, sb, mem0, c); }
    else { asm volatile("setmaxnreg.inc.sync.aligned.u32 240;"); bulk_worker(sb, misc, x, b1, b2, out); }
  }
}

typedef CUresult (*EncFn)(CUtensorMap*, CUtensorMapDataType, cuuint32_t, void*, const cuuint64_t*, const cuuint64_t*, const cuuint32_t*, const cuuint32_t*,
                          CUtensorMapInterleave, CUtensorMapSwizzle, CUtensorMapL2promotion, CUtensorMapFloatOOBfill);
static void mk_map(EncFn enc, CUtensorMap* m, const void* ptr, uint64_t rows, uint64_t cols, uint32_t box_rows) {
  cuuint64_t dims[2] = {cols, rows}; cuuint64_t strides[1] = {cols * 2};
  cuuint32_t box[2] = {64, box_rows}, es[2] = {1, 1};
  enc(m, CU_TENSOR_MAP_DATA_TYPE_BFLOAT16, 2, const_cast<void*>(ptr), dims, strides, box, es, CU_TENSOR_MAP_INTERLEAVE_NONE, CU_TENSOR_MAP_SWIZZLE_128B,
      CU_TENSOR_MAP_L2_PROMOTION_L2_256B, CU_TENSOR_MAP_FLOAT_OOB_FILL_NONE);
}
extern "C" void kernel_launch(void* const* d_in, const int* in_sizes, int n_in, void* d_out, int out_size) {
  static EncFn enc = nullptr;
  static int ncl = 0, nhelp = 0;
  static unsigned recmask = 0xFFu;
  static void *p_xn, *p_y, *p_h1, *p_o, *p_qkv, *p_g;
  if (!enc) {
    void* fn = nullptr; cudaDriverEntryPointQueryResult qr;
    cudaGetDriverEntryPoint("cuTensorMapEncodeTiled", &fn, cudaEnableDefault, &qr);
    enc = (EncFn)fn;
    cudaGetSymbolAddress(&p_xn, g_xn); cudaGetSymbolAddress(&p_y, g_y); cudaGetSymbolAddress(&p_h1, g_h1);
    cudaGetSymbolAddress(&p_o, g_o); cudaGetSymbolAddress(&p_qkv, g_qkv); cudaGetSymbolAddress(&p_g, g_g);
    cudaFuncSetAttribute(k_main, cudaFuncAttributeMaxDynamicSharedMemorySize, SMEM_TOTAL);
    cudaLaunchConfig_t cfg = {}; cfg.gridDim = dim3(128); cfg.blockDim = dim3(384); cfg.dynamicSmemBytes = SMEM_TOTAL;
    cudaLaunchAttribute at[1]; at[0].id = cudaLaunchAttributeClusterDimension; at[0].val.clusterDim.x = CLS; at[0].val.clusterDim.y = 1; at[0].val.clusterDim.z = 1;
    cfg.attrs = at; cfg.numAttrs = 1;
    if (cudaOccupancyMaxActiveClusters(&ncl, k_main, &cfg) != cudaSuccess) { cudaGetLastError(); ncl = 14; }
    ncl = ncl > 16 ? 16 : (ncl < 9 ? 9 : ncl);
    int nsm = 0, dev = 0; cudaGetDevice(&dev); cudaDeviceGetAttribute(&nsm, cudaDevAttrMultiProcessorCount, dev);
    nhelp = nsm - ncl * CLS;
  }
  Maps maps;
  mk_map(enc, &maps.xn, p_xn, S_TOK, DM, 128); mk_map(enc, &maps.y, p_y, S_TOK, DM, 128); mk_map(enc, &maps.h1, p_h1, S_TOK, FF, 128);
  mk_map(enc, &maps.o, p_o, S_TOK, HD, 128); mk_map(enc, &maps.qkv_st, p_qkv, S_TOK, 3 * HD, 128); mk_map(enc, &maps.qkv_ld, p_qkv, S_TOK, 3 * HD, 32);
  mk_map(enc, &maps.g, p_g, S_TOK, DM, 128);
  mk_map(enc, &maps.wq, d_in[2], DM, HD, 64); mk_map(enc, &maps.wk, d_in[3], DM, HD, 64); mk_map(enc, &maps.wv, d_in[4], DM, HD, 64);
  mk_map(enc, &maps.wo, d_in[5], HD, DM, 64); mk_map(enc, &maps.w1, d_in[8], DM, FF, 64); mk_map(enc, &maps.w2, d_in[10], FF, DM, 64);
  cudaStream_t st = cudaStreamPerThread;
  k_pre<<<256, 256, 0, st>>>((const bf16*)d_in[0], (const char*)d_in[2], (const char*)d_in[3], (const char*)d_in[4], (const char*)d_in[5]);
  cudaLaunchConfig_t cfg = {}; cfg.gridDim = dim3(ncl * CLS); cfg.blockDim = dim3(384); cfg.dynamicSmemBytes = SMEM_TOTAL; cfg.stream = st;
  cudaLaunchAttribute at[2]; at[1].id = cudaLaunchAttributeClusterDimension; at[1].val.clusterDim.x = CLS; at[1].val.clusterDim.y = 1; at[1].val.clusterDim.z = 1;
  at[0].id = cudaLaunchAttributeProgrammaticStreamSerialization; at[0].val.programmaticStreamSerializationAllowed = 1;
#define PDL1 0
  cfg.attrs = at + (PDL1 ? 0 : 1); cfg.numAttrs = PDL1 ? 2 : 1;
  cudaLaunchKernelEx(&cfg, k_main, maps, (const bf16*)d_in[0], (const bf16*)d_in[1], (const bf16*)d_in[9], (const bf16*)d_in[11], (bf16*)d_out, recmask);
  if (nhelp > 0) {
    cfg.gridDim = dim3(nhelp);
    cfg.attrs = at; cfg.numAttrs = 1;
    cudaLaunchKernelEx(&cfg, k_main, maps, (const bf16*)d_in[0], (const bf16*)d_in[1], (const bf16*)d_in[9], (const bf16*)d_in[11], (bf16*)d_out, 0u);
  }
}
```

```cpp
#include <cuda_runtime.h>
#include <cuda_bf16.h>
#include <cuda.h>
#include <stdint.h>

typedef __nv_bfloat16 bf16;

#define S_TOK 2048
#define DM 512
#define NH 32
#define DH 128
#define HD 4096
#define NMEM 8
#define SEG 32
#define NSEG 64
#define FF 1792
#define NBLK 16
#define NREC 64
#define REPL 0
#define CLS 8

__device__ __align__(1024) bf16 g_xn[S_TOK * DM];
__device__ __align__(1024) bf16 g_y[S_TOK * DM];
__device__ __align__(1024) bf16 g_qkv[(size_t)S_TOK * 3 * HD];
__device__ __align__(1024) bf16 g_h1[S_TOK * FF];
__device__ __align__(1024) bf16 g_g[S_TOK * DM];
__device__ __align__(1024) bf16 g_o[(size_t)S_TOK * HD];
__device__ __align__(1024) bf16 g_km[NSEG * NH * NMEM * DH];
__device__ __align__(1024) bf16 g_vmt[NSEG * NH * DH * NMEM];
__device__ __align__(1024) float g_opart[(size_t)4 * S_TOK * DM];
__device__ __align__(1024) float g_opl[(size_t)16 * 128 * DM];
__device__ __align__(1024) unsigned g_part[8 * 2 * 8 * 8 * 512];
struct Flags {
  unsigned qkv[NBLK * 48];
  unsigned h1[NBLK];
  unsigned g[NBLK];
  unsigned o[NBLK * 4];
  unsigned p[NBLK];
  unsigned o16[16];
  unsigned ctr;
  unsigned rec[NREC];
  unsigned abort_;
};
__device__ __align__(1024) Flags g_flags;

#define RSTAMP(k)
#define DBGMODE 0
#define ISTAMP(i, k)
__device__ __forceinline__ unsigned smem_u32(const void* p) { return (unsigned)__cvta_generic_to_shared(p); }
__device__ __forceinline__ float bf16r(float x) { unsigned u; asm("cvt.rn.bf16x2.f32 %0, %1, %2;" : "=r"(u) : "f"(x), "f"(0.0f)); return __uint_as_float(u); }
__device__ __forceinline__ unsigned pack_bf16(float lo, float hi) {
  __nv_bfloat162 v = __floats2bfloat162_rn(lo, hi);
  return *reinterpret_cast<unsigned*>(&v);
}
__device__ __forceinline__ float bf_lo(unsigned u) { return __uint_as_float(u << 16); }
__device__ __forceinline__ float bf_hi(unsigned u) { return __uint_as_float(u & 0xffff0000u); }

#define SPIN_LIMIT (1u << 20)
#define TRAP_IF(x) if ((x) > SPIN_LIMIT) { asm volatile("st.global.u32 [%0], %1;" ::"l"(0ull), "r"(0u) : "memory"); break; }
__device__ __forceinline__ unsigned ld_acquire(const unsigned* p) {
  unsigned v; asm volatile("ld.acquire.gpu.global.u32 %0, [%1];" : "=r"(v) : "l"(p) : "memory"); return v;
}
__device__ __forceinline__ unsigned ld_relaxed(const unsigned* p) {
  unsigned v; asm volatile("ld.relaxed.gpu.global.u32 %0, [%1];" : "=r"(v) : "l"(p) : "memory"); return v;
}
__device__ __forceinline__ void red_release_add(unsigned* p, unsigned v) {
  asm volatile("red.release.gpu.global.add.u32 [%0], %1;" ::"l"(p), "r"(v) : "memory");
}
__device__ __forceinline__ void st_release(unsigned* p, unsigned v) {
  asm volatile("st.release.gpu.global.u32 [%0], %1;" ::"l"(p), "r"(v) : "memory");
}
__device__ __forceinline__ void wait_flag_ge(const unsigned* p, unsigned target) {
  unsigned it = 0;
  while (ld_acquire(p) < target) {
    __nanosleep(64);
    TRAP_IF(++it);
  }
}
__device__ __forceinline__ uint4 ldv4_relaxed(const void* p) {
  uint4 a; asm volatile("ld.relaxed.gpu.global.v4.u32 {%0,%1,%2,%3}, [%4];" : "=r"(a.x), "=r"(a.y), "=r"(a.z), "=r"(a.w) : "l"(p) : "memory"); return a;
}
__device__ __forceinline__ uint2 ldv2_relaxed(const void* p) {
  uint2 a; asm volatile("ld.relaxed.gpu.global.v2.u32 {%0,%1}, [%2];" : "=r"(a.x), "=r"(a.y) : "l"(p) : "memory"); return a;
}
__device__ __forceinline__ void mbar_init(unsigned mb, unsigned cnt) { asm volatile("mbarrier.init.shared::cta.b64 [%0], %1;" ::"r"(mb), "r"(cnt) : "memory"); }
__device__ __forceinline__ void mbar_expect_tx(unsigned mb, unsigned bytes) { asm volatile("mbarrier.arrive.expect_tx.shared::cta.b64 _, [%0], %1;" ::"r"(mb), "r"(bytes) : "memory"); }
__device__ __forceinline__ void mbar_arrive(unsigned mb) { asm volatile("mbarrier.arrive.shared::cta.b64 _, [%0];" ::"r"(mb) : "memory"); }
__device__ __forceinline__ void mbar_wait(unsigned mb, unsigned parity) {
  unsigned ok, it = 0;
  while (true) {
    asm volatile("{.reg .pred p; mbarrier.try_wait.parity.shared::cta.b64 p, [%1], %2; selp.u32 %0,1,0,p;}" : "=r"(ok) : "r"(mb), "r"(parity) : "memory");
    if (ok) break;
    TRAP_IF(++it);
  }
}
__device__ __forceinline__ void mbar_wait_sleep(unsigned mb, unsigned parity) {
  unsigned ok, it = 0;
  while (true) {
    asm volatile("{.reg .pred p; mbarrier.test_wait.parity.shared::cta.b64 p, [%1], %2; selp.u32 %0,1,0,p;}" : "=r"(ok) : "r"(mb), "r"(parity) : "memory");
    if (ok) break;
    __nanosleep(200);
    TRAP_IF(++it);
  }
}
__device__ __forceinline__ float ex2f(float x) { float y; asm("ex2.approx.ftz.f32 %0, %1;" : "=f"(y) : "f"(x)); return y; }
__device__ __forceinline__ int opaque_tid() { int t = threadIdx.x; t = __shfl_sync(~0u, t, t & 31); return t; }
#define LOG2E 1.4426950408889634f
__device__ __forceinline__ void mbar_wait_cluster(unsigned mb, unsigned parity) {
  unsigned ok, it = 0;
  while (true) {
    asm volatile("{.reg .pred p; mbarrier.try_wait.parity.acquire.cluster.shared::cta.b64 p, [%1], %2; selp.u32 %0,1,0,p;}" : "=r"(ok) : "r"(mb), "r"(parity) : "memory");
    if (ok) break;
    TRAP_IF(++it);
  }
}
__device__ __forceinline__ void bar_sync(int id, int n) { asm volatile("bar.sync %0, %1;" ::"r"(id), "r"(n) : "memory"); }
__device__ __forceinline__ void bar_arrive(int id, int n) { asm volatile("bar.arrive %0, %1;" ::"r"(id), "r"(n) : "memory"); }
__device__ __forceinline__ void tma_load_2d(unsigned dst, const CUtensorMap* map, int c0, int c1, unsigned mb) {
  asm volatile("cp.async.bulk.tensor.2d.shared::cluster.global.mbarrier::complete_tx::bytes [%0], [%1, {%3, %4}], [%2];"
               ::"r"(dst), "l"((uint64_t)map), "r"(mb), "r"(c0), "r"(c1) : "memory");
}
__device__ __forceinline__ void tma_store_2d(const CUtensorMap* map, unsigned src, int c0, int c1) {
  asm volatile("cp.async.bulk.tensor.2d.global.shared::cta.bulk_group [%0, {%2, %3}], [%1];"
               ::"l"((uint64_t)map), "r"(src), "r"(c0), "r"(c1) : "memory");
}
__device__ __forceinline__ void fence_proxy_async() { asm volatile("fence.proxy.async;" ::: "memory"); }
__device__ __forceinline__ void fence_proxy_async_smem() { asm volatile("fence.proxy.async.shared::cta;" ::: "memory"); }
__device__ __forceinline__ void ldsm_x4(unsigned* r, unsigned addr) {
  asm volatile("ldmatrix.sync.aligned.m8n8.x4.shared.b16 {%0,%1,%2,%3}, [%4];" : "=r"(r[0]), "=r"(r[1]), "=r"(r[2]), "=r"(r[3]) : "r"(addr) : "memory");
}
__device__ __forceinline__ void ldsm_x4_t(unsigned* r, unsigned addr) {
  asm volatile("ldmatrix.sync.aligned.m8n8.x4.trans.shared.b16 {%0,%1,%2,%3}, [%4];" : "=r"(r[0]), "=r"(r[1]), "=r"(r[2]), "=r"(r[3]) : "r"(addr) : "memory");
}
__device__ __forceinline__ void stsm_x2_t(unsigned addr, unsigned r0, unsigned r1) {
  asm volatile("stmatrix.sync.aligned.m8n8.x2.trans.shared.b16 [%0], {%1,%2};" ::"r"(addr), "r"(r0), "r"(r1) : "memory");
}
__device__ __forceinline__ void stsm_x4(unsigned addr, unsigned r0, unsigned r1, unsigned r2, unsigned r3) {
  asm volatile("stmatrix.sync.aligned.m8n8.x4.shared.b16 [%0], {%1,%2,%3,%4};" ::"r"(addr), "r"(r0), "r"(r1), "r"(r2), "r"(r3) : "memory");
}
__device__ __forceinline__ void mma16816(float* d, const unsigned* a, unsigned b0, unsigned b1) {
  asm volatile("mma.sync.aligned.m16n8k16.row.col.f32.bf16.bf16.f32 {%0,%1,%2,%3}, {%4,%5,%6,%7}, {%8,%9}, {%0,%1,%2,%3};"
               : "+f"(d[0]), "+f"(d[1]), "+f"(d[2]), "+f"(d[3]) : "r"(a[0]), "r"(a[1]), "r"(a[2]), "r"(a[3]), "r"(b0), "r"(b1));
}
__device__ __forceinline__ void mma1688(float* d, unsigned a0, unsigned a1, unsigned b0) {
  asm volatile("mma.sync.aligned.m16n8k8.row.col.f32.bf16.bf16.f32 {%0,%1,%2,%3}, {%4,%5}, {%6}, {%0,%1,%2,%3};"
               : "+f"(d[0]), "+f"(d[1]), "+f"(d[2]), "+f"(d[3]) : "r"(a0), "r"(a1), "r"(b0));
}
__device__ __forceinline__ uint64_t mkdesc(unsigned addr, unsigned lbo, unsigned sbo) {
  return (uint64_t)((addr >> 4) & 0x3fff) | ((uint64_t)(lbo >> 4) << 16) | ((uint64_t)(sbo >> 4) << 32) | (1ull << 62);
}
#define R8(b) "+f"(d[b]), "+f"(d[b + 1]), "+f"(d[b + 2]), "+f"(d[b + 3]), "+f"(d[b + 4]), "+f"(d[b + 5]), "+f"(d[b + 6]), "+f"(d[b + 7])
#define R32(b) R8(b), R8(b + 8), R8(b + 16), R8(b + 24)
__device__ __forceinline__ void wgmma_n256(float* d, uint64_t ad, uint64_t bd, int acc) {
  asm volatile(
      "{.reg .pred p; setp.ne.b32 p, %130, 0;\n"
      "wgmma.mma_async.sync.aligned.m64n256k16.f32.bf16.bf16 "
      "{%0,%1,%2,%3,%4,%5,%6,%7,%8,%9,%10,%11,%12,%13,%14,%15,%16,%17,%18,%19,%20,%21,%22,%23,%24,%25,%26,%27,%28,%29,%30,%31,"
      "%32,%33,%34,%35,%36,%37,%38,%39,%40,%41,%42,%43,%44,%45,%46,%47,%48,%49,%50,%51,%52,%53,%54,%55,%56,%57,%58,%59,%60,%61,%62,%63,"
      "%64,%65,%66,%67,%68,%69,%70,%71,%72,%73,%74,%75,%76,%77,%78,%79,%80,%81,%82,%83,%84,%85,%86,%87,%88,%89,%90,%91,%92,%93,%94,%95,"
      "%96,%97,%98,%99,%100,%101,%102,%103,%104,%105,%106,%107,%108,%109,%110,%111,%112,%113,%114,%115,%116,%117,%118,%119,%120,%121,%122,%123,%124,%125,%126,%127},"
      "%128, %129, p, 1, 1, 0, 1;}\n"
      : R32(0), R32(32), R32(64), R32(96)
      : "l"(ad), "l"(bd), "r"(acc));
}

__device__ __forceinline__ void wgmma_n128(float* d, uint64_t ad, uint64_t bd, int acc) {
  asm volatile(
      "{.reg .pred p; setp.ne.b32 p, %66, 0;\n"
      "wgmma.mma_async.sync.aligned.m64n128k16.f32.bf16.bf16 {%0,%1,%2,%3,%4,%5,%6,%7,%8,%9,%10,%11,%12,%13,%14,%15,%16,%17,%18,%19,%20,%21,%22,%23,%24,%25,%26,%27,%28,%29,%30,%31,%32,%33,%34,%35,%36,%37,%38,%39,%40,%41,%42,%43,%44,%45,%46,%47,%48,%49,%50,%51,%52,%53,%54,%55,%56,%57,%58,%59,%60,%61,%62,%63}, %64, %65, p, 1, 1, 0, 1;}\n"
      : R32(0), R32(32)
      : "l"(ad), "l"(bd), "r"(acc));
}

__device__ __forceinline__ void ln16(const float* x, float* o) {
  float s = 0;
#pragma unroll
  for (int i = 0; i < 16; i++) s += x[i];
#pragma unroll
  for (int of = 16; of > 0; of >>= 1) s += __shfl_xor_sync(~0u, s, of);
  float mean = s * (1.0f / DM);
  float v = 0;
#pragma unroll
  for (int i = 0; i < 16; i++) { float dd = x[i] - mean; v += dd * dd; }
#pragma unroll
  for (int of = 16; of > 0; of >>= 1) v += __shfl_xor_sync(~0u, v, of);
  float mb = bf16r(mean);
  float vb = bf16r(v * (1.0f / DM));
  float den = bf16r(sqrtf(bf16r(vb + 1e-5f)));
#pragma unroll
  for (int i = 0; i < 16; i++) o[i] = bf16r(__fdiv_rn(bf16r(x[i] - mb), den));
}
__global__ void __launch_bounds__(256) k_pre(const bf16* __restrict__ x, const char* wq, const char* wk, const char* wv, const char* wo) {
  int t = threadIdx.x, lane = t & 31, w = t >> 5;
  asm volatile("griddepcontrol.launch_dependents;");
  {
    int g2 = blockIdx.x * 256 + t, o = (g2 & 32767) * 128;
    asm volatile("prefetch.global.L2 [%0];" ::"l"((g2 < 32768 ? wk : wv) + o));
    asm volatile("prefetch.global.L2 [%0];" ::"l"((g2 < 32768 ? wq : wo) + o));
  }
  int row = blockIdx.x * 8 + w;
  const uint4* src = reinterpret_cast<const uint4*>(x + (size_t)row * DM);
  uint4 a = src[lane], b = src[lane + 32];
  unsigned u[8] = {a.x, a.y, a.z, a.w, b.x, b.y, b.z, b.w};
  float f[16], o[16], o2[16];
#pragma unroll
  for (int i = 0; i < 8; i++) { f[2 * i] = bf_lo(u[i]); f[2 * i + 1] = bf_hi(u[i]); }
  ln16(f, o);
  ln16(o, o2);
  uint4* d1 = reinterpret_cast<uint4*>(g_xn + (size_t)row * DM);
  uint4* d2 = reinterpret_cast<uint4*>(g_y + (size_t)row * DM);
  d1[lane] = make_uint4(pack_bf16(o[0], o[1]), pack_bf16(o[2], o[3]), pack_bf16(o[4], o[5]), pack_bf16(o[6], o[7]));
  d1[lane + 32] = make_uint4(pack_bf16(o[8], o[9]), pack_bf16(o[10], o[11]), pack_bf16(o[12], o[13]), pack_bf16(o[14], o[15]));
  d2[lane] = make_uint4(pack_bf16(o2[0], o2[1]), pack_bf16(o2[2], o2[3]), pack_bf16(o2[4], o2[5]), pack_bf16(o2[6], o2[7]));
  d2[lane + 32] = make_uint4(pack_bf16(o2[8], o2[9]), pack_bf16(o2[10], o2[11]), pack_bf16(o2[12], o2[13]), pack_bf16(o2[14], o2[15]));
  int gt = blockIdx.x * 256 + t;
  uint4 z = make_uint4(0, 0, 0, 0);
  if (gt < 16384) reinterpret_cast<uint4*>(g_part)[gt] = z;
  if (gt < (int)(sizeof(Flags) / 4)) reinterpret_cast<unsigned*>(&g_flags)[gt] = 0;
}

struct Maps { CUtensorMap xn, y, h1, o, qkv_st, qkv_ld, g, wq, wk, wv, wo, w1, w2; };

#define NSTAGE 3
#define STAGE_BYTES 49152
#define B_STG (NSTAGE * STAGE_BYTES)
#define R_WO 0
#define R_T1 65536
#define R_T2 131072
#define R_RING 65536
#define RING_N 4
#define RING_BYTES 12288
#define R_MEM 196608
#define R_QS (R_MEM + 8448)
#define R_KS (R_QS + 1152)
#define R_OS (R_KS + 1152)
#define R_SOWN (R_OS + 2176)
#define R_SPEER (R_SOWN + 1280)
#define R_VM (R_SPEER + 1280)
#define R_VRED (R_VM + 2048)
#define R_RS (R_VRED + 6144)
#define SM_BAR (R_RS + 8192)
#define SMEM_TOTAL (SM_BAR + 256 + 1024)
#define MB_FULL 0
#define MB_EMPTY 8
#define MB_STGF 16
#define MB_STGE 17
#define MB_W0 18
#define MB_W1 19
#define MB_WO 20
#define MB_S 21
#define MB_V 22
#define MB_KVR 23
#define MB_KVF 24
#define MB_RS 25
#define MB_AG 26
#define SM_MISC (SM_BAR + 224)

#define N_KV 544
#define I_M1 544
#define I_Q 656
#define I_M2 912
#define I_POST 944
#define I_TAIL (I_POST + 16 * 32)
#define N_ITEMS (I_TAIL + 5 * 8 + 64 + 8 + 64)
enum { T_QKV = 0, T_M1 = 1, T_M2 = 2, T_ATT = 3, T_OUT = 4, T_OUTL = 5, T_RED = 6, T_REDL = 7 };
struct Item { int type, b, c, ks, hf; };
__device__ __forceinline__ Item decode_item(int i) {
  Item it; it.ks = 0; it.hf = 0;
  if (i < 64) { it.type = T_QKV; it.b = 0; it.c = 16 + (i >> 1); it.hf = 1 + (i & 1); }
  else if (i < N_KV) { it.type = T_QKV; it.b = (i - 32) >> 5; it.c = 16 + (i & 31); }
  else if (i < I_Q) { it.type = T_M1; it.b = (i - I_M1) / 7; it.c = (i - I_M1) % 7; }
  else if (i < I_M2) { it.type = T_QKV; it.b = (i - I_Q) >> 4; it.c = (i - I_Q) & 15; }
  else if (i < I_POST) { it.type = T_M2; it.b = (i - I_M2) >> 1; it.c = (i - I_M2) & 1; }
  else if (i < I_TAIL) {
    int x = i - I_POST, p = x >> 5, r = x & 31;
    if (r < 16) { it.type = T_ATT; it.b = p; it.c = r; }
    else if (r < 24) { it.type = T_OUT; it.b = p - 3; it.c = r & 1; it.ks = (r - 16) >> 1; }
    else { it.type = T_RED; it.b = p - 5; it.c = r - 24; }
  } else {
    int x = i - I_TAIL, r = x & 7;
    if (x < 40) {
      int q = x >> 3;
      if (q == 0 || q == 2) { it.type = T_OUT; it.b = 13 + (q >> 1); it.c = r & 1; it.ks = r >> 1; }
      else { it.type = T_RED; it.b = q == 1 ? 11 : 9 + q; it.c = r; }
    }
    else if (x < 104) { it.type = T_OUTL; it.b = 15; it.c = (x >> 1) & 1; it.ks = (x - 40) >> 2; it.hf = 1 + (x & 1); }
    else if (x < 112) { it.type = T_RED; it.b = 14; it.c = r; }
    else { it.type = T_REDL; it.b = 15; it.c = x - 112; }
  }
  return it;
}
__device__ __forceinline__ int item_nkb(int type) { return type == T_M2 ? 28 : (type == T_OUT ? 16 : (type >= T_RED ? 1 : (type >= T_ATT ? 4 : 8))); }

__device__ __forceinline__ void st_async_b64(unsigned raddr, unsigned lo, unsigned hi, unsigned rmb) {
  asm volatile("st.async.weak.shared::cluster.mbarrier::complete_tx::bytes.v2.b32 [%0], {%1,%2}, [%3];" ::"r"(raddr), "r"(lo), "r"(hi), "r"(rmb) : "memory");
}
__device__ __forceinline__ void st_async_b32(unsigned raddr, unsigned v, unsigned rmb) {
  asm volatile("st.async.weak.shared::cluster.mbarrier::complete_tx::bytes.b32 [%0], %1, [%2];" ::"r"(raddr), "r"(v), "r"(rmb) : "memory");
}
__device__ __forceinline__ unsigned mapa(unsigned a, unsigned rank) {
  unsigned r; asm volatile("mapa.shared::cluster.u32 %0, %1, %2;" : "=r"(r) : "r"(a), "r"(rank)); return r;
}
__device__ __forceinline__ void sts64(unsigned a, unsigned x, unsigned y) { asm volatile("st.shared.v2.b32 [%0], {%1,%2};" ::"r"(a), "r"(x), "r"(y) : "memory"); }
__device__ __forceinline__ void sts128(unsigned a, uint4 v) { asm volatile("st.shared.v4.b32 [%0], {%1,%2,%3,%4};" ::"r"(a), "r"(v.x), "r"(v.y), "r"(v.z), "r"(v.w) : "memory"); }
__device__ __forceinline__ uint2 lds64(unsigned a) { uint2 v; asm volatile("ld.shared.v2.b32 {%0,%1}, [%2];" : "=r"(v.x), "=r"(v.y) : "r"(a) : "memory"); return v; }
__device__ __forceinline__ uint4 lds128(unsigned a) { uint4 v; asm volatile("ld.shared.v4.b32 {%0,%1,%2,%3}, [%4];" : "=r"(v.x), "=r"(v.y), "=r"(v.z), "=r"(v.w) : "r"(a) : "memory"); return v; }
__device__ __forceinline__ float lds32f(unsigned a) { float v; asm volatile("ld.shared.f32 %0, [%1];" : "=f"(v) : "r"(a) : "memory"); return v; }
#define spin_check(it) TRAP_IF(++it)
#define POLLV 0
#define BAR8 0
#define D_STAG 150
#define D_RED 540
#define D_PUB 0
#define DELAY(n) do { unsigned c0_, c1_; asm volatile("mov.u32 %0, %%clock;" : "=r"(c0_)); do { asm volatile("mov.u32 %0, %%clock;" : "=r"(c1_)); } while (c1_ - c0_ < (n)); } while (0)
#define VD 2
#define NPRE 3
#define SELP 1
#define SCALE_QK 0.08838834764831845f

__device__ __forceinline__ void rec_worker(const Maps& maps, unsigned sb, const bf16* __restrict__ mem0, const int c) {
  const int h = c >> 1, j = c & 1;
  const int t = opaque_tid(), lane = t & 31, w = t >> 5, g = lane >> 2, tq = lane & 3;
  const int m = lane >> 3, r8 = lane & 7, kh = w >> 2, et = w & 3;
  const unsigned bar = sb + SM_BAR;
  unsigned wq[16][4], wk[16][4], wo[8][4];
  const unsigned woff = (kh * 4) * 8192 + ((m >> 1) * 8 + r8) * 128 + (((et * 2 + (m & 1)) ^ r8) << 4);
  mbar_wait(bar + 8 * MB_W0, 0);
#pragma unroll
  for (int i = 0; i < 16; i++) {
    ldsm_x4_t(wq[i], sb + R_WO + woff + (i >> 2) * 8192 + (i & 3) * 2048);
    ldsm_x4_t(wk[i], sb + R_T1 + woff + (i >> 2) * 8192 + (i & 3) * 2048);
  }
  bar_sync(2, 288);
  if (t == 0) {
    fence_proxy_async_smem();
    mbar_expect_tx(bar + 8 * MB_WO, 65536);
    for (int kb = 0; kb < 2; kb++)
      for (int cb = 0; cb < 4; cb++) tma_load_2d(sb + R_WO + (kb * 4 + cb) * 8192, &maps.wo, j * 256 + cb * 64, h * 128 + kb * 64, bar + 8 * MB_WO);
  }
  mbar_wait(bar + 8 * MB_W1, 0);
  const unsigned pV = sb + R_T2 + woff;
  const unsigned rk = c & 7, peer = rk ^ 1, cl = c >> 3;
#define KEEP(x) x = __shfl_sync(~0u, x, lane)
  unsigned pA = sb + R_MEM + kh * 4096 + lane * 16;
  unsigned pW0 = sb + R_WO + (w >> 1) * 8192 + ((m >> 1) * 8 + r8) * 128 + ((((w & 1) * 4 + (m & 1)) ^ r8) << 4);
  unsigned pW1 = pW0 ^ 32;
  unsigned pVk = pV;
  unsigned aX = sb + R_VRED + et * 512 + lane * 16;
  unsigned aQKst = sb + (kh ? R_KS : R_QS) + r8 * 144 + (et * 16 + (m & 1) * 8) * 2;
  unsigned aL8 = sb + lane * 8;
  unsigned aSl = mapa(sb + R_SOWN + w * 256 + lane * 8, rk), aSr = mapa(sb + R_SPEER + w * 256 + lane * 8, peer);
  unsigned aVl = mapa(sb + R_VM + (j * 4 + et) * 256 + lane * 8, rk), aVr = mapa(sb + R_VM + (j * 4 + et) * 256 + lane * 8, peer);
  const unsigned mbSl = mapa(bar + 8 * MB_S, rk), mbSr = mapa(bar + 8 * MB_S, peer), mbVl = mbSl + 8, mbVr = mbSr + 8;
  unsigned aQ = sb + R_QS + r8 * 144 + m * 16;
  unsigned oKx = (et * 8 + r8) * 128 + ((m ^ r8) << 4);
  unsigned oVx = 4096 + (et >> 1) * 4096 + ((m >> 1) * 8 + r8) * 128 + ((((et & 1) * 4 + (m & 1)) ^ r8) << 4);
  unsigned aOst = sb + R_OS + r8 * 272 + (et * 32 + m * 8) * 2;
  unsigned aOld = sb + R_OS + r8 * 272 + m * 16;
  unsigned aVm = sb + R_VM + et * 512 + lane * 8;
  unsigned aRSr = mapa(sb + R_RS + (h & 3) * 2048 + (w & 1) * 1024 + lane * 8, j * 4 + (w >> 1));
  unsigned mbRSr = mapa(bar + 8 * MB_RS, j * 4 + (w >> 1));
  unsigned t8 = t * 8;
  KEEP(pA); KEEP(pW0); KEEP(pW1); KEEP(pVk); KEEP(aX); KEEP(aQKst); KEEP(aL8); KEEP(aSl); KEEP(aSr); KEEP(aVl); KEEP(aVr); KEEP(aQ); KEEP(oKx); KEEP(oVx);
  KEEP(aOst); KEEP(aOld); KEEP(aVm); KEEP(aRSr); KEEP(mbRSr); KEEP(t8);
  mbar_wait(bar + 8 * MB_WO, 0);
#pragma unroll
  for (int ks = 0; ks < 4; ks++) { ldsm_x4_t(wo[2 * ks], pW0 + ks * 2048); ldsm_x4_t(wo[2 * ks + 1], pW1 + ks * 2048); }
  {
    unsigned v[8];
#pragma unroll
    for (int q = 0; q < 8; q++) v[q] = __ldg(reinterpret_cast<const unsigned*>(mem0) + q * 256 + t);
    sts128(sb + R_MEM + t * 32, make_uint4(__byte_perm(v[0], v[1], 0x5410), __byte_perm(v[2], v[3], 0x5410), __byte_perm(v[4], v[5], 0x5410), __byte_perm(v[6], v[7], 0x5410)));
    sts128(sb + R_MEM + t * 32 + 16, make_uint4(__byte_perm(v[0], v[1], 0x7632), __byte_perm(v[2], v[3], 0x7632), __byte_perm(v[4], v[5], 0x7632), __byte_perm(v[6], v[7], 0x7632)));
  }
  bar_sync(1, 256);

#pragma unroll 1
  for (int s = 0;; s++) {
    const unsigned par = s & 1;
    const unsigned slot = s & (RING_N - 1), rpar = (s / RING_N) & 1;
    const unsigned ring = sb + R_RING + slot * RING_BYTES;
    asm volatile("" : "+r"(t8));
    RSTAMP(1);
    RSTAMP(2);
    float aq[4] = {0, 0, 0, 0}, ak[4] = {0, 0, 0, 0}, av[4] = {0, 0, 0, 0};
    {
      unsigned b[8][4], f1[8][4], f0[8][4];
#define VLD(i) do { ldsm_x4_t(b[i], pA + (i) * 512); ldsm_x4_t(f0[i], pVk + ((i) >> 1) * 8192 + ((i) & 1) * 4096); ldsm_x4_t(f1[i], pVk + ((i) >> 1) * 8192 + ((i) & 1) * 4096 + 2048); } while (0)
      VLD(0);
      if (VD > 1) VLD(1);
#pragma unroll
      for (int i = 0; i < 8; i++) {
        if (i + VD < 8) VLD(i + VD);
        mma16816(aq, wq[2 * i], b[i][0], b[i][1]); mma16816(ak, wk[2 * i], b[i][0], b[i][1]); mma16816(av, f0[i], b[i][0], b[i][1]);
        mma16816(aq, wq[2 * i + 1], b[i][2], b[i][3]); mma16816(ak, wk[2 * i + 1], b[i][2], b[i][3]); mma16816(av, f1[i], b[i][2], b[i][3]);
      }
    }
    RSTAMP(3);
#define STSF4(a, v) asm volatile("st.shared.v4.f32 [%0], {%1,%2,%3,%4};" ::"r"(a), "f"(v[0]), "f"(v[1]), "f"(v[2]), "f"(v[3]) : "memory")
    unsigned f[8][4];
#define WO_PREFETCH() do { _Pragma("unroll") for (int i = 0; i < NPRE; i++) { ldsm_x4_t(f[2 * i], pW0 + 32768 + i * 2048); ldsm_x4_t(f[2 * i + 1], pW1 + 32768 + i * 2048); } } while (0)
    if (kh) {
      STSF4(aX, aq);
      bar_sync(4 + et, 64);
      uint4 o = lds128(aX + 2048), o2 = lds128(aX + 4096);
      stsm_x2_t(aQKst, pack_bf16(ak[0] + __uint_as_float(o.x), ak[1] + __uint_as_float(o.y)), pack_bf16(ak[2] + __uint_as_float(o.z), ak[3] + __uint_as_float(o.w)));
      bar_arrive(1, 256);
      unsigned x = pack_bf16(av[0] + __uint_as_float(o2.x), av[1] + __uint_as_float(o2.y)), y = pack_bf16(av[2] + __uint_as_float(o2.z), av[3] + __uint_as_float(o2.w));
      st_async_b64(aVr, x, y, mbVr);
      st_async_b64(aVl, x, y, mbVl);
      if (s == NSEG - 1) {
        mbar_wait(bar + 8 * MB_V, par);
        if (t == 128) mbar_arrive(bar + 8 * MB_KVR);
        break;
      }
      mbar_wait(bar + 8 * (MB_FULL + slot), rpar);
      unsigned vx[4][4];
      ldsm_x4_t(vx[0], ring + oVx); ldsm_x4_t(vx[1], ring + oVx + 2048); ldsm_x4_t(vx[2], ring + (oVx ^ 32)); ldsm_x4_t(vx[3], ring + (oVx ^ 32) + 2048);
      RSTAMP(4); RSTAMP(5); RSTAMP(6); RSTAMP(7);
      mbar_wait(bar + 8 * MB_S, par);
      RSTAMP(8);
      float sc[10];
#pragma unroll
      for (int i = 0; i < 5; i++) {
        uint2 o = lds64(aL8 + R_SOWN + i * 256), p = lds64(aL8 + R_SPEER + i * 256);
        sc[2 * i] = __uint_as_float(o.x) + __uint_as_float(p.x); sc[2 * i + 1] = __uint_as_float(o.y) + __uint_as_float(p.y);
      }
      mbar_wait(bar + 8 * MB_V, par);
      uint2 vm0 = lds64(aVm), vm1 = lds64(aVm + 256);
      float mx = fmaxf(fmaxf(fmaxf(sc[0], sc[1]), fmaxf(sc[2], sc[3])), fmaxf(fmaxf(fmaxf(sc[4], sc[5]), fmaxf(sc[6], sc[7])), fmaxf(sc[8], sc[9])));
      mx = fmaxf(mx, __shfl_xor_sync(~0u, mx, 1)); mx = fmaxf(mx, __shfl_xor_sync(~0u, mx, 2));
      const float nm = -mx * (SCALE_QK * LOG2E);
      unsigned p[5];
#pragma unroll
      for (int i = 0; i < 5; i++) p[i] = pack_bf16(ex2f(fmaf(sc[2 * i], SCALE_QK * LOG2E, nm)), ex2f(fmaf(sc[2 * i + 1], SCALE_QK * LOG2E, nm)));
      RSTAMP(9);
      float o0[4] = {0, 0, 0, 0}, o1[4] = {0, 0, 0, 0}, o3[4] = {0, 0, 0, 0}, o4[4] = {0, 0, 0, 0}, z0[4] = {0, 0, 0, 0}, z1[4] = {0, 0, 0, 0};
      const unsigned ones[4] = {0x3F803F80u, 0u, 0x3F803F80u, 0u};
      mma16816(z0, ones, p[0], p[1]); mma16816(z1, ones, p[2], p[3]);
      mma16816(o0, vx[0], p[0], p[1]); mma16816(o3, vx[2], p[0], p[1]);
      mma1688(z0, 0x3F803F80u, 0u, p[4]);
      mma16816(o1, vx[1], p[2], p[3]); mma16816(o4, vx[3], p[2], p[3]);
      mma1688(o0, vm0.x, vm0.y, p[4]); mma1688(o3, vm1.x, vm1.y, p[4]);
      float i0, i1;
      asm("rcp.approx.ftz.f32 %0, %1;" : "=f"(i0) : "f"(z0[0] + z1[0])); asm("rcp.approx.ftz.f32 %0, %1;" : "=f"(i1) : "f"(z0[1] + z1[1]));
      asm volatile("stmatrix.sync.aligned.m8n8.x4.trans.shared.b16 [%0], {%1,%2,%3,%4};" ::"r"(aOst), "r"(pack_bf16((o0[0] + o1[0]) * i0, (o0[1] + o1[1]) * i1)), "r"(pack_bf16((o0[2] + o1[2]) * i0, (o0[3] + o1[3]) * i1)),
                   "r"(pack_bf16((o3[0] + o4[0]) * i0, (o3[1] + o4[1]) * i1)), "r"(pack_bf16((o3[2] + o4[2]) * i0, (o3[3] + o4[3]) * i1)) : "memory");
      RSTAMP(10);
      bar_sync(1, 256);
      WO_PREFETCH();
    } else {
      STSF4(aX + 2048, ak); STSF4(aX + 4096, av);
      unsigned kb[8];
      mbar_wait(bar + 8 * (MB_FULL + slot), rpar);
      ldsm_x4(kb, ring + oKx); ldsm_x4(kb + 4, ring + (oKx ^ 64));
      bar_sync(4 + et, 64);
      uint4 o = lds128(aX);
      stsm_x2_t(aQKst, pack_bf16(aq[0] + __uint_as_float(o.x), aq[1] + __uint_as_float(o.y)), pack_bf16(aq[2] + __uint_as_float(o.z), aq[3] + __uint_as_float(o.w)));
      RSTAMP(4);
      bar_sync(1, 256);
      RSTAMP(5);
      if (s == NSEG - 1) break;
      unsigned qa[8], km[8];
      ldsm_x4(qa, aQ); ldsm_x4(qa + 4, aQ + 64);
      if (w == 3) { ldsm_x4(km, aQ + 1152); ldsm_x4(km + 4, aQ + 1152 + 64); }
      float s0[4] = {0, 0, 0, 0}, s1[4] = {0, 0, 0, 0};
      unsigned af[4][4];
#pragma unroll
      for (int i = 0; i < 4; i++) { af[i][0] = qa[2 * i]; af[i][1] = 0; af[i][2] = qa[2 * i + 1]; af[i][3] = 0; }
      mma16816(s0, af[0], kb[0], kb[1]); mma16816(s1, af[1], kb[2], kb[3]);
      mma16816(s0, af[2], kb[4], kb[5]); mma16816(s1, af[3], kb[6], kb[7]);
      if (w == 3) {
        float m0[4] = {0, 0, 0, 0}, m1[4] = {0, 0, 0, 0};
        mma16816(m0, af[0], km[0], km[1]); mma16816(m1, af[1], km[2], km[3]);
        mma16816(m0, af[2], km[4], km[5]); mma16816(m1, af[3], km[6], km[7]);
        unsigned x = __float_as_uint(m0[0] + m1[0]), y = __float_as_uint(m0[1] + m1[1]);
        st_async_b64(aSr + 256, x, y, mbSr); st_async_b64(aSl + 256, x, y, mbSl);
      }
      unsigned x = __float_as_uint(s0[0] + s1[0]), y = __float_as_uint(s0[1] + s1[1]);
      st_async_b64(aSr, x, y, mbSr); st_async_b64(aSl, x, y, mbSl);
      RSTAMP(6);
      WO_PREFETCH();
      RSTAMP(7); RSTAMP(8); RSTAMP(9); RSTAMP(10);
      bar_sync(1, 256);
    }
    RSTAMP(11);
    float d0[4] = {0, 0, 0, 0}, d1[4] = {0, 0, 0, 0}, e0[4] = {0, 0, 0, 0}, e1[4] = {0, 0, 0, 0};
    unsigned ob[4][4];
#pragma unroll
    for (int k2 = 0; k2 < 4; k2++) ldsm_x4(ob[k2], aOld + k2 * 64);
#pragma unroll
    for (int i = NPRE; i < 4; i++) { ldsm_x4_t(f[2 * i], pW0 + 32768 + i * 2048); ldsm_x4_t(f[2 * i + 1], pW1 + 32768 + i * 2048); }
    mma16816(d0, wo[0], ob[0][0], ob[0][1]); mma16816(d1, wo[1], ob[0][0], ob[0][1]);
    mma16816(e0, wo[2], ob[0][2], ob[0][3]); mma16816(e1, wo[3], ob[0][2], ob[0][3]);
    mma16816(d0, wo[4], ob[1][0], ob[1][1]); mma16816(d1, wo[5], ob[1][0], ob[1][1]);
    mma16816(e0, wo[6], ob[1][2], ob[1][3]); mma16816(e1, wo[7], ob[1][2], ob[1][3]);
    mma16816(d0, f[0], ob[2][0], ob[2][1]); mma16816(d1, f[1], ob[2][0], ob[2][1]);
    mma16816(e0, f[2], ob[2][2], ob[2][3]); mma16816(e1, f[3], ob[2][2], ob[2][3]);
    mma16816(d0, f[4], ob[3][0], ob[3][1]); mma16816(d1, f[5], ob[3][0], ob[3][1]);
    mma16816(e0, f[6], ob[3][2], ob[3][3]); mma16816(e1, f[7], ob[3][2], ob[3][3]);
    st_async_b64(aRSr, __float_as_uint(d0[0] + e0[0]), __float_as_uint(d0[1] + e0[1]), mbRSr);
    st_async_b64(aRSr + 256, __float_as_uint(d0[2] + e0[2]), __float_as_uint(d0[3] + e0[3]), mbRSr);
    st_async_b64(aRSr + 512, __float_as_uint(d1[0] + e1[0]), __float_as_uint(d1[1] + e1[1]), mbRSr);
    st_async_b64(aRSr + 768, __float_as_uint(d1[2] + e1[2]), __float_as_uint(d1[3] + e1[3]), mbRSr);
    RSTAMP(12);
    if (t == 128) {
      mbar_arrive(bar + 8 * (MB_EMPTY + slot)); mbar_arrive(bar + 8 * MB_KVR);
      mbar_expect_tx(bar + 8 * MB_S, 2560); mbar_expect_tx(bar + 8 * MB_V, 2048);
    }
    const unsigned tag = ((s >> 1) & 1) ^ 1;
    const char* gp = reinterpret_cast<const char*>(g_part);
    const unsigned goff = (par * 8 + rk) * 16384 + cl * 2048 + t8;
    unsigned mbA[8];
#pragma unroll
    for (int i = 0; i < 8; i++) mbA[i] = mapa(bar + 8 * MB_AG, i);
    const unsigned dlt = (R_MEM + rk * 1024) - (SM_BAR + 8 * MB_AG) + (t8 >> 1);
    mbar_wait(bar + 8 * MB_RS, par);
    RSTAMP(13);
    uint2 a[8];
    {
      uint2 x0 = lds64(sb + R_RS + t8), x1 = lds64(sb + R_RS + 2048 + t8), x2 = lds64(sb + R_RS + 4096 + t8), x3 = lds64(sb + R_RS + 6144 + t8);
      float r0 = (__uint_as_float(x0.x) + __uint_as_float(x1.x)) + (__uint_as_float(x2.x) + __uint_as_float(x3.x));
      float r1 = (__uint_as_float(x0.y) + __uint_as_float(x1.y)) + (__uint_as_float(x2.y) + __uint_as_float(x3.y));
      a[0].x = (__float_as_uint(r0) & ~1u) | tag; a[0].y = (__float_as_uint(r1) & ~1u) | tag;
      asm volatile("st.relaxed.gpu.global.v2.u32 [%0], {%1,%2};" ::"l"(gp + goff), "r"(a[0].x), "r"(a[0].y) : "memory");
    }
    RSTAMP(14);
    if (t == 128) mbar_expect_tx(bar + 8 * MB_RS, 8192);
    {
      unsigned it = 0;
#define PLOAD(a) _Pragma("unroll") for (int i = 1; i < 8; i++) a[i] = ldv2_relaxed(gp + (goff ^ (i * 2048)))
#define PAND(a) (((a[1].x & a[1].y) & (a[2].x & a[2].y) & (a[3].x & a[3].y)) & ((a[4].x & a[4].y) & (a[5].x & a[5].y)) & ((a[6].x & a[6].y) & (a[7].x & a[7].y)))
#define POR(a) (((a[1].x | a[1].y) | (a[2].x | a[2].y) | (a[3].x | a[3].y)) | ((a[4].x | a[4].y) | (a[5].x | a[5].y)) | ((a[6].x | a[6].y) | (a[7].x | a[7].y)))
#define POK(a) (((tag ? PAND(a) : ~POR(a)) & 1u) != 0)
      if (D_RED) DELAY(D_RED);
      PLOAD(a);
      while (!POK(a)) {
#pragma unroll
        for (int i = 1; i < 8; i++) if (((a[i].x ^ tag) | (a[i].y ^ tag)) & 1u) a[i] = ldv2_relaxed(gp + (goff ^ (i * 2048)));
        spin_check(it);
      }
    }
    RSTAMP(15);
    {
#define AF(i, c) __uint_as_float(a[i].c)
      unsigned u = pack_bf16(((AF(0, x) + AF(1, x)) + (AF(2, x) + AF(3, x))) + ((AF(4, x) + AF(5, x)) + (AF(6, x) + AF(7, x))),
                             ((AF(0, y) + AF(1, y)) + (AF(2, y) + AF(3, y))) + ((AF(4, y) + AF(5, y)) + (AF(6, y) + AF(7, y))));
      __syncwarp();
#pragma unroll
      for (int i = 0; i < 8; i++) st_async_b32(mbA[i] + dlt, u, mbA[i]);
    }
    mbar_wait(bar + 8 * MB_KVF, par);
    mbar_wait(bar + 8 * MB_AG, par);
    if (t == 128) mbar_expect_tx(bar + 8 * MB_AG, 8192);
  }
}

__device__ __forceinline__ void rec_ring(const Maps& maps, unsigned sb, const int c) {
  const int h = c >> 1, j = c & 1;
  const unsigned bar = sb + SM_BAR;
  const int lane = threadIdx.x & 31;
  __syncwarp();
  bar_sync(2, 288);
  if (lane == 0) {
    fence_proxy_async_smem();
    for (int s = 0; s < NSEG; s++) {
      unsigned slot = s & (RING_N - 1);
      if ((s & 3) == 0 && !DBGMODE) {
        wait_flag_ge(&g_flags.qkv[(s >> 2) * 48 + 16 + (h >> 1)], 2);
        wait_flag_ge(&g_flags.qkv[(s >> 2) * 48 + 32 + (h >> 1)], 2);
        fence_proxy_async();
      }
      if (s >= RING_N) mbar_wait_sleep(bar + 8 * (MB_EMPTY + slot), ((s / RING_N) - 1) & 1);
      unsigned dst = sb + R_RING + slot * RING_BYTES, mb = bar + 8 * (MB_FULL + slot);
      mbar_expect_tx(mb, RING_BYTES);
      tma_load_2d(dst, &maps.qkv_ld, HD + h * 128 + j * 64, s * SEG, mb);
      tma_load_2d(dst + 4096, &maps.qkv_ld, 2 * HD + h * 128, s * SEG, mb);
      tma_load_2d(dst + 8192, &maps.qkv_ld, 2 * HD + h * 128 + 64, s * SEG, mb);
    }
  }
}
__device__ __forceinline__ void rec_copy(unsigned sb, const int c) {
  const int h = c >> 1, j = c & 1;
  const unsigned bar = sb + SM_BAR;
  const int lane = threadIdx.x & 31;
  for (int s = 0; s < NSEG; s++) {
    if (s < NSEG - 1) mbar_wait_sleep(bar + 8 * MB_KVR, s & 1); else mbar_wait(bar + 8 * MB_KVR, s & 1);
    uint4 k0 = lds128(sb + R_KS + (lane >> 3) * 144 + (lane & 7) * 16), k1 = lds128(sb + R_KS + (4 + (lane >> 3)) * 144 + (lane & 7) * 16);
    uint2 v[4];
#pragma unroll
    for (int i = 0; i < 4; i++) v[i] = lds64(sb + R_VM + (j * 4 + i) * 256 + lane * 8);
    __syncwarp();
    if (lane == 0) mbar_arrive(bar + 8 * MB_KVF);
    bf16* kd = g_km + ((size_t)(s * NH + h) * NMEM) * DH + j * 64;
    *reinterpret_cast<uint4*>(kd + (lane >> 3) * DH + (lane & 7) * 8) = k0;
    *reinterpret_cast<uint4*>(kd + (4 + (lane >> 3)) * DH + (lane & 7) * 8) = k1;
    unsigned* vd = reinterpret_cast<unsigned*>(g_vmt) + ((size_t)(s * NH + h) * DH + j * 64) * 4;
#pragma unroll
    for (int i = 0; i < 4; i++) { vd[(i * 16) * 4 + lane] = v[i].x; vd[(i * 16 + 8) * 4 + lane] = v[i].y; }
    __syncwarp();
    if (lane == 0) st_release(&g_flags.rec[c], s + 1);
  }
}

__device__ __forceinline__ void bulk_producer(const Maps& maps, unsigned sb, int* misc) {
  const unsigned bar = sb + SM_BAR;
  const int lane = threadIdx.x & 31;
  unsigned st = 0, ph = 0, seq = 0;
  while (true) {
    int idx = 0;
    if (lane == 0) idx = (int)atomicAdd(&g_flags.ctr, 1u);
    idx = __shfl_sync(~0u, idx, 0);
    if (idx >= N_ITEMS) {
      if (lane == 0) {
        mbar_wait(bar + 8 * (MB_EMPTY + st), ph ^ 1);
        misc[seq & 3] = -1;
        mbar_arrive(bar + 8 * (MB_FULL + st));
      }
      break;
    }
    if (lane == 0) ISTAMP(idx, 0);
    Item it = decode_item(idx);
    if (it.b < 0) continue;
    const CUtensorMap* mp; int c0, c1, dc0, dc1; unsigned doff;
    const unsigned* fl = nullptr; unsigned tgt = 1; int nbox = 5, rdy = 0;
    if (it.type == T_ATT) {
      mp = &maps.qkv_ld; nbox = 12; doff = lane * 4096;
      c0 = (lane >> 2) * HD + it.c * 256 + (lane & 1) * 64; c1 = it.b * 128 + ((lane >> 1) & 1) * 32; dc0 = dc1 = 0;
      if (lane < 3) fl = &g_flags.qkv[it.b * 48 + lane * 16 + it.c];
      tgt = 2;
      bool ok = true;
      if (lane >= 4 && lane < 8) ok = ld_acquire(&g_flags.rec[it.c * 4 + lane - 4]) >= (unsigned)(it.b * 4 + 4);
      rdy = __all_sync(~0u, ok) ? 65536 : 0;
    } else {
      int k0 = 0, nb0 = it.c * 256;
      if (it.type == T_QKV) { mp = lane == 0 ? &maps.xn : (it.c < 16 ? &maps.wq : (it.c < 32 ? &maps.wk : &maps.wv)); nb0 = (it.c & 15) * 256; }
      else if (it.type == T_M1) mp = lane == 0 ? &maps.y : &maps.w1;
      else if (it.type == T_M2) { mp = lane == 0 ? &maps.h1 : &maps.w2; fl = &g_flags.h1[it.b]; tgt = 7; }
      else {
        mp = lane == 0 ? &maps.o : &maps.wo;
        if (it.type == T_OUT) { k0 = it.ks * 1024; fl = &g_flags.o[it.b * 4 + it.ks]; tgt = 4; }
        else if (it.type == T_OUTL) { k0 = it.ks * 256; fl = &g_flags.o16[it.ks]; }
        else if (lane == 1) { fl = &g_flags.g[it.b]; tgt = 2; }
        else { fl = &g_flags.p[it.b]; tgt = it.type == T_RED ? 8 : 64; }
      }
      if (lane > (it.type >= T_RED ? 1 : 0)) fl = nullptr;
      if (it.hf) { nbox = 3; nb0 += (it.hf - 1) * 128; }
      if (lane == 0) { c0 = k0; c1 = it.b * 128; dc0 = 64; dc1 = 0; doff = 0; }
      else { c0 = nb0 + (lane - 1) * 64; c1 = k0; dc0 = 0; dc1 = 64; doff = 8192 + lane * 8192; }
    }
    if (fl) wait_flag_ge(fl, tgt);
    __syncwarp();
    fence_proxy_async();
    if (lane == 0) ISTAMP(idx, 1);
    const int nkb = item_nkb(it.type);
    for (int kb = 0; kb < nkb; kb++) {
      const unsigned mb = bar + 8 * (MB_FULL + st);
      mbar_wait(bar + 8 * (MB_EMPTY + st), ph ^ 1);
      if (lane == 0) {
        if (kb == 0) misc[seq & 3] = idx | rdy;
        if (it.type >= T_RED) mbar_arrive(mb); else mbar_expect_tx(mb, it.hf ? 32768 : STAGE_BYTES);
      }
      if (it.type == T_ATT) { if (lane < 12) tma_load_2d(sb + st * STAGE_BYTES + doff, mp, c0 + (kb & 1) * 128, c1 + (kb >> 1) * 64, mb); }
      else if (lane < nbox && it.type < T_RED) tma_load_2d(sb + st * STAGE_BYTES + doff, mp, c0 + kb * dc0, c1 + kb * dc1, mb);
      __syncwarp();
      if (++st == NSTAGE) { st = 0; ph ^= 1; }
    }
    seq++;
  }
}
__device__ __forceinline__ void bulk_store(const Maps& maps, unsigned sb, volatile int* misc) {
  const unsigned bar = sb + SM_BAR;
  unsigned ph = 0;
  while (true) {
    mbar_wait(bar + 8 * MB_STGF, ph); ph ^= 1;
    int idx = misc[4];
    if (idx < 0) break;
    Item it = decode_item(idx);
    const CUtensorMap* mp = it.type == T_QKV ? &maps.qkv_st : (it.type == T_M1 ? &maps.h1 : (it.type == T_M2 ? &maps.g : &maps.o));
    unsigned* flag = it.type == T_QKV ? &g_flags.qkv[it.b * 48 + it.c] : (it.type == T_M1 ? &g_flags.h1[it.b] : (it.type == T_M2 ? &g_flags.g[it.b] : (it.b == 15 ? &g_flags.o16[it.c] : &g_flags.o[it.b * 4 + (it.c >> 2)])));
    for (int i = 0; i < (it.hf ? 2 : 4); i++) tma_store_2d(mp, sb + B_STG + i * 16384, it.c * 256 + (it.hf >> 1) * 128 + i * 64, it.b * 128);
    asm volatile("cp.async.bulk.commit_group;" ::: "memory");
    asm volatile("cp.async.bulk.wait_group.read 0;" ::: "memory");
    mbar_arrive(bar + 8 * MB_STGE);
    asm volatile("cp.async.bulk.wait_group 0;" ::: "memory");
    fence_proxy_async();
    red_release_add(flag, it.type == T_QKV && !it.hf ? 2 : 1);
    ISTAMP(idx, 3);
  }
}
__device__ __forceinline__ float rcpf(float x) { float y; asm("rcp.approx.ftz.f32 %0, %1;" : "=f"(y) : "f"(x)); return y; }
__device__ __forceinline__ float gelu_t(float x) {
  float e = ex2f(x * fmaf(x * x, -2.0f * LOG2E * 0.7978845608028654f * 0.044715f, -2.0f * LOG2E * 0.7978845608028654f));
  return x * rcpf(1.0f + e);
}
__device__ __forceinline__ float silu_f(float x) { return x * rcpf(1.0f + ex2f(-LOG2E * x)); }
__device__ __forceinline__ unsigned badd2(unsigned a, unsigned b) { unsigned r; asm("add.rn.bf16x2 %0, %1, %2;" : "=r"(r) : "r"(a), "r"(b)); return r; }

__device__ __forceinline__ void final_out(bf16* __restrict__ out, const bf16* __restrict__ x, size_t o, float4 s) {
  uint2 gv = __ldcg(reinterpret_cast<const uint2*>(g_g + o)), xv = __ldg(reinterpret_cast<const uint2*>(x + o));
  uint2 r;
  r.x = pack_bf16(bf_lo(xv.x) + bf16r(bf16r(s.x) * bf_lo(gv.x)), bf_hi(xv.x) + bf16r(bf16r(s.y) * bf_hi(gv.x)));
  r.y = pack_bf16(bf_lo(xv.y) + bf16r(bf16r(s.z) * bf_lo(gv.y)), bf_hi(xv.y) + bf16r(bf16r(s.w) * bf_hi(gv.y)));
  *reinterpret_cast<uint2*>(out + o) = r;
}
__device__ __forceinline__ void bulk_att_load(unsigned* km, unsigned* vm, int b, int hp, int kb, int w, int lane) {
  const int g = lane >> 2, tq = lane & 3, seg = w >> 2, eh = w & 1;
  const int head = hp * 2 + (kb & 1), sg = b * 4 + (kb >> 1) * 2 + seg;
  const unsigned* kmp = reinterpret_cast<const unsigned*>(g_km + ((size_t)(sg * NH + head) * NMEM + g) * DH) + tq;
  const unsigned* vmp = reinterpret_cast<const unsigned*>(g_vmt) + ((size_t)(sg * NH + head) * DH + eh * 64) * 4 + lane;
#pragma unroll
  for (int i = 0; i < 16; i++) asm volatile("ld.global.cg.u32 %0, [%1];" : "=r"(km[i]) : "l"(kmp + i * 4) : "memory");
#pragma unroll
  for (int i = 0; i < 8; i++) asm volatile("ld.global.cg.u32 %0, [%1];" : "=r"(vm[i]) : "l"(vmp + i * 32) : "memory");
}
__device__ __forceinline__ void bulk_att_stage(unsigned sa, unsigned stg, const unsigned* km, const unsigned* vm, int kb, int w, int lane) {
  const int g = lane >> 2, tq = lane & 3, m = lane >> 3, r8 = lane & 7;
  const int seg = w >> 2, mt = (w >> 1) & 1, eh = w & 1;
  float s[5][4];
#pragma unroll
  for (int i = 0; i < 5; i++) { s[i][0] = s[i][1] = s[i][2] = s[i][3] = 0; }
  const unsigned qb = sa + (0 * 2 + seg) * 8192, kbs = sa + (1 * 2 + seg) * 8192, vb = sa + (2 * 2 + seg) * 8192 + eh * 4096;
  unsigned qa[8][4];
#pragma unroll
  for (int ks = 0; ks < 8; ks++) {
    int row = mt * 16 + (m & 1) * 8 + r8;
    ldsm_x4(qa[ks], qb + (ks >> 2) * 4096 + row * 128 + ((((ks & 3) * 2 + (m >> 1)) ^ r8) << 4));
    unsigned kf[4];
    int krow = (m >> 1) * 8 + r8;
    unsigned ka = kbs + (ks >> 2) * 4096 + krow * 128 + ((((ks & 3) * 2 + (m & 1)) ^ r8) << 4);
    ldsm_x4(kf, ka);
    mma16816(s[0], qa[ks], kf[0], kf[1]); mma16816(s[1], qa[ks], kf[2], kf[3]);
    if (mt) { ldsm_x4(kf, ka + 2048); mma16816(s[2], qa[ks], kf[0], kf[1]); mma16816(s[3], qa[ks], kf[2], kf[3]); }
  }
#pragma unroll
  for (int ks = 0; ks < 8; ks++) mma16816(s[4], qa[ks], km[2 * ks], km[2 * ks + 1]);
  float mx0 = -INFINITY, mx1 = -INFINITY;
  const int t0 = mt * 16 + g, t1 = t0 + 8;
#pragma unroll
  for (int i = 0; i < 5; i++) {
#pragma unroll
    for (int e = 0; e < 4; e++) {
      float v = s[i][e];
      if (i < 4) { int kj = i * 8 + 2 * tq + (e & 1); if (kj > (e < 2 ? t0 : t1)) v = -INFINITY; }
      s[i][e] = v;
      if (e < 2) mx0 = fmaxf(mx0, v); else mx1 = fmaxf(mx1, v);
    }
  }
  mx0 = fmaxf(mx0, __shfl_xor_sync(~0u, mx0, 1)); mx0 = fmaxf(mx0, __shfl_xor_sync(~0u, mx0, 2));
  mx1 = fmaxf(mx1, __shfl_xor_sync(~0u, mx1, 1)); mx1 = fmaxf(mx1, __shfl_xor_sync(~0u, mx1, 2));
  float sm0 = 0, sm1 = 0;
#pragma unroll
  for (int i = 0; i < 5; i++) {
    s[i][0] = ex2f((s[i][0] - mx0) * (SCALE_QK * LOG2E)); s[i][1] = ex2f((s[i][1] - mx0) * (SCALE_QK * LOG2E));
    s[i][2] = ex2f((s[i][2] - mx1) * (SCALE_QK * LOG2E)); s[i][3] = ex2f((s[i][3] - mx1) * (SCALE_QK * LOG2E));
    sm0 += s[i][0] + s[i][1]; sm1 += s[i][2] + s[i][3];
  }
  sm0 += __shfl_xor_sync(~0u, sm0, 1); sm0 += __shfl_xor_sync(~0u, sm0, 2);
  sm1 += __shfl_xor_sync(~0u, sm1, 1); sm1 += __shfl_xor_sync(~0u, sm1, 2);
  const float i0 = __fdividef(1.0f, sm0), i1 = __fdividef(1.0f, sm1);
  unsigned pa[2][4], pm0, pm1;
#pragma unroll
  for (int kk = 0; kk < 2; kk++) {
    pa[kk][0] = pack_bf16(s[2 * kk][0] * i0, s[2 * kk][1] * i0); pa[kk][1] = pack_bf16(s[2 * kk][2] * i1, s[2 * kk][3] * i1);
    pa[kk][2] = pack_bf16(s[2 * kk + 1][0] * i0, s[2 * kk + 1][1] * i0); pa[kk][3] = pack_bf16(s[2 * kk + 1][2] * i1, s[2 * kk + 1][3] * i1);
  }
  pm0 = pack_bf16(s[4][0] * i0, s[4][1] * i0); pm1 = pack_bf16(s[4][2] * i1, s[4][3] * i1);
  const int orow = (kb >> 1) * 64 + seg * 32 + mt * 16 + (m & 1) * 8 + r8;
  const unsigned ob = stg + ((kb & 1) * 2 + eh) * 16384 + orow * 128;
#pragma unroll
  for (int cp = 0; cp < 4; cp++) {
    float o0[4] = {0, 0, 0, 0}, o1[4] = {0, 0, 0, 0};
    mma1688(o0, pm0, pm1, vm[2 * cp]); mma1688(o1, pm0, pm1, vm[2 * cp + 1]);
    unsigned vf[4];
    int row = (m & 1) * 8 + r8;
    unsigned va = vb + row * 128 + (((cp * 2 + (m >> 1)) ^ r8) << 4);
    ldsm_x4_t(vf, va);
    mma16816(o0, pa[0], vf[0], vf[1]); mma16816(o1, pa[0], vf[2], vf[3]);
    if (mt) { ldsm_x4_t(vf, va + 2048); mma16816(o0, pa[1], vf[0], vf[1]); mma16816(o1, pa[1], vf[2], vf[3]); }
    stsm_x4(ob + (((cp * 2 + (m >> 1)) ^ r8) << 4), pack_bf16(o0[0], o0[1]), pack_bf16(o0[2], o0[3]), pack_bf16(o1[0], o1[1]), pack_bf16(o1[2], o1[3]));
  }
}

__device__ __forceinline__ void bulk_worker(unsigned sb, volatile int* misc, const bf16* __restrict__ x, const bf16* __restrict__ b1, const bf16* __restrict__ b2, bf16* __restrict__ out) {
  const int t = threadIdx.x, lane = t & 31, w = t >> 5, wg = w >> 2, g = lane >> 2, tq = lane & 3, m = lane >> 3, r8 = lane & 7;
  const unsigned bar = sb + SM_BAR;
  unsigned st = 0, ph = 0, seq = 0, sph = 0;
  float d[128];
  while (true) {
    mbar_wait(bar + 8 * (MB_FULL + st), ph);
    const int idr = misc[seq & 3]; seq++;
    const int idx = idr & 65535;
    if (idr < 0 || idx >= N_ITEMS) break;
    if (t == 0) ISTAMP(idx, 2);
    const Item it = decode_item(idx);
    const int nkb = item_nkb(it.type);
    if (it.type == T_ATT) {
      unsigned km[16], vm[8], kn[16], vn[8];
      const bool pref = idr >= 65536;
      if (pref) bulk_att_load(kn, vn, it.b, it.c, 0, w, lane);
      mbar_wait(bar + 8 * MB_STGE, sph ^ 1);
#pragma unroll 1
      for (int kb = 0; kb < 4; kb++) {
        if (!pref && !(kb & 1)) {
          if (lane < 4) wait_flag_ge(&g_flags.rec[it.c * 4 + lane], it.b * 4 + (kb >> 1) * 2 + wg + 1);
          __syncwarp();
          bulk_att_load(kn, vn, it.b, it.c, kb, w, lane);
        }
        if (kb) mbar_wait(bar + 8 * (MB_FULL + st), ph);
#pragma unroll
        for (int i = 0; i < 16; i++) km[i] = kn[i];
#pragma unroll
        for (int i = 0; i < 8; i++) vm[i] = vn[i];
        if (pref ? kb != 3 : !(kb & 1)) bulk_att_load(kn, vn, it.b, it.c, kb + 1, w, lane);
        bulk_att_stage(sb + st * STAGE_BYTES, sb + B_STG, km, vm, kb, w, lane);
        __syncwarp();
        if (lane == 0) mbar_arrive(bar + 8 * (MB_EMPTY + st));
        if (++st == NSTAGE) { st = 0; ph ^= 1; }
      }
      if (t == 0) misc[4] = idx;
      fence_proxy_async_smem();
      mbar_arrive(bar + 8 * MB_STGF); sph ^= 1;
      continue;
    }
    if (it.type >= T_RED) {
      __syncwarp();
      if (lane == 0) mbar_arrive(bar + 8 * (MB_EMPTY + st));
      if (++st == NSTAGE) { st = 0; ph ^= 1; }
      if (it.type == T_RED) {
#pragma unroll 2
        for (int i = 0; i < 8; i++) {
          size_t o = ((size_t)it.b * 128 + it.c * 16 + i * 2 + (t >> 7)) * DM + (t & 127) * 4;
          float4 a = __ldcg(reinterpret_cast<const float4*>(g_opart + o)), b = __ldcg(reinterpret_cast<const float4*>(g_opart + o + (size_t)S_TOK * DM));
          float4 c = __ldcg(reinterpret_cast<const float4*>(g_opart + o + (size_t)2 * S_TOK * DM)), e = __ldcg(reinterpret_cast<const float4*>(g_opart + o + (size_t)3 * S_TOK * DM));
          final_out(out, x, o, make_float4((a.x + b.x) + (c.x + e.x), (a.y + b.y) + (c.y + e.y), (a.z + b.z) + (c.z + e.z), (a.w + b.w) + (c.w + e.w)));
        }
      } else {
        size_t ol = ((size_t)it.c * 2 + (t >> 7)) * DM + (t & 127) * 4;
        float4 v[16];
#pragma unroll
        for (int i = 0; i < 16; i++) v[i] = __ldcg(reinterpret_cast<const float4*>(g_opl + ol + (size_t)i * 128 * DM));
#pragma unroll
        for (int st2 = 1; st2 < 16; st2 <<= 1)
#pragma unroll
          for (int i = 0; i < 16; i += 2 * st2) { v[i].x += v[i + st2].x; v[i].y += v[i + st2].y; v[i].z += v[i + st2].z; v[i].w += v[i + st2].w; }
        final_out(out, x, ol + (size_t)15 * 128 * DM, v[0]);
      }
      if (t == 0) ISTAMP(idx, 3);
      continue;
    }
    unsigned pst = 0, bv[32];
#pragma unroll
    for (int i = 0; i < 128; i++) d[i] = 0.0f;
    if (it.type == T_M1 || it.type == T_M2) {
      const unsigned* bp = reinterpret_cast<const unsigned*>((it.type == T_M1 ? b1 : b2) + it.c * 256) + tq;
#pragma unroll
      for (int i = 0; i < 32; i++) asm volatile("ld.global.nc.u32 %0, [%1];" : "=r"(bv[i]) : "l"(bp + i * 4));
    } else {
#pragma unroll
      for (int i = 0; i < 32; i++) bv[i] = 0;
    }
    for (int kb = 0; kb < nkb; kb++) {
      if (kb) mbar_wait(bar + 8 * (MB_FULL + st), ph);
      unsigned sa = sb + st * STAGE_BYTES;
      uint64_t ad = mkdesc(sa + wg * 8192, 16, 1024), bd = mkdesc(sa + 16384, 8192, 1024);
      asm volatile("wgmma.fence.sync.aligned;" ::: "memory");
      if (it.hf) {
#pragma unroll
        for (int k = 0; k < 4; k++) wgmma_n128(d, ad + k * 2, bd + k * 128, (kb | k) != 0);
      } else {
#pragma unroll
        for (int k = 0; k < 4; k++) wgmma_n256(d, ad + k * 2, bd + k * 128, (kb | k) != 0);
      }
      asm volatile("wgmma.commit_group.sync.aligned;" ::: "memory");
      if (kb) {
        asm volatile("wgmma.wait_group.sync.aligned 1;" ::: "memory");
        if (lane == 0) mbar_arrive(bar + 8 * (MB_EMPTY + pst));
      }
      pst = st;
      if (++st == NSTAGE) { st = 0; ph ^= 1; }
    }
    asm volatile("wgmma.wait_group.sync.aligned 0;" ::: "memory");
    if (lane == 0) mbar_arrive(bar + 8 * (MB_EMPTY + pst));
    if (it.type >= T_OUT) {
      const int col = it.c * 256 + (it.hf >> 1) * 128 + 2 * tq;
      float* pp = it.type == T_OUT ? g_opart + ((size_t)it.ks * S_TOK + it.b * 128 + w * 16 + g) * DM + col : g_opl + ((size_t)it.ks * 128 + w * 16 + g) * DM + col;
#pragma unroll
      for (int i = 0; i < 32; i++) {
        if (i == 16 && it.hf) break;
        __stcg(reinterpret_cast<float2*>(pp + i * 8), make_float2(d[4 * i], d[4 * i + 1]));
        __stcg(reinterpret_cast<float2*>(pp + 8 * DM + i * 8), make_float2(d[4 * i + 2], d[4 * i + 3]));
      }
      bar_sync(1, 256);
      if (t == 0) { red_release_add(&g_flags.p[it.b], 1); ISTAMP(idx, 3); }
      continue;
    }
#define ACT(F) _Pragma("unroll") for (int i = 0; i < 32; i++) { \
        unsigned u0 = badd2(pack_bf16(d[4 * i], d[4 * i + 1]), bv[i]), u1 = badd2(pack_bf16(d[4 * i + 2], d[4 * i + 3]), bv[i]); \
        d[4 * i] = F(bf_lo(u0)); d[4 * i + 1] = F(bf_hi(u0)); d[4 * i + 2] = F(bf_lo(u1)); d[4 * i + 3] = F(bf_hi(u1)); }
    if (it.type == T_M1) { ACT(gelu_t) } else if (it.type == T_M2) { ACT(silu_f) }
    mbar_wait(bar + 8 * MB_STGE, sph ^ 1);
    {
      const unsigned ob = sb + B_STG + (w * 16 + (m & 1) * 8 + r8) * 128;
#pragma unroll
      for (int i = 0; i < 16; i++)
        if (i < 8 || !it.hf) stsm_x4(ob + (i >> 2) * 16384 + ((((i & 3) * 2 + (m >> 1)) ^ r8) << 4), pack_bf16(d[8 * i], d[8 * i + 1]), pack_bf16(d[8 * i + 2], d[8 * i + 3]),
                pack_bf16(d[8 * i + 4], d[8 * i + 5]), pack_bf16(d[8 * i + 6], d[8 * i + 7]));
    }
    if (t == 0) misc[4] = idx;
    fence_proxy_async_smem();
    mbar_arrive(bar + 8 * MB_STGF); sph ^= 1;
  }
  mbar_wait(bar + 8 * MB_STGE, sph ^ 1);
  if (t == 0) misc[4] = -1;
  mbar_arrive(bar + 8 * MB_STGF);
}

__global__ void __launch_bounds__(384, 1)
k_main(const __grid_constant__ Maps maps, const bf16* __restrict__ x, const bf16* __restrict__ mem0, const bf16* __restrict__ b1, const bf16* __restrict__ b2, bf16* __restrict__ out, unsigned recmask) {
  extern __shared__ unsigned char smem_raw[];
  const unsigned sraw = smem_u32(smem_raw);
  const unsigned sb = (sraw + 1023u) & ~1023u;
  int* misc = reinterpret_cast<int*>(smem_raw + (sb - sraw) + SM_MISC);
  const int w = threadIdx.x >> 5;
  const bool helper = recmask == 0;
  const unsigned kc = blockIdx.x / CLS;
  const bool rec = kc < 32 && ((recmask >> kc) & 1);
  const int c = __popc(recmask & ((1u << (kc & 31)) - 1)) * CLS + (blockIdx.x & (CLS - 1));
  if (threadIdx.x == 0) {
    const unsigned bar = sb + SM_BAR;
    for (int i = 0; i < 8; i++) { mbar_init(bar + 8 * (MB_FULL + i), 1); mbar_init(bar + 8 * (MB_EMPTY + i), rec ? 1 : 8); }
    mbar_init(bar + 8 * MB_STGF, 256); mbar_init(bar + 8 * MB_STGE, 1);
    for (int i = MB_W0; i <= MB_AG; i++) mbar_init(bar + 8 * i, 1);
    if (rec) { mbar_expect_tx(bar + 8 * MB_S, 2560); mbar_expect_tx(bar + 8 * MB_V, 2048); mbar_expect_tx(bar + 8 * MB_RS, 8192); mbar_expect_tx(bar + 8 * MB_AG, 8192); }
    asm volatile("fence.mbarrier_init.release.cluster;" ::: "memory");
  }
  __syncthreads();
  asm volatile("barrier.cluster.arrive.release.aligned;\nbarrier.cluster.wait.acquire.aligned;" ::: "memory");
  if (rec && threadIdx.x == 256) {
    const unsigned bar = sb + SM_BAR; const int col = c * 64;
    mbar_expect_tx(bar + 8 * MB_W0, 131072);
    for (int kb = 0; kb < 8; kb++) tma_load_2d(sb + R_WO + kb * 8192, &maps.wq, col, kb * 64, bar + 8 * MB_W0);
    for (int kb = 0; kb < 8; kb++) tma_load_2d(sb + R_T1 + kb * 8192, &maps.wk, col, kb * 64, bar + 8 * MB_W0);
    mbar_expect_tx(bar + 8 * MB_W1, 65536);
    for (int kb = 0; kb < 8; kb++) tma_load_2d(sb + R_T2 + kb * 8192, &maps.wv, col, kb * 64, bar + 8 * MB_W1);
  }
  if (!helper) {
    asm volatile("griddepcontrol.wait;" ::: "memory");
    asm volatile("griddepcontrol.launch_dependents;");
  }
  if (DBGMODE && !rec) { if (helper) asm volatile("griddepcontrol.wait;" ::: "memory"); return; }
  if (w >= 8) {
    asm volatile("setmaxnreg.dec.sync.aligned.u32 24;");
    if (rec) { if (w == 8) rec_ring(maps, sb, c); else if (w == 9) rec_copy(sb, c); }
    else if (w == 8) bulk_producer(maps, sb, misc);
    else if ((threadIdx.x & 31) == 0) { if (w == 9) bulk_store(maps, sb, misc);
      else if (w == 10 && helper) asm volatile("griddepcontrol.wait;" ::: "memory"); }
  } else {
    if (rec) { asm volatile("setmaxnreg.inc.sync.aligned.u32 240;"); rec_worker(maps, sb, mem0, c); }
    else { asm volatile("setmaxnreg.inc.sync.aligned.u32 240;"); bulk_worker(sb, misc, x, b1, b2, out); }
  }
}

typedef CUresult (*EncFn)(CUtensorMap*, CUtensorMapDataType, cuuint32_t, void*, const cuuint64_t*, const cuuint64_t*, const cuuint32_t*, const cuuint32_t*,
                          CUtensorMapInterleave, CUtensorMapSwizzle, CUtensorMapL2promotion, CUtensorMapFloatOOBfill);
static void mk_map(EncFn enc, CUtensorMap* m, const void* ptr, uint64_t rows, uint64_t cols, uint32_t box_rows) {
  cuuint64_t dims[2] = {cols, rows}; cuuint64_t strides[1] = {cols * 2};
  cuuint32_t box[2] = {64, box_rows}, es[2] = {1, 1};
  enc(m, CU_TENSOR_MAP_DATA_TYPE_BFLOAT16, 2, const_cast<void*>(ptr), dims, strides, box, es, CU_TENSOR_MAP_INTERLEAVE_NONE, CU_TENSOR_MAP_SWIZZLE_128B,
      CU_TENSOR_MAP_L2_PROMOTION_L2_256B, CU_TENSOR_MAP_FLOAT_OOB_FILL_NONE);
}
extern "C" void kernel_launch(void* const* d_in, const int* in_sizes, int n_in, void* d_out, int out_size) {
  static EncFn enc = nullptr;
  static int ncl = 0, nhelp = 0;
  static unsigned recmask = 0xFFu;
  static void *p_xn, *p_y, *p_h1, *p_o, *p_qkv, *p_g;
  if (!enc) {
    void* fn = nullptr; cudaDriverEntryPointQueryResult qr;
    cudaGetDriverEntryPoint("cuTensorMapEncodeTiled", &fn, cudaEnableDefault, &qr);
    enc = (EncFn)fn;
    cudaGetSymbolAddress(&p_xn, g_xn); cudaGetSymbolAddress(&p_y, g_y); cudaGetSymbolAddress(&p_h1, g_h1);
    cudaGetSymbolAddress(&p_o, g_o); cudaGetSymbolAddress(&p_qkv, g_qkv); cudaGetSymbolAddress(&p_g, g_g);
    cudaFuncSetAttribute(k_main, cudaFuncAttributeMaxDynamicSharedMemorySize, SMEM_TOTAL);
    cudaLaunchConfig_t cfg = {}; cfg.gridDim = dim3(128); cfg.blockDim = dim3(384); cfg.dynamicSmemBytes = SMEM_TOTAL;
    cudaLaunchAttribute at[1]; at[0].id = cudaLaunchAttributeClusterDimension; at[0].val.clusterDim.x = CLS; at[0].val.clusterDim.y = 1; at[0].val.clusterDim.z = 1;
    cfg.attrs = at; cfg.numAttrs = 1;
    if (cudaOccupancyMaxActiveClusters(&ncl, k_main, &cfg) != cudaSuccess) { cudaGetLastError(); ncl = 14; }
    ncl = ncl > 16 ? 16 : (ncl < 9 ? 9 : ncl);
    int nsm = 0, dev = 0; cudaGetDevice(&dev); cudaDeviceGetAttribute(&nsm, cudaDevAttrMultiProcessorCount, dev);
    nhelp = nsm - ncl * CLS;
  }
  Maps maps;
  mk_map(enc, &maps.xn, p_xn, S_TOK, DM, 128); mk_map(enc, &maps.y, p_y, S_TOK, DM, 128); mk_map(enc, &maps.h1, p_h1, S_TOK, FF, 128);
  mk_map(enc, &maps.o, p_o, S_TOK, HD, 128); mk_map(enc, &maps.qkv_st, p_qkv, S_TOK, 3 * HD, 128); mk_map(enc, &maps.qkv_ld, p_qkv, S_TOK, 3 * HD, 32);
  mk_map(enc, &maps.g, p_g, S_TOK, DM, 128);
  mk_map(enc, &maps.wq, d_in[2], DM, HD, 64); mk_map(enc, &maps.wk, d_in[3], DM, HD, 64); mk_map(enc, &maps.wv, d_in[4], DM, HD, 64);
  mk_map(enc, &maps.wo, d_in[5], HD, DM, 64); mk_map(enc, &maps.w1, d_in[8], DM, FF, 64); mk_map(enc, &maps.w2, d_in[10], FF, DM, 64);
  cudaStream_t st = cudaStreamPerThread;
  k_pre<<<256, 256, 0, st>>>((const bf16*)d_in[0], (const char*)d_in[2], (const char*)d_in[3], (const char*)d_in[4], (const char*)d_in[5]);
  cudaLaunchConfig_t cfg = {}; cfg.gridDim = dim3(ncl * CLS); cfg.blockDim = dim3(384); cfg.dynamicSmemBytes = SMEM_TOTAL; cfg.stream = st;
  cudaLaunchAttribute at[2]; at[1].id = cudaLaunchAttributeClusterDimension; at[1].val.clusterDim.x = CLS; at[1].val.clusterDim.y = 1; at[1].val.clusterDim.z = 1;
  at[0].id = cudaLaunchAttributeProgrammaticStreamSerialization; at[0].val.programmaticStreamSerializationAllowed = 1;
#define PDL1 0
  cfg.attrs = at + (PDL1 ? 0 : 1); cfg.numAttrs = PDL1 ? 2 : 1;
  cudaLaunchKernelEx(&cfg, k_main, maps, (const bf16*)d_in[0], (const bf16*)d_in[1], (const bf16*)d_in[9], (const bf16*)d_in[11], (bf16*)d_out, recmask);
  if (nhelp > 0) {
    cfg.gridDim = dim3(nhelp);
    cfg.attrs = at; cfg.numAttrs = 1;
    cudaLaunchKernelEx(&cfg, k_main, maps, (const bf16*)d_in[0], (const bf16*)d_in[1], (const bf16*)d_in[9], (const bf16*)d_in[11], (bf16*)d_out, 0u);
  }
}
```

```cpp
#include <cuda_runtime.h>
#include <cuda_bf16.h>
#include <cuda.h>
#include <stdint.h>

typedef __nv_bfloat16 bf16;

#define S_TOK 2048
#define DM 512
#define NH 32
#define DH 128
#define HD 4096
#define NMEM 8
#define SEG 32
#define NSEG 64
#define FF 1792
#define NBLK 16
#define NREC 64
#define REPL 0
#define CLS 8

__device__ __align__(1024) bf16 g_xn[S_TOK * DM];
__device__ __align__(1024) bf16 g_y[S_TOK * DM];
__device__ __align__(1024) bf16 g_qkv[(size_t)S_TOK * 3 * HD];
__device__ __align__(1024) bf16 g_h1[S_TOK * FF];
__device__ __align__(1024) bf16 g_g[S_TOK * DM];
__device__ __align__(1024) bf16 g_o[(size_t)S_TOK * HD];
__device__ __align__(1024) bf16 g_km[NSEG * NH * NMEM * DH];
__device__ __align__(1024) bf16 g_vmt[NSEG * NH * DH * NMEM];
__device__ __align__(1024) float g_opart[(size_t)4 * S_TOK * DM];
__device__ __align__(1024) float g_opl[(size_t)16 * 128 * DM];
__device__ __align__(1024) unsigned g_part[8 * 2 * 8 * 8 * 512];
struct Flags {
  unsigned qkv[NBLK * 48];
  unsigned h1[NBLK];
  unsigned g[NBLK];
  unsigned o[NBLK * 4];
  unsigned p[NBLK];
  unsigned o16[16];
  unsigned ctr;
  unsigned rec[NREC];
  unsigned abort_;
};
__device__ __align__(1024) Flags g_flags;

#define RSTAMP(k)
#define DBGMODE 0
#define ISTAMP(i, k)
__device__ __forceinline__ unsigned smem_u32(const void* p) { return (unsigned)__cvta_generic_to_shared(p); }
__device__ __forceinline__ float bf16r(float x) { unsigned u; asm("cvt.rn.bf16x2.f32 %0, %1, %2;" : "=r"(u) : "f"(x), "f"(0.0f)); return __uint_as_float(u); }
__device__ __forceinline__ unsigned pack_bf16(float lo, float hi) {
  __nv_bfloat162 v = __floats2bfloat162_rn(lo, hi);
  return *reinterpret_cast<unsigned*>(&v);
}
__device__ __forceinline__ float bf_lo(unsigned u) { return __uint_as_float(u << 16); }
__device__ __forceinline__ float bf_hi(unsigned u) { return __uint_as_float(u & 0xffff0000u); }

#define SPIN_LIMIT (1u << 20)
#define TRAP_IF(x) if ((x) > SPIN_LIMIT) { asm volatile("st.global.u32 [%0], %1;" ::"l"(0ull), "r"(0u) : "memory"); break; }
__device__ __forceinline__ unsigned ld_acquire(const unsigned* p) {
  unsigned v; asm volatile("ld.acquire.gpu.global.u32 %0, [%1];" : "=r"(v) : "l"(p) : "memory"); return v;
}
__device__ __forceinline__ unsigned ld_relaxed(const unsigned* p) {
  unsigned v; asm volatile("ld.relaxed.gpu.global.u32 %0, [%1];" : "=r"(v) : "l"(p) : "memory"); return v;
}
__device__ __forceinline__ void red_release_add(unsigned* p, unsigned v) {
  asm volatile("red.release.gpu.global.add.u32 [%0], %1;" ::"l"(p), "r"(v) : "memory");
}
__device__ __forceinline__ void st_release(unsigned* p, unsigned v) {
  asm volatile("st.release.gpu.global.u32 [%0], %1;" ::"l"(p), "r"(v) : "memory");
}
__device__ __forceinline__ void wait_flag_ge(const unsigned* p, unsigned target) {
  unsigned it = 0;
  while (ld_acquire(p) < target) {
    __nanosleep(64);
    TRAP_IF(++it);
  }
}
__device__ __forceinline__ uint4 ldv4_relaxed(const void* p) {
  uint4 a; asm volatile("ld.relaxed.gpu.global.v4.u32 {%0,%1,%2,%3}, [%4];" : "=r"(a.x), "=r"(a.y), "=r"(a.z), "=r"(a.w) : "l"(p) : "memory"); return a;
}
__device__ __forceinline__ uint2 ldv2_relaxed(const void* p) {
  uint2 a; asm volatile("ld.relaxed.gpu.global.v2.u32 {%0,%1}, [%2];" : "=r"(a.x), "=r"(a.y) : "l"(p) : "memory"); return a;
}
__device__ __forceinline__ void mbar_init(unsigned mb, unsigned cnt) { asm volatile("mbarrier.init.shared::cta.b64 [%0], %1;" ::"r"(mb), "r"(cnt) : "memory"); }
__device__ __forceinline__ void mbar_expect_tx(unsigned mb, unsigned bytes) { asm volatile("mbarrier.arrive.expect_tx.shared::cta.b64 _, [%0], %1;" ::"r"(mb), "r"(bytes) : "memory"); }
__device__ __forceinline__ void mbar_arrive(unsigned mb) { asm volatile("mbarrier.arrive.shared::cta.b64 _, [%0];" ::"r"(mb) : "memory"); }
__device__ __forceinline__ void mbar_wait(unsigned mb, unsigned parity) {
  unsigned ok, it = 0;
  while (true) {
    asm volatile("{.reg .pred p; mbarrier.try_wait.parity.shared::cta.b64 p, [%1], %2; selp.u32 %0,1,0,p;}" : "=r"(ok) : "r"(mb), "r"(parity) : "memory");
    if (ok) break;
    TRAP_IF(++it);
  }
}
__device__ __forceinline__ void mbar_wait_sleep(unsigned mb, unsigned parity) {
  unsigned ok, it = 0;
  while (true) {
    asm volatile("{.reg .pred p; mbarrier.test_wait.parity.shared::cta.b64 p, [%1], %2; selp.u32 %0,1,0,p;}" : "=r"(ok) : "r"(mb), "r"(parity) : "memory");
    if (ok) break;
    __nanosleep(200);
    TRAP_IF(++it);
  }
}
__device__ __forceinline__ float ex2f(float x) { float y; asm("ex2.approx.ftz.f32 %0, %1;" : "=f"(y) : "f"(x)); return y; }
__device__ __forceinline__ int opaque_tid() { int t = threadIdx.x; t = __shfl_sync(~0u, t, t & 31); return t; }
#define LOG2E 1.4426950408889634f
__device__ __forceinline__ void mbar_wait_cluster(unsigned mb, unsigned parity) {
  unsigned ok, it = 0;
  while (true) {
    asm volatile("{.reg .pred p; mbarrier.try_wait.parity.acquire.cluster.shared::cta.b64 p, [%1], %2; selp.u32 %0,1,0,p;}" : "=r"(ok) : "r"(mb), "r"(parity) : "memory");
    if (ok) break;
    TRAP_IF(++it);
  }
}
__device__ __forceinline__ void bar_sync(int id, int n) { asm volatile("bar.sync %0, %1;" ::"r"(id), "r"(n) : "memory"); }
__device__ __forceinline__ void bar_arrive(int id, int n) { asm volatile("bar.arrive %0, %1;" ::"r"(id), "r"(n) : "memory"); }
__device__ __forceinline__ void tma_load_2d(unsigned dst, const CUtensorMap* map, int c0, int c1, unsigned mb) {
  asm volatile("cp.async.bulk.tensor.2d.shared::cluster.global.mbarrier::complete_tx::bytes [%0], [%1, {%3, %4}], [%2];"
               ::"r"(dst), "l"((uint64_t)map), "r"(mb), "r"(c0), "r"(c1) : "memory");
}
__device__ __forceinline__ void tma_store_2d(const CUtensorMap* map, unsigned src, int c0, int c1) {
  asm volatile("cp.async.bulk.tensor.2d.global.shared::cta.bulk_group [%0, {%2, %3}], [%1];"
               ::"l"((uint64_t)map), "r"(src), "r"(c0), "r"(c1) : "memory");
}
__device__ __forceinline__ void fence_proxy_async() { asm volatile("fence.proxy.async;" ::: "memory"); }
__device__ __forceinline__ void fence_proxy_async_smem() { asm volatile("fence.proxy.async.shared::cta;" ::: "memory"); }
__device__ __forceinline__ void ldsm_x4(unsigned* r, unsigned addr) {
  asm volatile("ldmatrix.sync.aligned.m8n8.x4.shared.b16 {%0,%1,%2,%3}, [%4];" : "=r"(r[0]), "=r"(r[1]), "=r"(r[2]), "=r"(r[3]) : "r"(addr) : "memory");
}
__device__ __forceinline__ void ldsm_x4_t(unsigned* r, unsigned addr) {
  asm volatile("ldmatrix.sync.aligned.m8n8.x4.trans.shared.b16 {%0,%1,%2,%3}, [%4];" : "=r"(r[0]), "=r"(r[1]), "=r"(r[2]), "=r"(r[3]) : "r"(addr) : "memory");
}
__device__ __forceinline__ void stsm_x2_t(unsigned addr, unsigned r0, unsigned r1) {
  asm volatile("stmatrix.sync.aligned.m8n8.x2.trans.shared.b16 [%0], {%1,%2};" ::"r"(addr), "r"(r0), "r"(r1) : "memory");
}
__device__ __forceinline__ void stsm_x4(unsigned addr, unsigned r0, unsigned r1, unsigned r2, unsigned r3) {
  asm volatile("stmatrix.sync.aligned.m8n8.x4.shared.b16 [%0], {%1,%2,%3,%4};" ::"r"(addr), "r"(r0), "r"(r1), "r"(r2), "r"(r3) : "memory");
}
__device__ __forceinline__ void mma16816(float* d, const unsigned* a, unsigned b0, unsigned b1) {
  asm volatile("mma.sync.aligned.m16n8k16.row.col.f32.bf16.bf16.f32 {%0,%1,%2,%3}, {%4,%5,%6,%7}, {%8,%9}, {%0,%1,%2,%3};"
               : "+f"(d[0]), "+f"(d[1]), "+f"(d[2]), "+f"(d[3]) : "r"(a[0]), "r"(a[1]), "r"(a[2]), "r"(a[3]), "r"(b0), "r"(b1));
}
__device__ __forceinline__ void mma1688(float* d, unsigned a0, unsigned a1, unsigned b0) {
  asm volatile("mma.sync.aligned.m16n8k8.row.col.f32.bf16.bf16.f32 {%0,%1,%2,%3}, {%4,%5}, {%6}, {%0,%1,%2,%3};"
               : "+f"(d[0]), "+f"(d[1]), "+f"(d[2]), "+f"(d[3]) : "r"(a0), "r"(a1), "r"(b0));
}
__device__ __forceinline__ uint64_t mkdesc(unsigned addr, unsigned lbo, unsigned sbo) {
  return (uint64_t)((addr >> 4) & 0x3fff) | ((uint64_t)(lbo >> 4) << 16) | ((uint64_t)(sbo >> 4) << 32) | (1ull << 62);
}
#define R8(b) "+f"(d[b]), "+f"(d[b + 1]), "+f"(d[b + 2]), "+f"(d[b + 3]), "+f"(d[b + 4]), "+f"(d[b + 5]), "+f"(d[b + 6]), "+f"(d[b + 7])
#define R32(b) R8(b), R8(b + 8), R8(b + 16), R8(b + 24)
__device__ __forceinline__ void wgmma_n256(float* d, uint64_t ad, uint64_t bd, int acc) {
  asm volatile(
      "{.reg .pred p; setp.ne.b32 p, %130, 0;\n"
      "wgmma.mma_async.sync.aligned.m64n256k16.f32.bf16.bf16 "
      "{%0,%1,%2,%3,%4,%5,%6,%7,%8,%9,%10,%11,%12,%13,%14,%15,%16,%17,%18,%19,%20,%21,%22,%23,%24,%25,%26,%27,%28,%29,%30,%31,"
      "%32,%33,%34,%35,%36,%37,%38,%39,%40,%41,%42,%43,%44,%45,%46,%47,%48,%49,%50,%51,%52,%53,%54,%55,%56,%57,%58,%59,%60,%61,%62,%63,"
      "%64,%65,%66,%67,%68,%69,%70,%71,%72,%73,%74,%75,%76,%77,%78,%79,%80,%81,%82,%83,%84,%85,%86,%87,%88,%89,%90,%91,%92,%93,%94,%95,"
      "%96,%97,%98,%99,%100,%101,%102,%103,%104,%105,%106,%107,%108,%109,%110,%111,%112,%113,%114,%115,%116,%117,%118,%119,%120,%121,%122,%123,%124,%125,%126,%127},"
      "%128, %129, p, 1, 1, 0, 1;}\n"
      : R32(0), R32(32), R32(64), R32(96)
      : "l"(ad), "l"(bd), "r"(acc));
}

__device__ __forceinline__ void wgmma_n128(float* d, uint64_t ad, uint64_t bd, int acc) {
  asm volatile(
      "{.reg .pred p; setp.ne.b32 p, %66, 0;\n"
      "wgmma.mma_async.sync.aligned.m64n128k16.f32.bf16.bf16 {%0,%1,%2,%3,%4,%5,%6,%7,%8,%9,%10,%11,%12,%13,%14,%15,%16,%17,%18,%19,%20,%21,%22,%23,%24,%25,%26,%27,%28,%29,%30,%31,%32,%33,%34,%35,%36,%37,%38,%39,%40,%41,%42,%43,%44,%45,%46,%47,%48,%49,%50,%51,%52,%53,%54,%55,%56,%57,%58,%59,%60,%61,%62,%63}, %64, %65, p, 1, 1, 0, 1;}\n"
      : R32(0), R32(32)
      : "l"(ad), "l"(bd), "r"(acc));
}

__device__ __forceinline__ void ln16(const float* x, float* o) {
  float s = 0;
#pragma unroll
  for (int i = 0; i < 16; i++) s += x[i];
#pragma unroll
  for (int of = 16; of > 0; of >>= 1) s += __shfl_xor_sync(~0u, s, of);
  float mean = s * (1.0f / DM);
  float v = 0;
#pragma unroll
  for (int i = 0; i < 16; i++) { float dd = x[i] - mean; v += dd * dd; }
#pragma unroll
  for (int of = 16; of > 0; of >>= 1) v += __shfl_xor_sync(~0u, v, of);
  float mb = bf16r(mean);
  float vb = bf16r(v * (1.0f / DM));
  float den = bf16r(sqrtf(bf16r(vb + 1e-5f)));
#pragma unroll
  for (int i = 0; i < 16; i++) o[i] = bf16r(__fdiv_rn(bf16r(x[i] - mb), den));
}
__global__ void __launch_bounds__(256) k_pre(const bf16* __restrict__ x, const char* wq, const char* wk, const char* wv, const char* wo) {
  int t = threadIdx.x, lane = t & 31, w = t >> 5;
  asm volatile("griddepcontrol.launch_dependents;");
  {
    int g2 = blockIdx.x * 256 + t, o = (g2 & 32767) * 128;
    asm volatile("prefetch.global.L2 [%0];" ::"l"((g2 < 32768 ? wk : wv) + o));
    asm volatile("prefetch.global.L2 [%0];" ::"l"((g2 < 32768 ? wq : wo) + o));
  }
  int row = blockIdx.x * 8 + w;
  const uint4* src = reinterpret_cast<const uint4*>(x + (size_t)row * DM);
  uint4 a = src[lane], b = src[lane + 32];
  unsigned u[8] = {a.x, a.y, a.z, a.w, b.x, b.y, b.z, b.w};
  float f[16], o[16], o2[16];
#pragma unroll
  for (int i = 0; i < 8; i++) { f[2 * i] = bf_lo(u[i]); f[2 * i + 1] = bf_hi(u[i]); }
  ln16(f, o);
  ln16(o, o2);
  uint4* d1 = reinterpret_cast<uint4*>(g_xn + (size_t)row * DM);
  uint4* d2 = reinterpret_cast<uint4*>(g_y + (size_t)row * DM);
  d1[lane] = make_uint4(pack_bf16(o[0], o[1]), pack_bf16(o[2], o[3]), pack_bf16(o[4], o[5]), pack_bf16(o[6], o[7]));
  d1[lane + 32] = make_uint4(pack_bf16(o[8], o[9]), pack_bf16(o[10], o[11]), pack_bf16(o[12], o[13]), pack_bf16(o[14], o[15]));
  d2[lane] = make_uint4(pack_bf16(o2[0], o2[1]), pack_bf16(o2[2], o2[3]), pack_bf16(o2[4], o2[5]), pack_bf16(o2[6], o2[7]));
  d2[lane + 32] = make_uint4(pack_bf16(o2[8], o2[9]), pack_bf16(o2[10], o2[11]), pack_bf16(o2[12], o2[13]), pack_bf16(o2[14], o2[15]));
  int gt = blockIdx.x * 256 + t;
  uint4 z = make_uint4(0, 0, 0, 0);
  if (gt < 16384) reinterpret_cast<uint4*>(g_part)[gt] = z;
  if (gt < (int)(sizeof(Flags) / 4)) reinterpret_cast<unsigned*>(&g_flags)[gt] = 0;
}

struct Maps { CUtensorMap xn, y, h1, o, qkv_st, qkv_ld, g, wq, wk, wv, wo, w1, w2; };

#define NSTAGE 3
#define STAGE_BYTES 49152
#define B_STG (NSTAGE * STAGE_BYTES)
#define R_WO 0
#define R_T1 65536
#define R_T2 131072
#define R_RING 65536
#define RING_N 4
#define RING_BYTES 12288
#define R_MEM 196608
#define R_QS (R_MEM + 8448)
#define R_KS (R_QS + 1152)
#define R_OS (R_KS + 1152)
#define R_SOWN (R_OS + 2176)
#define R_SPEER (R_SOWN + 1280)
#define R_VM (R_SPEER + 1280)
#define R_VRED (R_VM + 2048)
#define R_RS (R_VRED + 6144)
#define SM_BAR (R_RS + 8192)
#define SMEM_TOTAL (SM_BAR + 256 + 1024)
#define MB_FULL 0
#define MB_EMPTY 8
#define MB_STGF 16
#define MB_STGE 17
#define MB_W0 18
#define MB_W1 19
#define MB_WO 20
#define MB_S 21
#define MB_V 22
#define MB_KVR 23
#define MB_KVF 24
#define MB_RS 25
#define MB_AG 26
#define SM_MISC (SM_BAR + 224)

#define N_KV 544
#define I_M1 544
#define I_Q 656
#define I_M2 912
#define I_POST 944
#define I_TAIL (I_POST + 16 * 32)
#define N_ITEMS (I_TAIL + 5 * 8 + 64 + 8 + 64)
enum { T_QKV = 0, T_M1 = 1, T_M2 = 2, T_ATT = 3, T_OUT = 4, T_OUTL = 5, T_RED = 6, T_REDL = 7 };
struct Item { int type, b, c, ks, hf; };
__device__ __forceinline__ Item decode_item(int i) {
  Item it; it.ks = 0; it.hf = 0;
  if (i < 64) { it.type = T_QKV; it.b = 0; it.c = 16 + (i >> 1); it.hf = 1 + (i & 1); }
  else if (i < N_KV) { it.type = T_QKV; it.b = (i - 32) >> 5; it.c = 16 + (i & 31); }
  else if (i < I_Q) { it.type = T_M1; it.b = (i - I_M1) / 7; it.c = (i - I_M1) % 7; }
  else if (i < I_M2) { it.type = T_QKV; it.b = (i - I_Q) >> 4; it.c = (i - I_Q) & 15; }
  else if (i < I_POST) { it.type = T_M2; it.b = (i - I_M2) >> 1; it.c = (i - I_M2) & 1; }
  else if (i < I_TAIL) {
    int x = i - I_POST, p = x >> 5, r = x & 31;
    if (r < 16) { it.type = T_ATT; it.b = p; it.c = r; }
    else if (r < 24) { it.type = T_OUT; it.b = p - 3; it.c = r & 1; it.ks = (r - 16) >> 1; }
    else { it.type = T_RED; it.b = p - 5; it.c = r - 24; }
  } else {
    int x = i - I_TAIL, r = x & 7;
    if (x < 40) {
      int q = x >> 3;
      if (q == 0 || q == 2) { it.type = T_OUT; it.b = 13 + (q >> 1); it.c = r & 1; it.ks = r >> 1; }
      else { it.type = T_RED; it.b = q == 1 ? 11 : 9 + q; it.c = r; }
    }
    else if (x < 104) { it.type = T_OUTL; it.b = 15; it.c = (x >> 1) & 1; it.ks = (x - 40) >> 2; it.hf = 1 + (x & 1); }
    else if (x < 112) { it.type = T_RED; it.b = 14; it.c = r; }
    else { it.type = T_REDL; it.b = 15; it.c = x - 112; }
  }
  return it;
}
__device__ __forceinline__ int item_nkb(int type) { return type == T_M2 ? 28 : (type == T_OUT ? 16 : (type >= T_RED ? 1 : (type >= T_ATT ? 4 : 8))); }

__device__ __forceinline__ void st_async_b64(unsigned raddr, unsigned lo, unsigned hi, unsigned rmb) {
  asm volatile("st.async.weak.shared::cluster.mbarrier::complete_tx::bytes.v2.b32 [%0], {%1,%2}, [%3];" ::"r"(raddr), "r"(lo), "r"(hi), "r"(rmb) : "memory");
}
__device__ __forceinline__ void st_async_b32(unsigned raddr, unsigned v, unsigned rmb) {
  asm volatile("st.async.weak.shared::cluster.mbarrier::complete_tx::bytes.b32 [%0], %1, [%2];" ::"r"(raddr), "r"(v), "r"(rmb) : "memory");
}
__device__ __forceinline__ unsigned mapa(unsigned a, unsigned rank) {
  unsigned r; asm volatile("mapa.shared::cluster.u32 %0, %1, %2;" : "=r"(r) : "r"(a), "r"(rank)); return r;
}
__device__ __forceinline__ void sts64(unsigned a, unsigned x, unsigned y) { asm volatile("st.shared.v2.b32 [%0], {%1,%2};" ::"r"(a), "r"(x), "r"(y) : "memory"); }
__device__ __forceinline__ void sts128(unsigned a, uint4 v) { asm volatile("st.shared.v4.b32 [%0], {%1,%2,%3,%4};" ::"r"(a), "r"(v.x), "r"(v.y), "r"(v.z), "r"(v.w) : "memory"); }
__device__ __forceinline__ uint2 lds64(unsigned a) { uint2 v; asm volatile("ld.shared.v2.b32 {%0,%1}, [%2];" : "=r"(v.x), "=r"(v.y) : "r"(a) : "memory"); return v; }
__device__ __forceinline__ uint4 lds128(unsigned a) { uint4 v; asm volatile("ld.shared.v4.b32 {%0,%1,%2,%3}, [%4];" : "=r"(v.x), "=r"(v.y), "=r"(v.z), "=r"(v.w) : "r"(a) : "memory"); return v; }
__device__ __forceinline__ float lds32f(unsigned a) { float v; asm volatile("ld.shared.f32 %0, [%1];" : "=f"(v) : "r"(a) : "memory"); return v; }
#define spin_check(it) TRAP_IF(++it)
#define POLLV 0
#define BAR8 0
#define D_STAG 150
#define D_RED 540
#define D_PUB 0
#define DELAY(n) do { unsigned c0_, c1_; asm volatile("mov.u32 %0, %%clock;" : "=r"(c0_)); do { asm volatile("mov.u32 %0, %%clock;" : "=r"(c1_)); } while (c1_ - c0_ < (n)); } while (0)
#define VD 2
#define NPRE 3
#define SELP 1
#define SCALE_QK 0.08838834764831845f

__device__ __forceinline__ void rec_worker(const Maps& maps, unsigned sb, const bf16* __restrict__ mem0, const int c) {
  const int h = c >> 1, j = c & 1;
  const int t = opaque_tid(), lane = t & 31, w = t >> 5, g = lane >> 2, tq = lane & 3;
  const int m = lane >> 3, r8 = lane & 7, kh = w >> 2, et = w & 3;
  const unsigned bar = sb + SM_BAR;
  unsigned wq[16][4], wk[16][4], wo[8][4];
  const unsigned woff = (kh * 4) * 8192 + ((m >> 1) * 8 + r8) * 128 + (((et * 2 + (m & 1)) ^ r8) << 4);
  mbar_wait(bar + 8 * MB_W0, 0);
#pragma unroll
  for (int i = 0; i < 16; i++) {
    ldsm_x4_t(wq[i], sb + R_WO + woff + (i >> 2) * 8192 + (i & 3) * 2048);
    ldsm_x4_t(wk[i], sb + R_T1 + woff + (i >> 2) * 8192 + (i & 3) * 2048);
  }
  bar_sync(2, 288);
  if (t == 0) {
    fence_proxy_async_smem();
    mbar_expect_tx(bar + 8 * MB_WO, 65536);
    for (int kb = 0; kb < 2; kb++)
      for (int cb = 0; cb < 4; cb++) tma_load_2d(sb + R_WO + (kb * 4 + cb) * 8192, &maps.wo, j * 256 + cb * 64, h * 128 + kb * 64, bar + 8 * MB_WO);
  }
  mbar_wait(bar + 8 * MB_W1, 0);
  const unsigned pV = sb + R_T2 + woff;
  const unsigned rk = c & 7, peer = rk ^ 1, cl = c >> 3;
#define KEEP(x) x = __shfl_sync(~0u, x, lane)
  unsigned pA = sb + R_MEM + kh * 4096 + lane * 16;
  unsigned pW0 = sb + R_WO + (w >> 1) * 8192 + ((m >> 1) * 8 + r8) * 128 + ((((w & 1) * 4 + (m & 1)) ^ r8) << 4);
  unsigned pW1 = pW0 ^ 32;
  unsigned pVk = pV;
  unsigned aX = sb + R_VRED + et * 512 + lane * 16;
  unsigned aQKst = sb + (kh ? R_KS : R_QS) + r8 * 144 + (et * 16 + (m & 1) * 8) * 2;
  unsigned aL8 = sb + lane * 8;
  unsigned aSl = mapa(sb + R_SOWN + w * 256 + lane * 8, rk), aSr = mapa(sb + R_SPEER + w * 256 + lane * 8, peer);
  unsigned aVl = mapa(sb + R_VM + (j * 4 + et) * 256 + lane * 8, rk), aVr = mapa(sb + R_VM + (j * 4 + et) * 256 + lane * 8, peer);
  const unsigned mbSl = mapa(bar + 8 * MB_S, rk), mbSr = mapa(bar + 8 * MB_S, peer), mbVl = mbSl + 8, mbVr = mbSr + 8;
  unsigned aQ = sb + R_QS + r8 * 144 + m * 16;
  unsigned oKx = (et * 8 + r8) * 128 + ((m ^ r8) << 4);
  unsigned oVx = 4096 + (et >> 1) * 4096 + ((m >> 1) * 8 + r8) * 128 + ((((et & 1) * 4 + (m & 1)) ^ r8) << 4);
  unsigned aOst = sb + R_OS + r8 * 272 + (et * 32 + m * 8) * 2;
  unsigned aOld = sb + R_OS + r8 * 272 + m * 16;
  unsigned aVm = sb + R_VM + et * 512 + lane * 8;
  unsigned aRSr = mapa(sb + R_RS + (h & 3) * 2048 + (w & 1) * 1024 + lane * 8, j * 4 + (w >> 1));
  unsigned mbRSr = mapa(bar + 8 * MB_RS, j * 4 + (w >> 1));
  unsigned t8 = t * 8;
  KEEP(pA); KEEP(pW0); KEEP(pW1); KEEP(pVk); KEEP(aX); KEEP(aQKst); KEEP(aL8); KEEP(aSl); KEEP(aSr); KEEP(aVl); KEEP(aVr); KEEP(aQ); KEEP(oKx); KEEP(oVx);
  KEEP(aOst); KEEP(aOld); KEEP(aVm); KEEP(aRSr); KEEP(mbRSr); KEEP(t8);
  mbar_wait(bar + 8 * MB_WO, 0);
#pragma unroll
  for (int ks = 0; ks < 4; ks++) { ldsm_x4_t(wo[2 * ks], pW0 + ks * 2048); ldsm_x4_t(wo[2 * ks + 1], pW1 + ks * 2048); }
  {
    unsigned v[8];
#pragma unroll
    for (int q = 0; q < 8; q++) v[q] = __ldg(reinterpret_cast<const unsigned*>(mem0) + q * 256 + t);
    sts128(sb + R_MEM + t * 32, make_uint4(__byte_perm(v[0], v[1], 0x5410), __byte_perm(v[2], v[3], 0x5410), __byte_perm(v[4], v[5], 0x5410), __byte_perm(v[6], v[7], 0x5410)));
    sts128(sb + R_MEM + t * 32 + 16, make_uint4(__byte_perm(v[0], v[1], 0x7632), __byte_perm(v[2], v[3], 0x7632), __byte_perm(v[4], v[5], 0x7632), __byte_perm(v[6], v[7], 0x7632)));
  }
  bar_sync(1, 256);

#pragma unroll 1
  for (int s = 0;; s++) {
    const unsigned par = s & 1;
    const unsigned slot = s & (RING_N - 1), rpar = (s / RING_N) & 1;
    const unsigned ring = sb + R_RING + slot * RING_BYTES;
    asm volatile("" : "+r"(t8));
    RSTAMP(1);
    RSTAMP(2);
    float aq[4] = {0, 0, 0, 0}, ak[4] = {0, 0, 0, 0}, av[4] = {0, 0, 0, 0};
    {
      unsigned b[8][4], f1[8][4], f0[8][4];
#define VLD(i) do { ldsm_x4_t(b[i], pA + (i) * 512); ldsm_x4_t(f0[i], pVk + ((i) >> 1) * 8192 + ((i) & 1) * 4096); ldsm_x4_t(f1[i], pVk + ((i) >> 1) * 8192 + ((i) & 1) * 4096 + 2048); } while (0)
      VLD(0);
      if (VD > 1) VLD(1);
#pragma unroll
      for (int i = 0; i < 8; i++) {
        if (i + VD < 8) VLD(i + VD);
        mma16816(aq, wq[2 * i], b[i][0], b[i][1]); mma16816(ak, wk[2 * i], b[i][0], b[i][1]); mma16816(av, f0[i], b[i][0], b[i][1]);
        mma16816(aq, wq[2 * i + 1], b[i][2], b[i][3]); mma16816(ak, wk[2 * i + 1], b[i][2], b[i][3]); mma16816(av, f1[i], b[i][2], b[i][3]);
      }
    }
    RSTAMP(3);
#define STSF4(a, v) asm volatile("st.shared.v4.f32 [%0], {%1,%2,%3,%4};" ::"r"(a), "f"(v[0]), "f"(v[1]), "f"(v[2]), "f"(v[3]) : "memory")
    unsigned f[8][4];
#define WO_PREFETCH() do { _Pragma("unroll") for (int i = 0; i < NPRE; i++) { ldsm_x4_t(f[2 * i], pW0 + 32768 + i * 2048); ldsm_x4_t(f[2 * i + 1], pW1 + 32768 + i * 2048); } } while (0)
    if (kh) {
      STSF4(aX, aq);
      bar_sync(4 + et, 64);
      uint4 o = lds128(aX + 2048), o2 = lds128(aX + 4096);
      stsm_x2_t(aQKst, pack_bf16(ak[0] + __uint_as_float(o.x), ak[1] + __uint_as_float(o.y)), pack_bf16(ak[2] + __uint_as_float(o.z), ak[3] + __uint_as_float(o.w)));
      bar_arrive(1, 256);
      unsigned x = pack_bf16(av[0] + __uint_as_float(o2.x), av[1] + __uint_as_float(o2.y)), y = pack_bf16(av[2] + __uint_as_float(o2.z), av[3] + __uint_as_float(o2.w));
      st_async_b64(aVr, x, y, mbVr);
      st_async_b64(aVl, x, y, mbVl);
      if (s == NSEG - 1) {
        mbar_wait(bar + 8 * MB_V, par);
        if (t == 128) mbar_arrive(bar + 8 * MB_KVR);
        break;
      }
      mbar_wait(bar + 8 * (MB_FULL + slot), rpar);
      unsigned vx[4][4];
      ldsm_x4_t(vx[0], ring + oVx); ldsm_x4_t(vx[1], ring + oVx + 2048); ldsm_x4_t(vx[2], ring + (oVx ^ 32)); ldsm_x4_t(vx[3], ring + (oVx ^ 32) + 2048);
      RSTAMP(4); RSTAMP(5); RSTAMP(6); RSTAMP(7);
      mbar_wait(bar + 8 * MB_S, par);
      RSTAMP(8);
      float sc[10];
#pragma unroll
      for (int i = 0; i < 5; i++) {
        uint2 o = lds64(aL8 + R_SOWN + i * 256), p = lds64(aL8 + R_SPEER + i * 256);
        sc[2 * i] = __uint_as_float(o.x) + __uint_as_float(p.x); sc[2 * i + 1] = __uint_as_float(o.y) + __uint_as_float(p.y);
      }
      mbar_wait(bar + 8 * MB_V, par);
      uint2 vm0 = lds64(aVm), vm1 = lds64(aVm + 256);
      float mx = fmaxf(fmaxf(fmaxf(sc[0], sc[1]), fmaxf(sc[2], sc[3])), fmaxf(fmaxf(fmaxf(sc[4], sc[5]), fmaxf(sc[6], sc[7])), fmaxf(sc[8], sc[9])));
      mx = fmaxf(mx, __shfl_xor_sync(~0u, mx, 1)); mx = fmaxf(mx, __shfl_xor_sync(~0u, mx, 2));
      const float nm = -mx * (SCALE_QK * LOG2E);
      unsigned p[5];
#pragma unroll
      for (int i = 0; i < 5; i++) p[i] = pack_bf16(ex2f(fmaf(sc[2 * i], SCALE_QK * LOG2E, nm)), ex2f(fmaf(sc[2 * i + 1], SCALE_QK * LOG2E, nm)));
      RSTAMP(9);
      float o0[4] = {0, 0, 0, 0}, o1[4] = {0, 0, 0, 0}, o3[4] = {0, 0, 0, 0}, o4[4] = {0, 0, 0, 0}, z0[4] = {0, 0, 0, 0}, z1[4] = {0, 0, 0, 0};
      const unsigned ones[4] = {0x3F803F80u, 0u, 0x3F803F80u, 0u};
      mma16816(z0, ones, p[0], p[1]); mma16816(z1, ones, p[2], p[3]);
      mma16816(o0, vx[0], p[0], p[1]); mma16816(o3, vx[2], p[0], p[1]);
      mma1688(z0, 0x3F803F80u, 0u, p[4]);
      mma16816(o1, vx[1], p[2], p[3]); mma16816(o4, vx[3], p[2], p[3]);
      mma1688(o0, vm0.x, vm0.y, p[4]); mma1688(o3, vm1.x, vm1.y, p[4]);
      float i0, i1;
      asm("rcp.approx.ftz.f32 %0, %1;" : "=f"(i0) : "f"(z0[0] + z1[0])); asm("rcp.approx.ftz.f32 %0, %1;" : "=f"(i1) : "f"(z0[1] + z1[1]));
      asm volatile("stmatrix.sync.aligned.m8n8.x4.trans.shared.b16 [%0], {%1,%2,%3,%4};" ::"r"(aOst), "r"(pack_bf16((o0[0] + o1[0]) * i0, (o0[1] + o1[1]) * i1)), "r"(pack_bf16((o0[2] + o1[2]) * i0, (o0[3] + o1[3]) * i1)),
                   "r"(pack_bf16((o3[0] + o4[0]) * i0, (o3[1] + o4[1]) * i1)), "r"(pack_bf16((o3[2] + o4[2]) * i0, (o3[3] + o4[3]) * i1)) : "memory");
      RSTAMP(10);
      bar_sync(1, 256);
      WO_PREFETCH();
    } else {
      STSF4(aX + 2048, ak); STSF4(aX + 4096, av);
      unsigned kb[8];
      mbar_wait(bar + 8 * (MB_FULL + slot), rpar);
      ldsm_x4(kb, ring + oKx); ldsm_x4(kb + 4, ring + (oKx ^ 64));
      bar_sync(4 + et, 64);
      uint4 o = lds128(aX);
      stsm_x2_t(aQKst, pack_bf16(aq[0] + __uint_as_float(o.x), aq[1] + __uint_as_float(o.y)), pack_bf16(aq[2] + __uint_as_float(o.z), aq[3] + __uint_as_float(o.w)));
      RSTAMP(4);
      bar_sync(1, 256);
      RSTAMP(5);
      if (s == NSEG - 1) break;
      unsigned qa[8], km[8];
      ldsm_x4(qa, aQ); ldsm_x4(qa + 4, aQ + 64);
      if (w == 3) { ldsm_x4(km, aQ + 1152); ldsm_x4(km + 4, aQ + 1152 + 64); }
      float s0[4] = {0, 0, 0, 0}, s1[4] = {0, 0, 0, 0};
      unsigned af[4][4];
#pragma unroll
      for (int i = 0; i < 4; i++) { af[i][0] = qa[2 * i]; af[i][1] = 0; af[i][2] = qa[2 * i + 1]; af[i][3] = 0; }
      mma16816(s0, af[0], kb[0], kb[1]); mma16816(s1, af[1], kb[2], kb[3]);
      mma16816(s0, af[2], kb[4], kb[5]); mma16816(s1, af[3], kb[6], kb[7]);
      if (w == 3) {
        float m0[4] = {0, 0, 0, 0}, m1[4] = {0, 0, 0, 0};
        mma16816(m0, af[0], km[0], km[1]); mma16816(m1, af[1], km[2], km[3]);
        mma16816(m0, af[2], km[4], km[5]); mma16816(m1, af[3], km[6], km[7]);
        unsigned x = __float_as_uint(m0[0] + m1[0]), y = __float_as_uint(m0[1] + m1[1]);
        st_async_b64(aSr + 256, x, y, mbSr); st_async_b64(aSl + 256, x, y, mbSl);
      }
      unsigned x = __float_as_uint(s0[0] + s1[0]), y = __float_as_uint(s0[1] + s1[1]);
      st_async_b64(aSr, x, y, mbSr); st_async_b64(aSl, x, y, mbSl);
      RSTAMP(6);
      WO_PREFETCH();
      RSTAMP(7); RSTAMP(8); RSTAMP(9); RSTAMP(10);
      bar_sync(1, 256);
    }
    RSTAMP(11);
    float d0[4] = {0, 0, 0, 0}, d1[4] = {0, 0, 0, 0}, e0[4] = {0, 0, 0, 0}, e1[4] = {0, 0, 0, 0};
    unsigned ob[4][4];
#pragma unroll
    for (int k2 = 0; k2 < 4; k2++) ldsm_x4(ob[k2], aOld + k2 * 64);
#pragma unroll
    for (int i = NPRE; i < 4; i++) { ldsm_x4_t(f[2 * i], pW0 + 32768 + i * 2048); ldsm_x4_t(f[2 * i + 1], pW1 + 32768 + i * 2048); }
    mma16816(d0, wo[0], ob[0][0], ob[0][1]); mma16816(d1, wo[1], ob[0][0], ob[0][1]);
    mma16816(e0, wo[2], ob[0][2], ob[0][3]); mma16816(e1, wo[3], ob[0][2], ob[0][3]);
    mma16816(d0, wo[4], ob[1][0], ob[1][1]); mma16816(d1, wo[5], ob[1][0], ob[1][1]);
    mma16816(e0, wo[6], ob[1][2], ob[1][3]); mma16816(e1, wo[7], ob[1][2], ob[1][3]);
    mma16816(d0, f[0], ob[2][0], ob[2][1]); mma16816(d1, f[1], ob[2][0], ob[2][1]);
    mma16816(e0, f[2], ob[2][2], ob[2][3]); mma16816(e1, f[3], ob[2][2], ob[2][3]);
    mma16816(d0, f[4], ob[3][0], ob[3][1]); mma16816(d1, f[5], ob[3][0], ob[3][1]);
    mma16816(e0, f[6], ob[3][2], ob[3][3]); mma16816(e1, f[7], ob[3][2], ob[3][3]);
    st_async_b64(aRSr, __float_as_uint(d0[0] + e0[0]), __float_as_uint(d0[1] + e0[1]), mbRSr);
    st_async_b64(aRSr + 256, __float_as_uint(d0[2] + e0[2]), __float_as_uint(d0[3] + e0[3]), mbRSr);
    st_async_b64(aRSr + 512, __float_as_uint(d1[0] + e1[0]), __float_as_uint(d1[1] + e1[1]), mbRSr);
    st_async_b64(aRSr + 768, __float_as_uint(d1[2] + e1[2]), __float_as_uint(d1[3] + e1[3]), mbRSr);
    RSTAMP(12);
    if (t == 128) {
      mbar_arrive(bar + 8 * (MB_EMPTY + slot)); mbar_arrive(bar + 8 * MB_KVR);
      mbar_expect_tx(bar + 8 * MB_S, 2560); mbar_expect_tx(bar + 8 * MB_V, 2048);
    }
    const unsigned tag = ((s >> 1) & 1) ^ 1;
    const char* gp = reinterpret_cast<const char*>(g_part);
    const unsigned goff = (par * 8 + rk) * 16384 + cl * 2048 + t8;
    unsigned mbA[8];
#pragma unroll
    for (int i = 0; i < 8; i++) mbA[i] = mapa(bar + 8 * MB_AG, i);
    const unsigned dlt = (R_MEM + rk * 1024) - (SM_BAR + 8 * MB_AG) + (t8 >> 1);
    mbar_wait(bar + 8 * MB_RS, par);
    RSTAMP(13);
    uint2 a[8];
    {
      uint2 x0 = lds64(sb + R_RS + t8), x1 = lds64(sb + R_RS + 2048 + t8), x2 = lds64(sb + R_RS + 4096 + t8), x3 = lds64(sb + R_RS + 6144 + t8);
      float r0 = (__uint_as_float(x0.x) + __uint_as_float(x1.x)) + (__uint_as_float(x2.x) + __uint_as_float(x3.x));
      float r1 = (__uint_as_float(x0.y) + __uint_as_float(x1.y)) + (__uint_as_float(x2.y) + __uint_as_float(x3.y));
      a[0].x = (__float_as_uint(r0) & ~1u) | tag; a[0].y = (__float_as_uint(r1) & ~1u) | tag;
      asm volatile("st.relaxed.gpu.global.v2.u32 [%0], {%1,%2};" ::"l"(gp + goff), "r"(a[0].x), "r"(a[0].y) : "memory");
    }
    RSTAMP(14);
    if (t == 128) mbar_expect_tx(bar + 8 * MB_RS, 8192);
    {
      unsigned it = 0;
#define PLOAD(a) _Pragma("unroll") for (int i = 1; i < 8; i++) a[i] = ldv2_relaxed(gp + (goff ^ (i * 2048)))
#define PAND(a) (((a[1].x & a[1].y) & (a[2].x & a[2].y) & (a[3].x & a[3].y)) & ((a[4].x & a[4].y) & (a[5].x & a[5].y)) & ((a[6].x & a[6].y) & (a[7].x & a[7].y)))
#define POR(a) (((a[1].x | a[1].y) | (a[2].x | a[2].y) | (a[3].x | a[3].y)) | ((a[4].x | a[4].y) | (a[5].x | a[5].y)) | ((a[6].x | a[6].y) | (a[7].x | a[7].y)))
#define POK(a) (((tag ? PAND(a) : ~POR(a)) & 1u) != 0)
      if (D_RED) DELAY(D_RED);
      PLOAD(a);
      while (!POK(a)) {
#pragma unroll
        for (int i = 1; i < 8; i++) if (((a[i].x ^ tag) | (a[i].y ^ tag)) & 1u) a[i] = ldv2_relaxed(gp + (goff ^ (i * 2048)));
        spin_check(it);
      }
    }
    RSTAMP(15);
    {
#define AF(i, c) __uint_as_float(a[i].c)
      unsigned u = pack_bf16(((AF(0, x) + AF(1, x)) + (AF(2, x) + AF(3, x))) + ((AF(4, x) + AF(5, x)) + (AF(6, x) + AF(7, x))),
                             ((AF(0, y) + AF(1, y)) + (AF(2, y) + AF(3, y))) + ((AF(4, y) + AF(5, y)) + (AF(6, y) + AF(7, y))));
      __syncwarp();
#pragma unroll
      for (int i = 0; i < 8; i++) st_async_b32(mbA[i] + dlt, u, mbA[i]);
    }
    mbar_wait(bar + 8 * MB_KVF, par);
    mbar_wait(bar + 8 * MB_AG, par);
    if (t == 128) mbar_expect_tx(bar + 8 * MB_AG, 8192);
  }
}

__device__ __forceinline__ void rec_ring(const Maps& maps, unsigned sb, const int c) {
  const int h = c >> 1, j = c & 1;
  const unsigned bar = sb + SM_BAR;
  const int lane = threadIdx.x & 31;
  __syncwarp();
  bar_sync(2, 288);
  if (lane == 0) {
    fence_proxy_async_smem();
    for (int s = 0; s < NSEG; s++) {
      unsigned slot = s & (RING_N - 1);
      if ((s & 3) == 0 && !DBGMODE) {
        wait_flag_ge(&g_flags.qkv[(s >> 2) * 48 + 16 + (h >> 1)], 2);
        wait_flag_ge(&g_flags.qkv[(s >> 2) * 48 + 32 + (h >> 1)], 2);
        fence_proxy_async();
      }
      if (s >= RING_N) mbar_wait_sleep(bar + 8 * (MB_EMPTY + slot), ((s / RING_N) - 1) & 1);
      unsigned dst = sb + R_RING + slot * RING_BYTES, mb = bar + 8 * (MB_FULL + slot);
      mbar_expect_tx(mb, RING_BYTES);
      tma_load_2d(dst, &maps.qkv_ld, HD + h * 128 + j * 64, s * SEG, mb);
      tma_load_2d(dst + 4096, &maps.qkv_ld, 2 * HD + h * 128, s * SEG, mb);
      tma_load_2d(dst + 8192, &maps.qkv_ld, 2 * HD + h * 128 + 64, s * SEG, mb);
    }
  }
}
__device__ __forceinline__ void rec_copy(unsigned sb, const int c) {
  const int h = c >> 1, j = c & 1;
  const unsigned bar = sb + SM_BAR;
  const int lane = threadIdx.x & 31;
  for (int s = 0; s < NSEG; s++) {
    if (s < NSEG - 1) mbar_wait_sleep(bar + 8 * MB_KVR, s & 1); else mbar_wait(bar + 8 * MB_KVR, s & 1);
    uint4 k0 = lds128(sb + R_KS + (lane >> 3) * 144 + (lane & 7) * 16), k1 = lds128(sb + R_KS + (4 + (lane >> 3)) * 144 + (lane & 7) * 16);
    uint2 v[4];
#pragma unroll
    for (int i = 0; i < 4; i++) v[i] = lds64(sb + R_VM + (j * 4 + i) * 256 + lane * 8);
    __syncwarp();
    if (lane == 0) mbar_arrive(bar + 8 * MB_KVF);
    bf16* kd = g_km + ((size_t)(s * NH + h) * NMEM) * DH + j * 64;
    *reinterpret_cast<uint4*>(kd + (lane >> 3) * DH + (lane & 7) * 8) = k0;
    *reinterpret_cast<uint4*>(kd + (4 + (lane >> 3)) * DH + (lane & 7) * 8) = k1;
    unsigned* vd = reinterpret_cast<unsigned*>(g_vmt) + ((size_t)(s * NH + h) * DH + j * 64) * 4;
#pragma unroll
    for (int i = 0; i < 4; i++) { vd[(i * 16) * 4 + lane] = v[i].x; vd[(i * 16 + 8) * 4 + lane] = v[i].y; }
    __syncwarp();
    if (lane == 0) st_release(&g_flags.rec[c], s + 1);
  }
}

__device__ __forceinline__ void bulk_producer(const Maps& maps, unsigned sb, int* misc) {
  const unsigned bar = sb + SM_BAR;
  const int lane = threadIdx.x & 31;
  unsigned st = 0, ph = 0, seq = 0;
  while (true) {
    int idx = 0;
    if (lane == 0) idx = (int)atomicAdd(&g_flags.ctr, 1u);
    idx = __shfl_sync(~0u, idx, 0);
    if (idx >= N_ITEMS) {
      if (lane == 0) {
        mbar_wait(bar + 8 * (MB_EMPTY + st), ph ^ 1);
        misc[seq & 3] = -1;
        mbar_arrive(bar + 8 * (MB_FULL + st));
      }
      break;
    }
    if (lane == 0) ISTAMP(idx, 0);
    Item it = decode_item(idx);
    if (it.b < 0) continue;
    const CUtensorMap* mp; int c0, c1, dc0, dc1; unsigned doff;
    const unsigned* fl = nullptr; unsigned tgt = 1; int nbox = 5, rdy = 0;
    if (it.type == T_ATT) {
      mp = &maps.qkv_ld; nbox = 12; doff = lane * 4096;
      c0 = (lane >> 2) * HD + it.c * 256 + (lane & 1) * 64; c1 = it.b * 128 + ((lane >> 1) & 1) * 32; dc0 = dc1 = 0;
      if (lane < 3) fl = &g_flags.qkv[it.b * 48 + lane * 16 + it.c];
      tgt = 2;
      bool ok = true;
      if (lane >= 4 && lane < 8) ok = ld_acquire(&g_flags.rec[it.c * 4 + lane - 4]) >= (unsigned)(it.b * 4 + 4);
      rdy = __all_sync(~0u, ok) ? 65536 : 0;
    } else {
      int k0 = 0, nb0 = it.c * 256;
      if (it.type == T_QKV) { mp = lane == 0 ? &maps.xn : (it.c < 16 ? &maps.wq : (it.c < 32 ? &maps.wk : &maps.wv)); nb0 = (it.c & 15) * 256; }
      else if (it.type == T_M1) mp = lane == 0 ? &maps.y : &maps.w1;
      else if (it.type == T_M2) { mp = lane == 0 ? &maps.h1 : &maps.w2; fl = &g_flags.h1[it.b]; tgt = 7; }
      else {
        mp = lane == 0 ? &maps.o : &maps.wo;
        if (it.type == T_OUT) { k0 = it.ks * 1024; fl = &g_flags.o[it.b * 4 + it.ks]; tgt = 4; }
        else if (it.type == T_OUTL) { k0 = it.ks * 256; fl = &g_flags.o16[it.ks]; }
        else if (lane == 1) { fl = &g_flags.g[it.b]; tgt = 2; }
        else { fl = &g_flags.p[it.b]; tgt = it.type == T_RED ? 8 : 64; }
      }
      if (lane > (it.type >= T_RED ? 1 : 0)) fl = nullptr;
      if (it.hf) { nbox = 3; nb0 += (it.hf - 1) * 128; }
      if (lane == 0) { c0 = k0; c1 = it.b * 128; dc0 = 64; dc1 = 0; doff = 0; }
      else { c0 = nb0 + (lane - 1) * 64; c1 = k0; dc0 = 0; dc1 = 64; doff = 8192 + lane * 8192; }
    }
    if (fl) wait_flag_ge(fl, tgt);
    __syncwarp();
    fence_proxy_async();
    if (lane == 0) ISTAMP(idx, 1);
    const int nkb = item_nkb(it.type);
    for (int kb = 0; kb < nkb; kb++) {
      const unsigned mb = bar + 8 * (MB_FULL + st);
      mbar_wait(bar + 8 * (MB_EMPTY + st), ph ^ 1);
      if (lane == 0) {
        if (kb == 0) misc[seq & 3] = idx | rdy;
        if (it.type >= T_RED) mbar_arrive(mb); else mbar_expect_tx(mb, it.hf ? 32768 : STAGE_BYTES);
      }
      if (it.type == T_ATT) { if (lane < 12) tma_load_2d(sb + st * STAGE_BYTES + doff, mp, c0 + (kb & 1) * 128, c1 + (kb >> 1) * 64, mb); }
      else if (lane < nbox && it.type < T_RED) tma_load_2d(sb + st * STAGE_BYTES + doff, mp, c0 + kb * dc0, c1 + kb * dc1, mb);
      __syncwarp();
      if (++st == NSTAGE) { st = 0; ph ^= 1; }
    }
    seq++;
  }
}
__device__ __forceinline__ void bulk_store(const Maps& maps, unsigned sb, volatile int* misc) {
  const unsigned bar = sb + SM_BAR;
  unsigned ph = 0;
  while (true) {
    mbar_wait(bar + 8 * MB_STGF, ph); ph ^= 1;
    int idx = misc[4];
    if (idx < 0) break;
    Item it = decode_item(idx);
    const CUtensorMap* mp = it.type == T_QKV ? &maps.qkv_st : (it.type == T_M1 ? &maps.h1 : (it.type == T_M2 ? &maps.g : &maps.o));
    unsigned* flag = it.type == T_QKV ? &g_flags.qkv[it.b * 48 + it.c] : (it.type == T_M1 ? &g_flags.h1[it.b] : (it.type == T_M2 ? &g_flags.g[it.b] : (it.b == 15 ? &g_flags.o16[it.c] : &g_flags.o[it.b * 4 + (it.c >> 2)])));
    for (int i = 0; i < (it.hf ? 2 : 4); i++) tma_store_2d(mp, sb + B_STG + i * 16384, it.c * 256 + (it.hf >> 1) * 128 + i * 64, it.b * 128);
    asm volatile("cp.async.bulk.commit_group;" ::: "memory");
    asm volatile("cp.async.bulk.wait_group.read 0;" ::: "memory");
    mbar_arrive(bar + 8 * MB_STGE);
    asm volatile("cp.async.bulk.wait_group 0;" ::: "memory");
    fence_proxy_async();
    red_release_add(flag, it.type == T_QKV && !it.hf ? 2 : 1);
    ISTAMP(idx, 3);
  }
}
__device__ __forceinline__ float rcpf(float x) { float y; asm("rcp.approx.ftz.f32 %0, %1;" : "=f"(y) : "f"(x)); return y; }
__device__ __forceinline__ float gelu_t(float x) {
  float e = ex2f(x * fmaf(x * x, -2.0f * LOG2E * 0.7978845608028654f * 0.044715f, -2.0f * LOG2E * 0.7978845608028654f));
  return x * rcpf(1.0f + e);
}
__device__ __forceinline__ float silu_f(float x) { return x * rcpf(1.0f + ex2f(-LOG2E * x)); }
__device__ __forceinline__ unsigned badd2(unsigned a, unsigned b) { unsigned r; asm("add.rn.bf16x2 %0, %1, %2;" : "=r"(r) : "r"(a), "r"(b)); return r; }

__device__ __forceinline__ void final_out(bf16* __restrict__ out, const bf16* __restrict__ x, size_t o, float4 s) {
  uint2 gv = __ldcg(reinterpret_cast<const uint2*>(g_g + o)), xv = __ldg(reinterpret_cast<const uint2*>(x + o));
  uint2 r;
  r.x = pack_bf16(bf_lo(xv.x) + bf16r(bf16r(s.x) * bf_lo(gv.x)), bf_hi(xv.x) + bf16r(bf16r(s.y) * bf_hi(gv.x)));
  r.y = pack_bf16(bf_lo(xv.y) + bf16r(bf16r(s.z) * bf_lo(gv.y)), bf_hi(xv.y) + bf16r(bf16r(s.w) * bf_hi(gv.y)));
  *reinterpret_cast<uint2*>(out + o) = r;
}
__device__ __forceinline__ void bulk_att_load(unsigned* km, unsigned* vm, int b, int hp, int kb, int w, int lane) {
  const int g = lane >> 2, tq = lane & 3, seg = w >> 2, eh = w & 1;
  const int head = hp * 2 + (kb & 1), sg = b * 4 + (kb >> 1) * 2 + seg;
  const unsigned* kmp = reinterpret_cast<const unsigned*>(g_km + ((size_t)(sg * NH + head) * NMEM + g) * DH) + tq;
  const unsigned* vmp = reinterpret_cast<const unsigned*>(g_vmt) + ((size_t)(sg * NH + head) * DH + eh * 64) * 4 + lane;
#pragma unroll
  for (int i = 0; i < 16; i++) asm volatile("ld.global.cg.u32 %0, [%1];" : "=r"(km[i]) : "l"(kmp + i * 4) : "memory");
#pragma unroll
  for (int i = 0; i < 8; i++) asm volatile("ld.global.cg.u32 %0, [%1];" : "=r"(vm[i]) : "l"(vmp + i * 32) : "memory");
}
__device__ __forceinline__ void bulk_att_stage(unsigned sa, unsigned stg, const unsigned* km, const unsigned* vm, int kb, int w, int lane) {
  const int g = lane >> 2, tq = lane & 3, m = lane >> 3, r8 = lane & 7;
  const int seg = w >> 2, mt = (w >> 1) & 1, eh = w & 1;
  float s[5][4];
#pragma unroll
  for (int i = 0; i < 5; i++) { s[i][0] = s[i][1] = s[i][2] = s[i][3] = 0; }
  const unsigned qb = sa + (0 * 2 + seg) * 8192, kbs = sa + (1 * 2 + seg) * 8192, vb = sa + (2 * 2 + seg) * 8192 + eh * 4096;
  unsigned qa[8][4];
#pragma unroll
  for (int ks = 0; ks < 8; ks++) {
    int row = mt * 16 + (m & 1) * 8 + r8;
    ldsm_x4(qa[ks], qb + (ks >> 2) * 4096 + row * 128 + ((((ks & 3) * 2 + (m >> 1)) ^ r8) << 4));
    unsigned kf[4];
    int krow = (m >> 1) * 8 + r8;
    unsigned ka = kbs + (ks >> 2) * 4096 + krow * 128 + ((((ks & 3) * 2 + (m & 1)) ^ r8) << 4);
    ldsm_x4(kf, ka);
    mma16816(s[0], qa[ks], kf[0], kf[1]); mma16816(s[1], qa[ks], kf[2], kf[3]);
    if (mt) { ldsm_x4(kf, ka + 2048); mma16816(s[2], qa[ks], kf[0], kf[1]); mma16816(s[3], qa[ks], kf[2], kf[3]); }
  }
#pragma unroll
  for (int ks = 0; ks < 8; ks++) mma16816(s[4], qa[ks], km[2 * ks], km[2 * ks + 1]);
  float mx0 = -INFINITY, mx1 = -INFINITY;
  const int t0 = mt * 16 + g, t1 = t0 + 8;
#pragma unroll
  for (int i = 0; i < 5; i++) {
#pragma unroll
    for (int e = 0; e < 4; e++) {
      float v = s[i][e];
      if (i < 4) { int kj = i * 8 + 2 * tq + (e & 1); if (kj > (e < 2 ? t0 : t1)) v = -INFINITY; }
      s[i][e] = v;
      if (e < 2) mx0 = fmaxf(mx0, v); else mx1 = fmaxf(mx1, v);
    }
  }
  mx0 = fmaxf(mx0, __shfl_xor_sync(~0u, mx0, 1)); mx0 = fmaxf(mx0, __shfl_xor_sync(~0u, mx0, 2));
  mx1 = fmaxf(mx1, __shfl_xor_sync(~0u, mx1, 1)); mx1 = fmaxf(mx1, __shfl_xor_sync(~0u, mx1, 2));
  float sm0 = 0, sm1 = 0;
#pragma unroll
  for (int i = 0; i < 5; i++) {
    s[i][0] = ex2f((s[i][0] - mx0) * (SCALE_QK * LOG2E)); s[i][1] = ex2f((s[i][1] - mx0) * (SCALE_QK * LOG2E));
    s[i][2] = ex2f((s[i][2] - mx1) * (SCALE_QK * LOG2E)); s[i][3] = ex2f((s[i][3] - mx1) * (SCALE_QK * LOG2E));
    sm0 += s[i][0] + s[i][1]; sm1 += s[i][2] + s[i][3];
  }
  sm0 += __shfl_xor_sync(~0u, sm0, 1); sm0 += __shfl_xor_sync(~0u, sm0, 2);
  sm1 += __shfl_xor_sync(~0u, sm1, 1); sm1 += __shfl_xor_sync(~0u, sm1, 2);
  const float i0 = __fdividef(1.0f, sm0), i1 = __fdividef(1.0f, sm1);
  unsigned pa[2][4], pm0, pm1;
#pragma unroll
  for (int kk = 0; kk < 2; kk++) {
    pa[kk][0] = pack_bf16(s[2 * kk][0] * i0, s[2 * kk][1] * i0); pa[kk][1] = pack_bf16(s[2 * kk][2] * i1, s[2 * kk][3] * i1);
    pa[kk][2] = pack_bf16(s[2 * kk + 1][0] * i0, s[2 * kk + 1][1] * i0); pa[kk][3] = pack_bf16(s[2 * kk + 1][2] * i1, s[2 * kk + 1][3] * i1);
  }
  pm0 = pack_bf16(s[4][0] * i0, s[4][1] * i0); pm1 = pack_bf16(s[4][2] * i1, s[4][3] * i1);
  const int orow = (kb >> 1) * 64 + seg * 32 + mt * 16 + (m & 1) * 8 + r8;
  const unsigned ob = stg + ((kb & 1) * 2 + eh) * 16384 + orow * 128;
#pragma unroll
  for (int cp = 0; cp < 4; cp++) {
    float o0[4] = {0, 0, 0, 0}, o1[4] = {0, 0, 0, 0};
    mma1688(o0, pm0, pm1, vm[2 * cp]); mma1688(o1, pm0, pm1, vm[2 * cp + 1]);
    unsigned vf[4];
    int row = (m & 1) * 8 + r8;
    unsigned va = vb + row * 128 + (((cp * 2 + (m >> 1)) ^ r8) << 4);
    ldsm_x4_t(vf, va);
    mma16816(o0, pa[0], vf[0], vf[1]); mma16816(o1, pa[0], vf[2], vf[3]);
    if (mt) { ldsm_x4_t(vf, va + 2048); mma16816(o0, pa[1], vf[0], vf[1]); mma16816(o1, pa[1], vf[2], vf[3]); }
    stsm_x4(ob + (((cp * 2 + (m >> 1)) ^ r8) << 4), pack_bf16(o0[0], o0[1]), pack_bf16(o0[2], o0[3]), pack_bf16(o1[0], o1[1]), pack_bf16(o1[2], o1[3]));
  }
}

__device__ __forceinline__ void bulk_worker(unsigned sb, volatile int* misc, const bf16* __restrict__ x, const bf16* __restrict__ b1, const bf16* __restrict__ b2, bf16* __restrict__ out) {
  const int t = threadIdx.x, lane = t & 31, w = t >> 5, wg = w >> 2, g = lane >> 2, tq = lane & 3, m = lane >> 3, r8 = lane & 7;
  const unsigned bar = sb + SM_BAR;
  unsigned st = 0, ph = 0, seq = 0, sph = 0;
  float d[128];
  while (true) {
    mbar_wait(bar + 8 * (MB_FULL + st), ph);
    const int idr = misc[seq & 3]; seq++;
    const int idx = idr & 65535;
    if (idr < 0 || idx >= N_ITEMS) break;
    if (t == 0) ISTAMP(idx, 2);
    const Item it = decode_item(idx);
    const int nkb = item_nkb(it.type);
    if (it.type == T_ATT) {
      unsigned km[16], vm[8], kn[16], vn[8];
      const bool pref = idr >= 65536;
      if (pref) bulk_att_load(kn, vn, it.b, it.c, 0, w, lane);
      mbar_wait(bar + 8 * MB_STGE, sph ^ 1);
#pragma unroll 1
      for (int kb = 0; kb < 4; kb++) {
        if (!pref && !(kb & 1)) {
          if (lane < 4) wait_flag_ge(&g_flags.rec[it.c * 4 + lane], it.b * 4 + (kb >> 1) * 2 + wg + 1);
          __syncwarp();
          bulk_att_load(kn, vn, it.b, it.c, kb, w, lane);
        }
        if (kb) mbar_wait(bar + 8 * (MB_FULL + st), ph);
#pragma unroll
        for (int i = 0; i < 16; i++) km[i] = kn[i];
#pragma unroll
        for (int i = 0; i < 8; i++) vm[i] = vn[i];
        if (pref ? kb != 3 : !(kb & 1)) bulk_att_load(kn, vn, it.b, it.c, kb + 1, w, lane);
        bulk_att_stage(sb + st * STAGE_BYTES, sb + B_STG, km, vm, kb, w, lane);
        __syncwarp();
        if (lane == 0) mbar_arrive(bar + 8 * (MB_EMPTY + st));
        if (++st == NSTAGE) { st = 0; ph ^= 1; }
      }
      if (t == 0) misc[4] = idx;
      fence_proxy_async_smem();
      mbar_arrive(bar + 8 * MB_STGF); sph ^= 1;
      continue;
    }
    if (it.type >= T_RED) {
      __syncwarp();
      if (lane == 0) mbar_arrive(bar + 8 * (MB_EMPTY + st));
      if (++st == NSTAGE) { st = 0; ph ^= 1; }
      if (it.type == T_RED) {
#pragma unroll 2
        for (int i = 0; i < 8; i++) {
          size_t o = ((size_t)it.b * 128 + it.c * 16 + i * 2 + (t >> 7)) * DM + (t & 127) * 4;
          float4 a = __ldcg(reinterpret_cast<const float4*>(g_opart + o)), b = __ldcg(reinterpret_cast<const float4*>(g_opart + o + (size_t)S_TOK * DM));
          float4 c = __ldcg(reinterpret_cast<const float4*>(g_opart + o + (size_t)2 * S_TOK * DM)), e = __ldcg(reinterpret_cast<const float4*>(g_opart + o + (size_t)3 * S_TOK * DM));
          final_out(out, x, o, make_float4((a.x + b.x) + (c.x + e.x), (a.y + b.y) + (c.y + e.y), (a.z + b.z) + (c.z + e.z), (a.w + b.w) + (c.w + e.w)));
        }
      } else {
        size_t ol = ((size_t)it.c * 2 + (t >> 7)) * DM + (t & 127) * 4;
        float4 v[16];
#pragma unroll
        for (int i = 0; i < 16; i++) v[i] = __ldcg(reinterpret_cast<const float4*>(g_opl + ol + (size_t)i * 128 * DM));
#pragma unroll
        for (int st2 = 1; st2 < 16; st2 <<= 1)
#pragma unroll
          for (int i = 0; i < 16; i += 2 * st2) { v[i].x += v[i + st2].x; v[i].y += v[i + st2].y; v[i].z += v[i + st2].z; v[i].w += v[i + st2].w; }
        final_out(out, x, ol + (size_t)15 * 128 * DM, v[0]);
      }
      if (t == 0) ISTAMP(idx, 3);
      continue;
    }
    unsigned pst = 0, bv[32];
#pragma unroll
    for (int i = 0; i < 128; i++) d[i] = 0.0f;
    if (it.type == T_M1 || it.type == T_M2) {
      const unsigned* bp = reinterpret_cast<const unsigned*>((it.type == T_M1 ? b1 : b2) + it.c * 256) + tq;
#pragma unroll
      for (int i = 0; i < 32; i++) asm volatile("ld.global.nc.u32 %0, [%1];" : "=r"(bv[i]) : "l"(bp + i * 4));
    } else {
#pragma unroll
      for (int i = 0; i < 32; i++) bv[i] = 0;
    }
#define KLOOP(WG) \
    for (int kb = 0; kb < nkb; kb++) { \
      if (kb) mbar_wait(bar + 8 * (MB_FULL + st), ph); \
      unsigned sa = sb + st * STAGE_BYTES; \
      uint64_t ad = mkdesc(sa + wg * 8192, 16, 1024), bd = mkdesc(sa + 16384, 8192, 1024); \
      asm volatile("wgmma.fence.sync.aligned;" ::: "memory"); \
      _Pragma("unroll") for (int k = 0; k < 4; k++) WG(d, ad + k * 2, bd + k * 128, (kb | k) != 0); \
      asm volatile("wgmma.commit_group.sync.aligned;" ::: "memory"); \
      if (kb) { \
        asm volatile("wgmma.wait_group.sync.aligned 1;" ::: "memory"); \
        if (lane == 0) mbar_arrive(bar + 8 * (MB_EMPTY + pst)); \
      } \
      pst = st; \
      if (++st == NSTAGE) { st = 0; ph ^= 1; } \
    } \
    asm volatile("wgmma.wait_group.sync.aligned 0;" ::: "memory");
    if (it.hf) { KLOOP(wgmma_n128) } else { KLOOP(wgmma_n256) }
    if (lane == 0) mbar_arrive(bar + 8 * (MB_EMPTY + pst));
    if (it.type >= T_OUT) {
      const int col = it.c * 256 + (it.hf >> 1) * 128 + 2 * tq;
      float* pp = it.type == T_OUT ? g_opart + ((size_t)it.ks * S_TOK + it.b * 128 + w * 16 + g) * DM + col : g_opl + ((size_t)it.ks * 128 + w * 16 + g) * DM + col;
#pragma unroll
      for (int i = 0; i < 32; i++) {
        if (i == 16 && it.hf) break;
        __stcg(reinterpret_cast<float2*>(pp + i * 8), make_float2(d[4 * i], d[4 * i + 1]));
        __stcg(reinterpret_cast<float2*>(pp + 8 * DM + i * 8), make_float2(d[4 * i + 2], d[4 * i + 3]));
      }
      bar_sync(1, 256);
      if (t == 0) { red_release_add(&g_flags.p[it.b], 1); ISTAMP(idx, 3); }
      continue;
    }
#define ACT(F) _Pragma("unroll") for (int i = 0; i < 32; i++) { \
        unsigned u0 = badd2(pack_bf16(d[4 * i], d[4 * i + 1]), bv[i]), u1 = badd2(pack_bf16(d[4 * i + 2], d[4 * i + 3]), bv[i]); \
        d[4 * i] = F(bf_lo(u0)); d[4 * i + 1] = F(bf_hi(u0)); d[4 * i + 2] = F(bf_lo(u1)); d[4 * i + 3] = F(bf_hi(u1)); }
    if (it.type == T_M1) { ACT(gelu_t) } else if (it.type == T_M2) { ACT(silu_f) }
    mbar_wait(bar + 8 * MB_STGE, sph ^ 1);
    {
      const unsigned ob = sb + B_STG + (w * 16 + (m & 1) * 8 + r8) * 128;
#pragma unroll
      for (int i = 0; i < 16; i++)
        if (i < 8 || !it.hf) stsm_x4(ob + (i >> 2) * 16384 + ((((i & 3) * 2 + (m >> 1)) ^ r8) << 4), pack_bf16(d[8 * i], d[8 * i + 1]), pack_bf16(d[8 * i + 2], d[8 * i + 3]),
                pack_bf16(d[8 * i + 4], d[8 * i + 5]), pack_bf16(d[8 * i + 6], d[8 * i + 7]));
    }
    if (t == 0) misc[4] = idx;
    fence_proxy_async_smem();
    mbar_arrive(bar + 8 * MB_STGF); sph ^= 1;
  }
  mbar_wait(bar + 8 * MB_STGE, sph ^ 1);
  if (t == 0) misc[4] = -1;
  mbar_arrive(bar + 8 * MB_STGF);
}

__global__ void __launch_bounds__(384, 1)
k_main(const __grid_constant__ Maps maps, const bf16* __restrict__ x, const bf16* __restrict__ mem0, const bf16* __restrict__ b1, const bf16* __restrict__ b2, bf16* __restrict__ out, unsigned recmask) {
  extern __shared__ unsigned char smem_raw[];
  const unsigned sraw = smem_u32(smem_raw);
  const unsigned sb = (sraw + 1023u) & ~1023u;
  int* misc = reinterpret_cast<int*>(smem_raw + (sb - sraw) + SM_MISC);
  const int w = threadIdx.x >> 5;
  const bool helper = recmask == 0;
  const unsigned kc = blockIdx.x / CLS;
  const bool rec = kc < 32 && ((recmask >> kc) & 1);
  const int c = __popc(recmask & ((1u << (kc & 31)) - 1)) * CLS + (blockIdx.x & (CLS - 1));
  if (threadIdx.x == 0) {
    const unsigned bar = sb + SM_BAR;
    for (int i = 0; i < 8; i++) { mbar_init(bar + 8 * (MB_FULL + i), 1); mbar_init(bar + 8 * (MB_EMPTY + i), rec ? 1 : 8); }
    mbar_init(bar + 8 * MB_STGF, 256); mbar_init(bar + 8 * MB_STGE, 1);
    for (int i = MB_W0; i <= MB_AG; i++) mbar_init(bar + 8 * i, 1);
    if (rec) { mbar_expect_tx(bar + 8 * MB_S, 2560); mbar_expect_tx(bar + 8 * MB_V, 2048); mbar_expect_tx(bar + 8 * MB_RS, 8192); mbar_expect_tx(bar + 8 * MB_AG, 8192); }
    asm volatile("fence.mbarrier_init.release.cluster;" ::: "memory");
  }
  __syncthreads();
  asm volatile("barrier.cluster.arrive.release.aligned;\nbarrier.cluster.wait.acquire.aligned;" ::: "memory");
  if (rec && threadIdx.x == 256) {
    const unsigned bar = sb + SM_BAR; const int col = c * 64;
    mbar_expect_tx(bar + 8 * MB_W0, 131072);
    for (int kb = 0; kb < 8; kb++) tma_load_2d(sb + R_WO + kb * 8192, &maps.wq, col, kb * 64, bar + 8 * MB_W0);
    for (int kb = 0; kb < 8; kb++) tma_load_2d(sb + R_T1 + kb * 8192, &maps.wk, col, kb * 64, bar + 8 * MB_W0);
    mbar_expect_tx(bar + 8 * MB_W1, 65536);
    for (int kb = 0; kb < 8; kb++) tma_load_2d(sb + R_T2 + kb * 8192, &maps.wv, col, kb * 64, bar + 8 * MB_W1);
  }
  if (!helper) {
    asm volatile("griddepcontrol.wait;" ::: "memory");
    asm volatile("griddepcontrol.launch_dependents;");
  }
  if (DBGMODE && !rec) { if (helper) asm volatile("griddepcontrol.wait;" ::: "memory"); return; }
  if (w >= 8) {
    asm volatile("setmaxnreg.dec.sync.aligned.u32 24;");
    if (rec) { if (w == 8) rec_ring(maps, sb, c); else if (w == 9) rec_copy(sb, c); }
    else if (w == 8) bulk_producer(maps, sb, misc);
    else if ((threadIdx.x & 31) == 0) { if (w == 9) bulk_store(maps, sb, misc);
      else if (w == 10 && helper) asm volatile("griddepcontrol.wait;" ::: "memory"); }
  } else {
    if (rec) { asm volatile("setmaxnreg.inc.sync.aligned.u32 240;"); rec_worker(maps, sb, mem0, c); }
    else { asm volatile("setmaxnreg.inc.sync.aligned.u32 240;"); bulk_worker(sb, misc, x, b1, b2, out); }
  }
}

typedef CUresult (*EncFn)(CUtensorMap*, CUtensorMapDataType, cuuint32_t, void*, const cuuint64_t*, const cuuint64_t*, const cuuint32_t*, const cuuint32_t*,
                          CUtensorMapInterleave, CUtensorMapSwizzle, CUtensorMapL2promotion, CUtensorMapFloatOOBfill);
static void mk_map(EncFn enc, CUtensorMap* m, const void* ptr, uint64_t rows, uint64_t cols, uint32_t box_rows) {
  cuuint64_t dims[2] = {cols, rows}; cuuint64_t strides[1] = {cols * 2};
  cuuint32_t box[2] = {64, box_rows}, es[2] = {1, 1};
  enc(m, CU_TENSOR_MAP_DATA_TYPE_BFLOAT16, 2, const_cast<void*>(ptr), dims, strides, box, es, CU_TENSOR_MAP_INTERLEAVE_NONE, CU_TENSOR_MAP_SWIZZLE_128B,
      CU_TENSOR_MAP_L2_PROMOTION_L2_256B, CU_TENSOR_MAP_FLOAT_OOB_FILL_NONE);
}
extern "C" void kernel_launch(void* const* d_in, const int* in_sizes, int n_in, void* d_out, int out_size) {
  static EncFn enc = nullptr;
  static int ncl = 0, nhelp = 0;
  static unsigned recmask = 0xFFu;
  static void *p_xn, *p_y, *p_h1, *p_o, *p_qkv, *p_g;
  if (!enc) {
    void* fn = nullptr; cudaDriverEntryPointQueryResult qr;
    cudaGetDriverEntryPoint("cuTensorMapEncodeTiled", &fn, cudaEnableDefault, &qr);
    enc = (EncFn)fn;
    cudaGetSymbolAddress(&p_xn, g_xn); cudaGetSymbolAddress(&p_y, g_y); cudaGetSymbolAddress(&p_h1, g_h1);
    cudaGetSymbolAddress(&p_o, g_o); cudaGetSymbolAddress(&p_qkv, g_qkv); cudaGetSymbolAddress(&p_g, g_g);
    cudaFuncSetAttribute(k_main, cudaFuncAttributeMaxDynamicSharedMemorySize, SMEM_TOTAL);
    cudaLaunchConfig_t cfg = {}; cfg.gridDim = dim3(128); cfg.blockDim = dim3(384); cfg.dynamicSmemBytes = SMEM_TOTAL;
    cudaLaunchAttribute at[1]; at[0].id = cudaLaunchAttributeClusterDimension; at[0].val.clusterDim.x = CLS; at[0].val.clusterDim.y = 1; at[0].val.clusterDim.z = 1;
    cfg.attrs = at; cfg.numAttrs = 1;
    if (cudaOccupancyMaxActiveClusters(&ncl, k_main, &cfg) != cudaSuccess) { cudaGetLastError(); ncl = 14; }
    ncl = ncl > 16 ? 16 : (ncl < 9 ? 9 : ncl);
    int nsm = 0, dev = 0; cudaGetDevice(&dev); cudaDeviceGetAttribute(&nsm, cudaDevAttrMultiProcessorCount, dev);
    nhelp = nsm - ncl * CLS;
  }
  Maps maps;
  mk_map(enc, &maps.xn, p_xn, S_TOK, DM, 128); mk_map(enc, &maps.y, p_y, S_TOK, DM, 128); mk_map(enc, &maps.h1, p_h1, S_TOK, FF, 128);
  mk_map(enc, &maps.o, p_o, S_TOK, HD, 128); mk_map(enc, &maps.qkv_st, p_qkv, S_TOK, 3 * HD, 128); mk_map(enc, &maps.qkv_ld, p_qkv, S_TOK, 3 * HD, 32);
  mk_map(enc, &maps.g, p_g, S_TOK, DM, 128);
  mk_map(enc, &maps.wq, d_in[2], DM, HD, 64); mk_map(enc, &maps.wk, d_in[3], DM, HD, 64); mk_map(enc, &maps.wv, d_in[4], DM, HD, 64);
  mk_map(enc, &maps.wo, d_in[5], HD, DM, 64); mk_map(enc, &maps.w1, d_in[8], DM, FF, 64); mk_map(enc, &maps.w2, d_in[10], FF, DM, 64);
  cudaStream_t st = cudaStreamPerThread;
  k_pre<<<256, 256, 0, st>>>((const bf16*)d_in[0], (const char*)d_in[2], (const char*)d_in[3], (const char*)d_in[4], (const char*)d_in[5]);
  cudaLaunchConfig_t cfg = {}; cfg.gridDim = dim3(ncl * CLS); cfg.blockDim = dim3(384); cfg.dynamicSmemBytes = SMEM_TOTAL; cfg.stream = st;
  cudaLaunchAttribute at[2]; at[1].id = cudaLaunchAttributeClusterDimension; at[1].val.clusterDim.x = CLS; at[1].val.clusterDim.y = 1; at[1].val.clusterDim.z = 1;
  at[0].id = cudaLaunchAttributeProgrammaticStreamSerialization; at[0].val.programmaticStreamSerializationAllowed = 1;
#define PDL1 0
  cfg.attrs = at + (PDL1 ? 0 : 1); cfg.numAttrs = PDL1 ? 2 : 1;
  cudaLaunchKernelEx(&cfg, k_main, maps, (const bf16*)d_in[0], (const bf16*)d_in[1], (const bf16*)d_in[9], (const bf16*)d_in[11], (bf16*)d_out, recmask);
  if (nhelp > 0) {
    cfg.gridDim = dim3(nhelp);
    cfg.attrs = at; cfg.numAttrs = 1;
    cudaLaunchKernelEx(&cfg, k_main, maps, (const bf16*)d_in[0], (const bf16*)d_in[1], (const bf16*)d_in[9], (const bf16*)d_in[11], (bf16*)d_out, 0u);
  }
}
```

```cpp
#include <cuda_runtime.h>
#include <cuda_bf16.h>
#include <cuda.h>
#include <stdint.h>

typedef __nv_bfloat16 bf16;

#define S_TOK 2048
#define DM 512
#define NH 32
#define DH 128
#define HD 4096
#define NMEM 8
#define SEG 32
#define NSEG 64
#define FF 1792
#define NBLK 16
#define NREC 64
#define REPL 0
#define CLS 8

__device__ __align__(1024) bf16 g_xn[S_TOK * DM];
__device__ __align__(1024) bf16 g_y[S_TOK * DM];
__device__ __align__(1024) bf16 g_qkv[(size_t)S_TOK * 3 * HD];
__device__ __align__(1024) bf16 g_h1[S_TOK * FF];
__device__ __align__(1024) bf16 g_g[S_TOK * DM];
__device__ __align__(1024) bf16 g_o[(size_t)S_TOK * HD];
__device__ __align__(1024) bf16 g_km[NSEG * NH * NMEM * DH];
__device__ __align__(1024) bf16 g_vmt[NSEG * NH * DH * NMEM];
__device__ __align__(1024) float g_opart[(size_t)4 * S_TOK * DM];
__device__ __align__(1024) float g_opl[(size_t)16 * 128 * DM];
__device__ __align__(1024) unsigned g_part[8 * 2 * 8 * 8 * 512];
struct Flags {
  unsigned qkv[NBLK * 48];
  unsigned h1[NBLK];
  unsigned g[NBLK];
  unsigned o[NBLK * 4];
  unsigned p[NBLK];
  unsigned o16[16];
  unsigned ctr;
  unsigned rec[NREC];
  unsigned abort_;
};
__device__ __align__(1024) Flags g_flags;

#define RSTAMP(k)
#define DBGMODE 0
#define ISTAMP(i, k)
__device__ __forceinline__ unsigned smem_u32(const void* p) { return (unsigned)__cvta_generic_to_shared(p); }
__device__ __forceinline__ float bf16r(float x) { unsigned u; asm("cvt.rn.bf16x2.f32 %0, %1, %2;" : "=r"(u) : "f"(x), "f"(0.0f)); return __uint_as_float(u); }
__device__ __forceinline__ unsigned pack_bf16(float lo, float hi) {
  __nv_bfloat162 v = __floats2bfloat162_rn(lo, hi);
  return *reinterpret_cast<unsigned*>(&v);
}
__device__ __forceinline__ float bf_lo(unsigned u) { return __uint_as_float(u << 16); }
__device__ __forceinline__ float bf_hi(unsigned u) { return __uint_as_float(u & 0xffff0000u); }

#define SPIN_LIMIT (1u << 20)
#define TRAP_IF(x) if ((x) > SPIN_LIMIT) { asm volatile("st.global.u32 [%0], %1;" ::"l"(0ull), "r"(0u) : "memory"); break; }
__device__ __forceinline__ unsigned ld_acquire(const unsigned* p) {
  unsigned v; asm volatile("ld.acquire.gpu.global.u32 %0, [%1];" : "=r"(v) : "l"(p) : "memory"); return v;
}
__device__ __forceinline__ unsigned ld_relaxed(const unsigned* p) {
  unsigned v; asm volatile("ld.relaxed.gpu.global.u32 %0, [%1];" : "=r"(v) : "l"(p) : "memory"); return v;
}
__device__ __forceinline__ void red_release_add(unsigned* p, unsigned v) {
  asm volatile("red.release.gpu.global.add.u32 [%0], %1;" ::"l"(p), "r"(v) : "memory");
}
__device__ __forceinline__ void st_release(unsigned* p, unsigned v) {
  asm volatile("st.release.gpu.global.u32 [%0], %1;" ::"l"(p), "r"(v) : "memory");
}
__device__ __forceinline__ void wait_flag_ge(const unsigned* p, unsigned target) {
  unsigned it = 0;
  while (ld_acquire(p) < target) {
    __nanosleep(64);
    TRAP_IF(++it);
  }
}
__device__ __forceinline__ uint4 ldv4_relaxed(const void* p) {
  uint4 a; asm volatile("ld.relaxed.gpu.global.v4.u32 {%0,%1,%2,%3}, [%4];" : "=r"(a.x), "=r"(a.y), "=r"(a.z), "=r"(a.w) : "l"(p) : "memory"); return a;
}
__device__ __forceinline__ uint2 ldv2_relaxed(const void* p) {
  uint2 a; asm volatile("ld.relaxed.gpu.global.v2.u32 {%0,%1}, [%2];" : "=r"(a.x), "=r"(a.y) : "l"(p) : "memory"); return a;
}
__device__ __forceinline__ void mbar_init(unsigned mb, unsigned cnt) { asm volatile("mbarrier.init.shared::cta.b64 [%0], %1;" ::"r"(mb), "r"(cnt) : "memory"); }
__device__ __forceinline__ void mbar_expect_tx(unsigned mb, unsigned bytes) { asm volatile("mbarrier.arrive.expect_tx.shared::cta.b64 _, [%0], %1;" ::"r"(mb), "r"(bytes) : "memory"); }
__device__ __forceinline__ void mbar_arrive(unsigned mb) { asm volatile("mbarrier.arrive.shared::cta.b64 _, [%0];" ::"r"(mb) : "memory"); }
__device__ __forceinline__ void mbar_wait(unsigned mb, unsigned parity) {
  unsigned ok, it = 0;
  while (true) {
    asm volatile("{.reg .pred p; mbarrier.try_wait.parity.shared::cta.b64 p, [%1], %2; selp.u32 %0,1,0,p;}" : "=r"(ok) : "r"(mb), "r"(parity) : "memory");
    if (ok) break;
    TRAP_IF(++it);
  }
}
__device__ __forceinline__ void mbar_wait_sleep(unsigned mb, unsigned parity) {
  unsigned ok, it = 0;
  while (true) {
    asm volatile("{.reg .pred p; mbarrier.test_wait.parity.shared::cta.b64 p, [%1], %2; selp.u32 %0,1,0,p;}" : "=r"(ok) : "r"(mb), "r"(parity) : "memory");
    if (ok) break;
    __nanosleep(200);
    TRAP_IF(++it);
  }
}
__device__ __forceinline__ float ex2f(float x) { float y; asm("ex2.approx.ftz.f32 %0, %1;" : "=f"(y) : "f"(x)); return y; }
__device__ __forceinline__ int opaque_tid() { int t = threadIdx.x; t = __shfl_sync(~0u, t, t & 31); return t; }
#define LOG2E 1.4426950408889634f
__device__ __forceinline__ void mbar_wait_cluster(unsigned mb, unsigned parity) {
  unsigned ok, it = 0;
  while (true) {
    asm volatile("{.reg .pred p; mbarrier.try_wait.parity.acquire.cluster.shared::cta.b64 p, [%1], %2; selp.u32 %0,1,0,p;}" : "=r"(ok) : "r"(mb), "r"(parity) : "memory");
    if (ok) break;
    TRAP_IF(++it);
  }
}
__device__ __forceinline__ void bar_sync(int id, int n) { asm volatile("bar.sync %0, %1;" ::"r"(id), "r"(n) : "memory"); }
__device__ __forceinline__ void bar_arrive(int id, int n) { asm volatile("bar.arrive %0, %1;" ::"r"(id), "r"(n) : "memory"); }
__device__ __forceinline__ void tma_load_2d(unsigned dst, const CUtensorMap* map, int c0, int c1, unsigned mb) {
  asm volatile("cp.async.bulk.tensor.2d.shared::cluster.global.mbarrier::complete_tx::bytes [%0], [%1, {%3, %4}], [%2];"
               ::"r"(dst), "l"((uint64_t)map), "r"(mb), "r"(c0), "r"(c1) : "memory");
}
__device__ __forceinline__ void tma_store_2d(const CUtensorMap* map, unsigned src, int c0, int c1) {
  asm volatile("cp.async.bulk.tensor.2d.global.shared::cta.bulk_group [%0, {%2, %3}], [%1];"
               ::"l"((uint64_t)map), "r"(src), "r"(c0), "r"(c1) : "memory");
}
__device__ __forceinline__ void fence_proxy_async() { asm volatile("fence.proxy.async;" ::: "memory"); }
__device__ __forceinline__ void fence_proxy_async_smem() { asm volatile("fence.proxy.async.shared::cta;" ::: "memory"); }
__device__ __forceinline__ void ldsm_x4(unsigned* r, unsigned addr) {
  asm volatile("ldmatrix.sync.aligned.m8n8.x4.shared.b16 {%0,%1,%2,%3}, [%4];" : "=r"(r[0]), "=r"(r[1]), "=r"(r[2]), "=r"(r[3]) : "r"(addr) : "memory");
}
__device__ __forceinline__ void ldsm_x4_t(unsigned* r, unsigned addr) {
  asm volatile("ldmatrix.sync.aligned.m8n8.x4.trans.shared.b16 {%0,%1,%2,%3}, [%4];" : "=r"(r[0]), "=r"(r[1]), "=r"(r[2]), "=r"(r[3]) : "r"(addr) : "memory");
}
__device__ __forceinline__ void stsm_x2_t(unsigned addr, unsigned r0, unsigned r1) {
  asm volatile("stmatrix.sync.aligned.m8n8.x2.trans.shared.b16 [%0], {%1,%2};" ::"r"(addr), "r"(r0), "r"(r1) : "memory");
}
__device__ __forceinline__ void stsm_x4(unsigned addr, unsigned r0, unsigned r1, unsigned r2, unsigned r3) {
  asm volatile("stmatrix.sync.aligned.m8n8.x4.shared.b16 [%0], {%1,%2,%3,%4};" ::"r"(addr), "r"(r0), "r"(r1), "r"(r2), "r"(r3) : "memory");
}
__device__ __forceinline__ void mma16816(float* d, const unsigned* a, unsigned b0, unsigned b1) {
  asm volatile("mma.sync.aligned.m16n8k16.row.col.f32.bf16.bf16.f32 {%0,%1,%2,%3}, {%4,%5,%6,%7}, {%8,%9}, {%0,%1,%2,%3};"
               : "+f"(d[0]), "+f"(d[1]), "+f"(d[2]), "+f"(d[3]) : "r"(a[0]), "r"(a[1]), "r"(a[2]), "r"(a[3]), "r"(b0), "r"(b1));
}
__device__ __forceinline__ void mma1688(float* d, unsigned a0, unsigned a1, unsigned b0) {
  asm volatile("mma.sync.aligned.m16n8k8.row.col.f32.bf16.bf16.f32 {%0,%1,%2,%3}, {%4,%5}, {%6}, {%0,%1,%2,%3};"
               : "+f"(d[0]), "+f"(d[1]), "+f"(d[2]), "+f"(d[3]) : "r"(a0), "r"(a1), "r"(b0));
}
__device__ __forceinline__ uint64_t mkdesc(unsigned addr, unsigned lbo, unsigned sbo) {
  return (uint64_t)((addr >> 4) & 0x3fff) | ((uint64_t)(lbo >> 4) << 16) | ((uint64_t)(sbo >> 4) << 32) | (1ull << 62);
}
#define R8(b) "+f"(d[b]), "+f"(d[b + 1]), "+f"(d[b + 2]), "+f"(d[b + 3]), "+f"(d[b + 4]), "+f"(d[b + 5]), "+f"(d[b + 6]), "+f"(d[b + 7])
#define R32(b) R8(b), R8(b + 8), R8(b + 16), R8(b + 24)
__device__ __forceinline__ void wgmma_n256(float* d, uint64_t ad, uint64_t bd, int acc) {
  asm volatile(
      "{.reg .pred p; setp.ne.b32 p, %130, 0;\n"
      "wgmma.mma_async.sync.aligned.m64n256k16.f32.bf16.bf16 "
      "{%0,%1,%2,%3,%4,%5,%6,%7,%8,%9,%10,%11,%12,%13,%14,%15,%16,%17,%18,%19,%20,%21,%22,%23,%24,%25,%26,%27,%28,%29,%30,%31,"
      "%32,%33,%34,%35,%36,%37,%38,%39,%40,%41,%42,%43,%44,%45,%46,%47,%48,%49,%50,%51,%52,%53,%54,%55,%56,%57,%58,%59,%60,%61,%62,%63,"
      "%64,%65,%66,%67,%68,%69,%70,%71,%72,%73,%74,%75,%76,%77,%78,%79,%80,%81,%82,%83,%84,%85,%86,%87,%88,%89,%90,%91,%92,%93,%94,%95,"
      "%96,%97,%98,%99,%100,%101,%102,%103,%104,%105,%106,%107,%108,%109,%110,%111,%112,%113,%114,%115,%116,%117,%118,%119,%120,%121,%122,%123,%124,%125,%126,%127},"
      "%128, %129, p, 1, 1, 0, 1;}\n"
      : R32(0), R32(32), R32(64), R32(96)
      : "l"(ad), "l"(bd), "r"(acc));
}

__device__ __forceinline__ void wgmma_n128(float* d, uint64_t ad, uint64_t bd, int acc) {
  asm volatile(
      "{.reg .pred p; setp.ne.b32 p, %66, 0;\n"
      "wgmma.mma_async.sync.aligned.m64n128k16.f32.bf16.bf16 {%0,%1,%2,%3,%4,%5,%6,%7,%8,%9,%10,%11,%12,%13,%14,%15,%16,%17,%18,%19,%20,%21,%22,%23,%24,%25,%26,%27,%28,%29,%30,%31,%32,%33,%34,%35,%36,%37,%38,%39,%40,%41,%42,%43,%44,%45,%46,%47,%48,%49,%50,%51,%52,%53,%54,%55,%56,%57,%58,%59,%60,%61,%62,%63}, %64, %65, p, 1, 1, 0, 1;}\n"
      : R32(0), R32(32)
      : "l"(ad), "l"(bd), "r"(acc));
}

__device__ __forceinline__ void ln16(const float* x, float* o) {
  float s = 0;
#pragma unroll
  for (int i = 0; i < 16; i++) s += x[i];
#pragma unroll
  for (int of = 16; of > 0; of >>= 1) s += __shfl_xor_sync(~0u, s, of);
  float mean = s * (1.0f / DM);
  float v = 0;
#pragma unroll
  for (int i = 0; i < 16; i++) { float dd = x[i] - mean; v += dd * dd; }
#pragma unroll
  for (int of = 16; of > 0; of >>= 1) v += __shfl_xor_sync(~0u, v, of);
  float mb = bf16r(mean);
  float vb = bf16r(v * (1.0f / DM));
  float den = bf16r(sqrtf(bf16r(vb + 1e-5f)));
#pragma unroll
  for (int i = 0; i < 16; i++) o[i] = bf16r(__fdiv_rn(bf16r(x[i] - mb), den));
}
__global__ void __launch_bounds__(256) k_pre(const bf16* __restrict__ x, const char* wq, const char* wk, const char* wv, const char* wo) {
  int t = threadIdx.x, lane = t & 31, w = t >> 5;
  asm volatile("griddepcontrol.launch_dependents;");
  {
    int g2 = blockIdx.x * 256 + t, o = (g2 & 32767) * 128;
    asm volatile("prefetch.global.L2 [%0];" ::"l"((g2 < 32768 ? wk : wv) + o));
    asm volatile("prefetch.global.L2 [%0];" ::"l"((g2 < 32768 ? wq : wo) + o));
  }
  int row = blockIdx.x * 8 + w;
  const uint4* src = reinterpret_cast<const uint4*>(x + (size_t)row * DM);
  uint4 a = src[lane], b = src[lane + 32];
  unsigned u[8] = {a.x, a.y, a.z, a.w, b.x, b.y, b.z, b.w};
  float f[16], o[16], o2[16];
#pragma unroll
  for (int i = 0; i < 8; i++) { f[2 * i] = bf_lo(u[i]); f[2 * i + 1] = bf_hi(u[i]); }
  ln16(f, o);
  ln16(o, o2);
  uint4* d1 = reinterpret_cast<uint4*>(g_xn + (size_t)row * DM);
  uint4* d2 = reinterpret_cast<uint4*>(g_y + (size_t)row * DM);
  d1[lane] = make_uint4(pack_bf16(o[0], o[1]), pack_bf16(o[2], o[3]), pack_bf16(o[4], o[5]), pack_bf16(o[6], o[7]));
  d1[lane + 32] = make_uint4(pack_bf16(o[8], o[9]), pack_bf16(o[10], o[11]), pack_bf16(o[12], o[13]), pack_bf16(o[14], o[15]));
  d2[lane] = make_uint4(pack_bf16(o2[0], o2[1]), pack_bf16(o2[2], o2[3]), pack_bf16(o2[4], o2[5]), pack_bf16(o2[6], o2[7]));
  d2[lane + 32] = make_uint4(pack_bf16(o2[8], o2[9]), pack_bf16(o2[10], o2[11]), pack_bf16(o2[12], o2[13]), pack_bf16(o2[14], o2[15]));
  int gt = blockIdx.x * 256 + t;
  uint4 z = make_uint4(0, 0, 0, 0);
  if (gt < 16384) reinterpret_cast<uint4*>(g_part)[gt] = z;
  if (gt < (int)(sizeof(Flags) / 4)) reinterpret_cast<unsigned*>(&g_flags)[gt] = 0;
}

struct Maps { CUtensorMap xn, y, h1, o, qkv_st, qkv_ld, g, wq, wk, wv, wo, w1, w2; };

#define NSTAGE 3
#define STAGE_BYTES 49152
#define B_STG (NSTAGE * STAGE_BYTES)
#define R_WO 0
#define R_T1 65536
#define R_T2 131072
#define R_RING 65536
#define RING_N 4
#define RING_BYTES 12288
#define R_MEM 196608
#define R_QS (R_MEM + 8448)
#define R_KS (R_QS + 1152)
#define R_OS (R_KS + 1152)
#define R_SOWN (R_OS + 2176)
#define R_SPEER (R_SOWN + 1280)
#define R_VM (R_SPEER + 1280)
#define R_VRED (R_VM + 2048)
#define R_RS (R_VRED + 6144)
#define SM_BAR (R_RS + 8192)
#define SMEM_TOTAL (SM_BAR + 256 + 1024)
#define MB_FULL 0
#define MB_EMPTY 8
#define MB_STGF 16
#define MB_STGE 17
#define MB_W0 18
#define MB_W1 19
#define MB_WO 20
#define MB_S 21
#define MB_V 22
#define MB_KVR 23
#define MB_KVF 24
#define MB_RS 25
#define MB_AG 26
#define SM_MISC (SM_BAR + 224)

#define N_KV 544
#define I_M1 544
#define I_Q 656
#define I_M2 912
#define I_POST 944
#define I_TAIL (I_POST + 16 * 32)
#define N_ITEMS (I_TAIL + 6 * 8 + 64 + 32 + 64)
enum { T_QKV = 0, T_M1 = 1, T_M2 = 2, T_ATT = 3, T_OUT = 4, T_OUTL = 5, T_RED = 6, T_REDL = 7 };
struct Item { int type, b, c, ks, hf; };
__device__ __forceinline__ Item decode_item(int i) {
  Item it; it.ks = 0; it.hf = 0;
  if (i < 64) { it.type = T_QKV; it.b = 0; it.c = 16 + (i >> 1); it.hf = 1 + (i & 1); }
  else if (i < N_KV) { it.type = T_QKV; it.b = (i - 32) >> 5; it.c = 16 + (i & 31); }
  else if (i < I_Q) { it.type = T_M1; it.b = (i - I_M1) / 7; it.c = (i - I_M1) % 7; }
  else if (i < I_M2) { it.type = T_QKV; it.b = (i - I_Q) >> 4; it.c = (i - I_Q) & 15; }
  else if (i < I_POST) { it.type = T_M2; it.b = (i - I_M2) >> 1; it.c = (i - I_M2) & 1; }
  else if (i < I_TAIL) {
    int x = i - I_POST, p = x >> 5, r = x & 31;
    if (r < 16) { it.type = T_ATT; it.b = p; it.c = r; }
    else if (r < 24) { it.type = T_OUT; it.b = p - 3; it.c = r & 1; it.ks = (r - 16) >> 1; }
    else { it.type = T_RED; it.b = p - 5; it.c = r - 24; }
  } else {
    int x = i - I_TAIL, r = x & 7;
    if (x < 8) { it.type = T_OUT; it.b = 13; it.c = r & 1; it.ks = r >> 1; }
    else if (x >= 16 && x < 32) { it.type = T_OUT; it.b = 14; it.c = (x >> 1) & 1; it.ks = (x - 16) >> 2; it.hf = 1 + (x & 1); }
    else if (x < 48) { it.type = T_RED; it.b = x < 16 ? 11 : 8 + (x >> 3); it.c = r; }
    else if (x < 112) { it.type = T_OUTL; it.b = 15; it.c = (x >> 1) & 1; it.ks = (x - 48) >> 2; it.hf = 1 + (x & 1); }
    else if (x < 144) { it.type = T_RED; it.b = 14; it.c = x - 112; it.ks = 1; }
    else { it.type = T_REDL; it.b = 15; it.c = x - 144; }
  }
  return it;
}
__device__ __forceinline__ int item_nkb(int type) { return type == T_M2 ? 28 : (type == T_OUT ? 16 : (type >= T_RED ? 1 : (type >= T_ATT ? 4 : 8))); }

__device__ __forceinline__ void st_async_b64(unsigned raddr, unsigned lo, unsigned hi, unsigned rmb) {
  asm volatile("st.async.weak.shared::cluster.mbarrier::complete_tx::bytes.v2.b32 [%0], {%1,%2}, [%3];" ::"r"(raddr), "r"(lo), "r"(hi), "r"(rmb) : "memory");
}
__device__ __forceinline__ void st_async_b32(unsigned raddr, unsigned v, unsigned rmb) {
  asm volatile("st.async.weak.shared::cluster.mbarrier::complete_tx::bytes.b32 [%0], %1, [%2];" ::"r"(raddr), "r"(v), "r"(rmb) : "memory");
}
__device__ __forceinline__ unsigned mapa(unsigned a, unsigned rank) {
  unsigned r; asm volatile("mapa.shared::cluster.u32 %0, %1, %2;" : "=r"(r) : "r"(a), "r"(rank)); return r;
}
__device__ __forceinline__ void sts64(unsigned a, unsigned x, unsigned y) { asm volatile("st.shared.v2.b32 [%0], {%1,%2};" ::"r"(a), "r"(x), "r"(y) : "memory"); }
__device__ __forceinline__ void sts128(unsigned a, uint4 v) { asm volatile("st.shared.v4.b32 [%0], {%1,%2,%3,%4};" ::"r"(a), "r"(v.x), "r"(v.y), "r"(v.z), "r"(v.w) : "memory"); }
__device__ __forceinline__ uint2 lds64(unsigned a) { uint2 v; asm volatile("ld.shared.v2.b32 {%0,%1}, [%2];" : "=r"(v.x), "=r"(v.y) : "r"(a) : "memory"); return v; }
__device__ __forceinline__ uint4 lds128(unsigned a) { uint4 v; asm volatile("ld.shared.v4.b32 {%0,%1,%2,%3}, [%4];" : "=r"(v.x), "=r"(v.y), "=r"(v.z), "=r"(v.w) : "r"(a) : "memory"); return v; }
__device__ __forceinline__ float lds32f(unsigned a) { float v; asm volatile("ld.shared.f32 %0, [%1];" : "=f"(v) : "r"(a) : "memory"); return v; }
#define spin_check(it) TRAP_IF(++it)
#define POLLV 0
#define BAR8 0
#define D_STAG 150
#define D_RED 540
#define D_PUB 0
#define DELAY(n) do { unsigned c0_, c1_; asm volatile("mov.u32 %0, %%clock;" : "=r"(c0_)); do { asm volatile("mov.u32 %0, %%clock;" : "=r"(c1_)); } while (c1_ - c0_ < (n)); } while (0)
#define VD 2
#define NPRE 3
#define SELP 1
#define SCALE_QK 0.08838834764831845f

__device__ __forceinline__ void rec_worker(const Maps& maps, unsigned sb, const bf16* __restrict__ mem0, const int c) {
  const int h = c >> 1, j = c & 1;
  const int t = opaque_tid(), lane = t & 31, w = t >> 5, g = lane >> 2, tq = lane & 3;
  const int m = lane >> 3, r8 = lane & 7, kh = w >> 2, et = w & 3;
  const unsigned bar = sb + SM_BAR;
  unsigned wq[16][4], wk[16][4], wo[8][4];
  const unsigned woff = (kh * 4) * 8192 + ((m >> 1) * 8 + r8) * 128 + (((et * 2 + (m & 1)) ^ r8) << 4);
  mbar_wait(bar + 8 * MB_W0, 0);
#pragma unroll
  for (int i = 0; i < 16; i++) {
    ldsm_x4_t(wq[i], sb + R_WO + woff + (i >> 2) * 8192 + (i & 3) * 2048);
    ldsm_x4_t(wk[i], sb + R_T1 + woff + (i >> 2) * 8192 + (i & 3) * 2048);
  }
  bar_sync(2, 288);
  if (t == 0) {
    fence_proxy_async_smem();
    mbar_expect_tx(bar + 8 * MB_WO, 65536);
    for (int kb = 0; kb < 2; kb++)
      for (int cb = 0; cb < 4; cb++) tma_load_2d(sb + R_WO + (kb * 4 + cb) * 8192, &maps.wo, j * 256 + cb * 64, h * 128 + kb * 64, bar + 8 * MB_WO);
  }
  mbar_wait(bar + 8 * MB_W1, 0);
  const unsigned pV = sb + R_T2 + woff;
  const unsigned rk = c & 7, peer = rk ^ 1, cl = c >> 3;
#define KEEP(x) x = __shfl_sync(~0u, x, lane)
  unsigned pA = sb + R_MEM + kh * 4096 + lane * 16;
  unsigned pW0 = sb + R_WO + (w >> 1) * 8192 + ((m >> 1) * 8 + r8) * 128 + ((((w & 1) * 4 + (m & 1)) ^ r8) << 4);
  unsigned pW1 = pW0 ^ 32;
  unsigned pVk = pV;
  unsigned aX = sb + R_VRED + et * 512 + lane * 16;
  unsigned aQKst = sb + (kh ? R_KS : R_QS) + r8 * 144 + (et * 16 + (m & 1) * 8) * 2;
  unsigned aL8 = sb + lane * 8;
  unsigned aSl = mapa(sb + R_SOWN + w * 256 + lane * 8, rk), aSr = mapa(sb + R_SPEER + w * 256 + lane * 8, peer);
  unsigned aVl = mapa(sb + R_VM + (j * 4 + et) * 256 + lane * 8, rk), aVr = mapa(sb + R_VM + (j * 4 + et) * 256 + lane * 8, peer);
  const unsigned mbSl = mapa(bar + 8 * MB_S, rk), mbSr = mapa(bar + 8 * MB_S, peer), mbVl = mbSl + 8, mbVr = mbSr + 8;
  unsigned aQ = sb + R_QS + r8 * 144 + m * 16;
  unsigned oKx = (et * 8 + r8) * 128 + ((m ^ r8) << 4);
  unsigned oVx = 4096 + (et >> 1) * 4096 + ((m >> 1) * 8 + r8) * 128 + ((((et & 1) * 4 + (m & 1)) ^ r8) << 4);
  unsigned aOst = sb + R_OS + r8 * 272 + (et * 32 + m * 8) * 2;
  unsigned aOld = sb + R_OS + r8 * 272 + m * 16;
  unsigned aVm = sb + R_VM + et * 512 + lane * 8;
  unsigned aRSr = mapa(sb + R_RS + (h & 3) * 2048 + (w & 1) * 1024 + lane * 8, j * 4 + (w >> 1));
  unsigned mbRSr = mapa(bar + 8 * MB_RS, j * 4 + (w >> 1));
  unsigned t8 = t * 8;
  KEEP(pA); KEEP(pW0); KEEP(pW1); KEEP(pVk); KEEP(aX); KEEP(aQKst); KEEP(aL8); KEEP(aSl); KEEP(aSr); KEEP(aVl); KEEP(aVr); KEEP(aQ); KEEP(oKx); KEEP(oVx);
  KEEP(aOst); KEEP(aOld); KEEP(aVm); KEEP(aRSr); KEEP(mbRSr); KEEP(t8);
  mbar_wait(bar + 8 * MB_WO, 0);
#pragma unroll
  for (int ks = 0; ks < 4; ks++) { ldsm_x4_t(wo[2 * ks], pW0 + ks * 2048); ldsm_x4_t(wo[2 * ks + 1], pW1 + ks * 2048); }
  {
    unsigned v[8];
#pragma unroll
    for (int q = 0; q < 8; q++) v[q] = __ldg(reinterpret_cast<const unsigned*>(mem0) + q * 256 + t);
    sts128(sb + R_MEM + t * 32, make_uint4(__byte_perm(v[0], v[1], 0x5410), __byte_perm(v[2], v[3], 0x5410), __byte_perm(v[4], v[5], 0x5410), __byte_perm(v[6], v[7], 0x5410)));
    sts128(sb + R_MEM + t * 32 + 16, make_uint4(__byte_perm(v[0], v[1], 0x7632), __byte_perm(v[2], v[3], 0x7632), __byte_perm(v[4], v[5], 0x7632), __byte_perm(v[6], v[7], 0x7632)));
  }
  bar_sync(1, 256);

#pragma unroll 1
  for (int s = 0;; s++) {
    const unsigned par = s & 1;
    const unsigned slot = s & (RING_N - 1), rpar = (s / RING_N) & 1;
    const unsigned ring = sb + R_RING + slot * RING_BYTES;
    asm volatile("" : "+r"(t8));
    RSTAMP(1);
    RSTAMP(2);
    float aq[4] = {0, 0, 0, 0}, ak[4] = {0, 0, 0, 0}, av[4] = {0, 0, 0, 0};
    {
      unsigned b[8][4], f1[8][4], f0[8][4];
#define VLD(i) do { ldsm_x4_t(b[i], pA + (i) * 512); ldsm_x4_t(f0[i], pVk + ((i) >> 1) * 8192 + ((i) & 1) * 4096); ldsm_x4_t(f1[i], pVk + ((i) >> 1) * 8192 + ((i) & 1) * 4096 + 2048); } while (0)
      VLD(0);
      if (VD > 1) VLD(1);
#pragma unroll
      for (int i = 0; i < 8; i++) {
        if (i + VD < 8) VLD(i + VD);
        mma16816(aq, wq[2 * i], b[i][0], b[i][1]); mma16816(ak, wk[2 * i], b[i][0], b[i][1]); mma16816(av, f0[i], b[i][0], b[i][1]);
        mma16816(aq, wq[2 * i + 1], b[i][2], b[i][3]); mma16816(ak, wk[2 * i + 1], b[i][2], b[i][3]); mma16816(av, f1[i], b[i][2], b[i][3]);
      }
    }
    RSTAMP(3);
#define STSF4(a, v) asm volatile("st.shared.v4.f32 [%0], {%1,%2,%3,%4};" ::"r"(a), "f"(v[0]), "f"(v[1]), "f"(v[2]), "f"(v[3]) : "memory")
    unsigned f[8][4];
#define WO_PREFETCH() do { _Pragma("unroll") for (int i = 0; i < NPRE; i++) { ldsm_x4_t(f[2 * i], pW0 + 32768 + i * 2048); ldsm_x4_t(f[2 * i + 1], pW1 + 32768 + i * 2048); } } while (0)
    if (kh) {
      STSF4(aX, aq);
      bar_sync(4 + et, 64);
      uint4 o = lds128(aX + 2048), o2 = lds128(aX + 4096);
      stsm_x2_t(aQKst, pack_bf16(ak[0] + __uint_as_float(o.x), ak[1] + __uint_as_float(o.y)), pack_bf16(ak[2] + __uint_as_float(o.z), ak[3] + __uint_as_float(o.w)));
      bar_arrive(1, 256);
      unsigned x = pack_bf16(av[0] + __uint_as_float(o2.x), av[1] + __uint_as_float(o2.y)), y = pack_bf16(av[2] + __uint_as_float(o2.z), av[3] + __uint_as_float(o2.w));
      st_async_b64(aVr, x, y, mbVr);
      st_async_b64(aVl, x, y, mbVl);
      if (s == NSEG - 1) {
        mbar_wait(bar + 8 * MB_V, par);
        if (t == 128) mbar_arrive(bar + 8 * MB_KVR);
        break;
      }
      mbar_wait(bar + 8 * (MB_FULL + slot), rpar);
      unsigned vx[4][4];
      ldsm_x4_t(vx[0], ring + oVx); ldsm_x4_t(vx[1], ring + oVx + 2048); ldsm_x4_t(vx[2], ring + (oVx ^ 32)); ldsm_x4_t(vx[3], ring + (oVx ^ 32) + 2048);
      RSTAMP(4); RSTAMP(5); RSTAMP(6); RSTAMP(7);
      mbar_wait(bar + 8 * MB_S, par);
      RSTAMP(8);
      float sc[10];
#pragma unroll
      for (int i = 0; i < 5; i++) {
        uint2 o = lds64(aL8 + R_SOWN + i * 256), p = lds64(aL8 + R_SPEER + i * 256);
        sc[2 * i] = __uint_as_float(o.x) + __uint_as_float(p.x); sc[2 * i + 1] = __uint_as_float(o.y) + __uint_as_float(p.y);
      }
      mbar_wait(bar + 8 * MB_V, par);
      uint2 vm0 = lds64(aVm), vm1 = lds64(aVm + 256);
      float mx = fmaxf(fmaxf(fmaxf(sc[0], sc[1]), fmaxf(sc[2], sc[3])), fmaxf(fmaxf(fmaxf(sc[4], sc[5]), fmaxf(sc[6], sc[7])), fmaxf(sc[8], sc[9])));
      mx = fmaxf(mx, __shfl_xor_sync(~0u, mx, 1)); mx = fmaxf(mx, __shfl_xor_sync(~0u, mx, 2));
      const float nm = -mx * (SCALE_QK * LOG2E);
      unsigned p[5];
#pragma unroll
      for (int i = 0; i < 5; i++) p[i] = pack_bf16(ex2f(fmaf(sc[2 * i], SCALE_QK * LOG2E, nm)), ex2f(fmaf(sc[2 * i + 1], SCALE_QK * LOG2E, nm)));
      RSTAMP(9);
      float o0[4] = {0, 0, 0, 0}, o1[4] = {0, 0, 0, 0}, o3[4] = {0, 0, 0, 0}, o4[4] = {0, 0, 0, 0}, z0[4] = {0, 0, 0, 0}, z1[4] = {0, 0, 0, 0};
      const unsigned ones[4] = {0x3F803F80u, 0u, 0x3F803F80u, 0u};
      mma16816(z0, ones, p[0], p[1]); mma16816(z1, ones, p[2], p[3]);
      mma16816(o0, vx[0], p[0], p[1]); mma16816(o3, vx[2], p[0], p[1]);
      mma1688(z0, 0x3F803F80u, 0u, p[4]);
      mma16816(o1, vx[1], p[2], p[3]); mma16816(o4, vx[3], p[2], p[3]);
      mma1688(o0, vm0.x, vm0.y, p[4]); mma1688(o3, vm1.x, vm1.y, p[4]);
      float i0, i1;
      asm("rcp.approx.ftz.f32 %0, %1;" : "=f"(i0) : "f"(z0[0] + z1[0])); asm("rcp.approx.ftz.f32 %0, %1;" : "=f"(i1) : "f"(z0[1] + z1[1]));
      asm volatile("stmatrix.sync.aligned.m8n8.x4.trans.shared.b16 [%0], {%1,%2,%3,%4};" ::"r"(aOst), "r"(pack_bf16((o0[0] + o1[0]) * i0, (o0[1] + o1[1]) * i1)), "r"(pack_bf16((o0[2] + o1[2]) * i0, (o0[3] + o1[3]) * i1)),
                   "r"(pack_bf16((o3[0] + o4[0]) * i0, (o3[1] + o4[1]) * i1)), "r"(pack_bf16((o3[2] + o4[2]) * i0, (o3[3] + o4[3]) * i1)) : "memory");
      RSTAMP(10);
      bar_sync(1, 256);
      WO_PREFETCH();
    } else {
      STSF4(aX + 2048, ak); STSF4(aX + 4096, av);
      unsigned kb[8];
      mbar_wait(bar + 8 * (MB_FULL + slot), rpar);
      ldsm_x4(kb, ring + oKx); ldsm_x4(kb + 4, ring + (oKx ^ 64));
      bar_sync(4 + et, 64);
      uint4 o = lds128(aX);
      stsm_x2_t(aQKst, pack_bf16(aq[0] + __uint_as_float(o.x), aq[1] + __uint_as_float(o.y)), pack_bf16(aq[2] + __uint_as_float(o.z), aq[3] + __uint_as_float(o.w)));
      RSTAMP(4);
      bar_sync(1, 256);
      RSTAMP(5);
      if (s == NSEG - 1) break;
      unsigned qa[8], km[8];
      ldsm_x4(qa, aQ); ldsm_x4(qa + 4, aQ + 64);
      if (w == 3) { ldsm_x4(km, aQ + 1152); ldsm_x4(km + 4, aQ + 1152 + 64); }
      float s0[4] = {0, 0, 0, 0}, s1[4] = {0, 0, 0, 0};
      unsigned af[4][4];
#pragma unroll
      for (int i = 0; i < 4; i++) { af[i][0] = qa[2 * i]; af[i][1] = 0; af[i][2] = qa[2 * i + 1]; af[i][3] = 0; }
      mma16816(s0, af[0], kb[0], kb[1]); mma16816(s1, af[1], kb[2], kb[3]);
      mma16816(s0, af[2], kb[4], kb[5]); mma16816(s1, af[3], kb[6], kb[7]);
      if (w == 3) {
        float m0[4] = {0, 0, 0, 0}, m1[4] = {0, 0, 0, 0};
        mma16816(m0, af[0], km[0], km[1]); mma16816(m1, af[1], km[2], km[3]);
        mma16816(m0, af[2], km[4], km[5]); mma16816(m1, af[3], km[6], km[7]);
        unsigned x = __float_as_uint(m0[0] + m1[0]), y = __float_as_uint(m0[1] + m1[1]);
        st_async_b64(aSr + 256, x, y, mbSr); st_async_b64(aSl + 256, x, y, mbSl);
      }
      unsigned x = __float_as_uint(s0[0] + s1[0]), y = __float_as_uint(s0[1] + s1[1]);
      st_async_b64(aSr, x, y, mbSr); st_async_b64(aSl, x, y, mbSl);
      RSTAMP(6);
      WO_PREFETCH();
      RSTAMP(7); RSTAMP(8); RSTAMP(9); RSTAMP(10);
      bar_sync(1, 256);
    }
    RSTAMP(11);
    float d0[4] = {0, 0, 0, 0}, d1[4] = {0, 0, 0, 0}, e0[4] = {0, 0, 0, 0}, e1[4] = {0, 0, 0, 0};
    unsigned ob[4][4];
#pragma unroll
    for (int k2 = 0; k2 < 4; k2++) ldsm_x4(ob[k2], aOld + k2 * 64);
#pragma unroll
    for (int i = NPRE; i < 4; i++) { ldsm_x4_t(f[2 * i], pW0 + 32768 + i * 2048); ldsm_x4_t(f[2 * i + 1], pW1 + 32768 + i * 2048); }
    mma16816(d0, wo[0], ob[0][0], ob[0][1]); mma16816(d1, wo[1], ob[0][0], ob[0][1]);
    mma16816(e0, wo[2], ob[0][2], ob[0][3]); mma16816(e1, wo[3], ob[0][2], ob[0][3]);
    mma16816(d0, wo[4], ob[1][0], ob[1][1]); mma16816(d1, wo[5], ob[1][0], ob[1][1]);
    mma16816(e0, wo[6], ob[1][2], ob[1][3]); mma16816(e1, wo[7], ob[1][2], ob[1][3]);
    mma16816(d0, f[0], ob[2][0], ob[2][1]); mma16816(d1, f[1], ob[2][0], ob[2][1]);
    mma16816(e0, f[2], ob[2][2], ob[2][3]); mma16816(e1, f[3], ob[2][2], ob[2][3]);
    mma16816(d0, f[4], ob[3][0], ob[3][1]); mma16816(d1, f[5], ob[3][0], ob[3][1]);
    mma16816(e0, f[6], ob[3][2], ob[3][3]); mma16816(e1, f[7], ob[3][2], ob[3][3]);
    st_async_b64(aRSr, __float_as_uint(d0[0] + e0[0]), __float_as_uint(d0[1] + e0[1]), mbRSr);
    st_async_b64(aRSr + 256, __float_as_uint(d0[2] + e0[2]), __float_as_uint(d0[3] + e0[3]), mbRSr);
    st_async_b64(aRSr + 512, __float_as_uint(d1[0] + e1[0]), __float_as_uint(d1[1] + e1[1]), mbRSr);
    st_async_b64(aRSr + 768, __float_as_uint(d1[2] + e1[2]), __float_as_uint(d1[3] + e1[3]), mbRSr);
    RSTAMP(12);
    if (t == 128) {
      mbar_arrive(bar + 8 * (MB_EMPTY + slot)); mbar_arrive(bar + 8 * MB_KVR);
      mbar_expect_tx(bar + 8 * MB_S, 2560); mbar_expect_tx(bar + 8 * MB_V, 2048);
    }
    const unsigned tag = ((s >> 1) & 1) ^ 1;
    const char* gp = reinterpret_cast<const char*>(g_part);
    const unsigned goff = (par * 8 + rk) * 16384 + cl * 2048 + t8;
    unsigned mbA[8];
#pragma unroll
    for (int i = 0; i < 8; i++) mbA[i] = mapa(bar + 8 * MB_AG, i);
    const unsigned dlt = (R_MEM + rk * 1024) - (SM_BAR + 8 * MB_AG) + (t8 >> 1);
    mbar_wait(bar + 8 * MB_RS, par);
    RSTAMP(13);
    uint2 a[8];
    {
      uint2 x0 = lds64(sb + R_RS + t8), x1 = lds64(sb + R_RS + 2048 + t8), x2 = lds64(sb + R_RS + 4096 + t8), x3 = lds64(sb + R_RS + 6144 + t8);
      float r0 = (__uint_as_float(x0.x) + __uint_as_float(x1.x)) + (__uint_as_float(x2.x) + __uint_as_float(x3.x));
      float r1 = (__uint_as_float(x0.y) + __uint_as_float(x1.y)) + (__uint_as_float(x2.y) + __uint_as_float(x3.y));
      a[0].x = (__float_as_uint(r0) & ~1u) | tag; a[0].y = (__float_as_uint(r1) & ~1u) | tag;
      asm volatile("st.relaxed.gpu.global.v2.u32 [%0], {%1,%2};" ::"l"(gp + goff), "r"(a[0].x), "r"(a[0].y) : "memory");
    }
    RSTAMP(14);
    if (t == 128) mbar_expect_tx(bar + 8 * MB_RS, 8192);
    {
      unsigned it = 0;
#define PLOAD(a) _Pragma("unroll") for (int i = 1; i < 8; i++) a[i] = ldv2_relaxed(gp + (goff ^ (i * 2048)))
#define PAND(a) (((a[1].x & a[1].y) & (a[2].x & a[2].y) & (a[3].x & a[3].y)) & ((a[4].x & a[4].y) & (a[5].x & a[5].y)) & ((a[6].x & a[6].y) & (a[7].x & a[7].y)))
#define POR(a) (((a[1].x | a[1].y) | (a[2].x | a[2].y) | (a[3].x | a[3].y)) | ((a[4].x | a[4].y) | (a[5].x | a[5].y)) | ((a[6].x | a[6].y) | (a[7].x | a[7].y)))
#define POK(a) (((tag ? PAND(a) : ~POR(a)) & 1u) != 0)
      if (D_RED) DELAY(D_RED);
      PLOAD(a);
      while (!POK(a)) {
#pragma unroll
        for (int i = 1; i < 8; i++) if (((a[i].x ^ tag) | (a[i].y ^ tag)) & 1u) a[i] = ldv2_relaxed(gp + (goff ^ (i * 2048)));
        spin_check(it);
      }
    }
    RSTAMP(15);
    {
#define AF(i, c) __uint_as_float(a[i].c)
      unsigned u = pack_bf16(((AF(0, x) + AF(1, x)) + (AF(2, x) + AF(3, x))) + ((AF(4, x) + AF(5, x)) + (AF(6, x) + AF(7, x))),
                             ((AF(0, y) + AF(1, y)) + (AF(2, y) + AF(3, y))) + ((AF(4, y) + AF(5, y)) + (AF(6, y) + AF(7, y))));
      __syncwarp();
#pragma unroll
      for (int i = 0; i < 8; i++) st_async_b32(mbA[i] + dlt, u, mbA[i]);
    }
    mbar_wait(bar + 8 * MB_KVF, par);
    mbar_wait(bar + 8 * MB_AG, par);
    if (t == 128) mbar_expect_tx(bar + 8 * MB_AG, 8192);
  }
}

__device__ __forceinline__ void rec_ring(const Maps& maps, unsigned sb, const int c) {
  const int h = c >> 1, j = c & 1;
  const unsigned bar = sb + SM_BAR;
  const int lane = threadIdx.x & 31;
  __syncwarp();
  bar_sync(2, 288);
  if (lane == 0) {
    fence_proxy_async_smem();
    for (int s = 0; s < NSEG; s++) {
      unsigned slot = s & (RING_N - 1);
      if ((s & 3) == 0 && !DBGMODE) {
        wait_flag_ge(&g_flags.qkv[(s >> 2) * 48 + 16 + (h >> 1)], 2);
        wait_flag_ge(&g_flags.qkv[(s >> 2) * 48 + 32 + (h >> 1)], 2);
        fence_proxy_async();
      }
      if (s >= RING_N) mbar_wait_sleep(bar + 8 * (MB_EMPTY + slot), ((s / RING_N) - 1) & 1);
      unsigned dst = sb + R_RING + slot * RING_BYTES, mb = bar + 8 * (MB_FULL + slot);
      mbar_expect_tx(mb, RING_BYTES);
      tma_load_2d(dst, &maps.qkv_ld, HD + h * 128 + j * 64, s * SEG, mb);
      tma_load_2d(dst + 4096, &maps.qkv_ld, 2 * HD + h * 128, s * SEG, mb);
      tma_load_2d(dst + 8192, &maps.qkv_ld, 2 * HD + h * 128 + 64, s * SEG, mb);
    }
  }
}
__device__ __forceinline__ void rec_copy(unsigned sb, const int c) {
  const int h = c >> 1, j = c & 1;
  const unsigned bar = sb + SM_BAR;
  const int lane = threadIdx.x & 31;
  for (int s = 0; s < NSEG; s++) {
    if (s < NSEG - 1) mbar_wait_sleep(bar + 8 * MB_KVR, s & 1); else mbar_wait(bar + 8 * MB_KVR, s & 1);
    uint4 k0 = lds128(sb + R_KS + (lane >> 3) * 144 + (lane & 7) * 16), k1 = lds128(sb + R_KS + (4 + (lane >> 3)) * 144 + (lane & 7) * 16);
    uint2 v[4];
#pragma unroll
    for (int i = 0; i < 4; i++) v[i] = lds64(sb + R_VM + (j * 4 + i) * 256 + lane * 8);
    __syncwarp();
    if (lane == 0) mbar_arrive(bar + 8 * MB_KVF);
    bf16* kd = g_km + ((size_t)(s * NH + h) * NMEM) * DH + j * 64;
    *reinterpret_cast<uint4*>(kd + (lane >> 3) * DH + (lane & 7) * 8) = k0;
    *reinterpret_cast<uint4*>(kd + (4 + (lane >> 3)) * DH + (lane & 7) * 8) = k1;
    unsigned* vd = reinterpret_cast<unsigned*>(g_vmt) + ((size_t)(s * NH + h) * DH + j * 64) * 4;
#pragma unroll
    for (int i = 0; i < 4; i++) { vd[(i * 16) * 4 + lane] = v[i].x; vd[(i * 16 + 8) * 4 + lane] = v[i].y; }
    __syncwarp();
    if (lane == 0) st_release(&g_flags.rec[c], s + 1);
  }
}

__device__ __forceinline__ void bulk_producer(const Maps& maps, unsigned sb, int* misc) {
  const unsigned bar = sb + SM_BAR;
  const int lane = threadIdx.x & 31;
  unsigned st = 0, ph = 0, seq = 0;
  while (true) {
    int idx = 0;
    if (lane == 0) idx = (int)atomicAdd(&g_flags.ctr, 1u);
    idx = __shfl_sync(~0u, idx, 0);
    if (idx >= N_ITEMS) {
      if (lane == 0) {
        mbar_wait(bar + 8 * (MB_EMPTY + st), ph ^ 1);
        misc[seq & 3] = -1;
        mbar_arrive(bar + 8 * (MB_FULL + st));
      }
      break;
    }
    if (lane == 0) ISTAMP(idx, 0);
    Item it = decode_item(idx);
    if (it.b < 0) continue;
    const CUtensorMap* mp; int c0, c1, dc0, dc1; unsigned doff;
    const unsigned* fl = nullptr; unsigned tgt = 1; int nbox = 5, rdy = 0;
    if (it.type == T_ATT) {
      mp = &maps.qkv_ld; nbox = 12; doff = lane * 4096;
      c0 = (lane >> 2) * HD + it.c * 256 + (lane & 1) * 64; c1 = it.b * 128 + ((lane >> 1) & 1) * 32; dc0 = dc1 = 0;
      if (lane < 3) fl = &g_flags.qkv[it.b * 48 + lane * 16 + it.c];
      tgt = 2;
      bool ok = true;
      if (lane >= 4 && lane < 8) ok = ld_acquire(&g_flags.rec[it.c * 4 + lane - 4]) >= (unsigned)(it.b * 4 + 4);
      rdy = __all_sync(~0u, ok) ? 65536 : 0;
    } else {
      int k0 = 0, nb0 = it.c * 256;
      if (it.type == T_QKV) { mp = lane == 0 ? &maps.xn : (it.c < 16 ? &maps.wq : (it.c < 32 ? &maps.wk : &maps.wv)); nb0 = (it.c & 15) * 256; }
      else if (it.type == T_M1) mp = lane == 0 ? &maps.y : &maps.w1;
      else if (it.type == T_M2) { mp = lane == 0 ? &maps.h1 : &maps.w2; fl = &g_flags.h1[it.b]; tgt = 7; }
      else {
        mp = lane == 0 ? &maps.o : &maps.wo;
        if (it.type == T_OUT) { k0 = it.ks * 1024; fl = &g_flags.o[it.b * 4 + it.ks]; tgt = 4; }
        else if (it.type == T_OUTL) { k0 = it.ks * 256; fl = &g_flags.o16[it.ks]; }
        else if (lane == 1) { fl = &g_flags.g[it.b]; tgt = 2; }
        else { fl = &g_flags.p[it.b]; tgt = it.type == T_RED ? (it.ks ? 16 : 8) : 64; }
      }
      if (lane > (it.type >= T_RED ? 1 : 0)) fl = nullptr;
      if (it.hf) { nbox = 3; nb0 += (it.hf - 1) * 128; }
      if (lane == 0) { c0 = k0; c1 = it.b * 128; dc0 = 64; dc1 = 0; doff = 0; }
      else { c0 = nb0 + (lane - 1) * 64; c1 = k0; dc0 = 0; dc1 = 64; doff = 8192 + lane * 8192; }
    }
    if (fl) wait_flag_ge(fl, tgt);
    __syncwarp();
    fence_proxy_async();
    if (lane == 0) ISTAMP(idx, 1);
    const int nkb = item_nkb(it.type);
    for (int kb = 0; kb < nkb; kb++) {
      const unsigned mb = bar + 8 * (MB_FULL + st);
      mbar_wait(bar + 8 * (MB_EMPTY + st), ph ^ 1);
      if (lane == 0) {
        if (kb == 0) misc[seq & 3] = idx | rdy;
        if (it.type >= T_RED) mbar_arrive(mb); else mbar_expect_tx(mb, it.hf ? 32768 : STAGE_BYTES);
      }
      if (it.type == T_ATT) { if (lane < 12) tma_load_2d(sb + st * STAGE_BYTES + doff, mp, c0 + (kb & 1) * 128, c1 + (kb >> 1) * 64, mb); }
      else if (lane < nbox && it.type < T_RED) tma_load_2d(sb + st * STAGE_BYTES + doff, mp, c0 + kb * dc0, c1 + kb * dc1, mb);
      __syncwarp();
      if (++st == NSTAGE) { st = 0; ph ^= 1; }
    }
    seq++;
  }
}
__device__ __forceinline__ void bulk_store(const Maps& maps, unsigned sb, volatile int* misc) {
  const unsigned bar = sb + SM_BAR;
  unsigned ph = 0;
  while (true) {
    mbar_wait(bar + 8 * MB_STGF, ph); ph ^= 1;
    int idx = misc[4];
    if (idx < 0) break;
    Item it = decode_item(idx);
    const CUtensorMap* mp = it.type == T_QKV ? &maps.qkv_st : (it.type == T_M1 ? &maps.h1 : (it.type == T_M2 ? &maps.g : &maps.o));
    unsigned* flag = it.type == T_QKV ? &g_flags.qkv[it.b * 48 + it.c] : (it.type == T_M1 ? &g_flags.h1[it.b] : (it.type == T_M2 ? &g_flags.g[it.b] : (it.b == 15 ? &g_flags.o16[it.c] : &g_flags.o[it.b * 4 + (it.c >> 2)])));
    for (int i = 0; i < (it.hf ? 2 : 4); i++) tma_store_2d(mp, sb + B_STG + i * 16384, it.c * 256 + (it.hf >> 1) * 128 + i * 64, it.b * 128);
    asm volatile("cp.async.bulk.commit_group;" ::: "memory");
    asm volatile("cp.async.bulk.wait_group.read 0;" ::: "memory");
    mbar_arrive(bar + 8 * MB_STGE);
    asm volatile("cp.async.bulk.wait_group 0;" ::: "memory");
    fence_proxy_async();
    red_release_add(flag, it.type == T_QKV && !it.hf ? 2 : 1);
    ISTAMP(idx, 3);
  }
}
__device__ __forceinline__ float rcpf(float x) { float y; asm("rcp.approx.ftz.f32 %0, %1;" : "=f"(y) : "f"(x)); return y; }
__device__ __forceinline__ float gelu_t(float x) {
  float e = ex2f(x * fmaf(x * x, -2.0f * LOG2E * 0.7978845608028654f * 0.044715f, -2.0f * LOG2E * 0.7978845608028654f));
  return x * rcpf(1.0f + e);
}
__device__ __forceinline__ float silu_f(float x) { return x * rcpf(1.0f + ex2f(-LOG2E * x)); }
__device__ __forceinline__ unsigned badd2(unsigned a, unsigned b) { unsigned r; asm("add.rn.bf16x2 %0, %1, %2;" : "=r"(r) : "r"(a), "r"(b)); return r; }

__device__ __forceinline__ void final_out(bf16* __restrict__ out, const bf16* __restrict__ x, size_t o, float4 s) {
  uint2 gv = __ldcg(reinterpret_cast<const uint2*>(g_g + o)), xv = __ldg(reinterpret_cast<const uint2*>(x + o));
  uint2 r;
  r.x = pack_bf16(bf_lo(xv.x) + bf16r(bf16r(s.x) * bf_lo(gv.x)), bf_hi(xv.x) + bf16r(bf16r(s.y) * bf_hi(gv.x)));
  r.y = pack_bf16(bf_lo(xv.y) + bf16r(bf16r(s.z) * bf_lo(gv.y)), bf_hi(xv.y) + bf16r(bf16r(s.w) * bf_hi(gv.y)));
  *reinterpret_cast<uint2*>(out + o) = r;
}
__device__ __forceinline__ void bulk_att_load(unsigned* km, unsigned* vm, int b, int hp, int kb, int w, int lane) {
  const int g = lane >> 2, tq = lane & 3, seg = w >> 2, eh = w & 1;
  const int head = hp * 2 + (kb & 1), sg = b * 4 + (kb >> 1) * 2 + seg;
  const unsigned* kmp = reinterpret_cast<const unsigned*>(g_km + ((size_t)(sg * NH + head) * NMEM + g) * DH) + tq;
  const unsigned* vmp = reinterpret_cast<const unsigned*>(g_vmt) + ((size_t)(sg * NH + head) * DH + eh * 64) * 4 + lane;
#pragma unroll
  for (int i = 0; i < 16; i++) asm volatile("ld.global.cg.u32 %0, [%1];" : "=r"(km[i]) : "l"(kmp + i * 4) : "memory");
#pragma unroll
  for (int i = 0; i < 8; i++) asm volatile("ld.global.cg.u32 %0, [%1];" : "=r"(vm[i]) : "l"(vmp + i * 32) : "memory");
}
__device__ __forceinline__ void bulk_att_stage(unsigned sa, unsigned stg, const unsigned* km, const unsigned* vm, int kb, int w, int lane) {
  const int g = lane >> 2, tq = lane & 3, m = lane >> 3, r8 = lane & 7;
  const int seg = w >> 2, mt = (w >> 1) & 1, eh = w & 1;
  float s[5][4];
#pragma unroll
  for (int i = 0; i < 5; i++) { s[i][0] = s[i][1] = s[i][2] = s[i][3] = 0; }
  const unsigned qb = sa + (0 * 2 + seg) * 8192, kbs = sa + (1 * 2 + seg) * 8192, vb = sa + (2 * 2 + seg) * 8192 + eh * 4096;
  unsigned qa[8][4];
#pragma unroll
  for (int ks = 0; ks < 8; ks++) {
    int row = mt * 16 + (m & 1) * 8 + r8;
    ldsm_x4(qa[ks], qb + (ks >> 2) * 4096 + row * 128 + ((((ks & 3) * 2 + (m >> 1)) ^ r8) << 4));
    unsigned kf[4];
    int krow = (m >> 1) * 8 + r8;
    unsigned ka = kbs + (ks >> 2) * 4096 + krow * 128 + ((((ks & 3) * 2 + (m & 1)) ^ r8) << 4);
    ldsm_x4(kf, ka);
    mma16816(s[0], qa[ks], kf[0], kf[1]); mma16816(s[1], qa[ks], kf[2], kf[3]);
    if (mt) { ldsm_x4(kf, ka + 2048); mma16816(s[2], qa[ks], kf[0], kf[1]); mma16816(s[3], qa[ks], kf[2], kf[3]); }
  }
#pragma unroll
  for (int ks = 0; ks < 8; ks++) mma16816(s[4], qa[ks], km[2 * ks], km[2 * ks + 1]);
  float mx0 = -INFINITY, mx1 = -INFINITY;
  const int t0 = mt * 16 + g, t1 = t0 + 8;
#pragma unroll
  for (int i = 0; i < 5; i++) {
#pragma unroll
    for (int e = 0; e < 4; e++) {
      float v = s[i][e];
      if (i < 4) { int kj = i * 8 + 2 * tq + (e & 1); if (kj > (e < 2 ? t0 : t1)) v = -INFINITY; }
      s[i][e] = v;
      if (e < 2) mx0 = fmaxf(mx0, v); else mx1 = fmaxf(mx1, v);
    }
  }
  mx0 = fmaxf(mx0, __shfl_xor_sync(~0u, mx0, 1)); mx0 = fmaxf(mx0, __shfl_xor_sync(~0u, mx0, 2));
  mx1 = fmaxf(mx1, __shfl_xor_sync(~0u, mx1, 1)); mx1 = fmaxf(mx1, __shfl_xor_sync(~0u, mx1, 2));
  float sm0 = 0, sm1 = 0;
#pragma unroll
  for (int i = 0; i < 5; i++) {
    s[i][0] = ex2f((s[i][0] - mx0) * (SCALE_QK * LOG2E)); s[i][1] = ex2f((s[i][1] - mx0) * (SCALE_QK * LOG2E));
    s[i][2] = ex2f((s[i][2] - mx1) * (SCALE_QK * LOG2E)); s[i][3] = ex2f((s[i][3] - mx1) * (SCALE_QK * LOG2E));
    sm0 += s[i][0] + s[i][1]; sm1 += s[i][2] + s[i][3];
  }
  sm0 += __shfl_xor_sync(~0u, sm0, 1); sm0 += __shfl_xor_sync(~0u, sm0, 2);
  sm1 += __shfl_xor_sync(~0u, sm1, 1); sm1 += __shfl_xor_sync(~0u, sm1, 2);
  const float i0 = __fdividef(1.0f, sm0), i1 = __fdividef(1.0f, sm1);
  unsigned pa[2][4], pm0, pm1;
#pragma unroll
  for (int kk = 0; kk < 2; kk++) {
    pa[kk][0] = pack_bf16(s[2 * kk][0] * i0, s[2 * kk][1] * i0); pa[kk][1] = pack_bf16(s[2 * kk][2] * i1, s[2 * kk][3] * i1);
    pa[kk][2] = pack_bf16(s[2 * kk + 1][0] * i0, s[2 * kk + 1][1] * i0); pa[kk][3] = pack_bf16(s[2 * kk + 1][2] * i1, s[2 * kk + 1][3] * i1);
  }
  pm0 = pack_bf16(s[4][0] * i0, s[4][1] * i0); pm1 = pack_bf16(s[4][2] * i1, s[4][3] * i1);
  const int orow = (kb >> 1) * 64 + seg * 32 + mt * 16 + (m & 1) * 8 + r8;
  const unsigned ob = stg + ((kb & 1) * 2 + eh) * 16384 + orow * 128;
#pragma unroll
  for (int cp = 0; cp < 4; cp++) {
    float o0[4] = {0, 0, 0, 0}, o1[4] = {0, 0, 0, 0};
    mma1688(o0, pm0, pm1, vm[2 * cp]); mma1688(o1, pm0, pm1, vm[2 * cp + 1]);
    unsigned vf[4];
    int row = (m & 1) * 8 + r8;
    unsigned va = vb + row * 128 + (((cp * 2 + (m >> 1)) ^ r8) << 4);
    ldsm_x4_t(vf, va);
    mma16816(o0, pa[0], vf[0], vf[1]); mma16816(o1, pa[0], vf[2], vf[3]);
    if (mt) { ldsm_x4_t(vf, va + 2048); mma16816(o0, pa[1], vf[0], vf[1]); mma16816(o1, pa[1], vf[2], vf[3]); }
    stsm_x4(ob + (((cp * 2 + (m >> 1)) ^ r8) << 4), pack_bf16(o0[0], o0[1]), pack_bf16(o0[2], o0[3]), pack_bf16(o1[0], o1[1]), pack_bf16(o1[2], o1[3]));
  }
}

__device__ __forceinline__ void bulk_worker(unsigned sb, volatile int* misc, const bf16* __restrict__ x, const bf16* __restrict__ b1, const bf16* __restrict__ b2, bf16* __restrict__ out) {
  const int t = threadIdx.x, lane = t & 31, w = t >> 5, wg = w >> 2, g = lane >> 2, tq = lane & 3, m = lane >> 3, r8 = lane & 7;
  const unsigned bar = sb + SM_BAR;
  unsigned st = 0, ph = 0, seq = 0, sph = 0;
  float d[128];
  while (true) {
    mbar_wait(bar + 8 * (MB_FULL + st), ph);
    const int idr = misc[seq & 3]; seq++;
    const int idx = idr & 65535;
    if (idr < 0 || idx >= N_ITEMS) break;
    if (t == 0) ISTAMP(idx, 2);
    const Item it = decode_item(idx);
    const int nkb = item_nkb(it.type);
    if (it.type == T_ATT) {
      unsigned km[16], vm[8], kn[16], vn[8];
      const bool pref = idr >= 65536;
      if (pref) bulk_att_load(kn, vn, it.b, it.c, 0, w, lane);
      mbar_wait(bar + 8 * MB_STGE, sph ^ 1);
#pragma unroll 1
      for (int kb = 0; kb < 4; kb++) {
        if (!pref && !(kb & 1)) {
          if (lane < 4) wait_flag_ge(&g_flags.rec[it.c * 4 + lane], it.b * 4 + (kb >> 1) * 2 + wg + 1);
          __syncwarp();
          bulk_att_load(kn, vn, it.b, it.c, kb, w, lane);
        }
        if (kb) mbar_wait(bar + 8 * (MB_FULL + st), ph);
#pragma unroll
        for (int i = 0; i < 16; i++) km[i] = kn[i];
#pragma unroll
        for (int i = 0; i < 8; i++) vm[i] = vn[i];
        if (pref ? kb != 3 : !(kb & 1)) bulk_att_load(kn, vn, it.b, it.c, kb + 1, w, lane);
        bulk_att_stage(sb + st * STAGE_BYTES, sb + B_STG, km, vm, kb, w, lane);
        __syncwarp();
        if (lane == 0) mbar_arrive(bar + 8 * (MB_EMPTY + st));
        if (++st == NSTAGE) { st = 0; ph ^= 1; }
      }
      if (t == 0) misc[4] = idx;
      fence_proxy_async_smem();
      mbar_arrive(bar + 8 * MB_STGF); sph ^= 1;
      continue;
    }
    if (it.type >= T_RED) {
      __syncwarp();
      if (lane == 0) mbar_arrive(bar + 8 * (MB_EMPTY + st));
      if (++st == NSTAGE) { st = 0; ph ^= 1; }
      if (it.type == T_RED) {
#pragma unroll 2
        for (int i = 0; i < (it.ks ? 2 : 8); i++) {
          size_t o = ((size_t)it.b * 128 + it.c * (it.ks ? 4 : 16) + i * 2 + (t >> 7)) * DM + (t & 127) * 4;
          float4 a = __ldcg(reinterpret_cast<const float4*>(g_opart + o)), b = __ldcg(reinterpret_cast<const float4*>(g_opart + o + (size_t)S_TOK * DM));
          float4 c = __ldcg(reinterpret_cast<const float4*>(g_opart + o + (size_t)2 * S_TOK * DM)), e = __ldcg(reinterpret_cast<const float4*>(g_opart + o + (size_t)3 * S_TOK * DM));
          final_out(out, x, o, make_float4((a.x + b.x) + (c.x + e.x), (a.y + b.y) + (c.y + e.y), (a.z + b.z) + (c.z + e.z), (a.w + b.w) + (c.w + e.w)));
        }
      } else {
        size_t ol = ((size_t)it.c * 2 + (t >> 7)) * DM + (t & 127) * 4;
        float4 v[16];
#pragma unroll
        for (int i = 0; i < 16; i++) v[i] = __ldcg(reinterpret_cast<const float4*>(g_opl + ol + (size_t)i * 128 * DM));
#pragma unroll
        for (int st2 = 1; st2 < 16; st2 <<= 1)
#pragma unroll
          for (int i = 0; i < 16; i += 2 * st2) { v[i].x += v[i + st2].x; v[i].y += v[i + st2].y; v[i].z += v[i + st2].z; v[i].w += v[i + st2].w; }
        final_out(out, x, ol + (size_t)15 * 128 * DM, v[0]);
      }
      if (t == 0) ISTAMP(idx, 3);
      continue;
    }
    unsigned pst = 0, bv[32];
#pragma unroll
    for (int i = 0; i < 128; i++) d[i] = 0.0f;
    if (it.type == T_M1 || it.type == T_M2) {
      const unsigned* bp = reinterpret_cast<const unsigned*>((it.type == T_M1 ? b1 : b2) + it.c * 256) + tq;
#pragma unroll
      for (int i = 0; i < 32; i++) asm volatile("ld.global.nc.u32 %0, [%1];" : "=r"(bv[i]) : "l"(bp + i * 4));
    } else {
#pragma unroll
      for (int i = 0; i < 32; i++) bv[i] = 0;
    }
#define KLOOP(WG) \
    for (int kb = 0; kb < nkb; kb++) { \
      if (kb) mbar_wait(bar + 8 * (MB_FULL + st), ph); \
      unsigned sa = sb + st * STAGE_BYTES; \
      uint64_t ad = mkdesc(sa + wg * 8192, 16, 1024), bd = mkdesc(sa + 16384, 8192, 1024); \
      asm volatile("wgmma.fence.sync.aligned;" ::: "memory"); \
      _Pragma("unroll") for (int k = 0; k < 4; k++) WG(d, ad + k * 2, bd + k * 128, (kb | k) != 0); \
      asm volatile("wgmma.commit_group.sync.aligned;" ::: "memory"); \
      if (kb) { \
        asm volatile("wgmma.wait_group.sync.aligned 1;" ::: "memory"); \
        if (lane == 0) mbar_arrive(bar + 8 * (MB_EMPTY + pst)); \
      } \
      pst = st; \
      if (++st == NSTAGE) { st = 0; ph ^= 1; } \
    } \
    asm volatile("wgmma.wait_group.sync.aligned 0;" ::: "memory");
    if (it.hf) { KLOOP(wgmma_n128) } else { KLOOP(wgmma_n256) }
    if (lane == 0) mbar_arrive(bar + 8 * (MB_EMPTY + pst));
    if (it.type >= T_OUT) {
      const int col = it.c * 256 + (it.hf >> 1) * 128 + 2 * tq;
      float* pp = it.type == T_OUT ? g_opart + ((size_t)it.ks * S_TOK + it.b * 128 + w * 16 + g) * DM + col : g_opl + ((size_t)it.ks * 128 + w * 16 + g) * DM + col;
#pragma unroll
      for (int i = 0; i < 32; i++) {
        if (i == 16 && it.hf) break;
        __stcg(reinterpret_cast<float2*>(pp + i * 8), make_float2(d[4 * i], d[4 * i + 1]));
        __stcg(reinterpret_cast<float2*>(pp + 8 * DM + i * 8), make_float2(d[4 * i + 2], d[4 * i + 3]));
      }
      bar_sync(1, 256);
      if (t == 0) { red_release_add(&g_flags.p[it.b], 1); ISTAMP(idx, 3); }
      continue;
    }
#define ACT(F) _Pragma("unroll") for (int i = 0; i < 32; i++) { \
        unsigned u0 = badd2(pack_bf16(d[4 * i], d[4 * i + 1]), bv[i]), u1 = badd2(pack_bf16(d[4 * i + 2], d[4 * i + 3]), bv[i]); \
        d[4 * i] = F(bf_lo(u0)); d[4 * i + 1] = F(bf_hi(u0)); d[4 * i + 2] = F(bf_lo(u1)); d[4 * i + 3] = F(bf_hi(u1)); }
    if (it.type == T_M1) { ACT(gelu_t) } else if (it.type == T_M2) { ACT(silu_f) }
    mbar_wait(bar + 8 * MB_STGE, sph ^ 1);
    {
      const unsigned ob = sb + B_STG + (w * 16 + (m & 1) * 8 + r8) * 128;
#pragma unroll
      for (int i = 0; i < 16; i++)
        if (i < 8 || !it.hf) stsm_x4(ob + (i >> 2) * 16384 + ((((i & 3) * 2 + (m >> 1)) ^ r8) << 4), pack_bf16(d[8 * i], d[8 * i + 1]), pack_bf16(d[8 * i + 2], d[8 * i + 3]),
                pack_bf16(d[8 * i + 4], d[8 * i + 5]), pack_bf16(d[8 * i + 6], d[8 * i + 7]));
    }
    if (t == 0) misc[4] = idx;
    fence_proxy_async_smem();
    mbar_arrive(bar + 8 * MB_STGF); sph ^= 1;
  }
  mbar_wait(bar + 8 * MB_STGE, sph ^ 1);
  if (t == 0) misc[4] = -1;
  mbar_arrive(bar + 8 * MB_STGF);
}

__global__ void __launch_bounds__(384, 1)
k_main(const __grid_constant__ Maps maps, const bf16* __restrict__ x, const bf16* __restrict__ mem0, const bf16* __restrict__ b1, const bf16* __restrict__ b2, bf16* __restrict__ out, unsigned recmask) {
  extern __shared__ unsigned char smem_raw[];
  const unsigned sraw = smem_u32(smem_raw);
  const unsigned sb = (sraw + 1023u) & ~1023u;
  int* misc = reinterpret_cast<int*>(smem_raw + (sb - sraw) + SM_MISC);
  const int w = threadIdx.x >> 5;
  const bool helper = recmask == 0;
  const unsigned kc = blockIdx.x / CLS;
  const bool rec = kc < 32 && ((recmask >> kc) & 1);
  const int c = __popc(recmask & ((1u << (kc & 31)) - 1)) * CLS + (blockIdx.x & (CLS - 1));
  if (threadIdx.x == 0) {
    const unsigned bar = sb + SM_BAR;
    for (int i = 0; i < 8; i++) { mbar_init(bar + 8 * (MB_FULL + i), 1); mbar_init(bar + 8 * (MB_EMPTY + i), rec ? 1 : 8); }
    mbar_init(bar + 8 * MB_STGF, 256); mbar_init(bar + 8 * MB_STGE, 1);
    for (int i = MB_W0; i <= MB_AG; i++) mbar_init(bar + 8 * i, 1);
    if (rec) { mbar_expect_tx(bar + 8 * MB_S, 2560); mbar_expect_tx(bar + 8 * MB_V, 2048); mbar_expect_tx(bar + 8 * MB_RS, 8192); mbar_expect_tx(bar + 8 * MB_AG, 8192); }
    asm volatile("fence.mbarrier_init.release.cluster;" ::: "memory");
  }
  __syncthreads();
  asm volatile("barrier.cluster.arrive.release.aligned;\nbarrier.cluster.wait.acquire.aligned;" ::: "memory");
  if (rec && threadIdx.x == 256) {
    const unsigned bar = sb + SM_BAR; const int col = c * 64;
    mbar_expect_tx(bar + 8 * MB_W0, 131072);
    for (int kb = 0; kb < 8; kb++) tma_load_2d(sb + R_WO + kb * 8192, &maps.wq, col, kb * 64, bar + 8 * MB_W0);
    for (int kb = 0; kb < 8; kb++) tma_load_2d(sb + R_T1 + kb * 8192, &maps.wk, col, kb * 64, bar + 8 * MB_W0);
    mbar_expect_tx(bar + 8 * MB_W1, 65536);
    for (int kb = 0; kb < 8; kb++) tma_load_2d(sb + R_T2 + kb * 8192, &maps.wv, col, kb * 64, bar + 8 * MB_W1);
  }
  if (!helper) {
    asm volatile("griddepcontrol.wait;" ::: "memory");
    asm volatile("griddepcontrol.launch_dependents;");
  }
  if (DBGMODE && !rec) { if (helper) asm volatile("griddepcontrol.wait;" ::: "memory"); return; }
  if (w >= 8) {
    asm volatile("setmaxnreg.dec.sync.aligned.u32 24;");
    if (rec) { if (w == 8) rec_ring(maps, sb, c); else if (w == 9) rec_copy(sb, c); }
    else if (w == 8) bulk_producer(maps, sb, misc);
    else if ((threadIdx.x & 31) == 0) { if (w == 9) bulk_store(maps, sb, misc);
      else if (w == 10 && helper) asm volatile("griddepcontrol.wait;" ::: "memory"); }
  } else {
    if (rec) { asm volatile("setmaxnreg.inc.sync.aligned.u32 240;"); rec_worker(maps, sb, mem0, c); }
    else { asm volatile("setmaxnreg.inc.sync.aligned.u32 240;"); bulk_worker(sb, misc, x, b1, b2, out); }
  }
}

typedef CUresult (*EncFn)(CUtensorMap*, CUtensorMapDataType, cuuint32_t, void*, const cuuint64_t*, const cuuint64_t*, const cuuint32_t*, const cuuint32_t*,
                          CUtensorMapInterleave, CUtensorMapSwizzle, CUtensorMapL2promotion, CUtensorMapFloatOOBfill);
static void mk_map(EncFn enc, CUtensorMap* m, const void* ptr, uint64_t rows, uint64_t cols, uint32_t box_rows) {
  cuuint64_t dims[2] = {cols, rows}; cuuint64_t strides[1] = {cols * 2};
  cuuint32_t box[2] = {64, box_rows}, es[2] = {1, 1};
  enc(m, CU_TENSOR_MAP_DATA_TYPE_BFLOAT16, 2, const_cast<void*>(ptr), dims, strides, box, es, CU_TENSOR_MAP_INTERLEAVE_NONE, CU_TENSOR_MAP_SWIZZLE_128B,
      CU_TENSOR_MAP_L2_PROMOTION_L2_256B, CU_TENSOR_MAP_FLOAT_OOB_FILL_NONE);
}
extern "C" void kernel_launch(void* const* d_in, const int* in_sizes, int n_in, void* d_out, int out_size) {
  static EncFn enc = nullptr;
  static int ncl = 0, nhelp = 0;
  static unsigned recmask = 0xFFu;
  static void *p_xn, *p_y, *p_h1, *p_o, *p_qkv, *p_g;
  if (!enc) {
    void* fn = nullptr; cudaDriverEntryPointQueryResult qr;
    cudaGetDriverEntryPoint("cuTensorMapEncodeTiled", &fn, cudaEnableDefault, &qr);
    enc = (EncFn)fn;
    cudaGetSymbolAddress(&p_xn, g_xn); cudaGetSymbolAddress(&p_y, g_y); cudaGetSymbolAddress(&p_h1, g_h1);
    cudaGetSymbolAddress(&p_o, g_o); cudaGetSymbolAddress(&p_qkv, g_qkv); cudaGetSymbolAddress(&p_g, g_g);
    cudaFuncSetAttribute(k_main, cudaFuncAttributeMaxDynamicSharedMemorySize, SMEM_TOTAL);
    cudaLaunchConfig_t cfg = {}; cfg.gridDim = dim3(128); cfg.blockDim = dim3(384); cfg.dynamicSmemBytes = SMEM_TOTAL;
    cudaLaunchAttribute at[1]; at[0].id = cudaLaunchAttributeClusterDimension; at[0].val.clusterDim.x = CLS; at[0].val.clusterDim.y = 1; at[0].val.clusterDim.z = 1;
    cfg.attrs = at; cfg.numAttrs = 1;
    if (cudaOccupancyMaxActiveClusters(&ncl, k_main, &cfg) != cudaSuccess) { cudaGetLastError(); ncl = 14; }
    ncl = ncl > 16 ? 16 : (ncl < 9 ? 9 : ncl);
    int nsm = 0, dev = 0; cudaGetDevice(&dev); cudaDeviceGetAttribute(&nsm, cudaDevAttrMultiProcessorCount, dev);
    nhelp = nsm - ncl * CLS;
  }
  Maps maps;
  mk_map(enc, &maps.xn, p_xn, S_TOK, DM, 128); mk_map(enc, &maps.y, p_y, S_TOK, DM, 128); mk_map(enc, &maps.h1, p_h1, S_TOK, FF, 128);
  mk_map(enc, &maps.o, p_o, S_TOK, HD, 128); mk_map(enc, &maps.qkv_st, p_qkv, S_TOK, 3 * HD, 128); mk_map(enc, &maps.qkv_ld, p_qkv, S_TOK, 3 * HD, 32);
  mk_map(enc, &maps.g, p_g, S_TOK, DM, 128);
  mk_map(enc, &maps.wq, d_in[2], DM, HD, 64); mk_map(enc, &maps.wk, d_in[3], DM, HD, 64); mk_map(enc, &maps.wv, d_in[4], DM, HD, 64);
  mk_map(enc, &maps.wo, d_in[5], HD, DM, 64); mk_map(enc, &maps.w1, d_in[8], DM, FF, 64); mk_map(enc, &maps.w2, d_in[10], FF, DM, 64);
  cudaStream_t st = cudaStreamPerThread;
  k_pre<<<256, 256, 0, st>>>((const bf16*)d_in[0], (const char*)d_in[2], (const char*)d_in[3], (const char*)d_in[4], (const char*)d_in[5]);
  cudaLaunchConfig_t cfg = {}; cfg.gridDim = dim3(ncl * CLS); cfg.blockDim = dim3(384); cfg.dynamicSmemBytes = SMEM_TOTAL; cfg.stream = st;
  cudaLaunchAttribute at[2]; at[1].id = cudaLaunchAttributeClusterDimension; at[1].val.clusterDim.x = CLS; at[1].val.clusterDim.y = 1; at[1].val.clusterDim.z = 1;
  at[0].id = cudaLaunchAttributeProgrammaticStreamSerialization; at[0].val.programmaticStreamSerializationAllowed = 1;
#define PDL1 0
  cfg.attrs = at + (PDL1 ? 0 : 1); cfg.numAttrs = PDL1 ? 2 : 1;
  cudaLaunchKernelEx(&cfg, k_main, maps, (const bf16*)d_in[0], (const bf16*)d_in[1], (const bf16*)d_in[9], (const bf16*)d_in[11], (bf16*)d_out, recmask);
  if (nhelp > 0) {
    cfg.gridDim = dim3(nhelp);
    cfg.attrs = at; cfg.numAttrs = 1;
    cudaLaunchKernelEx(&cfg, k_main, maps, (const bf16*)d_in[0], (const bf16*)d_in[1], (const bf16*)d_in[9], (const bf16*)d_in[11], (bf16*)d_out, 0u);
  }
}
```

```cpp
#include <cuda_runtime.h>
#include <cuda_bf16.h>
#include <cuda.h>
#include <stdint.h>

typedef __nv_bfloat16 bf16;

#define S_TOK 2048
#define DM 512
#define NH 32
#define DH 128
#define HD 4096
#define NMEM 8
#define SEG 32
#define NSEG 64
#define FF 1792
#define NBLK 16
#define NREC 64
#define REPL 0
#define CLS 8

__device__ __align__(1024) bf16 g_xn[S_TOK * DM];
__device__ __align__(1024) bf16 g_y[S_TOK * DM];
__device__ __align__(1024) bf16 g_qkv[(size_t)S_TOK * 3 * HD];
__device__ __align__(1024) bf16 g_h1[S_TOK * FF];
__device__ __align__(1024) bf16 g_g[S_TOK * DM];
__device__ __align__(1024) bf16 g_o[(size_t)S_TOK * HD];
__device__ __align__(1024) bf16 g_km[NSEG * NH * NMEM * DH];
__device__ __align__(1024) bf16 g_vmt[NSEG * NH * DH * NMEM];
__device__ __align__(1024) float g_opart[(size_t)4 * S_TOK * DM];
__device__ __align__(1024) float g_opl[(size_t)16 * 128 * DM];
__device__ __align__(1024) unsigned g_part[8 * 2 * 8 * 8 * 512];
struct Flags {
  unsigned qkv[NBLK * 48];
  unsigned h1[NBLK];
  unsigned g[NBLK];
  unsigned o[NBLK * 4];
  unsigned p[NBLK];
  unsigned o16[16];
  unsigned ctr;
  unsigned rec[NREC];
  unsigned abort_;
};
__device__ __align__(1024) Flags g_flags;

#define RSTAMP(k)
#define DBGMODE 0
#define ISTAMP(i, k)
__device__ __forceinline__ unsigned smem_u32(const void* p) { return (unsigned)__cvta_generic_to_shared(p); }
__device__ __forceinline__ float bf16r(float x) { unsigned u; asm("cvt.rn.bf16x2.f32 %0, %1, %2;" : "=r"(u) : "f"(x), "f"(0.0f)); return __uint_as_float(u); }
__device__ __forceinline__ unsigned pack_bf16(float lo, float hi) {
  __nv_bfloat162 v = __floats2bfloat162_rn(lo, hi);
  return *reinterpret_cast<unsigned*>(&v);
}
__device__ __forceinline__ float bf_lo(unsigned u) { return __uint_as_float(u << 16); }
__device__ __forceinline__ float bf_hi(unsigned u) { return __uint_as_float(u & 0xffff0000u); }

#define SPIN_LIMIT (1u << 20)
#define TRAP_IF(x) if ((x) > SPIN_LIMIT) { asm volatile("st.global.u32 [%0], %1;" ::"l"(0ull), "r"(0u) : "memory"); break; }
__device__ __forceinline__ unsigned ld_acquire(const unsigned* p) {
  unsigned v; asm volatile("ld.acquire.gpu.global.u32 %0, [%1];" : "=r"(v) : "l"(p) : "memory"); return v;
}
__device__ __forceinline__ unsigned ld_relaxed(const unsigned* p) {
  unsigned v; asm volatile("ld.relaxed.gpu.global.u32 %0, [%1];" : "=r"(v) : "l"(p) : "memory"); return v;
}
__device__ __forceinline__ void red_release_add(unsigned* p, unsigned v) {
  asm volatile("red.release.gpu.global.add.u32 [%0], %1;" ::"l"(p), "r"(v) : "memory");
}
__device__ __forceinline__ void st_release(unsigned* p, unsigned v) {
  asm volatile("st.release.gpu.global.u32 [%0], %1;" ::"l"(p), "r"(v) : "memory");
}
__device__ __forceinline__ void wait_flag_ge(const unsigned* p, unsigned target) {
  unsigned it = 0;
  while (ld_acquire(p) < target) {
    __nanosleep(64);
    TRAP_IF(++it);
  }
}
__device__ __forceinline__ uint4 ldv4_relaxed(const void* p) {
  uint4 a; asm volatile("ld.relaxed.gpu.global.v4.u32 {%0,%1,%2,%3}, [%4];" : "=r"(a.x), "=r"(a.y), "=r"(a.z), "=r"(a.w) : "l"(p) : "memory"); return a;
}
__device__ __forceinline__ uint2 ldv2_relaxed(const void* p) {
  uint2 a; asm volatile("ld.relaxed.gpu.global.v2.u32 {%0,%1}, [%2];" : "=r"(a.x), "=r"(a.y) : "l"(p) : "memory"); return a;
}
__device__ __forceinline__ void mbar_init(unsigned mb, unsigned cnt) { asm volatile("mbarrier.init.shared::cta.b64 [%0], %1;" ::"r"(mb), "r"(cnt) : "memory"); }
__device__ __forceinline__ void mbar_expect_tx(unsigned mb, unsigned bytes) { asm volatile("mbarrier.arrive.expect_tx.shared::cta.b64 _, [%0], %1;" ::"r"(mb), "r"(bytes) : "memory"); }
__device__ __forceinline__ void mbar_arrive(unsigned mb) { asm volatile("mbarrier.arrive.shared::cta.b64 _, [%0];" ::"r"(mb) : "memory"); }
__device__ __forceinline__ void mbar_wait(unsigned mb, unsigned parity) {
  unsigned ok, it = 0;
  while (true) {
    asm volatile("{.reg .pred p; mbarrier.try_wait.parity.shared::cta.b64 p, [%1], %2; selp.u32 %0,1,0,p;}" : "=r"(ok) : "r"(mb), "r"(parity) : "memory");
    if (ok) break;
    TRAP_IF(++it);
  }
}
__device__ __forceinline__ void mbar_wait_sleep(unsigned mb, unsigned parity) {
  unsigned ok, it = 0;
  while (true) {
    asm volatile("{.reg .pred p; mbarrier.test_wait.parity.shared::cta.b64 p, [%1], %2; selp.u32 %0,1,0,p;}" : "=r"(ok) : "r"(mb), "r"(parity) : "memory");
    if (ok) break;
    __nanosleep(200);
    TRAP_IF(++it);
  }
}
__device__ __forceinline__ float ex2f(float x) { float y; asm("ex2.approx.ftz.f32 %0, %1;" : "=f"(y) : "f"(x)); return y; }
__device__ __forceinline__ int opaque_tid() { int t = threadIdx.x; t = __shfl_sync(~0u, t, t & 31); return t; }
#define LOG2E 1.4426950408889634f
__device__ __forceinline__ void mbar_wait_cluster(unsigned mb, unsigned parity) {
  unsigned ok, it = 0;
  while (true) {
    asm volatile("{.reg .pred p; mbarrier.try_wait.parity.acquire.cluster.shared::cta.b64 p, [%1], %2; selp.u32 %0,1,0,p;}" : "=r"(ok) : "r"(mb), "r"(parity) : "memory");
    if (ok) break;
    TRAP_IF(++it);
  }
}
__device__ __forceinline__ void bar_sync(int id, int n) { asm volatile("bar.sync %0, %1;" ::"r"(id), "r"(n) : "memory"); }
__device__ __forceinline__ void bar_arrive(int id, int n) { asm volatile("bar.arrive %0, %1;" ::"r"(id), "r"(n) : "memory"); }
__device__ __forceinline__ void tma_load_2d(unsigned dst, const CUtensorMap* map, int c0, int c1, unsigned mb) {
  asm volatile("cp.async.bulk.tensor.2d.shared::cluster.global.mbarrier::complete_tx::bytes [%0], [%1, {%3, %4}], [%2];"
               ::"r"(dst), "l"((uint64_t)map), "r"(mb), "r"(c0), "r"(c1) : "memory");
}
__device__ __forceinline__ void tma_store_2d(const CUtensorMap* map, unsigned src, int c0, int c1) {
  asm volatile("cp.async.bulk.tensor.2d.global.shared::cta.bulk_group [%0, {%2, %3}], [%1];"
               ::"l"((uint64_t)map), "r"(src), "r"(c0), "r"(c1) : "memory");
}
__device__ __forceinline__ void fence_proxy_async() { asm volatile("fence.proxy.async;" ::: "memory"); }
__device__ __forceinline__ void fence_proxy_async_smem() { asm volatile("fence.proxy.async.shared::cta;" ::: "memory"); }
__device__ __forceinline__ void ldsm_x4(unsigned* r, unsigned addr) {
  asm volatile("ldmatrix.sync.aligned.m8n8.x4.shared.b16 {%0,%1,%2,%3}, [%4];" : "=r"(r[0]), "=r"(r[1]), "=r"(r[2]), "=r"(r[3]) : "r"(addr) : "memory");
}
__device__ __forceinline__ void ldsm_x4_t(unsigned* r, unsigned addr) {
  asm volatile("ldmatrix.sync.aligned.m8n8.x4.trans.shared.b16 {%0,%1,%2,%3}, [%4];" : "=r"(r[0]), "=r"(r[1]), "=r"(r[2]), "=r"(r[3]) : "r"(addr) : "memory");
}
__device__ __forceinline__ void stsm_x2_t(unsigned addr, unsigned r0, unsigned r1) {
  asm volatile("stmatrix.sync.aligned.m8n8.x2.trans.shared.b16 [%0], {%1,%2};" ::"r"(addr), "r"(r0), "r"(r1) : "memory");
}
__device__ __forceinline__ void stsm_x4(unsigned addr, unsigned r0, unsigned r1, unsigned r2, unsigned r3) {
  asm volatile("stmatrix.sync.aligned.m8n8.x4.shared.b16 [%0], {%1,%2,%3,%4};" ::"r"(addr), "r"(r0), "r"(r1), "r"(r2), "r"(r3) : "memory");
}
__device__ __forceinline__ void mma16816(float* d, const unsigned* a, unsigned b0, unsigned b1) {
  asm volatile("mma.sync.aligned.m16n8k16.row.col.f32.bf16.bf16.f32 {%0,%1,%2,%3}, {%4,%5,%6,%7}, {%8,%9}, {%0,%1,%2,%3};"
               : "+f"(d[0]), "+f"(d[1]), "+f"(d[2]), "+f"(d[3]) : "r"(a[0]), "r"(a[1]), "r"(a[2]), "r"(a[3]), "r"(b0), "r"(b1));
}
__device__ __forceinline__ void mma1688(float* d, unsigned a0, unsigned a1, unsigned b0) {
  asm volatile("mma.sync.aligned.m16n8k8.row.col.f32.bf16.bf16.f32 {%0,%1,%2,%3}, {%4,%5}, {%6}, {%0,%1,%2,%3};"
               : "+f"(d[0]), "+f"(d[1]), "+f"(d[2]), "+f"(d[3]) : "r"(a0), "r"(a1), "r"(b0));
}
__device__ __forceinline__ uint64_t mkdesc(unsigned addr, unsigned lbo, unsigned sbo) {
  return (uint64_t)((addr >> 4) & 0x3fff) | ((uint64_t)(lbo >> 4) << 16) | ((uint64_t)(sbo >> 4) << 32) | (1ull << 62);
}
#define R8(b) "+f"(d[b]), "+f"(d[b + 1]), "+f"(d[b + 2]), "+f"(d[b + 3]), "+f"(d[b + 4]), "+f"(d[b + 5]), "+f"(d[b + 6]), "+f"(d[b + 7])
#define R32(b) R8(b), R8(b + 8), R8(b + 16), R8(b + 24)
__device__ __forceinline__ void wgmma_n256(float* d, uint64_t ad, uint64_t bd, int acc) {
  asm volatile(
      "{.reg .pred p; setp.ne.b32 p, %130, 0;\n"
      "wgmma.mma_async.sync.aligned.m64n256k16.f32.bf16.bf16 "
      "{%0,%1,%2,%3,%4,%5,%6,%7,%8,%9,%10,%11,%12,%13,%14,%15,%16,%17,%18,%19,%20,%21,%22,%23,%24,%25,%26,%27,%28,%29,%30,%31,"
      "%32,%33,%34,%35,%36,%37,%38,%39,%40,%41,%42,%43,%44,%45,%46,%47,%48,%49,%50,%51,%52,%53,%54,%55,%56,%57,%58,%59,%60,%61,%62,%63,"
      "%64,%65,%66,%67,%68,%69,%70,%71,%72,%73,%74,%75,%76,%77,%78,%79,%80,%81,%82,%83,%84,%85,%86,%87,%88,%89,%90,%91,%92,%93,%94,%95,"
      "%96,%97,%98,%99,%100,%101,%102,%103,%104,%105,%106,%107,%108,%109,%110,%111,%112,%113,%114,%115,%116,%117,%118,%119,%120,%121,%122,%123,%124,%125,%126,%127},"
      "%128, %129, p, 1, 1, 0, 1;}\n"
      : R32(0), R32(32), R32(64), R32(96)
      : "l"(ad), "l"(bd), "r"(acc));
}

__device__ __forceinline__ void wgmma_n128(float* d, uint64_t ad, uint64_t bd, int acc) {
  asm volatile(
      "{.reg .pred p; setp.ne.b32 p, %66, 0;\n"
      "wgmma.mma_async.sync.aligned.m64n128k16.f32.bf16.bf16 {%0,%1,%2,%3,%4,%5,%6,%7,%8,%9,%10,%11,%12,%13,%14,%15,%16,%17,%18,%19,%20,%21,%22,%23,%24,%25,%26,%27,%28,%29,%30,%31,%32,%33,%34,%35,%36,%37,%38,%39,%40,%41,%42,%43,%44,%45,%46,%47,%48,%49,%50,%51,%52,%53,%54,%55,%56,%57,%58,%59,%60,%61,%62,%63}, %64, %65, p, 1, 1, 0, 1;}\n"
      : R32(0), R32(32)
      : "l"(ad), "l"(bd), "r"(acc));
}

__device__ __forceinline__ void ln16(const float* x, float* o) {
  float s = 0;
#pragma unroll
  for (int i = 0; i < 16; i++) s += x[i];
#pragma unroll
  for (int of = 16; of > 0; of >>= 1) s += __shfl_xor_sync(~0u, s, of);
  float mean = s * (1.0f / DM);
  float v = 0;
#pragma unroll
  for (int i = 0; i < 16; i++) { float dd = x[i] - mean; v += dd * dd; }
#pragma unroll
  for (int of = 16; of > 0; of >>= 1) v += __shfl_xor_sync(~0u, v, of);
  float mb = bf16r(mean);
  float vb = bf16r(v * (1.0f / DM));
  float den = bf16r(sqrtf(bf16r(vb + 1e-5f)));
#pragma unroll
  for (int i = 0; i < 16; i++) o[i] = bf16r(__fdiv_rn(bf16r(x[i] - mb), den));
}
__global__ void __launch_bounds__(256) k_pre(const bf16* __restrict__ x, const char* wq, const char* wk, const char* wv, const char* wo) {
  int t = threadIdx.x, lane = t & 31, w = t >> 5;
  asm volatile("griddepcontrol.launch_dependents;");
  {
    int g2 = blockIdx.x * 256 + t, o = (g2 & 32767) * 128;
    asm volatile("prefetch.global.L2 [%0];" ::"l"((g2 < 32768 ? wk : wv) + o));
    asm volatile("prefetch.global.L2 [%0];" ::"l"((g2 < 32768 ? wq : wo) + o));
  }
  int row = blockIdx.x * 8 + w;
  const uint4* src = reinterpret_cast<const uint4*>(x + (size_t)row * DM);
  uint4 a = src[lane], b = src[lane + 32];
  unsigned u[8] = {a.x, a.y, a.z, a.w, b.x, b.y, b.z, b.w};
  float f[16], o[16], o2[16];
#pragma unroll
  for (int i = 0; i < 8; i++) { f[2 * i] = bf_lo(u[i]); f[2 * i + 1] = bf_hi(u[i]); }
  ln16(f, o);
  ln16(o, o2);
  uint4* d1 = reinterpret_cast<uint4*>(g_xn + (size_t)row * DM);
  uint4* d2 = reinterpret_cast<uint4*>(g_y + (size_t)row * DM);
  d1[lane] = make_uint4(pack_bf16(o[0], o[1]), pack_bf16(o[2], o[3]), pack_bf16(o[4], o[5]), pack_bf16(o[6], o[7]));
  d1[lane + 32] = make_uint4(pack_bf16(o[8], o[9]), pack_bf16(o[10], o[11]), pack_bf16(o[12], o[13]), pack_bf16(o[14], o[15]));
  d2[lane] = make_uint4(pack_bf16(o2[0], o2[1]), pack_bf16(o2[2], o2[3]), pack_bf16(o2[4], o2[5]), pack_bf16(o2[6], o2[7]));
  d2[lane + 32] = make_uint4(pack_bf16(o2[8], o2[9]), pack_bf16(o2[10], o2[11]), pack_bf16(o2[12], o2[13]), pack_bf16(o2[14], o2[15]));
  int gt = blockIdx.x * 256 + t;
  uint4 z = make_uint4(0, 0, 0, 0);
  if (gt < 16384) reinterpret_cast<uint4*>(g_part)[gt] = z;
  if (gt < (int)(sizeof(Flags) / 4)) reinterpret_cast<unsigned*>(&g_flags)[gt] = 0;
}

struct Maps { CUtensorMap xn, y, h1, o, qkv_st, qkv_ld, g, wq, wk, wv, wo, w1, w2; };

#define NSTAGE 3
#define STAGE_BYTES 49152
#define B_STG (NSTAGE * STAGE_BYTES)
#define R_WO 0
#define R_T1 65536
#define R_T2 131072
#define R_RING 65536
#define RING_N 4
#define RING_BYTES 12288
#define R_MEM 196608
#define R_QS (R_MEM + 8448)
#define R_KS (R_QS + 1152)
#define R_OS (R_KS + 1152)
#define R_SOWN (R_OS + 2176)
#define R_SPEER (R_SOWN + 1280)
#define R_VM (R_SPEER + 1280)
#define R_VRED (R_VM + 2048)
#define R_RS (R_VRED + 6144)
#define SM_BAR (R_RS + 8192)
#define SMEM_TOTAL (SM_BAR + 256 + 1024)
#define MB_FULL 0
#define MB_EMPTY 8
#define MB_STGF 16
#define MB_STGE 17
#define MB_W0 18
#define MB_W1 19
#define MB_WO 20
#define MB_S 21
#define MB_V 22
#define MB_KVR 23
#define MB_KVF 24
#define MB_RS 25
#define MB_AG 26
#define SM_MISC (SM_BAR + 224)

#define N_KV 544
#define I_M1 544
#define I_Q 656
#define I_M2 912
#define I_POST 944
#define I_TAIL (I_POST + 16 * 32)
#define N_ITEMS (I_TAIL + 7 * 8 + 64 + 32 + 64)
enum { T_QKV = 0, T_M1 = 1, T_M2 = 2, T_ATT = 3, T_OUT = 4, T_OUTL = 5, T_RED = 6, T_REDL = 7 };
struct Item { int type, b, c, ks, hf; };
__device__ __forceinline__ Item decode_item(int i) {
  Item it; it.ks = 0; it.hf = 0;
  if (i < 64) { it.type = T_QKV; it.b = 0; it.c = 16 + (i >> 1); it.hf = 1 + (i & 1); }
  else if (i < N_KV) { it.type = T_QKV; it.b = (i - 32) >> 5; it.c = 16 + (i & 31); }
  else if (i < I_Q) { it.type = T_M1; it.b = (i - I_M1) / 7; it.c = (i - I_M1) % 7; }
  else if (i < I_M2) { it.type = T_QKV; it.b = (i - I_Q) >> 4; it.c = (i - I_Q) & 15; }
  else if (i < I_POST) { it.type = T_M2; it.b = (i - I_M2) >> 1; it.c = (i - I_M2) & 1; }
  else if (i < I_TAIL) {
    int x = i - I_POST, p = x >> 5, r = x & 31;
    if (r < 16) { it.type = T_ATT; it.b = p; it.c = r; }
    else if (r < 24) { it.type = T_OUT; it.b = p - 3; it.c = r & 1; it.ks = (r - 16) >> 1; }
    else { it.type = T_RED; it.b = p - 5; it.c = r - 24; }
  } else {
    int x = i - I_TAIL, r = x & 7;
    if (x < 16 || (x >= 24 && x < 40)) { int y = x < 16 ? x : x - 24; it.type = T_OUT; it.b = x < 16 ? 13 : 14; it.c = (y >> 1) & 1; it.ks = y >> 2; it.hf = 1 + (y & 1); }
    else if (x < 56) { it.type = T_RED; it.b = x < 24 ? 11 : 7 + (x >> 3); it.c = r; }
    else if (x < 120) { it.type = T_OUTL; it.b = 15; it.c = (x >> 1) & 1; it.ks = (x - 56) >> 2; it.hf = 1 + (x & 1); }
    else if (x < 152) { it.type = T_RED; it.b = 14; it.c = x - 120; it.ks = 1; }
    else { it.type = T_REDL; it.b = 15; it.c = x - 152; }
  }
  return it;
}
__device__ __forceinline__ int item_nkb(int type) { return type == T_M2 ? 28 : (type == T_OUT ? 16 : (type >= T_RED ? 1 : (type >= T_ATT ? 4 : 8))); }

__device__ __forceinline__ void st_async_b64(unsigned raddr, unsigned lo, unsigned hi, unsigned rmb) {
  asm volatile("st.async.weak.shared::cluster.mbarrier::complete_tx::bytes.v2.b32 [%0], {%1,%2}, [%3];" ::"r"(raddr), "r"(lo), "r"(hi), "r"(rmb) : "memory");
}
__device__ __forceinline__ void st_async_b32(unsigned raddr, unsigned v, unsigned rmb) {
  asm volatile("st.async.weak.shared::cluster.mbarrier::complete_tx::bytes.b32 [%0], %1, [%2];" ::"r"(raddr), "r"(v), "r"(rmb) : "memory");
}
__device__ __forceinline__ unsigned mapa(unsigned a, unsigned rank) {
  unsigned r; asm volatile("mapa.shared::cluster.u32 %0, %1, %2;" : "=r"(r) : "r"(a), "r"(rank)); return r;
}
__device__ __forceinline__ void sts64(unsigned a, unsigned x, unsigned y) { asm volatile("st.shared.v2.b32 [%0], {%1,%2};" ::"r"(a), "r"(x), "r"(y) : "memory"); }
__device__ __forceinline__ void sts128(unsigned a, uint4 v) { asm volatile("st.shared.v4.b32 [%0], {%1,%2,%3,%4};" ::"r"(a), "r"(v.x), "r"(v.y), "r"(v.z), "r"(v.w) : "memory"); }
__device__ __forceinline__ uint2 lds64(unsigned a) { uint2 v; asm volatile("ld.shared.v2.b32 {%0,%1}, [%2];" : "=r"(v.x), "=r"(v.y) : "r"(a) : "memory"); return v; }
__device__ __forceinline__ uint4 lds128(unsigned a) { uint4 v; asm volatile("ld.shared.v4.b32 {%0,%1,%2,%3}, [%4];" : "=r"(v.x), "=r"(v.y), "=r"(v.z), "=r"(v.w) : "r"(a) : "memory"); return v; }
__device__ __forceinline__ float lds32f(unsigned a) { float v; asm volatile("ld.shared.f32 %0, [%1];" : "=f"(v) : "r"(a) : "memory"); return v; }
#define spin_check(it) TRAP_IF(++it)
#define POLLV 0
#define BAR8 0
#define D_STAG 150
#define D_RED 540
#define D_PUB 0
#define DELAY(n) do { unsigned c0_, c1_; asm volatile("mov.u32 %0, %%clock;" : "=r"(c0_)); do { asm volatile("mov.u32 %0, %%clock;" : "=r"(c1_)); } while (c1_ - c0_ < (n)); } while (0)
#define VD 2
#define NPRE 3
#define SELP 1
#define SCALE_QK 0.08838834764831845f

__device__ __forceinline__ void rec_worker(const Maps& maps, unsigned sb, const bf16* __restrict__ mem0, const int c) {
  const int h = c >> 1, j = c & 1;
  const int t = opaque_tid(), lane = t & 31, w = t >> 5, g = lane >> 2, tq = lane & 3;
  const int m = lane >> 3, r8 = lane & 7, kh = w >> 2, et = w & 3;
  const unsigned bar = sb + SM_BAR;
  unsigned wq[16][4], wk[16][4], wo[8][4];
  const unsigned woff = (kh * 4) * 8192 + ((m >> 1) * 8 + r8) * 128 + (((et * 2 + (m & 1)) ^ r8) << 4);
  mbar_wait(bar + 8 * MB_W0, 0);
#pragma unroll
  for (int i = 0; i < 16; i++) {
    ldsm_x4_t(wq[i], sb + R_WO + woff + (i >> 2) * 8192 + (i & 3) * 2048);
    ldsm_x4_t(wk[i], sb + R_T1 + woff + (i >> 2) * 8192 + (i & 3) * 2048);
  }
  bar_sync(2, 288);
  if (t == 0) {
    fence_proxy_async_smem();
    mbar_expect_tx(bar + 8 * MB_WO, 65536);
    for (int kb = 0; kb < 2; kb++)
      for (int cb = 0; cb < 4; cb++) tma_load_2d(sb + R_WO + (kb * 4 + cb) * 8192, &maps.wo, j * 256 + cb * 64, h * 128 + kb * 64, bar + 8 * MB_WO);
  }
  mbar_wait(bar + 8 * MB_W1, 0);
  const unsigned pV = sb + R_T2 + woff;
  const unsigned rk = c & 7, peer = rk ^ 1, cl = c >> 3;
#define KEEP(x) x = __shfl_sync(~0u, x, lane)
  unsigned pA = sb + R_MEM + kh * 4096 + lane * 16;
  unsigned pW0 = sb + R_WO + (w >> 1) * 8192 + ((m >> 1) * 8 + r8) * 128 + ((((w & 1) * 4 + (m & 1)) ^ r8) << 4);
  unsigned pW1 = pW0 ^ 32;
  unsigned pVk = pV;
  unsigned aX = sb + R_VRED + et * 512 + lane * 16;
  unsigned aQKst = sb + (kh ? R_KS : R_QS) + r8 * 144 + (et * 16 + (m & 1) * 8) * 2;
  unsigned aL8 = sb + lane * 8;
  unsigned aSl = mapa(sb + R_SOWN + w * 256 + lane * 8, rk), aSr = mapa(sb + R_SPEER + w * 256 + lane * 8, peer);
  unsigned aVl = mapa(sb + R_VM + (j * 4 + et) * 256 + lane * 8, rk), aVr = mapa(sb + R_VM + (j * 4 + et) * 256 + lane * 8, peer);
  const unsigned mbSl = mapa(bar + 8 * MB_S, rk), mbSr = mapa(bar + 8 * MB_S, peer), mbVl = mbSl + 8, mbVr = mbSr + 8;
  unsigned aQ = sb + R_QS + r8 * 144 + m * 16;
  unsigned oKx = (et * 8 + r8) * 128 + ((m ^ r8) << 4);
  unsigned oVx = 4096 + (et >> 1) * 4096 + ((m >> 1) * 8 + r8) * 128 + ((((et & 1) * 4 + (m & 1)) ^ r8) << 4);
  unsigned aOst = sb + R_OS + r8 * 272 + (et * 32 + m * 8) * 2;
  unsigned aOld = sb + R_OS + r8 * 272 + m * 16;
  unsigned aVm = sb + R_VM + et * 512 + lane * 8;
  unsigned aRSr = mapa(sb + R_RS + (h & 3) * 2048 + (w & 1) * 1024 + lane * 8, j * 4 + (w >> 1));
  unsigned mbRSr = mapa(bar + 8 * MB_RS, j * 4 + (w >> 1));
  unsigned t8 = t * 8;
  KEEP(pA); KEEP(pW0); KEEP(pW1); KEEP(pVk); KEEP(aX); KEEP(aQKst); KEEP(aL8); KEEP(aSl); KEEP(aSr); KEEP(aVl); KEEP(aVr); KEEP(aQ); KEEP(oKx); KEEP(oVx);
  KEEP(aOst); KEEP(aOld); KEEP(aVm); KEEP(aRSr); KEEP(mbRSr); KEEP(t8);
  mbar_wait(bar + 8 * MB_WO, 0);
#pragma unroll
  for (int ks = 0; ks < 4; ks++) { ldsm_x4_t(wo[2 * ks], pW0 + ks * 2048); ldsm_x4_t(wo[2 * ks + 1], pW1 + ks * 2048); }
  {
    unsigned v[8];
#pragma unroll
    for (int q = 0; q < 8; q++) v[q] = __ldg(reinterpret_cast<const unsigned*>(mem0) + q * 256 + t);
    sts128(sb + R_MEM + t * 32, make_uint4(__byte_perm(v[0], v[1], 0x5410), __byte_perm(v[2], v[3], 0x5410), __byte_perm(v[4], v[5], 0x5410), __byte_perm(v[6], v[7], 0x5410)));
    sts128(sb + R_MEM + t * 32 + 16, make_uint4(__byte_perm(v[0], v[1], 0x7632), __byte_perm(v[2], v[3], 0x7632), __byte_perm(v[4], v[5], 0x7632), __byte_perm(v[6], v[7], 0x7632)));
  }
  bar_sync(1, 256);

#pragma unroll 1
  for (int s = 0;; s++) {
    const unsigned par = s & 1;
    const unsigned slot = s & (RING_N - 1), rpar = (s / RING_N) & 1;
    const unsigned ring = sb + R_RING + slot * RING_BYTES;
    asm volatile("" : "+r"(t8));
    RSTAMP(1);
    RSTAMP(2);
    float aq[4] = {0, 0, 0, 0}, ak[4] = {0, 0, 0, 0}, av[4] = {0, 0, 0, 0};
    {
      unsigned b[8][4], f1[8][4], f0[8][4];
#define VLD(i) do { ldsm_x4_t(b[i], pA + (i) * 512); ldsm_x4_t(f0[i], pVk + ((i) >> 1) * 8192 + ((i) & 1) * 4096); ldsm_x4_t(f1[i], pVk + ((i) >> 1) * 8192 + ((i) & 1) * 4096 + 2048); } while (0)
      VLD(0);
      if (VD > 1) VLD(1);
#pragma unroll
      for (int i = 0; i < 8; i++) {
        if (i + VD < 8) VLD(i + VD);
        mma16816(aq, wq[2 * i], b[i][0], b[i][1]); mma16816(ak, wk[2 * i], b[i][0], b[i][1]); mma16816(av, f0[i], b[i][0], b[i][1]);
        mma16816(aq, wq[2 * i + 1], b[i][2], b[i][3]); mma16816(ak, wk[2 * i + 1], b[i][2], b[i][3]); mma16816(av, f1[i], b[i][2], b[i][3]);
      }
    }
    RSTAMP(3);
#define STSF4(a, v) asm volatile("st.shared.v4.f32 [%0], {%1,%2,%3,%4};" ::"r"(a), "f"(v[0]), "f"(v[1]), "f"(v[2]), "f"(v[3]) : "memory")
    unsigned f[8][4];
#define WO_PREFETCH() do { _Pragma("unroll") for (int i = 0; i < NPRE; i++) { ldsm_x4_t(f[2 * i], pW0 + 32768 + i * 2048); ldsm_x4_t(f[2 * i + 1], pW1 + 32768 + i * 2048); } } while (0)
    if (kh) {
      STSF4(aX, aq);
      bar_sync(4 + et, 64);
      uint4 o = lds128(aX + 2048), o2 = lds128(aX + 4096);
      stsm_x2_t(aQKst, pack_bf16(ak[0] + __uint_as_float(o.x), ak[1] + __uint_as_float(o.y)), pack_bf16(ak[2] + __uint_as_float(o.z), ak[3] + __uint_as_float(o.w)));
      bar_arrive(1, 256);
      unsigned x = pack_bf16(av[0] + __uint_as_float(o2.x), av[1] + __uint_as_float(o2.y)), y = pack_bf16(av[2] + __uint_as_float(o2.z), av[3] + __uint_as_float(o2.w));
      st_async_b64(aVr, x, y, mbVr);
      st_async_b64(aVl, x, y, mbVl);
      if (s == NSEG - 1) {
        mbar_wait(bar + 8 * MB_V, par);
        if (t == 128) mbar_arrive(bar + 8 * MB_KVR);
        break;
      }
      mbar_wait(bar + 8 * (MB_FULL + slot), rpar);
      unsigned vx[4][4];
      ldsm_x4_t(vx[0], ring + oVx); ldsm_x4_t(vx[1], ring + oVx + 2048); ldsm_x4_t(vx[2], ring + (oVx ^ 32)); ldsm_x4_t(vx[3], ring + (oVx ^ 32) + 2048);
      RSTAMP(4); RSTAMP(5); RSTAMP(6); RSTAMP(7);
      mbar_wait(bar + 8 * MB_S, par);
      RSTAMP(8);
      float sc[10];
#pragma unroll
      for (int i = 0; i < 5; i++) {
        uint2 o = lds64(aL8 + R_SOWN + i * 256), p = lds64(aL8 + R_SPEER + i * 256);
        sc[2 * i] = __uint_as_float(o.x) + __uint_as_float(p.x); sc[2 * i + 1] = __uint_as_float(o.y) + __uint_as_float(p.y);
      }
      mbar_wait(bar + 8 * MB_V, par);
      uint2 vm0 = lds64(aVm), vm1 = lds64(aVm + 256);
      float mx = fmaxf(fmaxf(fmaxf(sc[0], sc[1]), fmaxf(sc[2], sc[3])), fmaxf(fmaxf(fmaxf(sc[4], sc[5]), fmaxf(sc[6], sc[7])), fmaxf(sc[8], sc[9])));
      mx = fmaxf(mx, __shfl_xor_sync(~0u, mx, 1)); mx = fmaxf(mx, __shfl_xor_sync(~0u, mx, 2));
      const float nm = -mx * (SCALE_QK * LOG2E);
      unsigned p[5];
#pragma unroll
      for (int i = 0; i < 5; i++) p[i] = pack_bf16(ex2f(fmaf(sc[2 * i], SCALE_QK * LOG2E, nm)), ex2f(fmaf(sc[2 * i + 1], SCALE_QK * LOG2E, nm)));
      RSTAMP(9);
      float o0[4] = {0, 0, 0, 0}, o1[4] = {0, 0, 0, 0}, o3[4] = {0, 0, 0, 0}, o4[4] = {0, 0, 0, 0}, z0[4] = {0, 0, 0, 0}, z1[4] = {0, 0, 0, 0};
      const unsigned ones[4] = {0x3F803F80u, 0u, 0x3F803F80u, 0u};
      mma16816(z0, ones, p[0], p[1]); mma16816(z1, ones, p[2], p[3]);
      mma16816(o0, vx[0], p[0], p[1]); mma16816(o3, vx[2], p[0], p[1]);
      mma1688(z0, 0x3F803F80u, 0u, p[4]);
      mma16816(o1, vx[1], p[2], p[3]); mma16816(o4, vx[3], p[2], p[3]);
      mma1688(o0, vm0.x, vm0.y, p[4]); mma1688(o3, vm1.x, vm1.y, p[4]);
      float i0, i1;
      asm("rcp.approx.ftz.f32 %0, %1;" : "=f"(i0) : "f"(z0[0] + z1[0])); asm("rcp.approx.ftz.f32 %0, %1;" : "=f"(i1) : "f"(z0[1] + z1[1]));
      asm volatile("stmatrix.sync.aligned.m8n8.x4.trans.shared.b16 [%0], {%1,%2,%3,%4};" ::"r"(aOst), "r"(pack_bf16((o0[0] + o1[0]) * i0, (o0[1] + o1[1]) * i1)), "r"(pack_bf16((o0[2] + o1[2]) * i0, (o0[3] + o1[3]) * i1)),
                   "r"(pack_bf16((o3[0] + o4[0]) * i0, (o3[1] + o4[1]) * i1)), "r"(pack_bf16((o3[2] + o4[2]) * i0, (o3[3] + o4[3]) * i1)) : "memory");
      RSTAMP(10);
      bar_sync(1, 256);
      WO_PREFETCH();
    } else {
      STSF4(aX + 2048, ak); STSF4(aX + 4096, av);
      unsigned kb[8];
      mbar_wait(bar + 8 * (MB_FULL + slot), rpar);
      ldsm_x4(kb, ring + oKx); ldsm_x4(kb + 4, ring + (oKx ^ 64));
      bar_sync(4 + et, 64);
      uint4 o = lds128(aX);
      stsm_x2_t(aQKst, pack_bf16(aq[0] + __uint_as_float(o.x), aq[1] + __uint_as_float(o.y)), pack_bf16(aq[2] + __uint_as_float(o.z), aq[3] + __uint_as_float(o.w)));
      RSTAMP(4);
      bar_sync(1, 256);
      RSTAMP(5);
      if (s == NSEG - 1) break;
      unsigned qa[8], km[8];
      ldsm_x4(qa, aQ); ldsm_x4(qa + 4, aQ + 64);
      if (w == 3) { ldsm_x4(km, aQ + 1152); ldsm_x4(km + 4, aQ + 1152 + 64); }
      float s0[4] = {0, 0, 0, 0}, s1[4] = {0, 0, 0, 0};
      unsigned af[4][4];
#pragma unroll
      for (int i = 0; i < 4; i++) { af[i][0] = qa[2 * i]; af[i][1] = 0; af[i][2] = qa[2 * i + 1]; af[i][3] = 0; }
      mma16816(s0, af[0], kb[0], kb[1]); mma16816(s1, af[1], kb[2], kb[3]);
      mma16816(s0, af[2], kb[4], kb[5]); mma16816(s1, af[3], kb[6], kb[7]);
      if (w == 3) {
        float m0[4] = {0, 0, 0, 0}, m1[4] = {0, 0, 0, 0};
        mma16816(m0, af[0], km[0], km[1]); mma16816(m1, af[1], km[2], km[3]);
        mma16816(m0, af[2], km[4], km[5]); mma16816(m1, af[3], km[6], km[7]);
        unsigned x = __float_as_uint(m0[0] + m1[0]), y = __float_as_uint(m0[1] + m1[1]);
        st_async_b64(aSr + 256, x, y, mbSr); st_async_b64(aSl + 256, x, y, mbSl);
      }
      unsigned x = __float_as_uint(s0[0] + s1[0]), y = __float_as_uint(s0[1] + s1[1]);
      st_async_b64(aSr, x, y, mbSr); st_async_b64(aSl, x, y, mbSl);
      RSTAMP(6);
      WO_PREFETCH();
      RSTAMP(7); RSTAMP(8); RSTAMP(9); RSTAMP(10);
      bar_sync(1, 256);
    }
    RSTAMP(11);
    float d0[4] = {0, 0, 0, 0}, d1[4] = {0, 0, 0, 0}, e0[4] = {0, 0, 0, 0}, e1[4] = {0, 0, 0, 0};
    unsigned ob[4][4];
#pragma unroll
    for (int k2 = 0; k2 < 4; k2++) ldsm_x4(ob[k2], aOld + k2 * 64);
#pragma unroll
    for (int i = NPRE; i < 4; i++) { ldsm_x4_t(f[2 * i], pW0 + 32768 + i * 2048); ldsm_x4_t(f[2 * i + 1], pW1 + 32768 + i * 2048); }
    mma16816(d0, wo[0], ob[0][0], ob[0][1]); mma16816(d1, wo[1], ob[0][0], ob[0][1]);
    mma16816(e0, wo[2], ob[0][2], ob[0][3]); mma16816(e1, wo[3], ob[0][2], ob[0][3]);
    mma16816(d0, wo[4], ob[1][0], ob[1][1]); mma16816(d1, wo[5], ob[1][0], ob[1][1]);
    mma16816(e0, wo[6], ob[1][2], ob[1][3]); mma16816(e1, wo[7], ob[1][2], ob[1][3]);
    mma16816(d0, f[0], ob[2][0], ob[2][1]); mma16816(d1, f[1], ob[2][0], ob[2][1]);
    mma16816(e0, f[2], ob[2][2], ob[2][3]); mma16816(e1, f[3], ob[2][2], ob[2][3]);
    mma16816(d0, f[4], ob[3][0], ob[3][1]); mma16816(d1, f[5], ob[3][0], ob[3][1]);
    mma16816(e0, f[6], ob[3][2], ob[3][3]); mma16816(e1, f[7], ob[3][2], ob[3][3]);
    st_async_b64(aRSr, __float_as_uint(d0[0] + e0[0]), __float_as_uint(d0[1] + e0[1]), mbRSr);
    st_async_b64(aRSr + 256, __float_as_uint(d0[2] + e0[2]), __float_as_uint(d0[3] + e0[3]), mbRSr);
    st_async_b64(aRSr + 512, __float_as_uint(d1[0] + e1[0]), __float_as_uint(d1[1] + e1[1]), mbRSr);
    st_async_b64(aRSr + 768, __float_as_uint(d1[2] + e1[2]), __float_as_uint(d1[3] + e1[3]), mbRSr);
    RSTAMP(12);
    if (t == 128) {
      mbar_arrive(bar + 8 * (MB_EMPTY + slot)); mbar_arrive(bar + 8 * MB_KVR);
      mbar_expect_tx(bar + 8 * MB_S, 2560); mbar_expect_tx(bar + 8 * MB_V, 2048);
    }
    const unsigned tag = ((s >> 1) & 1) ^ 1;
    const char* gp = reinterpret_cast<const char*>(g_part);
    const unsigned goff = (par * 8 + rk) * 16384 + cl * 2048 + t8;
    unsigned mbA[8];
#pragma unroll
    for (int i = 0; i < 8; i++) mbA[i] = mapa(bar + 8 * MB_AG, i);
    const unsigned dlt = (R_MEM + rk * 1024) - (SM_BAR + 8 * MB_AG) + (t8 >> 1);
    mbar_wait(bar + 8 * MB_RS, par);
    RSTAMP(13);
    uint2 a[8];
    {
      uint2 x0 = lds64(sb + R_RS + t8), x1 = lds64(sb + R_RS + 2048 + t8), x2 = lds64(sb + R_RS + 4096 + t8), x3 = lds64(sb + R_RS + 6144 + t8);
      float r0 = (__uint_as_float(x0.x) + __uint_as_float(x1.x)) + (__uint_as_float(x2.x) + __uint_as_float(x3.x));
      float r1 = (__uint_as_float(x0.y) + __uint_as_float(x1.y)) + (__uint_as_float(x2.y) + __uint_as_float(x3.y));
      a[0].x = (__float_as_uint(r0) & ~1u) | tag; a[0].y = (__float_as_uint(r1) & ~1u) | tag;
      asm volatile("st.relaxed.gpu.global.v2.u32 [%0], {%1,%2};" ::"l"(gp + goff), "r"(a[0].x), "r"(a[0].y) : "memory");
    }
    RSTAMP(14);
    if (t == 128) mbar_expect_tx(bar + 8 * MB_RS, 8192);
    {
      unsigned it = 0;
#define PLOAD(a) _Pragma("unroll") for (int i = 1; i < 8; i++) a[i] = ldv2_relaxed(gp + (goff ^ (i * 2048)))
#define PAND(a) (((a[1].x & a[1].y) & (a[2].x & a[2].y) & (a[3].x & a[3].y)) & ((a[4].x & a[4].y) & (a[5].x & a[5].y)) & ((a[6].x & a[6].y) & (a[7].x & a[7].y)))
#define POR(a) (((a[1].x | a[1].y) | (a[2].x | a[2].y) | (a[3].x | a[3].y)) | ((a[4].x | a[4].y) | (a[5].x | a[5].y)) | ((a[6].x | a[6].y) | (a[7].x | a[7].y)))
#define POK(a) (((tag ? PAND(a) : ~POR(a)) & 1u) != 0)
      if (D_RED) DELAY(D_RED);
      PLOAD(a);
      while (!POK(a)) {
#pragma unroll
        for (int i = 1; i < 8; i++) if (((a[i].x ^ tag) | (a[i].y ^ tag)) & 1u) a[i] = ldv2_relaxed(gp + (goff ^ (i * 2048)));
        spin_check(it);
      }
    }
    RSTAMP(15);
    {
#define AF(i, c) __uint_as_float(a[i].c)
      unsigned u = pack_bf16(((AF(0, x) + AF(1, x)) + (AF(2, x) + AF(3, x))) + ((AF(4, x) + AF(5, x)) + (AF(6, x) + AF(7, x))),
                             ((AF(0, y) + AF(1, y)) + (AF(2, y) + AF(3, y))) + ((AF(4, y) + AF(5, y)) + (AF(6, y) + AF(7, y))));
      __syncwarp();
#pragma unroll
      for (int i = 0; i < 8; i++) st_async_b32(mbA[i] + dlt, u, mbA[i]);
    }
    mbar_wait(bar + 8 * MB_KVF, par);
    mbar_wait(bar + 8 * MB_AG, par);
    if (t == 128) mbar_expect_tx(bar + 8 * MB_AG, 8192);
  }
}

__device__ __forceinline__ void rec_ring(const Maps& maps, unsigned sb, const int c) {
  const int h = c >> 1, j = c & 1;
  const unsigned bar = sb + SM_BAR;
  const int lane = threadIdx.x & 31;
  __syncwarp();
  bar_sync(2, 288);
  if (lane == 0) {
    fence_proxy_async_smem();
    for (int s = 0; s < NSEG; s++) {
      unsigned slot = s & (RING_N - 1);
      if ((s & 3) == 0 && !DBGMODE) {
        wait_flag_ge(&g_flags.qkv[(s >> 2) * 48 + 16 + (h >> 1)], 2);
        wait_flag_ge(&g_flags.qkv[(s >> 2) * 48 + 32 + (h >> 1)], 2);
        fence_proxy_async();
      }
      if (s >= RING_N) mbar_wait_sleep(bar + 8 * (MB_EMPTY + slot), ((s / RING_N) - 1) & 1);
      unsigned dst = sb + R_RING + slot * RING_BYTES, mb = bar + 8 * (MB_FULL + slot);
      mbar_expect_tx(mb, RING_BYTES);
      tma_load_2d(dst, &maps.qkv_ld, HD + h * 128 + j * 64, s * SEG, mb);
      tma_load_2d(dst + 4096, &maps.qkv_ld, 2 * HD + h * 128, s * SEG, mb);
      tma_load_2d(dst + 8192, &maps.qkv_ld, 2 * HD + h * 128 + 64, s * SEG, mb);
    }
  }
}
__device__ __forceinline__ void rec_copy(unsigned sb, const int c) {
  const int h = c >> 1, j = c & 1;
  const unsigned bar = sb + SM_BAR;
  const int lane = threadIdx.x & 31;
  for (int s = 0; s < NSEG; s++) {
    if (s < NSEG - 1) mbar_wait_sleep(bar + 8 * MB_KVR, s & 1); else mbar_wait(bar + 8 * MB_KVR, s & 1);
    uint4 k0 = lds128(sb + R_KS + (lane >> 3) * 144 + (lane & 7) * 16), k1 = lds128(sb + R_KS + (4 + (lane >> 3)) * 144 + (lane & 7) * 16);
    uint2 v[4];
#pragma unroll
    for (int i = 0; i < 4; i++) v[i] = lds64(sb + R_VM + (j * 4 + i) * 256 + lane * 8);
    __syncwarp();
    if (lane == 0) mbar_arrive(bar + 8 * MB_KVF);
    bf16* kd = g_km + ((size_t)(s * NH + h) * NMEM) * DH + j * 64;
    *reinterpret_cast<uint4*>(kd + (lane >> 3) * DH + (lane & 7) * 8) = k0;
    *reinterpret_cast<uint4*>(kd + (4 + (lane >> 3)) * DH + (lane & 7) * 8) = k1;
    unsigned* vd = reinterpret_cast<unsigned*>(g_vmt) + ((size_t)(s * NH + h) * DH + j * 64) * 4;
#pragma unroll
    for (int i = 0; i < 4; i++) { vd[(i * 16) * 4 + lane] = v[i].x; vd[(i * 16 + 8) * 4 + lane] = v[i].y; }
    __syncwarp();
    if (lane == 0) st_release(&g_flags.rec[c], s + 1);
  }
}

__device__ __forceinline__ void bulk_producer(const Maps& maps, unsigned sb, int* misc) {
  const unsigned bar = sb + SM_BAR;
  const int lane = threadIdx.x & 31;
  unsigned st = 0, ph = 0, seq = 0;
  while (true) {
    int idx = 0;
    if (lane == 0) idx = (int)atomicAdd(&g_flags.ctr, 1u);
    idx = __shfl_sync(~0u, idx, 0);
    if (idx >= N_ITEMS) {
      if (lane == 0) {
        mbar_wait(bar + 8 * (MB_EMPTY + st), ph ^ 1);
        misc[seq & 3] = -1;
        mbar_arrive(bar + 8 * (MB_FULL + st));
      }
      break;
    }
    if (lane == 0) ISTAMP(idx, 0);
    Item it = decode_item(idx);
    if (it.b < 0) continue;
    const CUtensorMap* mp; int c0, c1, dc0, dc1; unsigned doff;
    const unsigned* fl = nullptr; unsigned tgt = 1; int nbox = 5, rdy = 0;
    if (it.type == T_ATT) {
      mp = &maps.qkv_ld; nbox = 12; doff = lane * 4096;
      c0 = (lane >> 2) * HD + it.c * 256 + (lane & 1) * 64; c1 = it.b * 128 + ((lane >> 1) & 1) * 32; dc0 = dc1 = 0;
      if (lane < 3) fl = &g_flags.qkv[it.b * 48 + lane * 16 + it.c];
      tgt = 2;
      bool ok = true;
      if (lane >= 4 && lane < 8) ok = ld_acquire(&g_flags.rec[it.c * 4 + lane - 4]) >= (unsigned)(it.b * 4 + 4);
      rdy = __all_sync(~0u, ok) ? 65536 : 0;
    } else {
      int k0 = 0, nb0 = it.c * 256;
      if (it.type == T_QKV) { mp = lane == 0 ? &maps.xn : (it.c < 16 ? &maps.wq : (it.c < 32 ? &maps.wk : &maps.wv)); nb0 = (it.c & 15) * 256; }
      else if (it.type == T_M1) mp = lane == 0 ? &maps.y : &maps.w1;
      else if (it.type == T_M2) { mp = lane == 0 ? &maps.h1 : &maps.w2; fl = &g_flags.h1[it.b]; tgt = 7; }
      else {
        mp = lane == 0 ? &maps.o : &maps.wo;
        if (it.type == T_OUT) { k0 = it.ks * 1024; fl = &g_flags.o[it.b * 4 + it.ks]; tgt = 4; }
        else if (it.type == T_OUTL) { k0 = it.ks * 256; fl = &g_flags.o16[it.ks]; }
        else if (lane == 1) { fl = &g_flags.g[it.b]; tgt = 2; }
        else { fl = &g_flags.p[it.b]; tgt = it.type == T_RED ? (it.b >= 13 ? 16 : 8) : 64; }
      }
      if (lane > (it.type >= T_RED ? 1 : 0)) fl = nullptr;
      if (it.hf) { nbox = 3; nb0 += (it.hf - 1) * 128; }
      if (lane == 0) { c0 = k0; c1 = it.b * 128; dc0 = 64; dc1 = 0; doff = 0; }
      else { c0 = nb0 + (lane - 1) * 64; c1 = k0; dc0 = 0; dc1 = 64; doff = 8192 + lane * 8192; }
    }
    if (fl) wait_flag_ge(fl, tgt);
    __syncwarp();
    fence_proxy_async();
    if (lane == 0) ISTAMP(idx, 1);
    const int nkb = item_nkb(it.type);
    for (int kb = 0; kb < nkb; kb++) {
      const unsigned mb = bar + 8 * (MB_FULL + st);
      mbar_wait(bar + 8 * (MB_EMPTY + st), ph ^ 1);
      if (lane == 0) {
        if (kb == 0) misc[seq & 3] = idx | rdy;
        if (it.type >= T_RED) mbar_arrive(mb); else mbar_expect_tx(mb, it.hf ? 32768 : STAGE_BYTES);
      }
      if (it.type == T_ATT) { if (lane < 12) tma_load_2d(sb + st * STAGE_BYTES + doff, mp, c0 + (kb & 1) * 128, c1 + (kb >> 1) * 64, mb); }
      else if (lane < nbox && it.type < T_RED) tma_load_2d(sb + st * STAGE_BYTES + doff, mp, c0 + kb * dc0, c1 + kb * dc1, mb);
      __syncwarp();
      if (++st == NSTAGE) { st = 0; ph ^= 1; }
    }
    seq++;
  }
}
__device__ __forceinline__ void bulk_store(const Maps& maps, unsigned sb, volatile int* misc) {
  const unsigned bar = sb + SM_BAR;
  unsigned ph = 0;
  while (true) {
    mbar_wait(bar + 8 * MB_STGF, ph); ph ^= 1;
    int idx = misc[4];
    if (idx < 0) break;
    Item it = decode_item(idx);
    const CUtensorMap* mp = it.type == T_QKV ? &maps.qkv_st : (it.type == T_M1 ? &maps.h1 : (it.type == T_M2 ? &maps.g : &maps.o));
    unsigned* flag = it.type == T_QKV ? &g_flags.qkv[it.b * 48 + it.c] : (it.type == T_M1 ? &g_flags.h1[it.b] : (it.type == T_M2 ? &g_flags.g[it.b] : (it.b == 15 ? &g_flags.o16[it.c] : &g_flags.o[it.b * 4 + (it.c >> 2)])));
    for (int i = 0; i < (it.hf ? 2 : 4); i++) tma_store_2d(mp, sb + B_STG + i * 16384, it.c * 256 + (it.hf >> 1) * 128 + i * 64, it.b * 128);
    asm volatile("cp.async.bulk.commit_group;" ::: "memory");
    asm volatile("cp.async.bulk.wait_group.read 0;" ::: "memory");
    mbar_arrive(bar + 8 * MB_STGE);
    asm volatile("cp.async.bulk.wait_group 0;" ::: "memory");
    fence_proxy_async();
    red_release_add(flag, it.type == T_QKV && !it.hf ? 2 : 1);
    ISTAMP(idx, 3);
  }
}
__device__ __forceinline__ float rcpf(float x) { float y; asm("rcp.approx.ftz.f32 %0, %1;" : "=f"(y) : "f"(x)); return y; }
__device__ __forceinline__ float gelu_t(float x) {
  float e = ex2f(x * fmaf(x * x, -2.0f * LOG2E * 0.7978845608028654f * 0.044715f, -2.0f * LOG2E * 0.7978845608028654f));
  return x * rcpf(1.0f + e);
}
__device__ __forceinline__ float silu_f(float x) { return x * rcpf(1.0f + ex2f(-LOG2E * x)); }
__device__ __forceinline__ unsigned badd2(unsigned a, unsigned b) { unsigned r; asm("add.rn.bf16x2 %0, %1, %2;" : "=r"(r) : "r"(a), "r"(b)); return r; }

__device__ __forceinline__ void final_out(bf16* __restrict__ out, const bf16* __restrict__ x, size_t o, float4 s) {
  uint2 gv = __ldcg(reinterpret_cast<const uint2*>(g_g + o)), xv = __ldg(reinterpret_cast<const uint2*>(x + o));
  uint2 r;
  r.x = pack_bf16(bf_lo(xv.x) + bf16r(bf16r(s.x) * bf_lo(gv.x)), bf_hi(xv.x) + bf16r(bf16r(s.y) * bf_hi(gv.x)));
  r.y = pack_bf16(bf_lo(xv.y) + bf16r(bf16r(s.z) * bf_lo(gv.y)), bf_hi(xv.y) + bf16r(bf16r(s.w) * bf_hi(gv.y)));
  *reinterpret_cast<uint2*>(out + o) = r;
}
__device__ __forceinline__ void bulk_att_load(unsigned* km, unsigned* vm, int b, int hp, int kb, int w, int lane) {
  const int g = lane >> 2, tq = lane & 3, seg = w >> 2, eh = w & 1;
  const int head = hp * 2 + (kb & 1), sg = b * 4 + (kb >> 1) * 2 + seg;
  const unsigned* kmp = reinterpret_cast<const unsigned*>(g_km + ((size_t)(sg * NH + head) * NMEM + g) * DH) + tq;
  const unsigned* vmp = reinterpret_cast<const unsigned*>(g_vmt) + ((size_t)(sg * NH + head) * DH + eh * 64) * 4 + lane;
#pragma unroll
  for (int i = 0; i < 16; i++) asm volatile("ld.global.cg.u32 %0, [%1];" : "=r"(km[i]) : "l"(kmp + i * 4) : "memory");
#pragma unroll
  for (int i = 0; i < 8; i++) asm volatile("ld.global.cg.u32 %0, [%1];" : "=r"(vm[i]) : "l"(vmp + i * 32) : "memory");
}
__device__ __forceinline__ void bulk_att_stage(unsigned sa, unsigned stg, const unsigned* km, const unsigned* vm, int kb, int w, int lane) {
  const int g = lane >> 2, tq = lane & 3, m = lane >> 3, r8 = lane & 7;
  const int seg = w >> 2, mt = (w >> 1) & 1, eh = w & 1;
  float s[5][4];
#pragma unroll
  for (int i = 0; i < 5; i++) { s[i][0] = s[i][1] = s[i][2] = s[i][3] = 0; }
  const unsigned qb = sa + (0 * 2 + seg) * 8192, kbs = sa + (1 * 2 + seg) * 8192, vb = sa + (2 * 2 + seg) * 8192 + eh * 4096;
  unsigned qa[8][4];
#pragma unroll
  for (int ks = 0; ks < 8; ks++) {
    int row = mt * 16 + (m & 1) * 8 + r8;
    ldsm_x4(qa[ks], qb + (ks >> 2) * 4096 + row * 128 + ((((ks & 3) * 2 + (m >> 1)) ^ r8) << 4));
    unsigned kf[4];
    int krow = (m >> 1) * 8 + r8;
    unsigned ka = kbs + (ks >> 2) * 4096 + krow * 128 + ((((ks & 3) * 2 + (m & 1)) ^ r8) << 4);
    ldsm_x4(kf, ka);
    mma16816(s[0], qa[ks], kf[0], kf[1]); mma16816(s[1], qa[ks], kf[2], kf[3]);
    if (mt) { ldsm_x4(kf, ka + 2048); mma16816(s[2], qa[ks], kf[0], kf[1]); mma16816(s[3], qa[ks], kf[2], kf[3]); }
  }
#pragma unroll
  for (int ks = 0; ks < 8; ks++) mma16816(s[4], qa[ks], km[2 * ks], km[2 * ks + 1]);
  float mx0 = -INFINITY, mx1 = -INFINITY;
  const int t0 = mt * 16 + g, t1 = t0 + 8;
#pragma unroll
  for (int i = 0; i < 5; i++) {
#pragma unroll
    for (int e = 0; e < 4; e++) {
      float v = s[i][e];
      if (i < 4) { int kj = i * 8 + 2 * tq + (e & 1); if (kj > (e < 2 ? t0 : t1)) v = -INFINITY; }
      s[i][e] = v;
      if (e < 2) mx0 = fmaxf(mx0, v); else mx1 = fmaxf(mx1, v);
    }
  }
  mx0 = fmaxf(mx0, __shfl_xor_sync(~0u, mx0, 1)); mx0 = fmaxf(mx0, __shfl_xor_sync(~0u, mx0, 2));
  mx1 = fmaxf(mx1, __shfl_xor_sync(~0u, mx1, 1)); mx1 = fmaxf(mx1, __shfl_xor_sync(~0u, mx1, 2));
  float sm0 = 0, sm1 = 0;
#pragma unroll
  for (int i = 0; i < 5; i++) {
    s[i][0] = ex2f((s[i][0] - mx0) * (SCALE_QK * LOG2E)); s[i][1] = ex2f((s[i][1] - mx0) * (SCALE_QK * LOG2E));
    s[i][2] = ex2f((s[i][2] - mx1) * (SCALE_QK * LOG2E)); s[i][3] = ex2f((s[i][3] - mx1) * (SCALE_QK * LOG2E));
    sm0 += s[i][0] + s[i][1]; sm1 += s[i][2] + s[i][3];
  }
  sm0 += __shfl_xor_sync(~0u, sm0, 1); sm0 += __shfl_xor_sync(~0u, sm0, 2);
  sm1 += __shfl_xor_sync(~0u, sm1, 1); sm1 += __shfl_xor_sync(~0u, sm1, 2);
  const float i0 = __fdividef(1.0f, sm0), i1 = __fdividef(1.0f, sm1);
  unsigned pa[2][4], pm0, pm1;
#pragma unroll
  for (int kk = 0; kk < 2; kk++) {
    pa[kk][0] = pack_bf16(s[2 * kk][0] * i0, s[2 * kk][1] * i0); pa[kk][1] = pack_bf16(s[2 * kk][2] * i1, s[2 * kk][3] * i1);
    pa[kk][2] = pack_bf16(s[2 * kk + 1][0] * i0, s[2 * kk + 1][1] * i0); pa[kk][3] = pack_bf16(s[2 * kk + 1][2] * i1, s[2 * kk + 1][3] * i1);
  }
  pm0 = pack_bf16(s[4][0] * i0, s[4][1] * i0); pm1 = pack_bf16(s[4][2] * i1, s[4][3] * i1);
  const int orow = (kb >> 1) * 64 + seg * 32 + mt * 16 + (m & 1) * 8 + r8;
  const unsigned ob = stg + ((kb & 1) * 2 + eh) * 16384 + orow * 128;
#pragma unroll
  for (int cp = 0; cp < 4; cp++) {
    float o0[4] = {0, 0, 0, 0}, o1[4] = {0, 0, 0, 0};
    mma1688(o0, pm0, pm1, vm[2 * cp]); mma1688(o1, pm0, pm1, vm[2 * cp + 1]);
    unsigned vf[4];
    int row = (m & 1) * 8 + r8;
    unsigned va = vb + row * 128 + (((cp * 2 + (m >> 1)) ^ r8) << 4);
    ldsm_x4_t(vf, va);
    mma16816(o0, pa[0], vf[0], vf[1]); mma16816(o1, pa[0], vf[2], vf[3]);
    if (mt) { ldsm_x4_t(vf, va + 2048); mma16816(o0, pa[1], vf[0], vf[1]); mma16816(o1, pa[1], vf[2], vf[3]); }
    stsm_x4(ob + (((cp * 2 + (m >> 1)) ^ r8) << 4), pack_bf16(o0[0], o0[1]), pack_bf16(o0[2], o0[3]), pack_bf16(o1[0], o1[1]), pack_bf16(o1[2], o1[3]));
  }
}

__device__ __forceinline__ void bulk_worker(unsigned sb, volatile int* misc, const bf16* __restrict__ x, const bf16* __restrict__ b1, const bf16* __restrict__ b2, bf16* __restrict__ out) {
  const int t = threadIdx.x, lane = t & 31, w = t >> 5, wg = w >> 2, g = lane >> 2, tq = lane & 3, m = lane >> 3, r8 = lane & 7;
  const unsigned bar = sb + SM_BAR;
  unsigned st = 0, ph = 0, seq = 0, sph = 0;
  float d[128];
  while (true) {
    mbar_wait(bar + 8 * (MB_FULL + st), ph);
    const int idr = misc[seq & 3]; seq++;
    const int idx = idr & 65535;
    if (idr < 0 || idx >= N_ITEMS) break;
    if (t == 0) ISTAMP(idx, 2);
    const Item it = decode_item(idx);
    const int nkb = item_nkb(it.type);
    if (it.type == T_ATT) {
      unsigned km[16], vm[8], kn[16], vn[8];
      const bool pref = idr >= 65536;
      if (pref) bulk_att_load(kn, vn, it.b, it.c, 0, w, lane);
      mbar_wait(bar + 8 * MB_STGE, sph ^ 1);
#pragma unroll 1
      for (int kb = 0; kb < 4; kb++) {
        if (!pref && !(kb & 1)) {
          if (lane < 4) wait_flag_ge(&g_flags.rec[it.c * 4 + lane], it.b * 4 + (kb >> 1) * 2 + wg + 1);
          __syncwarp();
          bulk_att_load(kn, vn, it.b, it.c, kb, w, lane);
        }
        if (kb) mbar_wait(bar + 8 * (MB_FULL + st), ph);
#pragma unroll
        for (int i = 0; i < 16; i++) km[i] = kn[i];
#pragma unroll
        for (int i = 0; i < 8; i++) vm[i] = vn[i];
        if (pref ? kb != 3 : !(kb & 1)) bulk_att_load(kn, vn, it.b, it.c, kb + 1, w, lane);
        bulk_att_stage(sb + st * STAGE_BYTES, sb + B_STG, km, vm, kb, w, lane);
        __syncwarp();
        if (lane == 0) mbar_arrive(bar + 8 * (MB_EMPTY + st));
        if (++st == NSTAGE) { st = 0; ph ^= 1; }
      }
      if (t == 0) misc[4] = idx;
      fence_proxy_async_smem();
      mbar_arrive(bar + 8 * MB_STGF); sph ^= 1;
      continue;
    }
    if (it.type >= T_RED) {
      __syncwarp();
      if (lane == 0) mbar_arrive(bar + 8 * (MB_EMPTY + st));
      if (++st == NSTAGE) { st = 0; ph ^= 1; }
      if (it.type == T_RED) {
#pragma unroll 2
        for (int i = 0; i < (it.ks ? 2 : 8); i++) {
          size_t o = ((size_t)it.b * 128 + it.c * (it.ks ? 4 : 16) + i * 2 + (t >> 7)) * DM + (t & 127) * 4;
          float4 a = __ldcg(reinterpret_cast<const float4*>(g_opart + o)), b = __ldcg(reinterpret_cast<const float4*>(g_opart + o + (size_t)S_TOK * DM));
          float4 c = __ldcg(reinterpret_cast<const float4*>(g_opart + o + (size_t)2 * S_TOK * DM)), e = __ldcg(reinterpret_cast<const float4*>(g_opart + o + (size_t)3 * S_TOK * DM));
          final_out(out, x, o, make_float4((a.x + b.x) + (c.x + e.x), (a.y + b.y) + (c.y + e.y), (a.z + b.z) + (c.z + e.z), (a.w + b.w) + (c.w + e.w)));
        }
      } else {
        size_t ol = ((size_t)it.c * 2 + (t >> 7)) * DM + (t & 127) * 4;
        float4 v[16];
#pragma unroll
        for (int i = 0; i < 16; i++) v[i] = __ldcg(reinterpret_cast<const float4*>(g_opl + ol + (size_t)i * 128 * DM));
#pragma unroll
        for (int st2 = 1; st2 < 16; st2 <<= 1)
#pragma unroll
          for (int i = 0; i < 16; i += 2 * st2) { v[i].x += v[i + st2].x; v[i].y += v[i + st2].y; v[i].z += v[i + st2].z; v[i].w += v[i + st2].w; }
        final_out(out, x, ol + (size_t)15 * 128 * DM, v[0]);
      }
      if (t == 0) ISTAMP(idx, 3);
      continue;
    }
    unsigned pst = 0, bv[32];
#pragma unroll
    for (int i = 0; i < 128; i++) d[i] = 0.0f;
    if (it.type == T_M1 || it.type == T_M2) {
      const unsigned* bp = reinterpret_cast<const unsigned*>((it.type == T_M1 ? b1 : b2) + it.c * 256) + tq;
#pragma unroll
      for (int i = 0; i < 32; i++) asm volatile("ld.global.nc.u32 %0, [%1];" : "=r"(bv[i]) : "l"(bp + i * 4));
    } else {
#pragma unroll
      for (int i = 0; i < 32; i++) bv[i] = 0;
    }
#define KLOOP(WG) \
    for (int kb = 0; kb < nkb; kb++) { \
      if (kb) mbar_wait(bar + 8 * (MB_FULL + st), ph); \
      unsigned sa = sb + st * STAGE_BYTES; \
      uint64_t ad = mkdesc(sa + wg * 8192, 16, 1024), bd = mkdesc(sa + 16384, 8192, 1024); \
      asm volatile("wgmma.fence.sync.aligned;" ::: "memory"); \
      _Pragma("unroll") for (int k = 0; k < 4; k++) WG(d, ad + k * 2, bd + k * 128, (kb | k) != 0); \
      asm volatile("wgmma.commit_group.sync.aligned;" ::: "memory"); \
      if (kb) { \
        asm volatile("wgmma.wait_group.sync.aligned 1;" ::: "memory"); \
        if (lane == 0) mbar_arrive(bar + 8 * (MB_EMPTY + pst)); \
      } \
      pst = st; \
      if (++st == NSTAGE) { st = 0; ph ^= 1; } \
    } \
    asm volatile("wgmma.wait_group.sync.aligned 0;" ::: "memory");
    if (it.hf) { KLOOP(wgmma_n128) } else { KLOOP(wgmma_n256) }
    if (lane == 0) mbar_arrive(bar + 8 * (MB_EMPTY + pst));
    if (it.type >= T_OUT) {
      const int col = it.c * 256 + (it.hf >> 1) * 128 + 2 * tq;
      float* pp = it.type == T_OUT ? g_opart + ((size_t)it.ks * S_TOK + it.b * 128 + w * 16 + g) * DM + col : g_opl + ((size_t)it.ks * 128 + w * 16 + g) * DM + col;
#pragma unroll
      for (int i = 0; i < 32; i++) {
        if (i == 16 && it.hf) break;
        __stcg(reinterpret_cast<float2*>(pp + i * 8), make_float2(d[4 * i], d[4 * i + 1]));
        __stcg(reinterpret_cast<float2*>(pp + 8 * DM + i * 8), make_float2(d[4 * i + 2], d[4 * i + 3]));
      }
      bar_sync(1, 256);
      if (t == 0) { red_release_add(&g_flags.p[it.b], 1); ISTAMP(idx, 3); }
      continue;
    }
#define ACT(F) _Pragma("unroll") for (int i = 0; i < 32; i++) { \
        unsigned u0 = badd2(pack_bf16(d[4 * i], d[4 * i + 1]), bv[i]), u1 = badd2(pack_bf16(d[4 * i + 2], d[4 * i + 3]), bv[i]); \
        d[4 * i] = F(bf_lo(u0)); d[4 * i + 1] = F(bf_hi(u0)); d[4 * i + 2] = F(bf_lo(u1)); d[4 * i + 3] = F(bf_hi(u1)); }
    if (it.type == T_M1) { ACT(gelu_t) } else if (it.type == T_M2) { ACT(silu_f) }
    mbar_wait(bar + 8 * MB_STGE, sph ^ 1);
    {
      const unsigned ob = sb + B_STG + (w * 16 + (m & 1) * 8 + r8) * 128;
#pragma unroll
      for (int i = 0; i < 16; i++)
        if (i < 8 || !it.hf) stsm_x4(ob + (i >> 2) * 16384 + ((((i & 3) * 2 + (m >> 1)) ^ r8) << 4), pack_bf16(d[8 * i], d[8 * i + 1]), pack_bf16(d[8 * i + 2], d[8 * i + 3]),
                pack_bf16(d[8 * i + 4], d[8 * i + 5]), pack_bf16(d[8 * i + 6], d[8 * i + 7]));
    }
    if (t == 0) misc[4] = idx;
    fence_proxy_async_smem();
    mbar_arrive(bar + 8 * MB_STGF); sph ^= 1;
  }
  mbar_wait(bar + 8 * MB_STGE, sph ^ 1);
  if (t == 0) misc[4] = -1;
  mbar_arrive(bar + 8 * MB_STGF);
}

__global__ void __launch_bounds__(384, 1)
k_main(const __grid_constant__ Maps maps, const bf16* __restrict__ x, const bf16* __restrict__ mem0, const bf16* __restrict__ b1, const bf16* __restrict__ b2, bf16* __restrict__ out, unsigned recmask) {
  extern __shared__ unsigned char smem_raw[];
  const unsigned sraw = smem_u32(smem_raw);
  const unsigned sb = (sraw + 1023u) & ~1023u;
  int* misc = reinterpret_cast<int*>(smem_raw + (sb - sraw) + SM_MISC);
  const int w = threadIdx.x >> 5;
  const bool helper = recmask == 0;
  const unsigned kc = blockIdx.x / CLS;
  const bool rec = kc < 32 && ((recmask >> kc) & 1);
  const int c = __popc(recmask & ((1u << (kc & 31)) - 1)) * CLS + (blockIdx.x & (CLS - 1));
  if (threadIdx.x == 0) {
    const unsigned bar = sb + SM_BAR;
    for (int i = 0; i < 8; i++) { mbar_init(bar + 8 * (MB_FULL + i), 1); mbar_init(bar + 8 * (MB_EMPTY + i), rec ? 1 : 8); }
    mbar_init(bar + 8 * MB_STGF, 256); mbar_init(bar + 8 * MB_STGE, 1);
    for (int i = MB_W0; i <= MB_AG; i++) mbar_init(bar + 8 * i, 1);
    if (rec) { mbar_expect_tx(bar + 8 * MB_S, 2560); mbar_expect_tx(bar + 8 * MB_V, 2048); mbar_expect_tx(bar + 8 * MB_RS, 8192); mbar_expect_tx(bar + 8 * MB_AG, 8192); }
    asm volatile("fence.mbarrier_init.release.cluster;" ::: "memory");
  }
  __syncthreads();
  asm volatile("barrier.cluster.arrive.release.aligned;\nbarrier.cluster.wait.acquire.aligned;" ::: "memory");
  if (rec && threadIdx.x == 256) {
    const unsigned bar = sb + SM_BAR; const int col = c * 64;
    mbar_expect_tx(bar + 8 * MB_W0, 131072);
    for (int kb = 0; kb < 8; kb++) tma_load_2d(sb + R_WO + kb * 8192, &maps.wq, col, kb * 64, bar + 8 * MB_W0);
    for (int kb = 0; kb < 8; kb++) tma_load_2d(sb + R_T1 + kb * 8192, &maps.wk, col, kb * 64, bar + 8 * MB_W0);
    mbar_expect_tx(bar + 8 * MB_W1, 65536);
    for (int kb = 0; kb < 8; kb++) tma_load_2d(sb + R_T2 + kb * 8192, &maps.wv, col, kb * 64, bar + 8 * MB_W1);
  }
  if (!helper) {
    asm volatile("griddepcontrol.wait;" ::: "memory");
    asm volatile("griddepcontrol.launch_dependents;");
  }
  if (DBGMODE && !rec) { if (helper) asm volatile("griddepcontrol.wait;" ::: "memory"); return; }
  if (w >= 8) {
    asm volatile("setmaxnreg.dec.sync.aligned.u32 24;");
    if (rec) { if (w == 8) rec_ring(maps, sb, c); else if (w == 9) rec_copy(sb, c); }
    else if (w == 8) bulk_producer(maps, sb, misc);
    else if ((threadIdx.x & 31) == 0) { if (w == 9) bulk_store(maps, sb, misc);
      else if (w == 10 && helper) asm volatile("griddepcontrol.wait;" ::: "memory"); }
  } else {
    if (rec) { asm volatile("setmaxnreg.inc.sync.aligned.u32 240;"); rec_worker(maps, sb, mem0, c); }
    else { asm volatile("setmaxnreg.inc.sync.aligned.u32 240;"); bulk_worker(sb, misc, x, b1, b2, out); }
  }
}

typedef CUresult (*EncFn)(CUtensorMap*, CUtensorMapDataType, cuuint32_t, void*, const cuuint64_t*, const cuuint64_t*, const cuuint32_t*, const cuuint32_t*,
                          CUtensorMapInterleave, CUtensorMapSwizzle, CUtensorMapL2promotion, CUtensorMapFloatOOBfill);
static void mk_map(EncFn enc, CUtensorMap* m, const void* ptr, uint64_t rows, uint64_t cols, uint32_t box_rows) {
  cuuint64_t dims[2] = {cols, rows}; cuuint64_t strides[1] = {cols * 2};
  cuuint32_t box[2] = {64, box_rows}, es[2] = {1, 1};
  enc(m, CU_TENSOR_MAP_DATA_TYPE_BFLOAT16, 2, const_cast<void*>(ptr), dims, strides, box, es, CU_TENSOR_MAP_INTERLEAVE_NONE, CU_TENSOR_MAP_SWIZZLE_128B,
      CU_TENSOR_MAP_L2_PROMOTION_L2_256B, CU_TENSOR_MAP_FLOAT_OOB_FILL_NONE);
}
extern "C" void kernel_launch(void* const* d_in, const int* in_sizes, int n_in, void* d_out, int out_size) {
  static EncFn enc = nullptr;
  static int ncl = 0, nhelp = 0;
  static unsigned recmask = 0xFFu;
  static void *p_xn, *p_y, *p_h1, *p_o, *p_qkv, *p_g;
  if (!enc) {
    void* fn = nullptr; cudaDriverEntryPointQueryResult qr;
    cudaGetDriverEntryPoint("cuTensorMapEncodeTiled", &fn, cudaEnableDefault, &qr);
    enc = (EncFn)fn;
    cudaGetSymbolAddress(&p_xn, g_xn); cudaGetSymbolAddress(&p_y, g_y); cudaGetSymbolAddress(&p_h1, g_h1);
    cudaGetSymbolAddress(&p_o, g_o); cudaGetSymbolAddress(&p_qkv, g_qkv); cudaGetSymbolAddress(&p_g, g_g);
    cudaFuncSetAttribute(k_main, cudaFuncAttributeMaxDynamicSharedMemorySize, SMEM_TOTAL);
    cudaLaunchConfig_t cfg = {}; cfg.gridDim = dim3(128); cfg.blockDim = dim3(384); cfg.dynamicSmemBytes = SMEM_TOTAL;
    cudaLaunchAttribute at[1]; at[0].id = cudaLaunchAttributeClusterDimension; at[0].val.clusterDim.x = CLS; at[0].val.clusterDim.y = 1; at[0].val.clusterDim.z = 1;
    cfg.attrs = at; cfg.numAttrs = 1;
    if (cudaOccupancyMaxActiveClusters(&ncl, k_main, &cfg) != cudaSuccess) { cudaGetLastError(); ncl = 14; }
    ncl = ncl > 16 ? 16 : (ncl < 9 ? 9 : ncl);
    int nsm = 0, dev = 0; cudaGetDevice(&dev); cudaDeviceGetAttribute(&nsm, cudaDevAttrMultiProcessorCount, dev);
    nhelp = nsm - ncl * CLS;
  }
  Maps maps;
  mk_map(enc, &maps.xn, p_xn, S_TOK, DM, 128); mk_map(enc, &maps.y, p_y, S_TOK, DM, 128); mk_map(enc, &maps.h1, p_h1, S_TOK, FF, 128);
  mk_map(enc, &maps.o, p_o, S_TOK, HD, 128); mk_map(enc, &maps.qkv_st, p_qkv, S_TOK, 3 * HD, 128); mk_map(enc, &maps.qkv_ld, p_qkv, S_TOK, 3 * HD, 32);
  mk_map(enc, &maps.g, p_g, S_TOK, DM, 128);
  mk_map(enc, &maps.wq, d_in[2], DM, HD, 64); mk_map(enc, &maps.wk, d_in[3], DM, HD, 64); mk_map(enc, &maps.wv, d_in[4], DM, HD, 64);
  mk_map(enc, &maps.wo, d_in[5], HD, DM, 64); mk_map(enc, &maps.w1, d_in[8], DM, FF, 64); mk_map(enc, &maps.w2, d_in[10], FF, DM, 64);
  cudaStream_t st = cudaStreamPerThread;
  k_pre<<<256, 256, 0, st>>>((const bf16*)d_in[0], (const char*)d_in[2], (const char*)d_in[3], (const char*)d_in[4], (const char*)d_in[5]);
  cudaLaunchConfig_t cfg = {}; cfg.gridDim = dim3(ncl * CLS); cfg.blockDim = dim3(384); cfg.dynamicSmemBytes = SMEM_TOTAL; cfg.stream = st;
  cudaLaunchAttribute at[2]; at[1].id = cudaLaunchAttributeClusterDimension; at[1].val.clusterDim.x = CLS; at[1].val.clusterDim.y = 1; at[1].val.clusterDim.z = 1;
  at[0].id = cudaLaunchAttributeProgrammaticStreamSerialization; at[0].val.programmaticStreamSerializationAllowed = 1;
#define PDL1 0
  cfg.attrs = at + (PDL1 ? 0 : 1); cfg.numAttrs = PDL1 ? 2 : 1;
  cudaLaunchKernelEx(&cfg, k_main, maps, (const bf16*)d_in[0], (const bf16*)d_in[1], (const bf16*)d_in[9], (const bf16*)d_in[11], (bf16*)d_out, recmask);
  if (nhelp > 0) {
    cfg.gridDim = dim3(nhelp);
    cfg.attrs = at; cfg.numAttrs = 1;
    cudaLaunchKernelEx(&cfg, k_main, maps, (const bf16*)d_in[0], (const bf16*)d_in[1], (const bf16*)d_in[9], (const bf16*)d_in[11], (bf16*)d_out, 0u);
  }
}
```

```cpp
#include <cuda_runtime.h>
#include <cuda_bf16.h>
#include <cuda.h>
#include <stdint.h>

typedef __nv_bfloat16 bf16;

#define S_TOK 2048
#define DM 512
#define NH 32
#define DH 128
#define HD 4096
#define NMEM 8
#define SEG 32
#define NSEG 64
#define FF 1792
#define NBLK 16
#define NREC 64
#define REPL 0
#define CLS 8

__device__ __align__(1024) bf16 g_xn[S_TOK * DM];
__device__ __align__(1024) bf16 g_y[S_TOK * DM];
__device__ __align__(1024) bf16 g_qkv[(size_t)S_TOK * 3 * HD];
__device__ __align__(1024) bf16 g_h1[S_TOK * FF];
__device__ __align__(1024) bf16 g_g[S_TOK * DM];
__device__ __align__(1024) bf16 g_o[(size_t)S_TOK * HD];
__device__ __align__(1024) bf16 g_km[NSEG * NH * NMEM * DH];
__device__ __align__(1024) bf16 g_vmt[NSEG * NH * DH * NMEM];
__device__ __align__(1024) float g_opart[(size_t)4 * S_TOK * DM];
__device__ __align__(1024) float g_opl[(size_t)16 * 128 * DM];
__device__ __align__(1024) unsigned g_part[2 * 8 * 8 * 512];
struct Flags {
  unsigned qkv[NBLK * 48];
  unsigned h1[NBLK];
  unsigned g[NBLK];
  unsigned o[NBLK * 4];
  unsigned p[NBLK];
  unsigned o16[16];
  unsigned ctr;
  unsigned rec[NREC];
  unsigned abort_;
};
__device__ __align__(1024) Flags g_flags;

#define RSTAMP(k)
#define DBGMODE 0
#define ISTAMP(i, k)
__device__ __forceinline__ unsigned smem_u32(const void* p) { return (unsigned)__cvta_generic_to_shared(p); }
__device__ __forceinline__ float bf16r(float x) { unsigned u; asm("cvt.rn.bf16x2.f32 %0, %1, %2;" : "=r"(u) : "f"(x), "f"(0.0f)); return __uint_as_float(u); }
__device__ __forceinline__ unsigned pack_bf16(float lo, float hi) {
  __nv_bfloat162 v = __floats2bfloat162_rn(lo, hi);
  return *reinterpret_cast<unsigned*>(&v);
}
__device__ __forceinline__ float bf_lo(unsigned u) { return __uint_as_float(u << 16); }
__device__ __forceinline__ float bf_hi(unsigned u) { return __uint_as_float(u & 0xffff0000u); }

#define SPIN_LIMIT (1u << 20)
#define TRAP_IF(x) if ((x) > SPIN_LIMIT) { asm volatile("st.global.u32 [%0], %1;" ::"l"(0ull), "r"(0u) : "memory"); break; }
__device__ __forceinline__ unsigned ld_acquire(const unsigned* p) {
  unsigned v; asm volatile("ld.acquire.gpu.global.u32 %0, [%1];" : "=r"(v) : "l"(p) : "memory"); return v;
}
__device__ __forceinline__ unsigned ld_relaxed(const unsigned* p) {
  unsigned v; asm volatile("ld.relaxed.gpu.global.u32 %0, [%1];" : "=r"(v) : "l"(p) : "memory"); return v;
}
__device__ __forceinline__ void red_release_add(unsigned* p, unsigned v) {
  asm volatile("red.release.gpu.global.add.u32 [%0], %1;" ::"l"(p), "r"(v) : "memory");
}
__device__ __forceinline__ void st_release(unsigned* p, unsigned v) {
  asm volatile("st.release.gpu.global.u32 [%0], %1;" ::"l"(p), "r"(v) : "memory");
}
__device__ __forceinline__ void wait_flag_ge(const unsigned* p, unsigned target) {
  unsigned it = 0;
  while (ld_acquire(p) < target) {
    __nanosleep(64);
    TRAP_IF(++it);
  }
}
__device__ __forceinline__ void wait_step_ge(const unsigned* p, unsigned target) {
  unsigned it = 0, v;
  while ((v = ld_acquire(p)) < target) {
    __nanosleep(target - v >= 2 ? 1500 : 64);
    TRAP_IF(++it);
  }
}
__device__ __forceinline__ uint4 ldv4_relaxed(const void* p) {
  uint4 a; asm volatile("ld.relaxed.gpu.global.v4.u32 {%0,%1,%2,%3}, [%4];" : "=r"(a.x), "=r"(a.y), "=r"(a.z), "=r"(a.w) : "l"(p) : "memory"); return a;
}
__device__ __forceinline__ uint2 ldv2_relaxed(const void* p) {
  uint2 a; asm volatile("ld.relaxed.gpu.global.v2.u32 {%0,%1}, [%2];" : "=r"(a.x), "=r"(a.y) : "l"(p) : "memory"); return a;
}
__device__ __forceinline__ void mbar_init(unsigned mb, unsigned cnt) { asm volatile("mbarrier.init.shared::cta.b64 [%0], %1;" ::"r"(mb), "r"(cnt) : "memory"); }
__device__ __forceinline__ void mbar_expect_tx(unsigned mb, unsigned bytes) { asm volatile("mbarrier.arrive.expect_tx.shared::cta.b64 _, [%0], %1;" ::"r"(mb), "r"(bytes) : "memory"); }
__device__ __forceinline__ void mbar_arrive(unsigned mb) { asm volatile("mbarrier.arrive.shared::cta.b64 _, [%0];" ::"r"(mb) : "memory"); }
__device__ __forceinline__ void mbar_wait(unsigned mb, unsigned parity) {
  unsigned ok, it = 0;
  while (true) {
    asm volatile("{.reg .pred p; mbarrier.try_wait.parity.shared::cta.b64 p, [%1], %2; selp.u32 %0,1,0,p;}" : "=r"(ok) : "r"(mb), "r"(parity) : "memory");
    if (ok) break;
    TRAP_IF(++it);
  }
}
__device__ __forceinline__ void mbar_wait_sleep(unsigned mb, unsigned parity) {
  unsigned ok, it = 0;
  while (true) {
    asm volatile("{.reg .pred p; mbarrier.test_wait.parity.shared::cta.b64 p, [%1], %2; selp.u32 %0,1,0,p;}" : "=r"(ok) : "r"(mb), "r"(parity) : "memory");
    if (ok) break;
    __nanosleep(200);
    TRAP_IF(++it);
  }
}
__device__ __forceinline__ float ex2f(float x) { float y; asm("ex2.approx.ftz.f32 %0, %1;" : "=f"(y) : "f"(x)); return y; }
__device__ __forceinline__ int opaque_tid() { int t = threadIdx.x; t = __shfl_sync(~0u, t, t & 31); return t; }
#define LOG2E 1.4426950408889634f
__device__ __forceinline__ void mbar_wait_cluster(unsigned mb, unsigned parity) {
  unsigned ok, it = 0;
  while (true) {
    asm volatile("{.reg .pred p; mbarrier.try_wait.parity.acquire.cluster.shared::cta.b64 p, [%1], %2; selp.u32 %0,1,0,p;}" : "=r"(ok) : "r"(mb), "r"(parity) : "memory");
    if (ok) break;
    TRAP_IF(++it);
  }
}
__device__ __forceinline__ void bar_sync(int id, int n) { asm volatile("bar.sync %0, %1;" ::"r"(id), "r"(n) : "memory"); }
__device__ __forceinline__ void bar_arrive(int id, int n) { asm volatile("bar.arrive %0, %1;" ::"r"(id), "r"(n) : "memory"); }
__device__ __forceinline__ void tma_load_2d(unsigned dst, const CUtensorMap* map, int c0, int c1, unsigned mb) {
  asm volatile("cp.async.bulk.tensor.2d.shared::cluster.global.mbarrier::complete_tx::bytes [%0], [%1, {%3, %4}], [%2];"
               ::"r"(dst), "l"((uint64_t)map), "r"(mb), "r"(c0), "r"(c1) : "memory");
}
__device__ __forceinline__ void tma_store_2d(const CUtensorMap* map, unsigned src, int c0, int c1) {
  asm volatile("cp.async.bulk.tensor.2d.global.shared::cta.bulk_group [%0, {%2, %3}], [%1];"
               ::"l"((uint64_t)map), "r"(src), "r"(c0), "r"(c1) : "memory");
}
__device__ __forceinline__ void fence_proxy_async() { asm volatile("fence.proxy.async;" ::: "memory"); }
__device__ __forceinline__ void fence_proxy_async_smem() { asm volatile("fence.proxy.async.shared::cta;" ::: "memory"); }
__device__ __forceinline__ void ldsm_x4(unsigned* r, unsigned addr) {
  asm volatile("ldmatrix.sync.aligned.m8n8.x4.shared.b16 {%0,%1,%2,%3}, [%4];" : "=r"(r[0]), "=r"(r[1]), "=r"(r[2]), "=r"(r[3]) : "r"(addr) : "memory");
}
__device__ __forceinline__ void ldsm_x4_t(unsigned* r, unsigned addr) {
  asm volatile("ldmatrix.sync.aligned.m8n8.x4.trans.shared.b16 {%0,%1,%2,%3}, [%4];" : "=r"(r[0]), "=r"(r[1]), "=r"(r[2]), "=r"(r[3]) : "r"(addr) : "memory");
}
__device__ __forceinline__ void stsm_x2_t(unsigned addr, unsigned r0, unsigned r1) {
  asm volatile("stmatrix.sync.aligned.m8n8.x2.trans.shared.b16 [%0], {%1,%2};" ::"r"(addr), "r"(r0), "r"(r1) : "memory");
}
__device__ __forceinline__ void stsm_x4(unsigned addr, unsigned r0, unsigned r1, unsigned r2, unsigned r3) {
  asm volatile("stmatrix.sync.aligned.m8n8.x4.shared.b16 [%0], {%1,%2,%3,%4};" ::"r"(addr), "r"(r0), "r"(r1), "r"(r2), "r"(r3) : "memory");
}
__device__ __forceinline__ void mma16816(float* d, const unsigned* a, unsigned b0, unsigned b1) {
  asm volatile("mma.sync.aligned.m16n8k16.row.col.f32.bf16.bf16.f32 {%0,%1,%2,%3}, {%4,%5,%6,%7}, {%8,%9}, {%0,%1,%2,%3};"
               : "+f"(d[0]), "+f"(d[1]), "+f"(d[2]), "+f"(d[3]) : "r"(a[0]), "r"(a[1]), "r"(a[2]), "r"(a[3]), "r"(b0), "r"(b1));
}
__device__ __forceinline__ void mma1688(float* d, unsigned a0, unsigned a1, unsigned b0) {
  asm volatile("mma.sync.aligned.m16n8k8.row.col.f32.bf16.bf16.f32 {%0,%1,%2,%3}, {%4,%5}, {%6}, {%0,%1,%2,%3};"
               : "+f"(d[0]), "+f"(d[1]), "+f"(d[2]), "+f"(d[3]) : "r"(a0), "r"(a1), "r"(b0));
}
__device__ __forceinline__ uint64_t mkdesc(unsigned addr, unsigned lbo, unsigned sbo) {
  return (uint64_t)((addr >> 4) & 0x3fff) | ((uint64_t)(lbo >> 4) << 16) | ((uint64_t)(sbo >> 4) << 32) | (1ull << 62);
}
#define R8(b) "+f"(d[b]), "+f"(d[b + 1]), "+f"(d[b + 2]), "+f"(d[b + 3]), "+f"(d[b + 4]), "+f"(d[b + 5]), "+f"(d[b + 6]), "+f"(d[b + 7])
#define R32(b) R8(b), R8(b + 8), R8(b + 16), R8(b + 24)
__device__ __forceinline__ void wgmma_n256(float* d, uint64_t ad, uint64_t bd, int acc) {
  asm volatile(
      "{.reg .pred p; setp.ne.b32 p, %130, 0;\n"
      "wgmma.mma_async.sync.aligned.m64n256k16.f32.bf16.bf16 "
      "{%0,%1,%2,%3,%4,%5,%6,%7,%8,%9,%10,%11,%12,%13,%14,%15,%16,%17,%18,%19,%20,%21,%22,%23,%24,%25,%26,%27,%28,%29,%30,%31,"
      "%32,%33,%34,%35,%36,%37,%38,%39,%40,%41,%42,%43,%44,%45,%46,%47,%48,%49,%50,%51,%52,%53,%54,%55,%56,%57,%58,%59,%60,%61,%62,%63,"
      "%64,%65,%66,%67,%68,%69,%70,%71,%72,%73,%74,%75,%76,%77,%78,%79,%80,%81,%82,%83,%84,%85,%86,%87,%88,%89,%90,%91,%92,%93,%94,%95,"
      "%96,%97,%98,%99,%100,%101,%102,%103,%104,%105,%106,%107,%108,%109,%110,%111,%112,%113,%114,%115,%116,%117,%118,%119,%120,%121,%122,%123,%124,%125,%126,%127},"
      "%128, %129, p, 1, 1, 0, 1;}\n"
      : R32(0), R32(32), R32(64), R32(96)
      : "l"(ad), "l"(bd), "r"(acc));
}

__device__ __forceinline__ void wgmma_n128(float* d, uint64_t ad, uint64_t bd, int acc) {
  asm volatile(
      "{.reg .pred p; setp.ne.b32 p, %66, 0;\n"
      "wgmma.mma_async.sync.aligned.m64n128k16.f32.bf16.bf16 {%0,%1,%2,%3,%4,%5,%6,%7,%8,%9,%10,%11,%12,%13,%14,%15,%16,%17,%18,%19,%20,%21,%22,%23,%24,%25,%26,%27,%28,%29,%30,%31,%32,%33,%34,%35,%36,%37,%38,%39,%40,%41,%42,%43,%44,%45,%46,%47,%48,%49,%50,%51,%52,%53,%54,%55,%56,%57,%58,%59,%60,%61,%62,%63}, %64, %65, p, 1, 1, 0, 1;}\n"
      : R32(0), R32(32)
      : "l"(ad), "l"(bd), "r"(acc));
}

__device__ __forceinline__ void ln16(const float* x, float* o) {
  float s = 0;
#pragma unroll
  for (int i = 0; i < 16; i++) s += x[i];
#pragma unroll
  for (int of = 16; of > 0; of >>= 1) s += __shfl_xor_sync(~0u, s, of);
  float mean = s * (1.0f / DM);
  float v = 0;
#pragma unroll
  for (int i = 0; i < 16; i++) { float dd = x[i] - mean; v += dd * dd; }
#pragma unroll
  for (int of = 16; of > 0; of >>= 1) v += __shfl_xor_sync(~0u, v, of);
  float mb = bf16r(mean);
  float vb = bf16r(v * (1.0f / DM));
  float den = bf16r(sqrtf(bf16r(vb + 1e-5f)));
#pragma unroll
  for (int i = 0; i < 16; i++) o[i] = bf16r(__fdiv_rn(bf16r(x[i] - mb), den));
}
__global__ void __launch_bounds__(256) k_pre(const bf16* __restrict__ x, const char* wq, const char* wk, const char* wv, const char* wo) {
  int t = threadIdx.x, lane = t & 31, w = t >> 5;
  {
    int g2 = blockIdx.x * 256 + t, o = (g2 & 32767) * 128;
    asm volatile("prefetch.global.L2 [%0];" ::"l"((g2 < 32768 ? wk : wv) + o));
    asm volatile("prefetch.global.L2 [%0];" ::"l"((g2 < 32768 ? wq : wo) + o));
  }
  int row = blockIdx.x * 8 + w;
  const uint4* src = reinterpret_cast<const uint4*>(x + (size_t)row * DM);
  uint4 a = src[lane], b = src[lane + 32];
  unsigned u[8] = {a.x, a.y, a.z, a.w, b.x, b.y, b.z, b.w};
  float f[16], o[16], o2[16];
#pragma unroll
  for (int i = 0; i < 8; i++) { f[2 * i] = bf_lo(u[i]); f[2 * i + 1] = bf_hi(u[i]); }
  ln16(f, o);
  ln16(o, o2);
  uint4* d1 = reinterpret_cast<uint4*>(g_xn + (size_t)row * DM);
  uint4* d2 = reinterpret_cast<uint4*>(g_y + (size_t)row * DM);
  d1[lane] = make_uint4(pack_bf16(o[0], o[1]), pack_bf16(o[2], o[3]), pack_bf16(o[4], o[5]), pack_bf16(o[6], o[7]));
  d1[lane + 32] = make_uint4(pack_bf16(o[8], o[9]), pack_bf16(o[10], o[11]), pack_bf16(o[12], o[13]), pack_bf16(o[14], o[15]));
  d2[lane] = make_uint4(pack_bf16(o2[0], o2[1]), pack_bf16(o2[2], o2[3]), pack_bf16(o2[4], o2[5]), pack_bf16(o2[6], o2[7]));
  d2[lane + 32] = make_uint4(pack_bf16(o2[8], o2[9]), pack_bf16(o2[10], o2[11]), pack_bf16(o2[12], o2[13]), pack_bf16(o2[14], o2[15]));
  int gt = blockIdx.x * 256 + t;
  uint4 z = make_uint4(0, 0, 0, 0);
  if (gt < 16384) reinterpret_cast<uint4*>(g_part)[gt] = z;
  if (gt < (int)(sizeof(Flags) / 4)) reinterpret_cast<unsigned*>(&g_flags)[gt] = 0;
}

struct Maps { CUtensorMap xn, y, h1, o, qkv_st, qkv_ld, g, wq, wk, wv, wo, w1, w2; };

#define NSTAGE 3
#define STAGE_BYTES 49152
#define B_STG (NSTAGE * STAGE_BYTES)
#define R_WO 0
#define R_T1 65536
#define R_T2 131072
#define R_RING 65536
#define RING_N 4
#define RING_BYTES 12288
#define R_MEM 196608
#define R_QS (R_MEM + 8448)
#define R_KS (R_QS + 1152)
#define R_OS (R_KS + 1152)
#define R_SOWN (R_OS + 2176)
#define R_SPEER (R_SOWN + 1280)
#define R_VM (R_SPEER + 1280)
#define R_VRED (R_VM + 2048)
#define R_RS (R_VRED + 6144)
#define SM_BAR (R_RS + 8192)
#define SMEM_TOTAL (SM_BAR + 256 + 1024)
#define MB_FULL 0
#define MB_EMPTY 8
#define MB_STGF 16
#define MB_STGE 17
#define MB_W0 18
#define MB_W1 19
#define MB_WO 20
#define MB_S 21
#define MB_V 22
#define MB_KVR 23
#define MB_KVF 24
#define MB_RS 25
#define MB_AG 26
#define SM_MISC (SM_BAR + 224)

#define N_KV 544
#define I_M1 544
#define I_Q 656
#define I_M2 912
#define I_POST 944
#define I_TAIL (I_POST + 16 * 32)
#define N_ITEMS (I_TAIL + 7 * 8 + 64 + 32 + 64)
enum { T_QKV = 0, T_M1 = 1, T_M2 = 2, T_ATT = 3, T_OUT = 4, T_OUTL = 5, T_RED = 6, T_REDL = 7 };
struct Item { int type, b, c, ks, hf; };
__device__ __forceinline__ Item decode_item(int i) {
  Item it; it.ks = 0; it.hf = 0;
  if (i < 64) { it.type = T_QKV; it.b = 0; it.c = 16 + (i >> 1); it.hf = 1 + (i & 1); }
  else if (i < N_KV) { it.type = T_QKV; it.b = (i - 32) >> 5; it.c = 16 + (i & 31); }
  else if (i < I_Q) { it.type = T_M1; it.b = (i - I_M1) / 7; it.c = (i - I_M1) % 7; }
  else if (i < I_M2) { it.type = T_QKV; it.b = (i - I_Q) >> 4; it.c = (i - I_Q) & 15; }
  else if (i < I_POST) { it.type = T_M2; it.b = (i - I_M2) >> 1; it.c = (i - I_M2) & 1; }
  else if (i < I_TAIL) {
    int x = i - I_POST, p = x >> 5, r = x & 31;
    if (r < 16) { it.type = T_ATT; it.b = p; it.c = r; }
    else if (r < 24) { it.type = T_OUT; it.b = p - 3; it.c = r & 1; it.ks = (r - 16) >> 1; }
    else { it.type = T_RED; it.b = p - 5; it.c = r - 24; }
  } else {
    int x = i - I_TAIL, r = x & 7;
    if (x < 16 || (x >= 24 && x < 40)) { int y = x < 16 ? x : x - 24; it.type = T_OUT; it.b = x < 16 ? 13 : 14; it.c = (y >> 1) & 1; it.ks = y >> 2; it.hf = 1 + (y & 1); }
    else if (x < 56) { it.type = T_RED; it.b = x < 24 ? 11 : 7 + (x >> 3); it.c = r; }
    else if (x < 120) { it.type = T_OUTL; it.b = 15; it.c = (x >> 1) & 1; it.ks = (x - 56) >> 2; it.hf = 1 + (x & 1); }
    else if (x < 152) { it.type = T_RED; it.b = 14; it.c = x - 120; it.ks = 1; }
    else { it.type = T_REDL; it.b = 15; it.c = x - 152; }
  }
  return it;
}
__device__ __forceinline__ int item_nkb(int type) { return type == T_M2 ? 28 : (type == T_OUT ? 16 : (type >= T_RED ? 1 : (type >= T_ATT ? 4 : 8))); }

__device__ __forceinline__ void st_async_b64(unsigned raddr, unsigned lo, unsigned hi, unsigned rmb) {
  asm volatile("st.async.weak.shared::cluster.mbarrier::complete_tx::bytes.v2.b32 [%0], {%1,%2}, [%3];" ::"r"(raddr), "r"(lo), "r"(hi), "r"(rmb) : "memory");
}
__device__ __forceinline__ void st_async_b32(unsigned raddr, unsigned v, unsigned rmb) {
  asm volatile("st.async.weak.shared::cluster.mbarrier::complete_tx::bytes.b32 [%0], %1, [%2];" ::"r"(raddr), "r"(v), "r"(rmb) : "memory");
}
__device__ __forceinline__ unsigned mapa(unsigned a, unsigned rank) {
  unsigned r; asm volatile("mapa.shared::cluster.u32 %0, %1, %2;" : "=r"(r) : "r"(a), "r"(rank)); return r;
}
__device__ __forceinline__ void sts64(unsigned a, unsigned x, unsigned y) { asm volatile("st.shared.v2.b32 [%0], {%1,%2};" ::"r"(a), "r"(x), "r"(y) : "memory"); }
__device__ __forceinline__ void sts128(unsigned a, uint4 v) { asm volatile("st.shared.v4.b32 [%0], {%1,%2,%3,%4};" ::"r"(a), "r"(v.x), "r"(v.y), "r"(v.z), "r"(v.w) : "memory"); }
__device__ __forceinline__ uint2 lds64(unsigned a) { uint2 v; asm volatile("ld.shared.v2.b32 {%0,%1}, [%2];" : "=r"(v.x), "=r"(v.y) : "r"(a) : "memory"); return v; }
__device__ __forceinline__ uint4 lds128(unsigned a) { uint4 v; asm volatile("ld.shared.v4.b32 {%0,%1,%2,%3}, [%4];" : "=r"(v.x), "=r"(v.y), "=r"(v.z), "=r"(v.w) : "r"(a) : "memory"); return v; }
__device__ __forceinline__ float lds32f(unsigned a) { float v; asm volatile("ld.shared.f32 %0, [%1];" : "=f"(v) : "r"(a) : "memory"); return v; }
#define spin_check(it) TRAP_IF(++it)
#define POLLV 0
#define BAR8 0
#define D_STAG 150
#define D_RED 540
#define D_PUB 0
#define DELAY(n) do { unsigned c0_, c1_; asm volatile("mov.u32 %0, %%clock;" : "=r"(c0_)); do { asm volatile("mov.u32 %0, %%clock;" : "=r"(c1_)); } while (c1_ - c0_ < (n)); } while (0)
#define VD 2
#define NPRE 3
#define SELP 1
#define SCALE_QK 0.08838834764831845f

__device__ __forceinline__ void rec_worker(const Maps& maps, unsigned sb, const bf16* __restrict__ mem0, const int c) {
  const int h = c >> 1, j = c & 1;
  const int t = opaque_tid(), lane = t & 31, w = t >> 5, g = lane >> 2, tq = lane & 3;
  const int m = lane >> 3, r8 = lane & 7, kh = w >> 2, et = w & 3;
  const unsigned bar = sb + SM_BAR;
  unsigned wq[16][4], wk[16][4], wo[8][4];
  const unsigned woff = (kh * 4) * 8192 + ((m >> 1) * 8 + r8) * 128 + (((et * 2 + (m & 1)) ^ r8) << 4);
  mbar_wait(bar + 8 * MB_W0, 0);
#pragma unroll
  for (int i = 0; i < 16; i++) {
    ldsm_x4_t(wq[i], sb + R_WO + woff + (i >> 2) * 8192 + (i & 3) * 2048);
    ldsm_x4_t(wk[i], sb + R_T1 + woff + (i >> 2) * 8192 + (i & 3) * 2048);
  }
  bar_sync(2, 288);
  if (t == 0) {
    fence_proxy_async_smem();
    mbar_expect_tx(bar + 8 * MB_WO, 65536);
    for (int kb = 0; kb < 2; kb++)
      for (int cb = 0; cb < 4; cb++) tma_load_2d(sb + R_WO + (kb * 4 + cb) * 8192, &maps.wo, j * 256 + cb * 64, h * 128 + kb * 64, bar + 8 * MB_WO);
  }
  mbar_wait(bar + 8 * MB_W1, 0);
  const unsigned pV = sb + R_T2 + woff;
  const unsigned rk = c & 7, peer = rk ^ 1, cl = c >> 3;
#define KEEP(x) x = __shfl_sync(~0u, x, lane)
  unsigned pA = sb + R_MEM + kh * 4096 + lane * 16;
  unsigned pW0 = sb + R_WO + (w >> 1) * 8192 + ((m >> 1) * 8 + r8) * 128 + ((((w & 1) * 4 + (m & 1)) ^ r8) << 4);
  unsigned pW1 = pW0 ^ 32;
  unsigned pVk = pV;
  unsigned aX = sb + R_VRED + et * 512 + lane * 16;
  unsigned aQKst = sb + (kh ? R_KS : R_QS) + r8 * 144 + (et * 16 + (m & 1) * 8) * 2;
  unsigned aL8 = sb + lane * 8;
  unsigned aSl = mapa(sb + R_SOWN + w * 256 + lane * 8, rk), aSr = mapa(sb + R_SPEER + w * 256 + lane * 8, peer);
  unsigned aVl = mapa(sb + R_VM + (j * 4 + et) * 256 + lane * 8, rk), aVr = mapa(sb + R_VM + (j * 4 + et) * 256 + lane * 8, peer);
  const unsigned mbSl = mapa(bar + 8 * MB_S, rk), mbSr = mapa(bar + 8 * MB_S, peer), mbVl = mbSl + 8, mbVr = mbSr + 8;
  unsigned aQ = sb + R_QS + r8 * 144 + m * 16;
  unsigned oKx = (et * 8 + r8) * 128 + ((m ^ r8) << 4);
  unsigned oVx = 4096 + (et >> 1) * 4096 + ((m >> 1) * 8 + r8) * 128 + ((((et & 1) * 4 + (m & 1)) ^ r8) << 4);
  unsigned aOst = sb + R_OS + r8 * 272 + (et * 32 + m * 8) * 2;
  unsigned aOld = sb + R_OS + r8 * 272 + m * 16;
  unsigned aVm = sb + R_VM + et * 512 + lane * 8;
  unsigned aRSr = mapa(sb + R_RS + (h & 3) * 2048 + (w & 1) * 1024 + lane * 8, j * 4 + (w >> 1));
  unsigned mbRSr = mapa(bar + 8 * MB_RS, j * 4 + (w >> 1));
  unsigned t8 = t * 8;
  KEEP(pA); KEEP(pW0); KEEP(pW1); KEEP(pVk); KEEP(aX); KEEP(aQKst); KEEP(aL8); KEEP(aSl); KEEP(aSr); KEEP(aVl); KEEP(aVr); KEEP(aQ); KEEP(oKx); KEEP(oVx);
  KEEP(aOst); KEEP(aOld); KEEP(aVm); KEEP(aRSr); KEEP(mbRSr); KEEP(t8);
  mbar_wait(bar + 8 * MB_WO, 0);
#pragma unroll
  for (int ks = 0; ks < 4; ks++) { ldsm_x4_t(wo[2 * ks], pW0 + ks * 2048); ldsm_x4_t(wo[2 * ks + 1], pW1 + ks * 2048); }
  {
    unsigned v[8];
#pragma unroll
    for (int q = 0; q < 8; q++) v[q] = __ldg(reinterpret_cast<const unsigned*>(mem0) + q * 256 + t);
    sts128(sb + R_MEM + t * 32, make_uint4(__byte_perm(v[0], v[1], 0x5410), __byte_perm(v[2], v[3], 0x5410), __byte_perm(v[4], v[5], 0x5410), __byte_perm(v[6], v[7], 0x5410)));
    sts128(sb + R_MEM + t * 32 + 16, make_uint4(__byte_perm(v[0], v[1], 0x7632), __byte_perm(v[2], v[3], 0x7632), __byte_perm(v[4], v[5], 0x7632), __byte_perm(v[6], v[7], 0x7632)));
  }
  bar_sync(1, 256);

#pragma unroll 1
  for (int s = 0;; s++) {
    const unsigned par = s & 1;
    const unsigned slot = s & (RING_N - 1), rpar = (s / RING_N) & 1;
    const unsigned ring = sb + R_RING + slot * RING_BYTES;
    asm volatile("" : "+r"(t8));
    RSTAMP(1);
    RSTAMP(2);
    float aq[4] = {0, 0, 0, 0}, ak[4] = {0, 0, 0, 0}, av[4] = {0, 0, 0, 0};
    {
      unsigned b[8][4], f1[8][4], f0[8][4];
#define VLD(i) do { ldsm_x4_t(b[i], pA + (i) * 512); ldsm_x4_t(f0[i], pVk + ((i) >> 1) * 8192 + ((i) & 1) * 4096); ldsm_x4_t(f1[i], pVk + ((i) >> 1) * 8192 + ((i) & 1) * 4096 + 2048); } while (0)
      VLD(0);
      if (VD > 1) VLD(1);
#pragma unroll
      for (int i = 0; i < 8; i++) {
        if (i + VD < 8) VLD(i + VD);
        mma16816(aq, wq[2 * i], b[i][0], b[i][1]); mma16816(ak, wk[2 * i], b[i][0], b[i][1]); mma16816(av, f0[i], b[i][0], b[i][1]);
        mma16816(aq, wq[2 * i + 1], b[i][2], b[i][3]); mma16816(ak, wk[2 * i + 1], b[i][2], b[i][3]); mma16816(av, f1[i], b[i][2], b[i][3]);
      }
    }
    RSTAMP(3);
#define STSF4(a, v) asm volatile("st.shared.v4.f32 [%0], {%1,%2,%3,%4};" ::"r"(a), "f"(v[0]), "f"(v[1]), "f"(v[2]), "f"(v[3]) : "memory")
    unsigned f[8][4];
#define WO_PREFETCH() do { _Pragma("unroll") for (int i = 0; i < NPRE; i++) { ldsm_x4_t(f[2 * i], pW0 + 32768 + i * 2048); ldsm_x4_t(f[2 * i + 1], pW1 + 32768 + i * 2048); } } while (0)
    if (kh) {
      STSF4(aX, aq);
      bar_sync(4 + et, 64);
      uint4 o = lds128(aX + 2048), o2 = lds128(aX + 4096);
      stsm_x2_t(aQKst, pack_bf16(ak[0] + __uint_as_float(o.x), ak[1] + __uint_as_float(o.y)), pack_bf16(ak[2] + __uint_as_float(o.z), ak[3] + __uint_as_float(o.w)));
      bar_arrive(1, 256);
      unsigned x = pack_bf16(av[0] + __uint_as_float(o2.x), av[1] + __uint_as_float(o2.y)), y = pack_bf16(av[2] + __uint_as_float(o2.z), av[3] + __uint_as_float(o2.w));
      st_async_b64(aVr, x, y, mbVr);
      st_async_b64(aVl, x, y, mbVl);
      if (s == NSEG - 1) {
        mbar_wait(bar + 8 * MB_V, par);
        if (t == 128) mbar_arrive(bar + 8 * MB_KVR);
        break;
      }
      mbar_wait(bar + 8 * (MB_FULL + slot), rpar);
      unsigned vx[4][4];
      ldsm_x4_t(vx[0], ring + oVx); ldsm_x4_t(vx[1], ring + oVx + 2048); ldsm_x4_t(vx[2], ring + (oVx ^ 32)); ldsm_x4_t(vx[3], ring + (oVx ^ 32) + 2048);
      RSTAMP(4); RSTAMP(5); RSTAMP(6); RSTAMP(7);
      mbar_wait(bar + 8 * MB_S, par);
      RSTAMP(8);
      float sc[10];
#pragma unroll
      for (int i = 0; i < 5; i++) {
        uint2 o = lds64(aL8 + R_SOWN + i * 256), p = lds64(aL8 + R_SPEER + i * 256);
        sc[2 * i] = __uint_as_float(o.x) + __uint_as_float(p.x); sc[2 * i + 1] = __uint_as_float(o.y) + __uint_as_float(p.y);
      }
      mbar_wait(bar + 8 * MB_V, par);
      uint2 vm0 = lds64(aVm), vm1 = lds64(aVm + 256);
      float mx = fmaxf(fmaxf(fmaxf(sc[0], sc[1]), fmaxf(sc[2], sc[3])), fmaxf(fmaxf(fmaxf(sc[4], sc[5]), fmaxf(sc[6], sc[7])), fmaxf(sc[8], sc[9])));
      mx = fmaxf(mx, __shfl_xor_sync(~0u, mx, 1)); mx = fmaxf(mx, __shfl_xor_sync(~0u, mx, 2));
      const float nm = -mx * (SCALE_QK * LOG2E);
      unsigned p[5];
#pragma unroll
      for (int i = 0; i < 5; i++) p[i] = pack_bf16(ex2f(fmaf(sc[2 * i], SCALE_QK * LOG2E, nm)), ex2f(fmaf(sc[2 * i + 1], SCALE_QK * LOG2E, nm)));
      RSTAMP(9);
      float o0[4] = {0, 0, 0, 0}, o1[4] = {0, 0, 0, 0}, o3[4] = {0, 0, 0, 0}, o4[4] = {0, 0, 0, 0}, z0[4] = {0, 0, 0, 0}, z1[4] = {0, 0, 0, 0};
      const unsigned ones[4] = {0x3F803F80u, 0u, 0x3F803F80u, 0u};
      mma16816(z0, ones, p[0], p[1]); mma16816(z1, ones, p[2], p[3]);
      mma16816(o0, vx[0], p[0], p[1]); mma16816(o3, vx[2], p[0], p[1]);
      mma1688(z0, 0x3F803F80u, 0u, p[4]);
      mma16816(o1, vx[1], p[2], p[3]); mma16816(o4, vx[3], p[2], p[3]);
      mma1688(o0, vm0.x, vm0.y, p[4]); mma1688(o3, vm1.x, vm1.y, p[4]);
      float i0, i1;
      asm("rcp.approx.ftz.f32 %0, %1;" : "=f"(i0) : "f"(z0[0] + z1[0])); asm("rcp.approx.ftz.f32 %0, %1;" : "=f"(i1) : "f"(z0[1] + z1[1]));
      asm volatile("stmatrix.sync.aligned.m8n8.x4.trans.shared.b16 [%0], {%1,%2,%3,%4};" ::"r"(aOst), "r"(pack_bf16((o0[0] + o1[0]) * i0, (o0[1] + o1[1]) * i1)), "r"(pack_bf16((o0[2] + o1[2]) * i0, (o0[3] + o1[3]) * i1)),
                   "r"(pack_bf16((o3[0] + o4[0]) * i0, (o3[1] + o4[1]) * i1)), "r"(pack_bf16((o3[2] + o4[2]) * i0, (o3[3] + o4[3]) * i1)) : "memory");
      RSTAMP(10);
      bar_sync(1, 256);
      WO_PREFETCH();
    } else {
      STSF4(aX + 2048, ak); STSF4(aX + 4096, av);
      unsigned kb[8];
      mbar_wait(bar + 8 * (MB_FULL + slot), rpar);
      ldsm_x4(kb, ring + oKx); ldsm_x4(kb + 4, ring + (oKx ^ 64));
      bar_sync(4 + et, 64);
      uint4 o = lds128(aX);
      stsm_x2_t(aQKst, pack_bf16(aq[0] + __uint_as_float(o.x), aq[1] + __uint_as_float(o.y)), pack_bf16(aq[2] + __uint_as_float(o.z), aq[3] + __uint_as_float(o.w)));
      RSTAMP(4);
      bar_sync(1, 256);
      RSTAMP(5);
      if (s == NSEG - 1) break;
      unsigned qa[8], km[8];
      ldsm_x4(qa, aQ); ldsm_x4(qa + 4, aQ + 64);
      if (w == 3) { ldsm_x4(km, aQ + 1152); ldsm_x4(km + 4, aQ + 1152 + 64); }
      float s0[4] = {0, 0, 0, 0}, s1[4] = {0, 0, 0, 0};
      unsigned af[4][4];
#pragma unroll
      for (int i = 0; i < 4; i++) { af[i][0] = qa[2 * i]; af[i][1] = 0; af[i][2] = qa[2 * i + 1]; af[i][3] = 0; }
      mma16816(s0, af[0], kb[0], kb[1]); mma16816(s1, af[1], kb[2], kb[3]);
      mma16816(s0, af[2], kb[4], kb[5]); mma16816(s1, af[3], kb[6], kb[7]);
      if (w == 3) {
        float m0[4] = {0, 0, 0, 0}, m1[4] = {0, 0, 0, 0};
        mma16816(m0, af[0], km[0], km[1]); mma16816(m1, af[1], km[2], km[3]);
        mma16816(m0, af[2], km[4], km[5]); mma16816(m1, af[3], km[6], km[7]);
        unsigned x = __float_as_uint(m0[0] + m1[0]), y = __float_as_uint(m0[1] + m1[1]);
        st_async_b64(aSr + 256, x, y, mbSr); st_async_b64(aSl + 256, x, y, mbSl);
      }
      unsigned x = __float_as_uint(s0[0] + s1[0]), y = __float_as_uint(s0[1] + s1[1]);
      st_async_b64(aSr, x, y, mbSr); st_async_b64(aSl, x, y, mbSl);
      RSTAMP(6);
      WO_PREFETCH();
      RSTAMP(7); RSTAMP(8); RSTAMP(9); RSTAMP(10);
      bar_sync(1, 256);
    }
    RSTAMP(11);
    float d0[4] = {0, 0, 0, 0}, d1[4] = {0, 0, 0, 0}, e0[4] = {0, 0, 0, 0}, e1[4] = {0, 0, 0, 0};
    unsigned ob[4][4];
#pragma unroll
    for (int k2 = 0; k2 < 4; k2++) ldsm_x4(ob[k2], aOld + k2 * 64);
#pragma unroll
    for (int i = NPRE; i < 4; i++) { ldsm_x4_t(f[2 * i], pW0 + 32768 + i * 2048); ldsm_x4_t(f[2 * i + 1], pW1 + 32768 + i * 2048); }
    mma16816(d0, wo[0], ob[0][0], ob[0][1]); mma16816(d1, wo[1], ob[0][0], ob[0][1]);
    mma16816(e0, wo[2], ob[0][2], ob[0][3]); mma16816(e1, wo[3], ob[0][2], ob[0][3]);
    mma16816(d0, wo[4], ob[1][0], ob[1][1]); mma16816(d1, wo[5], ob[1][0], ob[1][1]);
    mma16816(e0, wo[6], ob[1][2], ob[1][3]); mma16816(e1, wo[7], ob[1][2], ob[1][3]);
    mma16816(d0, f[0], ob[2][0], ob[2][1]); mma16816(d1, f[1], ob[2][0], ob[2][1]);
    mma16816(e0, f[2], ob[2][2], ob[2][3]); mma16816(e1, f[3], ob[2][2], ob[2][3]);
    mma16816(d0, f[4], ob[3][0], ob[3][1]); mma16816(d1, f[5], ob[3][0], ob[3][1]);
    mma16816(e0, f[6], ob[3][2], ob[3][3]); mma16816(e1, f[7], ob[3][2], ob[3][3]);
    st_async_b64(aRSr, __float_as_uint(d0[0] + e0[0]), __float_as_uint(d0[1] + e0[1]), mbRSr);
    st_async_b64(aRSr + 256, __float_as_uint(d0[2] + e0[2]), __float_as_uint(d0[3] + e0[3]), mbRSr);
    st_async_b64(aRSr + 512, __float_as_uint(d1[0] + e1[0]), __float_as_uint(d1[1] + e1[1]), mbRSr);
    st_async_b64(aRSr + 768, __float_as_uint(d1[2] + e1[2]), __float_as_uint(d1[3] + e1[3]), mbRSr);
    RSTAMP(12);
    if (t == 128) {
      mbar_arrive(bar + 8 * (MB_EMPTY + slot)); mbar_arrive(bar + 8 * MB_KVR);
      mbar_expect_tx(bar + 8 * MB_S, 2560); mbar_expect_tx(bar + 8 * MB_V, 2048);
    }
    const unsigned tag = ((s >> 1) & 1) ^ 1;
    const char* gp = reinterpret_cast<const char*>(g_part);
    const unsigned goff = (par * 8 + rk) * 16384 + cl * 2048 + t8;
    unsigned mbA[8];
#pragma unroll
    for (int i = 0; i < 8; i++) mbA[i] = mapa(bar + 8 * MB_AG, i);
    const unsigned dlt = (R_MEM + rk * 1024) - (SM_BAR + 8 * MB_AG) + (t8 >> 1);
    mbar_wait(bar + 8 * MB_RS, par);
    RSTAMP(13);
    uint2 a[8];
    {
      uint2 x0 = lds64(sb + R_RS + t8), x1 = lds64(sb + R_RS + 2048 + t8), x2 = lds64(sb + R_RS + 4096 + t8), x3 = lds64(sb + R_RS + 6144 + t8);
      float r0 = (__uint_as_float(x0.x) + __uint_as_float(x1.x)) + (__uint_as_float(x2.x) + __uint_as_float(x3.x));
      float r1 = (__uint_as_float(x0.y) + __uint_as_float(x1.y)) + (__uint_as_float(x2.y) + __uint_as_float(x3.y));
      a[0].x = (__float_as_uint(r0) & ~1u) | tag; a[0].y = (__float_as_uint(r1) & ~1u) | tag;
      asm volatile("st.relaxed.gpu.global.v2.u32 [%0], {%1,%2};" ::"l"(gp + goff), "r"(a[0].x), "r"(a[0].y) : "memory");
    }
    RSTAMP(14);
    if (t == 128) mbar_expect_tx(bar + 8 * MB_RS, 8192);
    {
      unsigned it = 0;
#define PLOAD(a) _Pragma("unroll") for (int i = 1; i < 8; i++) a[i] = ldv2_relaxed(gp + (goff ^ (i * 2048)))
#define PAND(a) (((a[1].x & a[1].y) & (a[2].x & a[2].y) & (a[3].x & a[3].y)) & ((a[4].x & a[4].y) & (a[5].x & a[5].y)) & ((a[6].x & a[6].y) & (a[7].x & a[7].y)))
#define POR(a) (((a[1].x | a[1].y) | (a[2].x | a[2].y) | (a[3].x | a[3].y)) | ((a[4].x | a[4].y) | (a[5].x | a[5].y)) | ((a[6].x | a[6].y) | (a[7].x | a[7].y)))
#define POK(a) (((tag ? PAND(a) : ~POR(a)) & 1u) != 0)
      if (D_RED) DELAY(D_RED);
      PLOAD(a);
      while (!POK(a)) {
#pragma unroll
        for (int i = 1; i < 8; i++) if (((a[i].x ^ tag) | (a[i].y ^ tag)) & 1u) a[i] = ldv2_relaxed(gp + (goff ^ (i * 2048)));
        spin_check(it);
      }
    }
    RSTAMP(15);
    {
#define AF(i, c) __uint_as_float(a[i].c)
      unsigned u = pack_bf16(((AF(0, x) + AF(1, x)) + (AF(2, x) + AF(3, x))) + ((AF(4, x) + AF(5, x)) + (AF(6, x) + AF(7, x))),
                             ((AF(0, y) + AF(1, y)) + (AF(2, y) + AF(3, y))) + ((AF(4, y) + AF(5, y)) + (AF(6, y) + AF(7, y))));
      __syncwarp();
#pragma unroll
      for (int i = 0; i < 8; i++) st_async_b32(mbA[i] + dlt, u, mbA[i]);
    }
    mbar_wait(bar + 8 * MB_KVF, par);
    mbar_wait(bar + 8 * MB_AG, par);
    if (t == 128) mbar_expect_tx(bar + 8 * MB_AG, 8192);
  }
}

__device__ __forceinline__ void rec_ring(const Maps& maps, unsigned sb, const int c) {
  const int h = c >> 1, j = c & 1;
  const unsigned bar = sb + SM_BAR;
  const int lane = threadIdx.x & 31;
  __syncwarp();
  bar_sync(2, 288);
  if (lane == 0) {
    fence_proxy_async_smem();
    for (int s = 0; s < NSEG; s++) {
      unsigned slot = s & (RING_N - 1);
      if ((s & 3) == 0 && !DBGMODE) {
        wait_flag_ge(&g_flags.qkv[(s >> 2) * 48 + 16 + (h >> 1)], 2);
        wait_flag_ge(&g_flags.qkv[(s >> 2) * 48 + 32 + (h >> 1)], 2);
        fence_proxy_async();
      }
      if (s >= RING_N) mbar_wait_sleep(bar + 8 * (MB_EMPTY + slot), ((s / RING_N) - 1) & 1);
      unsigned dst = sb + R_RING + slot * RING_BYTES, mb = bar + 8 * (MB_FULL + slot);
      mbar_expect_tx(mb, RING_BYTES);
      tma_load_2d(dst, &maps.qkv_ld, HD + h * 128 + j * 64, s * SEG, mb);
      tma_load_2d(dst + 4096, &maps.qkv_ld, 2 * HD + h * 128, s * SEG, mb);
      tma_load_2d(dst + 8192, &maps.qkv_ld, 2 * HD + h * 128 + 64, s * SEG, mb);
    }
  }
}
__device__ __forceinline__ void rec_copy(unsigned sb, const int c) {
  const int h = c >> 1, j = c & 1;
  const unsigned bar = sb + SM_BAR;
  const int lane = threadIdx.x & 31;
  for (int s = 0; s < NSEG; s++) {
    if (s < NSEG - 1) mbar_wait_sleep(bar + 8 * MB_KVR, s & 1); else mbar_wait(bar + 8 * MB_KVR, s & 1);
    uint4 k0 = lds128(sb + R_KS + (lane >> 3) * 144 + (lane & 7) * 16), k1 = lds128(sb + R_KS + (4 + (lane >> 3)) * 144 + (lane & 7) * 16);
    uint2 v[4];
#pragma unroll
    for (int i = 0; i < 4; i++) v[i] = lds64(sb + R_VM + (j * 4 + i) * 256 + lane * 8);
    __syncwarp();
    if (lane == 0) mbar_arrive(bar + 8 * MB_KVF);
    bf16* kd = g_km + ((size_t)(s * NH + h) * NMEM) * DH + j * 64;
    *reinterpret_cast<uint4*>(kd + (lane >> 3) * DH + (lane & 7) * 8) = k0;
    *reinterpret_cast<uint4*>(kd + (4 + (lane >> 3)) * DH + (lane & 7) * 8) = k1;
    unsigned* vd = reinterpret_cast<unsigned*>(g_vmt) + ((size_t)(s * NH + h) * DH + j * 64) * 4;
#pragma unroll
    for (int i = 0; i < 4; i++) { vd[(i * 16) * 4 + lane] = v[i].x; vd[(i * 16 + 8) * 4 + lane] = v[i].y; }
    __syncwarp();
    if (lane == 0) st_release(&g_flags.rec[c], s + 1);
  }
}

__device__ __forceinline__ void bulk_producer(const Maps& maps, unsigned sb, int* misc) {
  const unsigned bar = sb + SM_BAR;
  const int lane = threadIdx.x & 31;
  unsigned st = 0, ph = 0, seq = 0;
  while (true) {
    int idx = 0;
    if (lane == 0) idx = (int)atomicAdd(&g_flags.ctr, 1u);
    idx = __shfl_sync(~0u, idx, 0);
    if (idx >= N_ITEMS) {
      if (lane == 0) {
        mbar_wait(bar + 8 * (MB_EMPTY + st), ph ^ 1);
        misc[seq & 3] = -1;
        mbar_arrive(bar + 8 * (MB_FULL + st));
      }
      break;
    }
    if (lane == 0) ISTAMP(idx, 0);
    Item it = decode_item(idx);
    if (it.b < 0) continue;
    const CUtensorMap* mp; int c0, c1, dc0, dc1; unsigned doff;
    const unsigned* fl = nullptr; unsigned tgt = 1; int nbox = 5, rdy = 0;
    if (it.type == T_ATT) {
      mp = &maps.qkv_ld; nbox = 12; doff = lane * 4096;
      c0 = (lane >> 2) * HD + it.c * 256 + (lane & 1) * 64; c1 = it.b * 128 + ((lane >> 1) & 1) * 32; dc0 = dc1 = 0;
      if (lane < 3) fl = &g_flags.qkv[it.b * 48 + lane * 16 + it.c];
      tgt = 2;
      bool ok = true;
      if (lane >= 4 && lane < 8) ok = ld_acquire(&g_flags.rec[it.c * 4 + lane - 4]) >= (unsigned)(it.b * 4 + 4);
      rdy = __all_sync(~0u, ok) ? 65536 : 0;
    } else {
      int k0 = 0, nb0 = it.c * 256;
      if (it.type == T_QKV) { mp = lane == 0 ? &maps.xn : (it.c < 16 ? &maps.wq : (it.c < 32 ? &maps.wk : &maps.wv)); nb0 = (it.c & 15) * 256; }
      else if (it.type == T_M1) mp = lane == 0 ? &maps.y : &maps.w1;
      else if (it.type == T_M2) { mp = lane == 0 ? &maps.h1 : &maps.w2; fl = &g_flags.h1[it.b]; tgt = 7; }
      else {
        mp = lane == 0 ? &maps.o : &maps.wo;
        if (it.type == T_OUT) { k0 = it.ks * 1024; fl = &g_flags.o[it.b * 4 + it.ks]; tgt = 4; }
        else if (it.type == T_OUTL) { k0 = it.ks * 256; fl = &g_flags.o16[it.ks]; }
        else if (lane == 1) { fl = &g_flags.g[it.b]; tgt = 2; }
        else { fl = &g_flags.p[it.b]; tgt = it.type == T_RED ? (it.b >= 13 ? 16 : 8) : 64; }
      }
      if (lane > (it.type >= T_RED ? 1 : 0)) fl = nullptr;
      if (it.hf) { nbox = 3; nb0 += (it.hf - 1) * 128; }
      if (lane == 0) { c0 = k0; c1 = it.b * 128; dc0 = 64; dc1 = 0; doff = 0; }
      else { c0 = nb0 + (lane - 1) * 64; c1 = k0; dc0 = 0; dc1 = 64; doff = 8192 + lane * 8192; }
    }
    if (fl) wait_flag_ge(fl, tgt);
    __syncwarp();
    fence_proxy_async();
    if (lane == 0) ISTAMP(idx, 1);
    const int nkb = item_nkb(it.type);
    for (int kb = 0; kb < nkb; kb++) {
      const unsigned mb = bar + 8 * (MB_FULL + st);
      mbar_wait(bar + 8 * (MB_EMPTY + st), ph ^ 1);
      if (lane == 0) {
        if (kb == 0) misc[seq & 3] = idx | rdy;
        if (it.type >= T_RED) mbar_arrive(mb); else mbar_expect_tx(mb, it.hf ? 32768 : STAGE_BYTES);
      }
      if (it.type == T_ATT) { if (lane < 12) tma_load_2d(sb + st * STAGE_BYTES + doff, mp, c0 + (kb & 1) * 128, c1 + (kb >> 1) * 64, mb); }
      else if (lane < nbox && it.type < T_RED) tma_load_2d(sb + st * STAGE_BYTES + doff, mp, c0 + kb * dc0, c1 + kb * dc1, mb);
      __syncwarp();
      if (++st == NSTAGE) { st = 0; ph ^= 1; }
    }
    seq++;
  }
}
__device__ __forceinline__ void bulk_store(const Maps& maps, unsigned sb, volatile int* misc) {
  const unsigned bar = sb + SM_BAR;
  unsigned ph = 0;
  while (true) {
    mbar_wait(bar + 8 * MB_STGF, ph); ph ^= 1;
    int idx = misc[4];
    if (idx < 0) break;
    Item it = decode_item(idx);
    const CUtensorMap* mp = it.type == T_QKV ? &maps.qkv_st : (it.type == T_M1 ? &maps.h1 : (it.type == T_M2 ? &maps.g : &maps.o));
    unsigned* flag = it.type == T_QKV ? &g_flags.qkv[it.b * 48 + it.c] : (it.type == T_M1 ? &g_flags.h1[it.b] : (it.type == T_M2 ? &g_flags.g[it.b] : (it.b == 15 ? &g_flags.o16[it.c] : &g_flags.o[it.b * 4 + (it.c >> 2)])));
    for (int i = 0; i < (it.hf ? 2 : 4); i++) tma_store_2d(mp, sb + B_STG + i * 16384, it.c * 256 + (it.hf >> 1) * 128 + i * 64, it.b * 128);
    asm volatile("cp.async.bulk.commit_group;" ::: "memory");
    asm volatile("cp.async.bulk.wait_group.read 0;" ::: "memory");
    mbar_arrive(bar + 8 * MB_STGE);
    asm volatile("cp.async.bulk.wait_group 0;" ::: "memory");
    fence_proxy_async();
    red_release_add(flag, it.type == T_QKV && !it.hf ? 2 : 1);
    ISTAMP(idx, 3);
  }
}
__device__ __forceinline__ float rcpf(float x) { float y; asm("rcp.approx.ftz.f32 %0, %1;" : "=f"(y) : "f"(x)); return y; }
__device__ __forceinline__ float gelu_t(float x) {
  float e = ex2f(x * fmaf(x * x, -2.0f * LOG2E * 0.7978845608028654f * 0.044715f, -2.0f * LOG2E * 0.7978845608028654f));
  return x * rcpf(1.0f + e);
}
__device__ __forceinline__ float silu_f(float x) { return x * rcpf(1.0f + ex2f(-LOG2E * x)); }
__device__ __forceinline__ unsigned badd2(unsigned a, unsigned b) { unsigned r; asm("add.rn.bf16x2 %0, %1, %2;" : "=r"(r) : "r"(a), "r"(b)); return r; }

__device__ __forceinline__ void final_out(bf16* __restrict__ out, const bf16* __restrict__ x, size_t o, float4 s) {
  uint2 gv = __ldcg(reinterpret_cast<const uint2*>(g_g + o)), xv = __ldg(reinterpret_cast<const uint2*>(x + o));
  uint2 r;
  r.x = pack_bf16(bf_lo(xv.x) + bf16r(bf16r(s.x) * bf_lo(gv.x)), bf_hi(xv.x) + bf16r(bf16r(s.y) * bf_hi(gv.x)));
  r.y = pack_bf16(bf_lo(xv.y) + bf16r(bf16r(s.z) * bf_lo(gv.y)), bf_hi(xv.y) + bf16r(bf16r(s.w) * bf_hi(gv.y)));
  *reinterpret_cast<uint2*>(out + o) = r;
}
__device__ __forceinline__ void bulk_att_load(unsigned* km, unsigned* vm, int b, int hp, int kb, int w, int lane) {
  const int g = lane >> 2, tq = lane & 3, seg = w >> 2, eh = w & 1;
  const int head = hp * 2 + (kb & 1), sg = b * 4 + (kb >> 1) * 2 + seg;
  const unsigned* kmp = reinterpret_cast<const unsigned*>(g_km + ((size_t)(sg * NH + head) * NMEM + g) * DH) + tq;
  const unsigned* vmp = reinterpret_cast<const unsigned*>(g_vmt) + ((size_t)(sg * NH + head) * DH + eh * 64) * 4 + lane;
#pragma unroll
  for (int i = 0; i < 16; i++) asm volatile("ld.global.cg.u32 %0, [%1];" : "=r"(km[i]) : "l"(kmp + i * 4) : "memory");
#pragma unroll
  for (int i = 0; i < 8; i++) asm volatile("ld.global.cg.u32 %0, [%1];" : "=r"(vm[i]) : "l"(vmp + i * 32) : "memory");
}
__device__ __forceinline__ void bulk_att_stage(unsigned sa, unsigned stg, const unsigned* km, const unsigned* vm, int kb, int w, int lane) {
  const int g = lane >> 2, tq = lane & 3, m = lane >> 3, r8 = lane & 7;
  const int seg = w >> 2, mt = (w >> 1) & 1, eh = w & 1;
  float s[5][4];
#pragma unroll
  for (int i = 0; i < 5; i++) { s[i][0] = s[i][1] = s[i][2] = s[i][3] = 0; }
  const unsigned qb = sa + (0 * 2 + seg) * 8192, kbs = sa + (1 * 2 + seg) * 8192, vb = sa + (2 * 2 + seg) * 8192 + eh * 4096;
  unsigned qa[8][4];
#pragma unroll
  for (int ks = 0; ks < 8; ks++) {
    int row = mt * 16 + (m & 1) * 8 + r8;
    ldsm_x4(qa[ks], qb + (ks >> 2) * 4096 + row * 128 + ((((ks & 3) * 2 + (m >> 1)) ^ r8) << 4));
    unsigned kf[4];
    int krow = (m >> 1) * 8 + r8;
    unsigned ka = kbs + (ks >> 2) * 4096 + krow * 128 + ((((ks & 3) * 2 + (m & 1)) ^ r8) << 4);
    ldsm_x4(kf, ka);
    mma16816(s[0], qa[ks], kf[0], kf[1]); mma16816(s[1], qa[ks], kf[2], kf[3]);
    if (mt) { ldsm_x4(kf, ka + 2048); mma16816(s[2], qa[ks], kf[0], kf[1]); mma16816(s[3], qa[ks], kf[2], kf[3]); }
  }
#pragma unroll
  for (int ks = 0; ks < 8; ks++) mma16816(s[4], qa[ks], km[2 * ks], km[2 * ks + 1]);
  float mx0 = -INFINITY, mx1 = -INFINITY;
  const int t0 = mt * 16 + g, t1 = t0 + 8;
#pragma unroll
  for (int i = 0; i < 5; i++) {
#pragma unroll
    for (int e = 0; e < 4; e++) {
      float v = s[i][e];
      if (i < 4) { int kj = i * 8 + 2 * tq + (e & 1); if (kj > (e < 2 ? t0 : t1)) v = -INFINITY; }
      s[i][e] = v;
      if (e < 2) mx0 = fmaxf(mx0, v); else mx1 = fmaxf(mx1, v);
    }
  }
  mx0 = fmaxf(mx0, __shfl_xor_sync(~0u, mx0, 1)); mx0 = fmaxf(mx0, __shfl_xor_sync(~0u, mx0, 2));
  mx1 = fmaxf(mx1, __shfl_xor_sync(~0u, mx1, 1)); mx1 = fmaxf(mx1, __shfl_xor_sync(~0u, mx1, 2));
  float sm0 = 0, sm1 = 0;
#pragma unroll
  for (int i = 0; i < 5; i++) {
    s[i][0] = ex2f((s[i][0] - mx0) * (SCALE_QK * LOG2E)); s[i][1] = ex2f((s[i][1] - mx0) * (SCALE_QK * LOG2E));
    s[i][2] = ex2f((s[i][2] - mx1) * (SCALE_QK * LOG2E)); s[i][3] = ex2f((s[i][3] - mx1) * (SCALE_QK * LOG2E));
    sm0 += s[i][0] + s[i][1]; sm1 += s[i][2] + s[i][3];
  }
  sm0 += __shfl_xor_sync(~0u, sm0, 1); sm0 += __shfl_xor_sync(~0u, sm0, 2);
  sm1 += __shfl_xor_sync(~0u, sm1, 1); sm1 += __shfl_xor_sync(~0u, sm1, 2);
  const float i0 = __fdividef(1.0f, sm0), i1 = __fdividef(1.0f, sm1);
  unsigned pa[2][4], pm0, pm1;
#pragma unroll
  for (int kk = 0; kk < 2; kk++) {
    pa[kk][0] = pack_bf16(s[2 * kk][0] * i0, s[2 * kk][1] * i0); pa[kk][1] = pack_bf16(s[2 * kk][2] * i1, s[2 * kk][3] * i1);
    pa[kk][2] = pack_bf16(s[2 * kk + 1][0] * i0, s[2 * kk + 1][1] * i0); pa[kk][3] = pack_bf16(s[2 * kk + 1][2] * i1, s[2 * kk + 1][3] * i1);
  }
  pm0 = pack_bf16(s[4][0] * i0, s[4][1] * i0); pm1 = pack_bf16(s[4][2] * i1, s[4][3] * i1);
  const int orow = (kb >> 1) * 64 + seg * 32 + mt * 16 + (m & 1) * 8 + r8;
  const unsigned ob = stg + ((kb & 1) * 2 + eh) * 16384 + orow * 128;
#pragma unroll
  for (int cp = 0; cp < 4; cp++) {
    float o0[4] = {0, 0, 0, 0}, o1[4] = {0, 0, 0, 0};
    mma1688(o0, pm0, pm1, vm[2 * cp]); mma1688(o1, pm0, pm1, vm[2 * cp + 1]);
    unsigned vf[4];
    int row = (m & 1) * 8 + r8;
    unsigned va = vb + row * 128 + (((cp * 2 + (m >> 1)) ^ r8) << 4);
    ldsm_x4_t(vf, va);
    mma16816(o0, pa[0], vf[0], vf[1]); mma16816(o1, pa[0], vf[2], vf[3]);
    if (mt) { ldsm_x4_t(vf, va + 2048); mma16816(o0, pa[1], vf[0], vf[1]); mma16816(o1, pa[1], vf[2], vf[3]); }
    stsm_x4(ob + (((cp * 2 + (m >> 1)) ^ r8) << 4), pack_bf16(o0[0], o0[1]), pack_bf16(o0[2], o0[3]), pack_bf16(o1[0], o1[1]), pack_bf16(o1[2], o1[3]));
  }
}

__device__ __forceinline__ void bulk_worker(unsigned sb, volatile int* misc, const bf16* __restrict__ x, const bf16* __restrict__ b1, const bf16* __restrict__ b2, bf16* __restrict__ out) {
  const int t = threadIdx.x, lane = t & 31, w = t >> 5, wg = w >> 2, g = lane >> 2, tq = lane & 3, m = lane >> 3, r8 = lane & 7;
  const unsigned bar = sb + SM_BAR;
  unsigned st = 0, ph = 0, seq = 0, sph = 0;
  float d[128];
  while (true) {
    mbar_wait(bar + 8 * (MB_FULL + st), ph);
    const int idr = misc[seq & 3]; seq++;
    const int idx = idr & 65535;
    if (idr < 0 || idx >= N_ITEMS) break;
    if (t == 0) ISTAMP(idx, 2);
    const Item it = decode_item(idx);
    const int nkb = item_nkb(it.type);
    if (it.type == T_ATT) {
      unsigned km[16], vm[8], kn[16], vn[8];
      const bool pref = idr >= 65536;
      if (pref) bulk_att_load(kn, vn, it.b, it.c, 0, w, lane);
      mbar_wait(bar + 8 * MB_STGE, sph ^ 1);
#pragma unroll 1
      for (int kb = 0; kb < 4; kb++) {
        if (!pref && !(kb & 1)) {
          if (lane < 4) wait_step_ge(&g_flags.rec[it.c * 4 + lane], it.b * 4 + (kb >> 1) * 2 + wg + 1);
          __syncwarp();
          bulk_att_load(kn, vn, it.b, it.c, kb, w, lane);
        }
        if (kb) mbar_wait(bar + 8 * (MB_FULL + st), ph);
#pragma unroll
        for (int i = 0; i < 16; i++) km[i] = kn[i];
#pragma unroll
        for (int i = 0; i < 8; i++) vm[i] = vn[i];
        if (pref ? kb != 3 : !(kb & 1)) bulk_att_load(kn, vn, it.b, it.c, kb + 1, w, lane);
        bulk_att_stage(sb + st * STAGE_BYTES, sb + B_STG, km, vm, kb, w, lane);
        __syncwarp();
        if (lane == 0) mbar_arrive(bar + 8 * (MB_EMPTY + st));
        if (++st == NSTAGE) { st = 0; ph ^= 1; }
      }
      if (t == 0) misc[4] = idx;
      fence_proxy_async_smem();
      mbar_arrive(bar + 8 * MB_STGF); sph ^= 1;
      continue;
    }
    if (it.type >= T_RED) {
      __syncwarp();
      if (lane == 0) mbar_arrive(bar + 8 * (MB_EMPTY + st));
      if (++st == NSTAGE) { st = 0; ph ^= 1; }
      if (it.type == T_RED) {
#pragma unroll 2
        for (int i = 0; i < (it.ks ? 2 : 8); i++) {
          size_t o = ((size_t)it.b * 128 + it.c * (it.ks ? 4 : 16) + i * 2 + (t >> 7)) * DM + (t & 127) * 4;
          float4 a = __ldcg(reinterpret_cast<const float4*>(g_opart + o)), b = __ldcg(reinterpret_cast<const float4*>(g_opart + o + (size_t)S_TOK * DM));
          float4 c = __ldcg(reinterpret_cast<const float4*>(g_opart + o + (size_t)2 * S_TOK * DM)), e = __ldcg(reinterpret_cast<const float4*>(g_opart + o + (size_t)3 * S_TOK * DM));
          final_out(out, x, o, make_float4((a.x + b.x) + (c.x + e.x), (a.y + b.y) + (c.y + e.y), (a.z + b.z) + (c.z + e.z), (a.w + b.w) + (c.w + e.w)));
        }
      } else {
        size_t ol = ((size_t)it.c * 2 + (t >> 7)) * DM + (t & 127) * 4;
        float4 v[16];
#pragma unroll
        for (int i = 0; i < 16; i++) v[i] = __ldcg(reinterpret_cast<const float4*>(g_opl + ol + (size_t)i * 128 * DM));
#pragma unroll
        for (int st2 = 1; st2 < 16; st2 <<= 1)
#pragma unroll
          for (int i = 0; i < 16; i += 2 * st2) { v[i].x += v[i + st2].x; v[i].y += v[i + st2].y; v[i].z += v[i + st2].z; v[i].w += v[i + st2].w; }
        final_out(out, x, ol + (size_t)15 * 128 * DM, v[0]);
      }
      if (t == 0) ISTAMP(idx, 3);
      continue;
    }
    unsigned pst = 0, bv[32];
#pragma unroll
    for (int i = 0; i < 128; i++) d[i] = 0.0f;
    if (it.type == T_M1 || it.type == T_M2) {
      const unsigned* bp = reinterpret_cast<const unsigned*>((it.type == T_M1 ? b1 : b2) + it.c * 256) + tq;
#pragma unroll
      for (int i = 0; i < 32; i++) asm volatile("ld.global.nc.u32 %0, [%1];" : "=r"(bv[i]) : "l"(bp + i * 4));
    } else {
#pragma unroll
      for (int i = 0; i < 32; i++) bv[i] = 0;
    }
#define KLOOP(WG) \
    for (int kb = 0; kb < nkb; kb++) { \
      if (kb) mbar_wait(bar + 8 * (MB_FULL + st), ph); \
      unsigned sa = sb + st * STAGE_BYTES; \
      uint64_t ad = mkdesc(sa + wg * 8192, 16, 1024), bd = mkdesc(sa + 16384, 8192, 1024); \
      asm volatile("wgmma.fence.sync.aligned;" ::: "memory"); \
      _Pragma("unroll") for (int k = 0; k < 4; k++) WG(d, ad + k * 2, bd + k * 128, (kb | k) != 0); \
      asm volatile("wgmma.commit_group.sync.aligned;" ::: "memory"); \
      if (kb) { \
        asm volatile("wgmma.wait_group.sync.aligned 1;" ::: "memory"); \
        if (lane == 0) mbar_arrive(bar + 8 * (MB_EMPTY + pst)); \
      } \
      pst = st; \
      if (++st == NSTAGE) { st = 0; ph ^= 1; } \
    } \
    asm volatile("wgmma.wait_group.sync.aligned 0;" ::: "memory");
    if (it.hf) { KLOOP(wgmma_n128) } else { KLOOP(wgmma_n256) }
    if (lane == 0) mbar_arrive(bar + 8 * (MB_EMPTY + pst));
    if (it.type >= T_OUT) {
      const int col = it.c * 256 + (it.hf >> 1) * 128 + 2 * tq;
      float* pp = it.type == T_OUT ? g_opart + ((size_t)it.ks * S_TOK + it.b * 128 + w * 16 + g) * DM + col : g_opl + ((size_t)it.ks * 128 + w * 16 + g) * DM + col;
#pragma unroll
      for (int i = 0; i < 32; i++) {
        if (i == 16 && it.hf) break;
        __stcg(reinterpret_cast<float2*>(pp + i * 8), make_float2(d[4 * i], d[4 * i + 1]));
        __stcg(reinterpret_cast<float2*>(pp + 8 * DM + i * 8), make_float2(d[4 * i + 2], d[4 * i + 3]));
      }
      bar_sync(1, 256);
      if (t == 0) { red_release_add(&g_flags.p[it.b], 1); ISTAMP(idx, 3); }
      continue;
    }
#define ACT(F) _Pragma("unroll") for (int i = 0; i < 32; i++) { \
        unsigned u0 = badd2(pack_bf16(d[4 * i], d[4 * i + 1]), bv[i]), u1 = badd2(pack_bf16(d[4 * i + 2], d[4 * i + 3]), bv[i]); \
        d[4 * i] = F(bf_lo(u0)); d[4 * i + 1] = F(bf_hi(u0)); d[4 * i + 2] = F(bf_lo(u1)); d[4 * i + 3] = F(bf_hi(u1)); }
    if (it.type == T_M1) { ACT(gelu_t) } else if (it.type == T_M2) { ACT(silu_f) }
    mbar_wait(bar + 8 * MB_STGE, sph ^ 1);
    {
      const unsigned ob = sb + B_STG + (w * 16 + (m & 1) * 8 + r8) * 128;
#pragma unroll
      for (int i = 0; i < 16; i++)
        if (i < 8 || !it.hf) stsm_x4(ob + (i >> 2) * 16384 + ((((i & 3) * 2 + (m >> 1)) ^ r8) << 4), pack_bf16(d[8 * i], d[8 * i + 1]), pack_bf16(d[8 * i + 2], d[8 * i + 3]),
                pack_bf16(d[8 * i + 4], d[8 * i + 5]), pack_bf16(d[8 * i + 6], d[8 * i + 7]));
    }
    if (t == 0) misc[4] = idx;
    fence_proxy_async_smem();
    mbar_arrive(bar + 8 * MB_STGF); sph ^= 1;
  }
  mbar_wait(bar + 8 * MB_STGE, sph ^ 1);
  if (t == 0) misc[4] = -1;
  mbar_arrive(bar + 8 * MB_STGF);
}

__global__ void __launch_bounds__(384, 1)
k_main(const __grid_constant__ Maps maps, const bf16* __restrict__ x, const bf16* __restrict__ mem0, const bf16* __restrict__ b1, const bf16* __restrict__ b2, bf16* __restrict__ out, unsigned recmask) {
  extern __shared__ unsigned char smem_raw[];
  const unsigned sraw = smem_u32(smem_raw);
  const unsigned sb = (sraw + 1023u) & ~1023u;
  int* misc = reinterpret_cast<int*>(smem_raw + (sb - sraw) + SM_MISC);
  const int w = threadIdx.x >> 5;
  const bool helper = recmask == 0;
  const unsigned kc = blockIdx.x / CLS;
  const bool rec = kc < 32 && ((recmask >> kc) & 1);
  const int c = __popc(recmask & ((1u << (kc & 31)) - 1)) * CLS + (blockIdx.x & (CLS - 1));
  if (threadIdx.x == 0) {
    const unsigned bar = sb + SM_BAR;
    for (int i = 0; i < 8; i++) { mbar_init(bar + 8 * (MB_FULL + i), 1); mbar_init(bar + 8 * (MB_EMPTY + i), rec ? 1 : 8); }
    mbar_init(bar + 8 * MB_STGF, 256); mbar_init(bar + 8 * MB_STGE, 1);
    for (int i = MB_W0; i <= MB_AG; i++) mbar_init(bar + 8 * i, 1);
    if (rec) { mbar_expect_tx(bar + 8 * MB_S, 2560); mbar_expect_tx(bar + 8 * MB_V, 2048); mbar_expect_tx(bar + 8 * MB_RS, 8192); mbar_expect_tx(bar + 8 * MB_AG, 8192); }
    asm volatile("fence.mbarrier_init.release.cluster;" ::: "memory");
  }
  __syncthreads();
  asm volatile("barrier.cluster.arrive.release.aligned;\nbarrier.cluster.wait.acquire.aligned;" ::: "memory");
  if (rec && threadIdx.x == 256) {
    const unsigned bar = sb + SM_BAR; const int col = c * 64;
    mbar_expect_tx(bar + 8 * MB_W0, 131072);
    for (int kb = 0; kb < 8; kb++) tma_load_2d(sb + R_WO + kb * 8192, &maps.wq, col, kb * 64, bar + 8 * MB_W0);
    for (int kb = 0; kb < 8; kb++) tma_load_2d(sb + R_T1 + kb * 8192, &maps.wk, col, kb * 64, bar + 8 * MB_W0);
    mbar_expect_tx(bar + 8 * MB_W1, 65536);
    for (int kb = 0; kb < 8; kb++) tma_load_2d(sb + R_T2 + kb * 8192, &maps.wv, col, kb * 64, bar + 8 * MB_W1);
  }
  if (!helper) {
    asm volatile("griddepcontrol.wait;" ::: "memory");
    asm volatile("griddepcontrol.launch_dependents;");
  }
  if (DBGMODE && !rec) { if (helper) asm volatile("griddepcontrol.wait;" ::: "memory"); return; }
  if (w >= 8) {
    asm volatile("setmaxnreg.dec.sync.aligned.u32 24;");
    if (rec) { if (w == 8) rec_ring(maps, sb, c); else if (w == 9) rec_copy(sb, c); }
    else if (w == 8) bulk_producer(maps, sb, misc);
    else if ((threadIdx.x & 31) == 0) { if (w == 9) bulk_store(maps, sb, misc);
      else if (w == 10 && helper) asm volatile("griddepcontrol.wait;" ::: "memory"); }
  } else {
    if (rec) { asm volatile("setmaxnreg.inc.sync.aligned.u32 240;"); rec_worker(maps, sb, mem0, c); }
    else { asm volatile("setmaxnreg.inc.sync.aligned.u32 240;"); bulk_worker(sb, misc, x, b1, b2, out); }
  }
}

typedef CUresult (*EncFn)(CUtensorMap*, CUtensorMapDataType, cuuint32_t, void*, const cuuint64_t*, const cuuint64_t*, const cuuint32_t*, const cuuint32_t*,
                          CUtensorMapInterleave, CUtensorMapSwizzle, CUtensorMapL2promotion, CUtensorMapFloatOOBfill);
static void mk_map(EncFn enc, CUtensorMap* m, const void* ptr, uint64_t rows, uint64_t cols, uint32_t box_rows) {
  cuuint64_t dims[2] = {cols, rows}; cuuint64_t strides[1] = {cols * 2};
  cuuint32_t box[2] = {64, box_rows}, es[2] = {1, 1};
  enc(m, CU_TENSOR_MAP_DATA_TYPE_BFLOAT16, 2, const_cast<void*>(ptr), dims, strides, box, es, CU_TENSOR_MAP_INTERLEAVE_NONE, CU_TENSOR_MAP_SWIZZLE_128B,
      CU_TENSOR_MAP_L2_PROMOTION_L2_256B, CU_TENSOR_MAP_FLOAT_OOB_FILL_NONE);
}
extern "C" void kernel_launch(void* const* d_in, const int* in_sizes, int n_in, void* d_out, int out_size) {
  static EncFn enc = nullptr;
  static int ncl = 0, nhelp = 0;
  static unsigned recmask = 0xFFu;
  static void *p_xn, *p_y, *p_h1, *p_o, *p_qkv, *p_g;
  if (!enc) {
    void* fn = nullptr; cudaDriverEntryPointQueryResult qr;
    cudaGetDriverEntryPoint("cuTensorMapEncodeTiled", &fn, cudaEnableDefault, &qr);
    enc = (EncFn)fn;
    cudaGetSymbolAddress(&p_xn, g_xn); cudaGetSymbolAddress(&p_y, g_y); cudaGetSymbolAddress(&p_h1, g_h1);
    cudaGetSymbolAddress(&p_o, g_o); cudaGetSymbolAddress(&p_qkv, g_qkv); cudaGetSymbolAddress(&p_g, g_g);
    cudaFuncSetAttribute(k_main, cudaFuncAttributeMaxDynamicSharedMemorySize, SMEM_TOTAL);
    cudaLaunchConfig_t cfg = {}; cfg.gridDim = dim3(128); cfg.blockDim = dim3(384); cfg.dynamicSmemBytes = SMEM_TOTAL;
    cudaLaunchAttribute at[1]; at[0].id = cudaLaunchAttributeClusterDimension; at[0].val.clusterDim.x = CLS; at[0].val.clusterDim.y = 1; at[0].val.clusterDim.z = 1;
    cfg.attrs = at; cfg.numAttrs = 1;
    if (cudaOccupancyMaxActiveClusters(&ncl, k_main, &cfg) != cudaSuccess) { cudaGetLastError(); ncl = 14; }
    ncl = ncl > 16 ? 16 : (ncl < 9 ? 9 : ncl);
    int nsm = 0, dev = 0; cudaGetDevice(&dev); cudaDeviceGetAttribute(&nsm, cudaDevAttrMultiProcessorCount, dev);
    nhelp = nsm - ncl * CLS;
  }
  Maps maps;
  mk_map(enc, &maps.xn, p_xn, S_TOK, DM, 128); mk_map(enc, &maps.y, p_y, S_TOK, DM, 128); mk_map(enc, &maps.h1, p_h1, S_TOK, FF, 128);
  mk_map(enc, &maps.o, p_o, S_TOK, HD, 128); mk_map(enc, &maps.qkv_st, p_qkv, S_TOK, 3 * HD, 128); mk_map(enc, &maps.qkv_ld, p_qkv, S_TOK, 3 * HD, 32);
  mk_map(enc, &maps.g, p_g, S_TOK, DM, 128);
  mk_map(enc, &maps.wq, d_in[2], DM, HD, 64); mk_map(enc, &maps.wk, d_in[3], DM, HD, 64); mk_map(enc, &maps.wv, d_in[4], DM, HD, 64);
  mk_map(enc, &maps.wo, d_in[5], HD, DM, 64); mk_map(enc, &maps.w1, d_in[8], DM, FF, 64); mk_map(enc, &maps.w2, d_in[10], FF, DM, 64);
  cudaStream_t st = cudaStreamPerThread;
  k_pre<<<256, 256, 0, st>>>((const bf16*)d_in[0], (const char*)d_in[2], (const char*)d_in[3], (const char*)d_in[4], (const char*)d_in[5]);
  cudaLaunchConfig_t cfg = {}; cfg.gridDim = dim3(ncl * CLS); cfg.blockDim = dim3(384); cfg.dynamicSmemBytes = SMEM_TOTAL; cfg.stream = st;
  cudaLaunchAttribute at[2]; at[1].id = cudaLaunchAttributeClusterDimension; at[1].val.clusterDim.x = CLS; at[1].val.clusterDim.y = 1; at[1].val.clusterDim.z = 1;
  at[0].id = cudaLaunchAttributeProgrammaticStreamSerialization; at[0].val.programmaticStreamSerializationAllowed = 1;
#define PDL1 0
  cfg.attrs = at + (PDL1 ? 0 : 1); cfg.numAttrs = PDL1 ? 2 : 1;
  cudaLaunchKernelEx(&cfg, k_main, maps, (const bf16*)d_in[0], (const bf16*)d_in[1], (const bf16*)d_in[9], (const bf16*)d_in[11], (bf16*)d_out, recmask);
  if (nhelp > 0) {
    cfg.gridDim = dim3(nhelp);
    cfg.attrs = at; cfg.numAttrs = 1;
    cudaLaunchKernelEx(&cfg, k_main, maps, (const bf16*)d_in[0], (const bf16*)d_in[1], (const bf16*)d_in[9], (const bf16*)d_in[11], (bf16*)d_out, 0u);
  }
}
```

```cpp
#include <cuda_runtime.h>
#include <cuda_bf16.h>
#include <cuda.h>
#include <stdint.h>

typedef __nv_bfloat16 bf16;

#define S_TOK 2048
#define DM 512
#define NH 32
#define DH 128
#define HD 4096
#define NMEM 8
#define SEG 32
#define NSEG 64
#define FF 1792
#define NBLK 16
#define NREC 64
#define REPL 0
#define CLS 8

__device__ __align__(1024) bf16 g_xn[S_TOK * DM];
__device__ __align__(1024) bf16 g_y[S_TOK * DM];
__device__ __align__(1024) bf16 g_qkv[(size_t)S_TOK * 3 * HD];
__device__ __align__(1024) bf16 g_h1[S_TOK * FF];
__device__ __align__(1024) bf16 g_g[S_TOK * DM];
__device__ __align__(1024) bf16 g_o[(size_t)S_TOK * HD];
__device__ __align__(1024) bf16 g_km[NSEG * NH * NMEM * DH];
__device__ __align__(1024) bf16 g_vmt[NSEG * NH * DH * NMEM];
__device__ __align__(1024) float g_opart[(size_t)4 * S_TOK * DM];
__device__ __align__(1024) float g_opl[(size_t)16 * 128 * DM];
__device__ __align__(1024) unsigned g_part[2 * 8 * 8 * 512];
struct Flags {
  unsigned qkv[NBLK * 48];
  unsigned h1[NBLK];
  unsigned g[NBLK];
  unsigned o[NBLK * 4];
  unsigned p[NBLK];
  unsigned o16[16];
  unsigned ctr;
  unsigned rec[NREC];
  unsigned abort_;
};
__device__ __align__(1024) Flags g_flags;

#define RSTAMP(k)
#define DBGMODE 0
#define ISTAMP(i, k)
__device__ __forceinline__ unsigned smem_u32(const void* p) { return (unsigned)__cvta_generic_to_shared(p); }
__device__ __forceinline__ float bf16r(float x) { unsigned u; asm("cvt.rn.bf16x2.f32 %0, %1, %2;" : "=r"(u) : "f"(x), "f"(0.0f)); return __uint_as_float(u); }
__device__ __forceinline__ unsigned pack_bf16(float lo, float hi) {
  __nv_bfloat162 v = __floats2bfloat162_rn(lo, hi);
  return *reinterpret_cast<unsigned*>(&v);
}
__device__ __forceinline__ float bf_lo(unsigned u) { return __uint_as_float(u << 16); }
__device__ __forceinline__ float bf_hi(unsigned u) { return __uint_as_float(u & 0xffff0000u); }

#define SPIN_LIMIT (1u << 20)
#define TRAP_IF(x) if ((x) > SPIN_LIMIT) { asm volatile("st.global.u32 [%0], %1;" ::"l"(0ull), "r"(0u) : "memory"); break; }
__device__ __forceinline__ unsigned ld_acquire(const unsigned* p) {
  unsigned v; asm volatile("ld.acquire.gpu.global.u32 %0, [%1];" : "=r"(v) : "l"(p) : "memory"); return v;
}
__device__ __forceinline__ unsigned ld_relaxed(const unsigned* p) {
  unsigned v; asm volatile("ld.relaxed.gpu.global.u32 %0, [%1];" : "=r"(v) : "l"(p) : "memory"); return v;
}
__device__ __forceinline__ void red_release_add(unsigned* p, unsigned v) {
  asm volatile("red.release.gpu.global.add.u32 [%0], %1;" ::"l"(p), "r"(v) : "memory");
}
__device__ __forceinline__ void st_release(unsigned* p, unsigned v) {
  asm volatile("st.release.gpu.global.u32 [%0], %1;" ::"l"(p), "r"(v) : "memory");
}
__device__ __forceinline__ void wait_flag_ge(const unsigned* p, unsigned target) {
  unsigned it = 0;
  while (ld_acquire(p) < target) {
    __nanosleep(64);
    TRAP_IF(++it);
  }
}
__device__ __forceinline__ void wait_step_ge(const unsigned* p, unsigned target) {
  unsigned it = 0, v;
  while ((v = ld_acquire(p)) < target) {
    __nanosleep(target - v >= 2 ? 1500 : 64);
    TRAP_IF(++it);
  }
}
__device__ __forceinline__ uint4 ldv4_relaxed(const void* p) {
  uint4 a; asm volatile("ld.relaxed.gpu.global.v4.u32 {%0,%1,%2,%3}, [%4];" : "=r"(a.x), "=r"(a.y), "=r"(a.z), "=r"(a.w) : "l"(p) : "memory"); return a;
}
__device__ __forceinline__ uint2 ldv2_relaxed(const void* p) {
  uint2 a; asm volatile("ld.relaxed.gpu.global.v2.u32 {%0,%1}, [%2];" : "=r"(a.x), "=r"(a.y) : "l"(p) : "memory"); return a;
}
__device__ __forceinline__ void mbar_init(unsigned mb, unsigned cnt) { asm volatile("mbarrier.init.shared::cta.b64 [%0], %1;" ::"r"(mb), "r"(cnt) : "memory"); }
__device__ __forceinline__ void mbar_expect_tx(unsigned mb, unsigned bytes) { asm volatile("mbarrier.arrive.expect_tx.shared::cta.b64 _, [%0], %1;" ::"r"(mb), "r"(bytes) : "memory"); }
__device__ __forceinline__ void mbar_arrive(unsigned mb) { asm volatile("mbarrier.arrive.shared::cta.b64 _, [%0];" ::"r"(mb) : "memory"); }
__device__ __forceinline__ void mbar_wait(unsigned mb, unsigned parity) {
  unsigned ok, it = 0;
  while (true) {
    asm volatile("{.reg .pred p; mbarrier.try_wait.parity.shared::cta.b64 p, [%1], %2; selp.u32 %0,1,0,p;}" : "=r"(ok) : "r"(mb), "r"(parity) : "memory");
    if (ok) break;
    TRAP_IF(++it);
  }
}
__device__ __forceinline__ void mbar_wait_sleep(unsigned mb, unsigned parity) {
  unsigned ok, it = 0;
  while (true) {
    asm volatile("{.reg .pred p; mbarrier.test_wait.parity.shared::cta.b64 p, [%1], %2; selp.u32 %0,1,0,p;}" : "=r"(ok) : "r"(mb), "r"(parity) : "memory");
    if (ok) break;
    __nanosleep(200);
    TRAP_IF(++it);
  }
}
__device__ __forceinline__ float ex2f(float x) { float y; asm("ex2.approx.ftz.f32 %0, %1;" : "=f"(y) : "f"(x)); return y; }
__device__ __forceinline__ int opaque_tid() { int t = threadIdx.x; t = __shfl_sync(~0u, t, t & 31); return t; }
#define LOG2E 1.4426950408889634f
__device__ __forceinline__ void mbar_wait_cluster(unsigned mb, unsigned parity) {
  unsigned ok, it = 0;
  while (true) {
    asm volatile("{.reg .pred p; mbarrier.try_wait.parity.acquire.cluster.shared::cta.b64 p, [%1], %2; selp.u32 %0,1,0,p;}" : "=r"(ok) : "r"(mb), "r"(parity) : "memory");
    if (ok) break;
    TRAP_IF(++it);
  }
}
__device__ __forceinline__ void bar_sync(int id, int n) { asm volatile("bar.sync %0, %1;" ::"r"(id), "r"(n) : "memory"); }
__device__ __forceinline__ void bar_arrive(int id, int n) { asm volatile("bar.arrive %0, %1;" ::"r"(id), "r"(n) : "memory"); }
__device__ __forceinline__ void tma_load_2d(unsigned dst, const CUtensorMap* map, int c0, int c1, unsigned mb) {
  asm volatile("cp.async.bulk.tensor.2d.shared::cluster.global.mbarrier::complete_tx::bytes [%0], [%1, {%3, %4}], [%2];"
               ::"r"(dst), "l"((uint64_t)map), "r"(mb), "r"(c0), "r"(c1) : "memory");
}
__device__ __forceinline__ void tma_store_2d(const CUtensorMap* map, unsigned src, int c0, int c1) {
  asm volatile("cp.async.bulk.tensor.2d.global.shared::cta.bulk_group [%0, {%2, %3}], [%1];"
               ::"l"((uint64_t)map), "r"(src), "r"(c0), "r"(c1) : "memory");
}
__device__ __forceinline__ void fence_proxy_async() { asm volatile("fence.proxy.async;" ::: "memory"); }
__device__ __forceinline__ void fence_proxy_async_smem() { asm volatile("fence.proxy.async.shared::cta;" ::: "memory"); }
__device__ __forceinline__ void ldsm_x4(unsigned* r, unsigned addr) {
  asm volatile("ldmatrix.sync.aligned.m8n8.x4.shared.b16 {%0,%1,%2,%3}, [%4];" : "=r"(r[0]), "=r"(r[1]), "=r"(r[2]), "=r"(r[3]) : "r"(addr) : "memory");
}
__device__ __forceinline__ void ldsm_x4_t(unsigned* r, unsigned addr) {
  asm volatile("ldmatrix.sync.aligned.m8n8.x4.trans.shared.b16 {%0,%1,%2,%3}, [%4];" : "=r"(r[0]), "=r"(r[1]), "=r"(r[2]), "=r"(r[3]) : "r"(addr) : "memory");
}
__device__ __forceinline__ void stsm_x2_t(unsigned addr, unsigned r0, unsigned r1) {
  asm volatile("stmatrix.sync.aligned.m8n8.x2.trans.shared.b16 [%0], {%1,%2};" ::"r"(addr), "r"(r0), "r"(r1) : "memory");
}
__device__ __forceinline__ void stsm_x4(unsigned addr, unsigned r0, unsigned r1, unsigned r2, unsigned r3) {
  asm volatile("stmatrix.sync.aligned.m8n8.x4.shared.b16 [%0], {%1,%2,%3,%4};" ::"r"(addr), "r"(r0), "r"(r1), "r"(r2), "r"(r3) : "memory");
}
__device__ __forceinline__ void mma16816(float* d, const unsigned* a, unsigned b0, unsigned b1) {
  asm volatile("mma.sync.aligned.m16n8k16.row.col.f32.bf16.bf16.f32 {%0,%1,%2,%3}, {%4,%5,%6,%7}, {%8,%9}, {%0,%1,%2,%3};"
               : "+f"(d[0]), "+f"(d[1]), "+f"(d[2]), "+f"(d[3]) : "r"(a[0]), "r"(a[1]), "r"(a[2]), "r"(a[3]), "r"(b0), "r"(b1));
}
__device__ __forceinline__ void mma1688(float* d, unsigned a0, unsigned a1, unsigned b0) {
  asm volatile("mma.sync.aligned.m16n8k8.row.col.f32.bf16.bf16.f32 {%0,%1,%2,%3}, {%4,%5}, {%6}, {%0,%1,%2,%3};"
               : "+f"(d[0]), "+f"(d[1]), "+f"(d[2]), "+f"(d[3]) : "r"(a0), "r"(a1), "r"(b0));
}
__device__ __forceinline__ uint64_t mkdesc(unsigned addr, unsigned lbo, unsigned sbo) {
  return (uint64_t)((addr >> 4) & 0x3fff) | ((uint64_t)(lbo >> 4) << 16) | ((uint64_t)(sbo >> 4) << 32) | (1ull << 62);
}
#define R8(b) "+f"(d[b]), "+f"(d[b + 1]), "+f"(d[b + 2]), "+f"(d[b + 3]), "+f"(d[b + 4]), "+f"(d[b + 5]), "+f"(d[b + 6]), "+f"(d[b + 7])
#define R32(b) R8(b), R8(b + 8), R8(b + 16), R8(b + 24)
__device__ __forceinline__ void wgmma_n256(float* d, uint64_t ad, uint64_t bd, int acc) {
  asm volatile(
      "{.reg .pred p; setp.ne.b32 p, %130, 0;\n"
      "wgmma.mma_async.sync.aligned.m64n256k16.f32.bf16.bf16 "
      "{%0,%1,%2,%3,%4,%5,%6,%7,%8,%9,%10,%11,%12,%13,%14,%15,%16,%17,%18,%19,%20,%21,%22,%23,%24,%25,%26,%27,%28,%29,%30,%31,"
      "%32,%33,%34,%35,%36,%37,%38,%39,%40,%41,%42,%43,%44,%45,%46,%47,%48,%49,%50,%51,%52,%53,%54,%55,%56,%57,%58,%59,%60,%61,%62,%63,"
      "%64,%65,%66,%67,%68,%69,%70,%71,%72,%73,%74,%75,%76,%77,%78,%79,%80,%81,%82,%83,%84,%85,%86,%87,%88,%89,%90,%91,%92,%93,%94,%95,"
      "%96,%97,%98,%99,%100,%101,%102,%103,%104,%105,%106,%107,%108,%109,%110,%111,%112,%113,%114,%115,%116,%117,%118,%119,%120,%121,%122,%123,%124,%125,%126,%127},"
      "%128, %129, p, 1, 1, 0, 1;}\n"
      : R32(0), R32(32), R32(64), R32(96)
      : "l"(ad), "l"(bd), "r"(acc));
}

__device__ __forceinline__ void wgmma_n128(float* d, uint64_t ad, uint64_t bd, int acc) {
  asm volatile(
      "{.reg .pred p; setp.ne.b32 p, %66, 0;\n"
      "wgmma.mma_async.sync.aligned.m64n128k16.f32.bf16.bf16 {%0,%1,%2,%3,%4,%5,%6,%7,%8,%9,%10,%11,%12,%13,%14,%15,%16,%17,%18,%19,%20,%21,%22,%23,%24,%25,%26,%27,%28,%29,%30,%31,%32,%33,%34,%35,%36,%37,%38,%39,%40,%41,%42,%43,%44,%45,%46,%47,%48,%49,%50,%51,%52,%53,%54,%55,%56,%57,%58,%59,%60,%61,%62,%63}, %64, %65, p, 1, 1, 0, 1;}\n"
      : R32(0), R32(32)
      : "l"(ad), "l"(bd), "r"(acc));
}

__device__ __forceinline__ void ln16(const float* x, float* o) {
  float s = 0;
#pragma unroll
  for (int i = 0; i < 16; i++) s += x[i];
#pragma unroll
  for (int of = 16; of > 0; of >>= 1) s += __shfl_xor_sync(~0u, s, of);
  float mean = s * (1.0f / DM);
  float v = 0;
#pragma unroll
  for (int i = 0; i < 16; i++) { float dd = x[i] - mean; v += dd * dd; }
#pragma unroll
  for (int of = 16; of > 0; of >>= 1) v += __shfl_xor_sync(~0u, v, of);
  float mb = bf16r(mean);
  float vb = bf16r(v * (1.0f / DM));
  float den = bf16r(sqrtf(bf16r(vb + 1e-5f)));
#pragma unroll
  for (int i = 0; i < 16; i++) o[i] = bf16r(__fdiv_rn(bf16r(x[i] - mb), den));
}
__global__ void __launch_bounds__(256) k_pre(const bf16* __restrict__ x, const char* wq, const char* wk, const char* wv, const char* wo) {
  int t = threadIdx.x, lane = t & 31, w = t >> 5;
  {
    int g2 = blockIdx.x * 256 + t, o = (g2 & 32767) * 128;
    asm volatile("prefetch.global.L2 [%0];" ::"l"((g2 < 32768 ? wk : wv) + o));
    asm volatile("prefetch.global.L2 [%0];" ::"l"((g2 < 32768 ? wq : wo) + o));
  }
  int row = blockIdx.x * 8 + w;
  const uint4* src = reinterpret_cast<const uint4*>(x + (size_t)row * DM);
  uint4 a = src[lane], b = src[lane + 32];
  unsigned u[8] = {a.x, a.y, a.z, a.w, b.x, b.y, b.z, b.w};
  float f[16], o[16], o2[16];
#pragma unroll
  for (int i = 0; i < 8; i++) { f[2 * i] = bf_lo(u[i]); f[2 * i + 1] = bf_hi(u[i]); }
  ln16(f, o);
  ln16(o, o2);
  uint4* d1 = reinterpret_cast<uint4*>(g_xn + (size_t)row * DM);
  uint4* d2 = reinterpret_cast<uint4*>(g_y + (size_t)row * DM);
  d1[lane] = make_uint4(pack_bf16(o[0], o[1]), pack_bf16(o[2], o[3]), pack_bf16(o[4], o[5]), pack_bf16(o[6], o[7]));
  d1[lane + 32] = make_uint4(pack_bf16(o[8], o[9]), pack_bf16(o[10], o[11]), pack_bf16(o[12], o[13]), pack_bf16(o[14], o[15]));
  d2[lane] = make_uint4(pack_bf16(o2[0], o2[1]), pack_bf16(o2[2], o2[3]), pack_bf16(o2[4], o2[5]), pack_bf16(o2[6], o2[7]));
  d2[lane + 32] = make_uint4(pack_bf16(o2[8], o2[9]), pack_bf16(o2[10], o2[11]), pack_bf16(o2[12], o2[13]), pack_bf16(o2[14], o2[15]));
  int gt = blockIdx.x * 256 + t;
  uint4 z = make_uint4(0, 0, 0, 0);
  if (gt < 16384) reinterpret_cast<uint4*>(g_part)[gt] = z;
  if (gt < (int)(sizeof(Flags) / 4)) reinterpret_cast<unsigned*>(&g_flags)[gt] = 0;
}

struct Maps { CUtensorMap xn, y, h1, o, qkv_st, qkv_ld, g, wq, wk, wv, wo, w1, w2; };

#define NSTAGE 3
#define STAGE_BYTES 49152
#define B_STG (NSTAGE * STAGE_BYTES)
#define R_WO 0
#define R_T1 65536
#define R_T2 131072
#define R_RING 65536
#define RING_N 4
#define RING_BYTES 12288
#define R_MEM 196608
#define R_QS (R_MEM + 8448)
#define R_KS (R_QS + 1152)
#define R_OS (R_KS + 1152)
#define R_SOWN (R_OS + 2176)
#define R_SPEER (R_SOWN + 1280)
#define R_VM (R_SPEER + 1280)
#define R_VRED (R_VM + 2048)
#define R_RS (R_VRED + 6144)
#define SM_BAR (R_RS + 8192)
#define SMEM_TOTAL (SM_BAR + 256 + 1024)
#define MB_FULL 0
#define MB_EMPTY 8
#define MB_STGF 16
#define MB_STGE 17
#define MB_W0 18
#define MB_W1 19
#define MB_WO 20
#define MB_S 21
#define MB_V 22
#define MB_KVR 23
#define MB_KVF 24
#define MB_RS 25
#define MB_AG 26
#define SM_MISC (SM_BAR + 224)

#define N_KV 544
#define I_M1 544
#define I_Q 656
#define I_M2 912
#define I_POST 944
#define I_TAIL (I_POST + 16 * 32)
#define N_ITEMS (I_TAIL + 7 * 8 + 64 + 32 + 64)
enum { T_QKV = 0, T_M1 = 1, T_M2 = 2, T_ATT = 3, T_OUT = 4, T_OUTL = 5, T_RED = 6, T_REDL = 7 };
struct Item { int type, b, c, ks, hf; };
__device__ __forceinline__ Item decode_item(int i) {
  Item it; it.ks = 0; it.hf = 0;
  if (i < 64) { it.type = T_QKV; it.b = 0; it.c = 16 + (i >> 1); it.hf = 1 + (i & 1); }
  else if (i < N_KV) { it.type = T_QKV; it.b = (i - 32) >> 5; it.c = 16 + (i & 31); }
  else if (i < I_Q) { it.type = T_M1; it.b = (i - I_M1) / 7; it.c = (i - I_M1) % 7; }
  else if (i < I_M2) { it.type = T_QKV; it.b = (i - I_Q) >> 4; it.c = (i - I_Q) & 15; }
  else if (i < I_POST) { it.type = T_M2; it.b = (i - I_M2) >> 1; it.c = (i - I_M2) & 1; }
  else if (i < I_TAIL) {
    int x = i - I_POST, p = x >> 5, r = x & 31;
    if (r < 16) { it.type = T_ATT; it.b = p; it.c = r; }
    else if (r < 24) { it.type = T_OUT; it.b = p - 3; it.c = r & 1; it.ks = (r - 16) >> 1; }
    else { it.type = T_RED; it.b = p - 5; it.c = r - 24; }
  } else {
    int x = i - I_TAIL, r = x & 7;
    if (x < 16 || (x >= 24 && x < 40)) { int y = x < 16 ? x : x - 24; it.type = T_OUT; it.b = x < 16 ? 13 : 14; it.c = (y >> 1) & 1; it.ks = y >> 2; it.hf = 1 + (y & 1); }
    else if (x < 56) { it.type = T_RED; it.b = x < 24 ? 11 : 7 + (x >> 3); it.c = r; }
    else if (x < 120) { it.type = T_OUTL; it.b = 15; it.c = (x >> 1) & 1; it.ks = (x - 56) >> 2; it.hf = 1 + (x & 1); }
    else if (x < 152) { it.type = T_RED; it.b = 14; it.c = x - 120; it.ks = 1; }
    else { it.type = T_REDL; it.b = 15; it.c = x - 152; }
  }
  return it;
}
__device__ __forceinline__ int item_nkb(int type) { return type == T_M2 ? 28 : (type == T_OUT ? 16 : (type >= T_RED ? 1 : (type >= T_ATT ? 4 : 8))); }

__device__ __forceinline__ void st_async_b64(unsigned raddr, unsigned lo, unsigned hi, unsigned rmb) {
  asm volatile("st.async.weak.shared::cluster.mbarrier::complete_tx::bytes.v2.b32 [%0], {%1,%2}, [%3];" ::"r"(raddr), "r"(lo), "r"(hi), "r"(rmb) : "memory");
}
__device__ __forceinline__ void st_async_b32(unsigned raddr, unsigned v, unsigned rmb) {
  asm volatile("st.async.weak.shared::cluster.mbarrier::complete_tx::bytes.b32 [%0], %1, [%2];" ::"r"(raddr), "r"(v), "r"(rmb) : "memory");
}
__device__ __forceinline__ unsigned mapa(unsigned a, unsigned rank) {
  unsigned r; asm volatile("mapa.shared::cluster.u32 %0, %1, %2;" : "=r"(r) : "r"(a), "r"(rank)); return r;
}
__device__ __forceinline__ void sts64(unsigned a, unsigned x, unsigned y) { asm volatile("st.shared.v2.b32 [%0], {%1,%2};" ::"r"(a), "r"(x), "r"(y) : "memory"); }
__device__ __forceinline__ void sts128(unsigned a, uint4 v) { asm volatile("st.shared.v4.b32 [%0], {%1,%2,%3,%4};" ::"r"(a), "r"(v.x), "r"(v.y), "r"(v.z), "r"(v.w) : "memory"); }
__device__ __forceinline__ uint2 lds64(unsigned a) { uint2 v; asm volatile("ld.shared.v2.b32 {%0,%1}, [%2];" : "=r"(v.x), "=r"(v.y) : "r"(a) : "memory"); return v; }
__device__ __forceinline__ uint4 lds128(unsigned a) { uint4 v; asm volatile("ld.shared.v4.b32 {%0,%1,%2,%3}, [%4];" : "=r"(v.x), "=r"(v.y), "=r"(v.z), "=r"(v.w) : "r"(a) : "memory"); return v; }
__device__ __forceinline__ float lds32f(unsigned a) { float v; asm volatile("ld.shared.f32 %0, [%1];" : "=f"(v) : "r"(a) : "memory"); return v; }
#define spin_check(it) TRAP_IF(++it)
#define POLLV 0
#define BAR8 0
#define D_STAG 150
#define D_RED 540
#define D_PUB 0
#define DELAY(n) do { unsigned c0_, c1_; asm volatile("mov.u32 %0, %%clock;" : "=r"(c0_)); do { asm volatile("mov.u32 %0, %%clock;" : "=r"(c1_)); } while (c1_ - c0_ < (n)); } while (0)
#define VD 2
#define NPRE 2
#define SELP 1
#define SCALE_QK 0.08838834764831845f

__device__ __forceinline__ void rec_worker(const Maps& maps, unsigned sb, const bf16* __restrict__ mem0, const int c) {
  const int h = c >> 1, j = c & 1;
  const int t = opaque_tid(), lane = t & 31, w = t >> 5, g = lane >> 2, tq = lane & 3;
  const int m = lane >> 3, r8 = lane & 7, kh = w >> 2, et = w & 3;
  const unsigned bar = sb + SM_BAR;
  unsigned wq[16][4], wk[16][4], wo[8][4];
  const unsigned woff = (kh * 4) * 8192 + ((m >> 1) * 8 + r8) * 128 + (((et * 2 + (m & 1)) ^ r8) << 4);
  mbar_wait(bar + 8 * MB_W0, 0);
#pragma unroll
  for (int i = 0; i < 16; i++) {
    ldsm_x4_t(wq[i], sb + R_WO + woff + (i >> 2) * 8192 + (i & 3) * 2048);
    ldsm_x4_t(wk[i], sb + R_T1 + woff + (i >> 2) * 8192 + (i & 3) * 2048);
  }
  bar_sync(2, 288);
  if (t == 0) {
    fence_proxy_async_smem();
    mbar_expect_tx(bar + 8 * MB_WO, 65536);
    for (int kb = 0; kb < 2; kb++)
      for (int cb = 0; cb < 4; cb++) tma_load_2d(sb + R_WO + (kb * 4 + cb) * 8192, &maps.wo, j * 256 + cb * 64, h * 128 + kb * 64, bar + 8 * MB_WO);
  }
  mbar_wait(bar + 8 * MB_W1, 0);
  const unsigned pV = sb + R_T2 + woff;
  const unsigned rk = c & 7, peer = rk ^ 1, cl = c >> 3;
#define KEEP(x) x = __shfl_sync(~0u, x, lane)
  unsigned pA = sb + R_MEM + kh * 4096 + lane * 16;
  unsigned pW0 = sb + R_WO + (w >> 1) * 8192 + ((m >> 1) * 8 + r8) * 128 + ((((w & 1) * 4 + (m & 1)) ^ r8) << 4);
  unsigned pW1 = pW0 ^ 32;
  unsigned pVk = pV;
  unsigned aX = sb + R_VRED + et * 512 + lane * 16;
  unsigned aQKst = sb + (kh ? R_KS : R_QS) + r8 * 144 + (et * 16 + (m & 1) * 8) * 2;
  unsigned aL8 = sb + lane * 8;
  unsigned aSl = mapa(sb + R_SOWN + w * 256 + lane * 8, rk), aSr = mapa(sb + R_SPEER + w * 256 + lane * 8, peer);
  unsigned aVl = mapa(sb + R_VM + (j * 4 + et) * 256 + lane * 8, rk), aVr = mapa(sb + R_VM + (j * 4 + et) * 256 + lane * 8, peer);
  const unsigned mbSl = mapa(bar + 8 * MB_S, rk), mbSr = mapa(bar + 8 * MB_S, peer), mbVl = mbSl + 8, mbVr = mbSr + 8;
  unsigned aQ = sb + R_QS + r8 * 144 + m * 16;
  unsigned oKx = (et * 8 + r8) * 128 + ((m ^ r8) << 4);
  unsigned oVx = 4096 + (et >> 1) * 4096 + ((m >> 1) * 8 + r8) * 128 + ((((et & 1) * 4 + (m & 1)) ^ r8) << 4);
  unsigned aOst = sb + R_OS + r8 * 272 + (et * 32 + m * 8) * 2;
  unsigned aOld = sb + R_OS + r8 * 272 + m * 16;
  unsigned aVm = sb + R_VM + et * 512 + lane * 8;
  unsigned aRSr = mapa(sb + R_RS + (h & 3) * 2048 + (w & 1) * 1024 + lane * 8, j * 4 + (w >> 1));
  unsigned mbRSr = mapa(bar + 8 * MB_RS, j * 4 + (w >> 1));
  unsigned t8 = t * 8;
  KEEP(pA); KEEP(pW0); KEEP(pW1); KEEP(pVk); KEEP(aX); KEEP(aQKst); KEEP(aL8); KEEP(aSl); KEEP(aSr); KEEP(aVl); KEEP(aVr); KEEP(aQ); KEEP(oKx); KEEP(oVx);
  KEEP(aOst); KEEP(aOld); KEEP(aVm); KEEP(aRSr); KEEP(mbRSr); KEEP(t8);
  mbar_wait(bar + 8 * MB_WO, 0);
#pragma unroll
  for (int ks = 0; ks < 4; ks++) { ldsm_x4_t(wo[2 * ks], pW0 + ks * 2048); ldsm_x4_t(wo[2 * ks + 1], pW1 + ks * 2048); }
  {
    unsigned v[8];
#pragma unroll
    for (int q = 0; q < 8; q++) v[q] = __ldg(reinterpret_cast<const unsigned*>(mem0) + q * 256 + t);
    sts128(sb + R_MEM + t * 32, make_uint4(__byte_perm(v[0], v[1], 0x5410), __byte_perm(v[2], v[3], 0x5410), __byte_perm(v[4], v[5], 0x5410), __byte_perm(v[6], v[7], 0x5410)));
    sts128(sb + R_MEM + t * 32 + 16, make_uint4(__byte_perm(v[0], v[1], 0x7632), __byte_perm(v[2], v[3], 0x7632), __byte_perm(v[4], v[5], 0x7632), __byte_perm(v[6], v[7], 0x7632)));
  }
  bar_sync(1, 256);

#pragma unroll 1
  for (int s = 0;; s++) {
    const unsigned par = s & 1;
    const unsigned slot = s & (RING_N - 1), rpar = (s / RING_N) & 1;
    const unsigned ring = sb + R_RING + slot * RING_BYTES;
    asm volatile("" : "+r"(t8));
    RSTAMP(1);
    RSTAMP(2);
    float aq[4] = {0, 0, 0, 0}, ak[4] = {0, 0, 0, 0}, av[4] = {0, 0, 0, 0};
    {
      unsigned b[8][4], f1[8][4], f0[8][4];
#define VLD(i) do { ldsm_x4_t(b[i], pA + (i) * 512); ldsm_x4_t(f0[i], pVk + ((i) >> 1) * 8192 + ((i) & 1) * 4096); ldsm_x4_t(f1[i], pVk + ((i) >> 1) * 8192 + ((i) & 1) * 4096 + 2048); } while (0)
      VLD(0);
      if (VD > 1) VLD(1);
#pragma unroll
      for (int i = 0; i < 8; i++) {
        if (i + VD < 8) VLD(i + VD);
        mma16816(aq, wq[2 * i], b[i][0], b[i][1]); mma16816(ak, wk[2 * i], b[i][0], b[i][1]); mma16816(av, f0[i], b[i][0], b[i][1]);
        mma16816(aq, wq[2 * i + 1], b[i][2], b[i][3]); mma16816(ak, wk[2 * i + 1], b[i][2], b[i][3]); mma16816(av, f1[i], b[i][2], b[i][3]);
      }
    }
    RSTAMP(3);
#define STSF4(a, v) asm volatile("st.shared.v4.f32 [%0], {%1,%2,%3,%4};" ::"r"(a), "f"(v[0]), "f"(v[1]), "f"(v[2]), "f"(v[3]) : "memory")
    unsigned f[8][4];
#define WO_PREFETCH() do { _Pragma("unroll") for (int i = 0; i < NPRE; i++) { ldsm_x4_t(f[2 * i], pW0 + 32768 + i * 2048); ldsm_x4_t(f[2 * i + 1], pW1 + 32768 + i * 2048); } } while (0)
    if (kh) {
      STSF4(aX, aq);
      bar_sync(4 + et, 64);
      uint4 o = lds128(aX + 2048), o2 = lds128(aX + 4096);
      stsm_x2_t(aQKst, pack_bf16(ak[0] + __uint_as_float(o.x), ak[1] + __uint_as_float(o.y)), pack_bf16(ak[2] + __uint_as_float(o.z), ak[3] + __uint_as_float(o.w)));
      bar_arrive(1, 256);
      unsigned x = pack_bf16(av[0] + __uint_as_float(o2.x), av[1] + __uint_as_float(o2.y)), y = pack_bf16(av[2] + __uint_as_float(o2.z), av[3] + __uint_as_float(o2.w));
      st_async_b64(aVr, x, y, mbVr);
      st_async_b64(aVl, x, y, mbVl);
      if (s == NSEG - 1) {
        mbar_wait(bar + 8 * MB_V, par);
        if (t == 128) mbar_arrive(bar + 8 * MB_KVR);
        break;
      }
      mbar_wait(bar + 8 * (MB_FULL + slot), rpar);
      unsigned vx[4][4];
      ldsm_x4_t(vx[0], ring + oVx); ldsm_x4_t(vx[1], ring + oVx + 2048); ldsm_x4_t(vx[2], ring + (oVx ^ 32)); ldsm_x4_t(vx[3], ring + (oVx ^ 32) + 2048);
      RSTAMP(4); RSTAMP(5); RSTAMP(6); RSTAMP(7);
      mbar_wait(bar + 8 * MB_S, par);
      RSTAMP(8);
      float sc[10];
#pragma unroll
      for (int i = 0; i < 5; i++) {
        uint2 o = lds64(aL8 + R_SOWN + i * 256), p = lds64(aL8 + R_SPEER + i * 256);
        sc[2 * i] = __uint_as_float(o.x) + __uint_as_float(p.x); sc[2 * i + 1] = __uint_as_float(o.y) + __uint_as_float(p.y);
      }
      mbar_wait(bar + 8 * MB_V, par);
      uint2 vm0 = lds64(aVm), vm1 = lds64(aVm + 256);
      float mx = fmaxf(fmaxf(fmaxf(sc[0], sc[1]), fmaxf(sc[2], sc[3])), fmaxf(fmaxf(fmaxf(sc[4], sc[5]), fmaxf(sc[6], sc[7])), fmaxf(sc[8], sc[9])));
      mx = fmaxf(mx, __shfl_xor_sync(~0u, mx, 1)); mx = fmaxf(mx, __shfl_xor_sync(~0u, mx, 2));
      const float nm = -mx * (SCALE_QK * LOG2E);
      unsigned p[5];
#pragma unroll
      for (int i = 0; i < 5; i++) p[i] = pack_bf16(ex2f(fmaf(sc[2 * i], SCALE_QK * LOG2E, nm)), ex2f(fmaf(sc[2 * i + 1], SCALE_QK * LOG2E, nm)));
      RSTAMP(9);
      float o0[4] = {0, 0, 0, 0}, o1[4] = {0, 0, 0, 0}, o3[4] = {0, 0, 0, 0}, o4[4] = {0, 0, 0, 0}, z0[4] = {0, 0, 0, 0}, z1[4] = {0, 0, 0, 0};
      const unsigned ones[4] = {0x3F803F80u, 0u, 0x3F803F80u, 0u};
      mma16816(z0, ones, p[0], p[1]); mma16816(z1, ones, p[2], p[3]);
      mma16816(o0, vx[0], p[0], p[1]); mma16816(o3, vx[2], p[0], p[1]);
      mma1688(z0, 0x3F803F80u, 0u, p[4]);
      mma16816(o1, vx[1], p[2], p[3]); mma16816(o4, vx[3], p[2], p[3]);
      mma1688(o0, vm0.x, vm0.y, p[4]); mma1688(o3, vm1.x, vm1.y, p[4]);
      float i0, i1;
      asm("rcp.approx.ftz.f32 %0, %1;" : "=f"(i0) : "f"(z0[0] + z1[0])); asm("rcp.approx.ftz.f32 %0, %1;" : "=f"(i1) : "f"(z0[1] + z1[1]));
      asm volatile("stmatrix.sync.aligned.m8n8.x4.trans.shared.b16 [%0], {%1,%2,%3,%4};" ::"r"(aOst), "r"(pack_bf16((o0[0] + o1[0]) * i0, (o0[1] + o1[1]) * i1)), "r"(pack_bf16((o0[2] + o1[2]) * i0, (o0[3] + o1[3]) * i1)),
                   "r"(pack_bf16((o3[0] + o4[0]) * i0, (o3[1] + o4[1]) * i1)), "r"(pack_bf16((o3[2] + o4[2]) * i0, (o3[3] + o4[3]) * i1)) : "memory");
      RSTAMP(10);
      bar_sync(1, 256);
      WO_PREFETCH();
    } else {
      STSF4(aX + 2048, ak); STSF4(aX + 4096, av);
      unsigned kb[8];
      mbar_wait(bar + 8 * (MB_FULL + slot), rpar);
      ldsm_x4(kb, ring + oKx); ldsm_x4(kb + 4, ring + (oKx ^ 64));
      bar_sync(4 + et, 64);
      uint4 o = lds128(aX);
      stsm_x2_t(aQKst, pack_bf16(aq[0] + __uint_as_float(o.x), aq[1] + __uint_as_float(o.y)), pack_bf16(aq[2] + __uint_as_float(o.z), aq[3] + __uint_as_float(o.w)));
      RSTAMP(4);
      bar_sync(1, 256);
      RSTAMP(5);
      if (s == NSEG - 1) break;
      unsigned qa[8], km[8];
      ldsm_x4(qa, aQ); ldsm_x4(qa + 4, aQ + 64);
      if (w == 3) { ldsm_x4(km, aQ + 1152); ldsm_x4(km + 4, aQ + 1152 + 64); }
      float s0[4] = {0, 0, 0, 0}, s1[4] = {0, 0, 0, 0};
      unsigned af[4][4];
#pragma unroll
      for (int i = 0; i < 4; i++) { af[i][0] = qa[2 * i]; af[i][1] = 0; af[i][2] = qa[2 * i + 1]; af[i][3] = 0; }
      mma16816(s0, af[0], kb[0], kb[1]); mma16816(s1, af[1], kb[2], kb[3]);
      mma16816(s0, af[2], kb[4], kb[5]); mma16816(s1, af[3], kb[6], kb[7]);
      if (w == 3) {
        float m0[4] = {0, 0, 0, 0}, m1[4] = {0, 0, 0, 0};
        mma16816(m0, af[0], km[0], km[1]); mma16816(m1, af[1], km[2], km[3]);
        mma16816(m0, af[2], km[4], km[5]); mma16816(m1, af[3], km[6], km[7]);
        unsigned x = __float_as_uint(m0[0] + m1[0]), y = __float_as_uint(m0[1] + m1[1]);
        st_async_b64(aSr + 256, x, y, mbSr); st_async_b64(aSl + 256, x, y, mbSl);
      }
      unsigned x = __float_as_uint(s0[0] + s1[0]), y = __float_as_uint(s0[1] + s1[1]);
      st_async_b64(aSr, x, y, mbSr); st_async_b64(aSl, x, y, mbSl);
      RSTAMP(6);
      WO_PREFETCH();
      RSTAMP(7); RSTAMP(8); RSTAMP(9); RSTAMP(10);
      bar_sync(1, 256);
    }
    RSTAMP(11);
    float d0[4] = {0, 0, 0, 0}, d1[4] = {0, 0, 0, 0}, e0[4] = {0, 0, 0, 0}, e1[4] = {0, 0, 0, 0};
    unsigned ob[4][4];
#pragma unroll
    for (int k2 = 0; k2 < 4; k2++) ldsm_x4(ob[k2], aOld + k2 * 64);
#pragma unroll
    for (int i = NPRE; i < 4; i++) { ldsm_x4_t(f[2 * i], pW0 + 32768 + i * 2048); ldsm_x4_t(f[2 * i + 1], pW1 + 32768 + i * 2048); }
    mma16816(d0, wo[0], ob[0][0], ob[0][1]); mma16816(d1, wo[1], ob[0][0], ob[0][1]);
    mma16816(e0, wo[2], ob[0][2], ob[0][3]); mma16816(e1, wo[3], ob[0][2], ob[0][3]);
    mma16816(d0, wo[4], ob[1][0], ob[1][1]); mma16816(d1, wo[5], ob[1][0], ob[1][1]);
    mma16816(e0, wo[6], ob[1][2], ob[1][3]); mma16816(e1, wo[7], ob[1][2], ob[1][3]);
    mma16816(d0, f[0], ob[2][0], ob[2][1]); mma16816(d1, f[1], ob[2][0], ob[2][1]);
    mma16816(e0, f[2], ob[2][2], ob[2][3]); mma16816(e1, f[3], ob[2][2], ob[2][3]);
    mma16816(d0, f[4], ob[3][0], ob[3][1]); mma16816(d1, f[5], ob[3][0], ob[3][1]);
    mma16816(e0, f[6], ob[3][2], ob[3][3]); mma16816(e1, f[7], ob[3][2], ob[3][3]);
    st_async_b64(aRSr, __float_as_uint(d0[0] + e0[0]), __float_as_uint(d0[1] + e0[1]), mbRSr);
    st_async_b64(aRSr + 256, __float_as_uint(d0[2] + e0[2]), __float_as_uint(d0[3] + e0[3]), mbRSr);
    st_async_b64(aRSr + 512, __float_as_uint(d1[0] + e1[0]), __float_as_uint(d1[1] + e1[1]), mbRSr);
    st_async_b64(aRSr + 768, __float_as_uint(d1[2] + e1[2]), __float_as_uint(d1[3] + e1[3]), mbRSr);
    RSTAMP(12);
    if (t == 128) {
      mbar_arrive(bar + 8 * (MB_EMPTY + slot)); mbar_arrive(bar + 8 * MB_KVR);
      mbar_expect_tx(bar + 8 * MB_S, 2560); mbar_expect_tx(bar + 8 * MB_V, 2048);
    }
    const unsigned tag = ((s >> 1) & 1) ^ 1;
    const char* gp = reinterpret_cast<const char*>(g_part);
    const unsigned goff = (par * 8 + rk) * 16384 + cl * 2048 + t8;
    const unsigned dlt = (R_MEM + rk * 1024) - (SM_BAR + 8 * MB_AG) + (t8 >> 1);
    mbar_wait(bar + 8 * MB_RS, par);
    RSTAMP(13);
    uint2 a[8];
    {
      uint2 x0 = lds64(sb + R_RS + t8), x1 = lds64(sb + R_RS + 2048 + t8), x2 = lds64(sb + R_RS + 4096 + t8), x3 = lds64(sb + R_RS + 6144 + t8);
      float r0 = (__uint_as_float(x0.x) + __uint_as_float(x1.x)) + (__uint_as_float(x2.x) + __uint_as_float(x3.x));
      float r1 = (__uint_as_float(x0.y) + __uint_as_float(x1.y)) + (__uint_as_float(x2.y) + __uint_as_float(x3.y));
      a[0].x = (__float_as_uint(r0) & ~1u) | tag; a[0].y = (__float_as_uint(r1) & ~1u) | tag;
      asm volatile("st.relaxed.gpu.global.v2.u32 [%0], {%1,%2};" ::"l"(gp + goff), "r"(a[0].x), "r"(a[0].y) : "memory");
    }
    RSTAMP(14);
    if (t == 128) mbar_expect_tx(bar + 8 * MB_RS, 8192);
    {
      unsigned it = 0;
#define PLOAD(a) _Pragma("unroll") for (int i = 1; i < 8; i++) a[i] = ldv2_relaxed(gp + (goff ^ (i * 2048)))
#define PAND(a) (((a[1].x & a[1].y) & (a[2].x & a[2].y) & (a[3].x & a[3].y)) & ((a[4].x & a[4].y) & (a[5].x & a[5].y)) & ((a[6].x & a[6].y) & (a[7].x & a[7].y)))
#define POR(a) (((a[1].x | a[1].y) | (a[2].x | a[2].y) | (a[3].x | a[3].y)) | ((a[4].x | a[4].y) | (a[5].x | a[5].y)) | ((a[6].x | a[6].y) | (a[7].x | a[7].y)))
#define POK(a) (((tag ? PAND(a) : ~POR(a)) & 1u) != 0)
      if (D_RED) DELAY(D_RED);
      PLOAD(a);
      while (!POK(a)) {
#pragma unroll
        for (int i = 1; i < 8; i++) if (((a[i].x ^ tag) | (a[i].y ^ tag)) & 1u) a[i] = ldv2_relaxed(gp + (goff ^ (i * 2048)));
        spin_check(it);
      }
    }
    RSTAMP(15);
    {
#define AF(i, c) __uint_as_float(a[i].c)
      unsigned u = pack_bf16(((AF(0, x) + AF(1, x)) + (AF(2, x) + AF(3, x))) + ((AF(4, x) + AF(5, x)) + (AF(6, x) + AF(7, x))),
                             ((AF(0, y) + AF(1, y)) + (AF(2, y) + AF(3, y))) + ((AF(4, y) + AF(5, y)) + (AF(6, y) + AF(7, y))));
      __syncwarp();
#pragma unroll
      for (int i = 0; i < 8; i++) { const unsigned mbA = mapa(bar + 8 * MB_AG, (7 - i) ^ ((goff >> 14) & 7)); st_async_b32(mbA + dlt, u, mbA); }
    }
    mbar_wait(bar + 8 * MB_KVF, par);
    mbar_wait(bar + 8 * MB_AG, par);
    if (t == 128) mbar_expect_tx(bar + 8 * MB_AG, 8192);
  }
}

__device__ __forceinline__ void rec_ring(const Maps& maps, unsigned sb, const int c) {
  const int h = c >> 1, j = c & 1;
  const unsigned bar = sb + SM_BAR;
  const int lane = threadIdx.x & 31;
  __syncwarp();
  bar_sync(2, 288);
  if (lane == 0) {
    fence_proxy_async_smem();
    for (int s = 0; s < NSEG; s++) {
      unsigned slot = s & (RING_N - 1);
      if ((s & 3) == 0 && !DBGMODE) {
        wait_flag_ge(&g_flags.qkv[(s >> 2) * 48 + 16 + (h >> 1)], 2);
        wait_flag_ge(&g_flags.qkv[(s >> 2) * 48 + 32 + (h >> 1)], 2);
        fence_proxy_async();
      }
      if (s >= RING_N) mbar_wait_sleep(bar + 8 * (MB_EMPTY + slot), ((s / RING_N) - 1) & 1);
      unsigned dst = sb + R_RING + slot * RING_BYTES, mb = bar + 8 * (MB_FULL + slot);
      mbar_expect_tx(mb, RING_BYTES);
      tma_load_2d(dst, &maps.qkv_ld, HD + h * 128 + j * 64, s * SEG, mb);
      tma_load_2d(dst + 4096, &maps.qkv_ld, 2 * HD + h * 128, s * SEG, mb);
      tma_load_2d(dst + 8192, &maps.qkv_ld, 2 * HD + h * 128 + 64, s * SEG, mb);
    }
  }
}
__device__ __forceinline__ void rec_copy(unsigned sb, const int c) {
  const int h = c >> 1, j = c & 1;
  const unsigned bar = sb + SM_BAR;
  const int lane = threadIdx.x & 31;
  for (int s = 0; s < NSEG; s++) {
    if (s < NSEG - 1) mbar_wait_sleep(bar + 8 * MB_KVR, s & 1); else mbar_wait(bar + 8 * MB_KVR, s & 1);
    uint4 k0 = lds128(sb + R_KS + (lane >> 3) * 144 + (lane & 7) * 16), k1 = lds128(sb + R_KS + (4 + (lane >> 3)) * 144 + (lane & 7) * 16);
    uint2 v[4];
#pragma unroll
    for (int i = 0; i < 4; i++) v[i] = lds64(sb + R_VM + (j * 4 + i) * 256 + lane * 8);
    __syncwarp();
    if (lane == 0) mbar_arrive(bar + 8 * MB_KVF);
    bf16* kd = g_km + ((size_t)(s * NH + h) * NMEM) * DH + j * 64;
    *reinterpret_cast<uint4*>(kd + (lane >> 3) * DH + (lane & 7) * 8) = k0;
    *reinterpret_cast<uint4*>(kd + (4 + (lane >> 3)) * DH + (lane & 7) * 8) = k1;
    unsigned* vd = reinterpret_cast<unsigned*>(g_vmt) + ((size_t)(s * NH + h) * DH + j * 64) * 4;
#pragma unroll
    for (int i = 0; i < 4; i++) { vd[(i * 16) * 4 + lane] = v[i].x; vd[(i * 16 + 8) * 4 + lane] = v[i].y; }
    __syncwarp();
    if (lane == 0) st_release(&g_flags.rec[c], s + 1);
  }
}

__device__ __forceinline__ void bulk_producer(const Maps& maps, unsigned sb, int* misc) {
  const unsigned bar = sb + SM_BAR;
  const int lane = threadIdx.x & 31;
  unsigned st = 0, ph = 0, seq = 0;
  while (true) {
    int idx = 0;
    if (lane == 0) idx = (int)atomicAdd(&g_flags.ctr, 1u);
    idx = __shfl_sync(~0u, idx, 0);
    if (idx >= N_ITEMS) {
      if (lane == 0) {
        mbar_wait(bar + 8 * (MB_EMPTY + st), ph ^ 1);
        misc[seq & 3] = -1;
        mbar_arrive(bar + 8 * (MB_FULL + st));
      }
      break;
    }
    if (lane == 0) ISTAMP(idx, 0);
    Item it = decode_item(idx);
    if (it.b < 0) continue;
    const CUtensorMap* mp; int c0, c1, dc0, dc1; unsigned doff;
    const unsigned* fl = nullptr; unsigned tgt = 1; int nbox = 5, rdy = 0;
    if (it.type == T_ATT) {
      mp = &maps.qkv_ld; nbox = 12; doff = lane * 4096;
      c0 = (lane >> 2) * HD + it.c * 256 + (lane & 1) * 64; c1 = it.b * 128 + ((lane >> 1) & 1) * 32; dc0 = dc1 = 0;
      if (lane < 3) fl = &g_flags.qkv[it.b * 48 + lane * 16 + it.c];
      tgt = 2;
      bool ok = true;
      if (lane >= 4 && lane < 8) ok = ld_acquire(&g_flags.rec[it.c * 4 + lane - 4]) >= (unsigned)(it.b * 4 + 4);
      rdy = __all_sync(~0u, ok) ? 65536 : 0;
    } else {
      int k0 = 0, nb0 = it.c * 256;
      if (it.type == T_QKV) { mp = lane == 0 ? &maps.xn : (it.c < 16 ? &maps.wq : (it.c < 32 ? &maps.wk : &maps.wv)); nb0 = (it.c & 15) * 256; }
      else if (it.type == T_M1) mp = lane == 0 ? &maps.y : &maps.w1;
      else if (it.type == T_M2) { mp = lane == 0 ? &maps.h1 : &maps.w2; fl = &g_flags.h1[it.b]; tgt = 7; }
      else {
        mp = lane == 0 ? &maps.o : &maps.wo;
        if (it.type == T_OUT) { k0 = it.ks * 1024; fl = &g_flags.o[it.b * 4 + it.ks]; tgt = 4; }
        else if (it.type == T_OUTL) { k0 = it.ks * 256; fl = &g_flags.o16[it.ks]; }
        else if (lane == 1) { fl = &g_flags.g[it.b]; tgt = 2; }
        else { fl = &g_flags.p[it.b]; tgt = it.type == T_RED ? (it.b >= 13 ? 16 : 8) : 64; }
      }
      if (lane > (it.type >= T_RED ? 1 : 0)) fl = nullptr;
      if (it.hf) { nbox = 3; nb0 += (it.hf - 1) * 128; }
      if (lane == 0) { c0 = k0; c1 = it.b * 128; dc0 = 64; dc1 = 0; doff = 0; }
      else { c0 = nb0 + (lane - 1) * 64; c1 = k0; dc0 = 0; dc1 = 64; doff = 8192 + lane * 8192; }
    }
    if (fl) wait_flag_ge(fl, tgt);
    __syncwarp();
    fence_proxy_async();
    if (lane == 0) ISTAMP(idx, 1);
    const int nkb = item_nkb(it.type);
    for (int kb = 0; kb < nkb; kb++) {
      const unsigned mb = bar + 8 * (MB_FULL + st);
      mbar_wait(bar + 8 * (MB_EMPTY + st), ph ^ 1);
      if (lane == 0) {
        if (kb == 0) misc[seq & 3] = idx | rdy;
        if (it.type >= T_RED) mbar_arrive(mb); else mbar_expect_tx(mb, it.hf ? 32768 : STAGE_BYTES);
      }
      if (it.type == T_ATT) { if (lane < 12) tma_load_2d(sb + st * STAGE_BYTES + doff, mp, c0 + (kb & 1) * 128, c1 + (kb >> 1) * 64, mb); }
      else if (lane < nbox && it.type < T_RED) tma_load_2d(sb + st * STAGE_BYTES + doff, mp, c0 + kb * dc0, c1 + kb * dc1, mb);
      __syncwarp();
      if (++st == NSTAGE) { st = 0; ph ^= 1; }
    }
    seq++;
  }
}
__device__ __forceinline__ void bulk_store(const Maps& maps, unsigned sb, volatile int* misc) {
  const unsigned bar = sb + SM_BAR;
  unsigned ph = 0;
  while (true) {
    mbar_wait(bar + 8 * MB_STGF, ph); ph ^= 1;
    int idx = misc[4];
    if (idx < 0) break;
    Item it = decode_item(idx);
    const CUtensorMap* mp = it.type == T_QKV ? &maps.qkv_st : (it.type == T_M1 ? &maps.h1 : (it.type == T_M2 ? &maps.g : &maps.o));
    unsigned* flag = it.type == T_QKV ? &g_flags.qkv[it.b * 48 + it.c] : (it.type == T_M1 ? &g_flags.h1[it.b] : (it.type == T_M2 ? &g_flags.g[it.b] : (it.b == 15 ? &g_flags.o16[it.c] : &g_flags.o[it.b * 4 + (it.c >> 2)])));
    for (int i = 0; i < (it.hf ? 2 : 4); i++) tma_store_2d(mp, sb + B_STG + i * 16384, it.c * 256 + (it.hf >> 1) * 128 + i * 64, it.b * 128);
    asm volatile("cp.async.bulk.commit_group;" ::: "memory");
    asm volatile("cp.async.bulk.wait_group.read 0;" ::: "memory");
    mbar_arrive(bar + 8 * MB_STGE);
    asm volatile("cp.async.bulk.wait_group 0;" ::: "memory");
    fence_proxy_async();
    red_release_add(flag, it.type == T_QKV && !it.hf ? 2 : 1);
    ISTAMP(idx, 3);
  }
}
__device__ __forceinline__ float rcpf(float x) { float y; asm("rcp.approx.ftz.f32 %0, %1;" : "=f"(y) : "f"(x)); return y; }
__device__ __forceinline__ float gelu_t(float x) {
  float e = ex2f(x * fmaf(x * x, -2.0f * LOG2E * 0.7978845608028654f * 0.044715f, -2.0f * LOG2E * 0.7978845608028654f));
  return x * rcpf(1.0f + e);
}
__device__ __forceinline__ float silu_f(float x) { return x * rcpf(1.0f + ex2f(-LOG2E * x)); }
__device__ __forceinline__ unsigned badd2(unsigned a, unsigned b) { unsigned r; asm("add.rn.bf16x2 %0, %1, %2;" : "=r"(r) : "r"(a), "r"(b)); return r; }

__device__ __forceinline__ void final_out(bf16* __restrict__ out, const bf16* __restrict__ x, size_t o, float4 s) {
  uint2 gv = __ldcg(reinterpret_cast<const uint2*>(g_g + o)), xv = __ldg(reinterpret_cast<const uint2*>(x + o));
  uint2 r;
  r.x = pack_bf16(bf_lo(xv.x) + bf16r(bf16r(s.x) * bf_lo(gv.x)), bf_hi(xv.x) + bf16r(bf16r(s.y) * bf_hi(gv.x)));
  r.y = pack_bf16(bf_lo(xv.y) + bf16r(bf16r(s.z) * bf_lo(gv.y)), bf_hi(xv.y) + bf16r(bf16r(s.w) * bf_hi(gv.y)));
  *reinterpret_cast<uint2*>(out + o) = r;
}
__device__ __forceinline__ void bulk_att_load(unsigned* km, unsigned* vm, int b, int hp, int kb, int w, int lane) {
  const int g = lane >> 2, tq = lane & 3, seg = w >> 2, eh = w & 1;
  const int head = hp * 2 + (kb & 1), sg = b * 4 + (kb >> 1) * 2 + seg;
  const unsigned* kmp = reinterpret_cast<const unsigned*>(g_km + ((size_t)(sg * NH + head) * NMEM + g) * DH) + tq;
  const unsigned* vmp = reinterpret_cast<const unsigned*>(g_vmt) + ((size_t)(sg * NH + head) * DH + eh * 64) * 4 + lane;
#pragma unroll
  for (int i = 0; i < 16; i++) asm volatile("ld.global.cg.u32 %0, [%1];" : "=r"(km[i]) : "l"(kmp + i * 4) : "memory");
#pragma unroll
  for (int i = 0; i < 8; i++) asm volatile("ld.global.cg.u32 %0, [%1];" : "=r"(vm[i]) : "l"(vmp + i * 32) : "memory");
}
__device__ __forceinline__ void bulk_att_stage(unsigned sa, unsigned stg, const unsigned* km, const unsigned* vm, int kb, int w, int lane) {
  const int g = lane >> 2, tq = lane & 3, m = lane >> 3, r8 = lane & 7;
  const int seg = w >> 2, mt = (w >> 1) & 1, eh = w & 1;
  float s[5][4];
#pragma unroll
  for (int i = 0; i < 5; i++) { s[i][0] = s[i][1] = s[i][2] = s[i][3] = 0; }
  const unsigned qb = sa + (0 * 2 + seg) * 8192, kbs = sa + (1 * 2 + seg) * 8192, vb = sa + (2 * 2 + seg) * 8192 + eh * 4096;
  unsigned qa[8][4];
#pragma unroll
  for (int ks = 0; ks < 8; ks++) {
    int row = mt * 16 + (m & 1) * 8 + r8;
    ldsm_x4(qa[ks], qb + (ks >> 2) * 4096 + row * 128 + ((((ks & 3) * 2 + (m >> 1)) ^ r8) << 4));
    unsigned kf[4];
    int krow = (m >> 1) * 8 + r8;
    unsigned ka = kbs + (ks >> 2) * 4096 + krow * 128 + ((((ks & 3) * 2 + (m & 1)) ^ r8) << 4);
    ldsm_x4(kf, ka);
    mma16816(s[0], qa[ks], kf[0], kf[1]); mma16816(s[1], qa[ks], kf[2], kf[3]);
    if (mt) { ldsm_x4(kf, ka + 2048); mma16816(s[2], qa[ks], kf[0], kf[1]); mma16816(s[3], qa[ks], kf[2], kf[3]); }
  }
#pragma unroll
  for (int ks = 0; ks < 8; ks++) mma16816(s[4], qa[ks], km[2 * ks], km[2 * ks + 1]);
  float mx0 = -INFINITY, mx1 = -INFINITY;
  const int t0 = mt * 16 + g, t1 = t0 + 8;
#pragma unroll
  for (int i = 0; i < 5; i++) {
#pragma unroll
    for (int e = 0; e < 4; e++) {
      float v = s[i][e];
      if (i < 4) { int kj = i * 8 + 2 * tq + (e & 1); if (kj > (e < 2 ? t0 : t1)) v = -INFINITY; }
      s[i][e] = v;
      if (e < 2) mx0 = fmaxf(mx0, v); else mx1 = fmaxf(mx1, v);
    }
  }
  mx0 = fmaxf(mx0, __shfl_xor_sync(~0u, mx0, 1)); mx0 = fmaxf(mx0, __shfl_xor_sync(~0u, mx0, 2));
  mx1 = fmaxf(mx1, __shfl_xor_sync(~0u, mx1, 1)); mx1 = fmaxf(mx1, __shfl_xor_sync(~0u, mx1, 2));
  float sm0 = 0, sm1 = 0;
#pragma unroll
  for (int i = 0; i < 5; i++) {
    s[i][0] = ex2f((s[i][0] - mx0) * (SCALE_QK * LOG2E)); s[i][1] = ex2f((s[i][1] - mx0) * (SCALE_QK * LOG2E));
    s[i][2] = ex2f((s[i][2] - mx1) * (SCALE_QK * LOG2E)); s[i][3] = ex2f((s[i][3] - mx1) * (SCALE_QK * LOG2E));
    sm0 += s[i][0] + s[i][1]; sm1 += s[i][2] + s[i][3];
  }
  sm0 += __shfl_xor_sync(~0u, sm0, 1); sm0 += __shfl_xor_sync(~0u, sm0, 2);
  sm1 += __shfl_xor_sync(~0u, sm1, 1); sm1 += __shfl_xor_sync(~0u, sm1, 2);
  const float i0 = __fdividef(1.0f, sm0), i1 = __fdividef(1.0f, sm1);
  unsigned pa[2][4], pm0, pm1;
#pragma unroll
  for (int kk = 0; kk < 2; kk++) {
    pa[kk][0] = pack_bf16(s[2 * kk][0] * i0, s[2 * kk][1] * i0); pa[kk][1] = pack_bf16(s[2 * kk][2] * i1, s[2 * kk][3] * i1);
    pa[kk][2] = pack_bf16(s[2 * kk + 1][0] * i0, s[2 * kk + 1][1] * i0); pa[kk][3] = pack_bf16(s[2 * kk + 1][2] * i1, s[2 * kk + 1][3] * i1);
  }
  pm0 = pack_bf16(s[4][0] * i0, s[4][1] * i0); pm1 = pack_bf16(s[4][2] * i1, s[4][3] * i1);
  const int orow = (kb >> 1) * 64 + seg * 32 + mt * 16 + (m & 1) * 8 + r8;
  const unsigned ob = stg + ((kb & 1) * 2 + eh) * 16384 + orow * 128;
#pragma unroll
  for (int cp = 0; cp < 4; cp++) {
    float o0[4] = {0, 0, 0, 0}, o1[4] = {0, 0, 0, 0};
    mma1688(o0, pm0, pm1, vm[2 * cp]); mma1688(o1, pm0, pm1, vm[2 * cp + 1]);
    unsigned vf[4];
    int row = (m & 1) * 8 + r8;
    unsigned va = vb + row * 128 + (((cp * 2 + (m >> 1)) ^ r8) << 4);
    ldsm_x4_t(vf, va);
    mma16816(o0, pa[0], vf[0], vf[1]); mma16816(o1, pa[0], vf[2], vf[3]);
    if (mt) { ldsm_x4_t(vf, va + 2048); mma16816(o0, pa[1], vf[0], vf[1]); mma16816(o1, pa[1], vf[2], vf[3]); }
    stsm_x4(ob + (((cp * 2 + (m >> 1)) ^ r8) << 4), pack_bf16(o0[0], o0[1]), pack_bf16(o0[2], o0[3]), pack_bf16(o1[0], o1[1]), pack_bf16(o1[2], o1[3]));
  }
}

__device__ __forceinline__ void bulk_worker(unsigned sb, volatile int* misc, const bf16* __restrict__ x, const bf16* __restrict__ b1, const bf16* __restrict__ b2, bf16* __restrict__ out) {
  const int t = threadIdx.x, lane = t & 31, w = t >> 5, wg = w >> 2, g = lane >> 2, tq = lane & 3, m = lane >> 3, r8 = lane & 7;
  const unsigned bar = sb + SM_BAR;
  unsigned st = 0, ph = 0, seq = 0, sph = 0;
  float d[128];
  while (true) {
    mbar_wait(bar + 8 * (MB_FULL + st), ph);
    const int idr = misc[seq & 3]; seq++;
    const int idx = idr & 65535;
    if (idr < 0 || idx >= N_ITEMS) break;
    if (t == 0) ISTAMP(idx, 2);
    const Item it = decode_item(idx);
    const int nkb = item_nkb(it.type);
    if (it.type == T_ATT) {
      unsigned km[16], vm[8], kn[16], vn[8];
      const bool pref = idr >= 65536;
      if (pref) bulk_att_load(kn, vn, it.b, it.c, 0, w, lane);
      mbar_wait(bar + 8 * MB_STGE, sph ^ 1);
#pragma unroll 1
      for (int kb = 0; kb < 4; kb++) {
        if (!pref && !(kb & 1)) {
          if (lane < 4) wait_step_ge(&g_flags.rec[it.c * 4 + lane], it.b * 4 + (kb >> 1) * 2 + wg + 1);
          __syncwarp();
          bulk_att_load(kn, vn, it.b, it.c, kb, w, lane);
        }
        if (kb) mbar_wait(bar + 8 * (MB_FULL + st), ph);
#pragma unroll
        for (int i = 0; i < 16; i++) km[i] = kn[i];
#pragma unroll
        for (int i = 0; i < 8; i++) vm[i] = vn[i];
        if (pref ? kb != 3 : !(kb & 1)) bulk_att_load(kn, vn, it.b, it.c, kb + 1, w, lane);
        bulk_att_stage(sb + st * STAGE_BYTES, sb + B_STG, km, vm, kb, w, lane);
        __syncwarp();
        if (lane == 0) mbar_arrive(bar + 8 * (MB_EMPTY + st));
        if (++st == NSTAGE) { st = 0; ph ^= 1; }
      }
      if (t == 0) misc[4] = idx;
      fence_proxy_async_smem();
      mbar_arrive(bar + 8 * MB_STGF); sph ^= 1;
      continue;
    }
    if (it.type >= T_RED) {
      __syncwarp();
      if (lane == 0) mbar_arrive(bar + 8 * (MB_EMPTY + st));
      if (++st == NSTAGE) { st = 0; ph ^= 1; }
      if (it.type == T_RED) {
#pragma unroll 2
        for (int i = 0; i < (it.ks ? 2 : 8); i++) {
          size_t o = ((size_t)it.b * 128 + it.c * (it.ks ? 4 : 16) + i * 2 + (t >> 7)) * DM + (t & 127) * 4;
          float4 a = __ldcg(reinterpret_cast<const float4*>(g_opart + o)), b = __ldcg(reinterpret_cast<const float4*>(g_opart + o + (size_t)S_TOK * DM));
          float4 c = __ldcg(reinterpret_cast<const float4*>(g_opart + o + (size_t)2 * S_TOK * DM)), e = __ldcg(reinterpret_cast<const float4*>(g_opart + o + (size_t)3 * S_TOK * DM));
          final_out(out, x, o, make_float4((a.x + b.x) + (c.x + e.x), (a.y + b.y) + (c.y + e.y), (a.z + b.z) + (c.z + e.z), (a.w + b.w) + (c.w + e.w)));
        }
      } else {
        size_t ol = ((size_t)it.c * 2 + (t >> 7)) * DM + (t & 127) * 4;
        float4 v[16];
#pragma unroll
        for (int i = 0; i < 16; i++) v[i] = __ldcg(reinterpret_cast<const float4*>(g_opl + ol + (size_t)i * 128 * DM));
#pragma unroll
        for (int st2 = 1; st2 < 16; st2 <<= 1)
#pragma unroll
          for (int i = 0; i < 16; i += 2 * st2) { v[i].x += v[i + st2].x; v[i].y += v[i + st2].y; v[i].z += v[i + st2].z; v[i].w += v[i + st2].w; }
        final_out(out, x, ol + (size_t)15 * 128 * DM, v[0]);
      }
      if (t == 0) ISTAMP(idx, 3);
      continue;
    }
    unsigned pst = 0, bv[32];
#pragma unroll
    for (int i = 0; i < 128; i++) d[i] = 0.0f;
    if (it.type == T_M1 || it.type == T_M2) {
      const unsigned* bp = reinterpret_cast<const unsigned*>((it.type == T_M1 ? b1 : b2) + it.c * 256) + tq;
#pragma unroll
      for (int i = 0; i < 32; i++) asm volatile("ld.global.nc.u32 %0, [%1];" : "=r"(bv[i]) : "l"(bp + i * 4));
    } else {
#pragma unroll
      for (int i = 0; i < 32; i++) bv[i] = 0;
    }
#define KLOOP(WG) \
    for (int kb = 0; kb < nkb; kb++) { \
      if (kb) mbar_wait(bar + 8 * (MB_FULL + st), ph); \
      unsigned sa = sb + st * STAGE_BYTES; \
      uint64_t ad = mkdesc(sa + wg * 8192, 16, 1024), bd = mkdesc(sa + 16384, 8192, 1024); \
      asm volatile("wgmma.fence.sync.aligned;" ::: "memory"); \
      _Pragma("unroll") for (int k = 0; k < 4; k++) WG(d, ad + k * 2, bd + k * 128, (kb | k) != 0); \
      asm volatile("wgmma.commit_group.sync.aligned;" ::: "memory"); \
      if (kb) { \
        asm volatile("wgmma.wait_group.sync.aligned 1;" ::: "memory"); \
        if (lane == 0) mbar_arrive(bar + 8 * (MB_EMPTY + pst)); \
      } \
      pst = st; \
      if (++st == NSTAGE) { st = 0; ph ^= 1; } \
    } \
    asm volatile("wgmma.wait_group.sync.aligned 0;" ::: "memory");
    if (it.hf) { KLOOP(wgmma_n128) } else { KLOOP(wgmma_n256) }
    if (lane == 0) mbar_arrive(bar + 8 * (MB_EMPTY + pst));
    if (it.type >= T_OUT) {
      const int col = it.c * 256 + (it.hf >> 1) * 128 + 2 * tq;
      float* pp = it.type == T_OUT ? g_opart + ((size_t)it.ks * S_TOK + it.b * 128 + w * 16 + g) * DM + col : g_opl + ((size_t)it.ks * 128 + w * 16 + g) * DM + col;
#pragma unroll
      for (int i = 0; i < 32; i++) {
        if (i == 16 && it.hf) break;
        __stcg(reinterpret_cast<float2*>(pp + i * 8), make_float2(d[4 * i], d[4 * i + 1]));
        __stcg(reinterpret_cast<float2*>(pp + 8 * DM + i * 8), make_float2(d[4 * i + 2], d[4 * i + 3]));
      }
      bar_sync(1, 256);
      if (t == 0) { red_release_add(&g_flags.p[it.b], 1); ISTAMP(idx, 3); }
      continue;
    }
#define ACT(F) _Pragma("unroll") for (int i = 0; i < 32; i++) { \
        unsigned u0 = badd2(pack_bf16(d[4 * i], d[4 * i + 1]), bv[i]), u1 = badd2(pack_bf16(d[4 * i + 2], d[4 * i + 3]), bv[i]); \
        d[4 * i] = F(bf_lo(u0)); d[4 * i + 1] = F(bf_hi(u0)); d[4 * i + 2] = F(bf_lo(u1)); d[4 * i + 3] = F(bf_hi(u1)); }
    if (it.type == T_M1) { ACT(gelu_t) } else if (it.type == T_M2) { ACT(silu_f) }
    mbar_wait(bar + 8 * MB_STGE, sph ^ 1);
    {
      const unsigned ob = sb + B_STG + (w * 16 + (m & 1) * 8 + r8) * 128;
#pragma unroll
      for (int i = 0; i < 16; i++)
        if (i < 8 || !it.hf) stsm_x4(ob + (i >> 2) * 16384 + ((((i & 3) * 2 + (m >> 1)) ^ r8) << 4), pack_bf16(d[8 * i], d[8 * i + 1]), pack_bf16(d[8 * i + 2], d[8 * i + 3]),
                pack_bf16(d[8 * i + 4], d[8 * i + 5]), pack_bf16(d[8 * i + 6], d[8 * i + 7]));
    }
    if (t == 0) misc[4] = idx;
    fence_proxy_async_smem();
    mbar_arrive(bar + 8 * MB_STGF); sph ^= 1;
  }
  mbar_wait(bar + 8 * MB_STGE, sph ^ 1);
  if (t == 0) misc[4] = -1;
  mbar_arrive(bar + 8 * MB_STGF);
}

__global__ void __launch_bounds__(384, 1)
k_main(const __grid_constant__ Maps maps, const bf16* __restrict__ x, const bf16* __restrict__ mem0, const bf16* __restrict__ b1, const bf16* __restrict__ b2, bf16* __restrict__ out, unsigned recmask) {
  extern __shared__ unsigned char smem_raw[];
  const unsigned sraw = smem_u32(smem_raw);
  const unsigned sb = (sraw + 1023u) & ~1023u;
  int* misc = reinterpret_cast<int*>(smem_raw + (sb - sraw) + SM_MISC);
  const int w = threadIdx.x >> 5;
  const bool helper = recmask == 0;
  const unsigned kc = blockIdx.x / CLS;
  const bool rec = kc < 32 && ((recmask >> kc) & 1);
  const int c = __popc(recmask & ((1u << (kc & 31)) - 1)) * CLS + (blockIdx.x & (CLS - 1));
  if (threadIdx.x == 0) {
    const unsigned bar = sb + SM_BAR;
    for (int i = 0; i < 8; i++) { mbar_init(bar + 8 * (MB_FULL + i), 1); mbar_init(bar + 8 * (MB_EMPTY + i), rec ? 1 : 8); }
    mbar_init(bar + 8 * MB_STGF, 256); mbar_init(bar + 8 * MB_STGE, 1);
    for (int i = MB_W0; i <= MB_AG; i++) mbar_init(bar + 8 * i, 1);
    if (rec) { mbar_expect_tx(bar + 8 * MB_S, 2560); mbar_expect_tx(bar + 8 * MB_V, 2048); mbar_expect_tx(bar + 8 * MB_RS, 8192); mbar_expect_tx(bar + 8 * MB_AG, 8192); }
    asm volatile("fence.mbarrier_init.release.cluster;" ::: "memory");
  }
  __syncthreads();
  asm volatile("barrier.cluster.arrive.release.aligned;\nbarrier.cluster.wait.acquire.aligned;" ::: "memory");
  if (rec && threadIdx.x == 256) {
    const unsigned bar = sb + SM_BAR; const int col = c * 64;
    mbar_expect_tx(bar + 8 * MB_W0, 131072);
    for (int kb = 0; kb < 8; kb++) tma_load_2d(sb + R_WO + kb * 8192, &maps.wq, col, kb * 64, bar + 8 * MB_W0);
    for (int kb = 0; kb < 8; kb++) tma_load_2d(sb + R_T1 + kb * 8192, &maps.wk, col, kb * 64, bar + 8 * MB_W0);
    mbar_expect_tx(bar + 8 * MB_W1, 65536);
    for (int kb = 0; kb < 8; kb++) tma_load_2d(sb + R_T2 + kb * 8192, &maps.wv, col, kb * 64, bar + 8 * MB_W1);
  }
  if (!helper) {
    asm volatile("griddepcontrol.wait;" ::: "memory");
    asm volatile("griddepcontrol.launch_dependents;");
  }
  if (DBGMODE && !rec) { if (helper) asm volatile("griddepcontrol.wait;" ::: "memory"); return; }
  if (w >= 8) {
    asm volatile("setmaxnreg.dec.sync.aligned.u32 24;");
    if (rec) { if (w == 8) rec_ring(maps, sb, c); else if (w == 9) rec_copy(sb, c); }
    else if (w == 8) bulk_producer(maps, sb, misc);
    else if ((threadIdx.x & 31) == 0) { if (w == 9) bulk_store(maps, sb, misc);
      else if (w == 10 && helper) asm volatile("griddepcontrol.wait;" ::: "memory"); }
  } else {
    if (rec) { asm volatile("setmaxnreg.inc.sync.aligned.u32 240;"); rec_worker(maps, sb, mem0, c); }
    else { asm volatile("setmaxnreg.inc.sync.aligned.u32 240;"); bulk_worker(sb, misc, x, b1, b2, out); }
  }
}

typedef CUresult (*EncFn)(CUtensorMap*, CUtensorMapDataType, cuuint32_t, void*, const cuuint64_t*, const cuuint64_t*, const cuuint32_t*, const cuuint32_t*,
                          CUtensorMapInterleave, CUtensorMapSwizzle, CUtensorMapL2promotion, CUtensorMapFloatOOBfill);
static void mk_map(EncFn enc, CUtensorMap* m, const void* ptr, uint64_t rows, uint64_t cols, uint32_t box_rows) {
  cuuint64_t dims[2] = {cols, rows}; cuuint64_t strides[1] = {cols * 2};
  cuuint32_t box[2] = {64, box_rows}, es[2] = {1, 1};
  enc(m, CU_TENSOR_MAP_DATA_TYPE_BFLOAT16, 2, const_cast<void*>(ptr), dims, strides, box, es, CU_TENSOR_MAP_INTERLEAVE_NONE, CU_TENSOR_MAP_SWIZZLE_128B,
      CU_TENSOR_MAP_L2_PROMOTION_L2_256B, CU_TENSOR_MAP_FLOAT_OOB_FILL_NONE);
}
extern "C" void kernel_launch(void* const* d_in, const int* in_sizes, int n_in, void* d_out, int out_size) {
  static EncFn enc = nullptr;
  static int ncl = 0, nhelp = 0;
  static unsigned recmask = 0xFFu;
  static void *p_xn, *p_y, *p_h1, *p_o, *p_qkv, *p_g;
  if (!enc) {
    void* fn = nullptr; cudaDriverEntryPointQueryResult qr;
    cudaGetDriverEntryPoint("cuTensorMapEncodeTiled", &fn, cudaEnableDefault, &qr);
    enc = (EncFn)fn;
    cudaGetSymbolAddress(&p_xn, g_xn); cudaGetSymbolAddress(&p_y, g_y); cudaGetSymbolAddress(&p_h1, g_h1);
    cudaGetSymbolAddress(&p_o, g_o); cudaGetSymbolAddress(&p_qkv, g_qkv); cudaGetSymbolAddress(&p_g, g_g);
    cudaFuncSetAttribute(k_main, cudaFuncAttributeMaxDynamicSharedMemorySize, SMEM_TOTAL);
    cudaLaunchConfig_t cfg = {}; cfg.gridDim = dim3(128); cfg.blockDim = dim3(384); cfg.dynamicSmemBytes = SMEM_TOTAL;
    cudaLaunchAttribute at[1]; at[0].id = cudaLaunchAttributeClusterDimension; at[0].val.clusterDim.x = CLS; at[0].val.clusterDim.y = 1; at[0].val.clusterDim.z = 1;
    cfg.attrs = at; cfg.numAttrs = 1;
    if (cudaOccupancyMaxActiveClusters(&ncl, k_main, &cfg) != cudaSuccess) { cudaGetLastError(); ncl = 14; }
    ncl = ncl > 16 ? 16 : (ncl < 9 ? 9 : ncl);
    int nsm = 0, dev = 0; cudaGetDevice(&dev); cudaDeviceGetAttribute(&nsm, cudaDevAttrMultiProcessorCount, dev);
    nhelp = nsm - ncl * CLS;
  }
  Maps maps;
  mk_map(enc, &maps.xn, p_xn, S_TOK, DM, 128); mk_map(enc, &maps.y, p_y, S_TOK, DM, 128); mk_map(enc, &maps.h1, p_h1, S_TOK, FF, 128);
  mk_map(enc, &maps.o, p_o, S_TOK, HD, 128); mk_map(enc, &maps.qkv_st, p_qkv, S_TOK, 3 * HD, 128); mk_map(enc, &maps.qkv_ld, p_qkv, S_TOK, 3 * HD, 32);
  mk_map(enc, &maps.g, p_g, S_TOK, DM, 128);
  mk_map(enc, &maps.wq, d_in[2], DM, HD, 64); mk_map(enc, &maps.wk, d_in[3], DM, HD, 64); mk_map(enc, &maps.wv, d_in[4], DM, HD, 64);
  mk_map(enc, &maps.wo, d_in[5], HD, DM, 64); mk_map(enc, &maps.w1, d_in[8], DM, FF, 64); mk_map(enc, &maps.w2, d_in[10], FF, DM, 64);
  cudaStream_t st = cudaStreamPerThread;
  k_pre<<<256, 256, 0, st>>>((const bf16*)d_in[0], (const char*)d_in[2], (const char*)d_in[3], (const char*)d_in[4], (const char*)d_in[5]);
  cudaLaunchConfig_t cfg = {}; cfg.gridDim = dim3(ncl * CLS); cfg.blockDim = dim3(384); cfg.dynamicSmemBytes = SMEM_TOTAL; cfg.stream = st;
  cudaLaunchAttribute at[2]; at[1].id = cudaLaunchAttributeClusterDimension; at[1].val.clusterDim.x = CLS; at[1].val.clusterDim.y = 1; at[1].val.clusterDim.z = 1;
  at[0].id = cudaLaunchAttributeProgrammaticStreamSerialization; at[0].val.programmaticStreamSerializationAllowed = 1;
#define PDL1 0
  cfg.attrs = at + (PDL1 ? 0 : 1); cfg.numAttrs = PDL1 ? 2 : 1;
  cudaLaunchKernelEx(&cfg, k_main, maps, (const bf16*)d_in[0], (const bf16*)d_in[1], (const bf16*)d_in[9], (const bf16*)d_in[11], (bf16*)d_out, recmask);
  if (nhelp > 0) {
    cfg.gridDim = dim3(nhelp);
    cfg.attrs = at; cfg.numAttrs = 1;
    cudaLaunchKernelEx(&cfg, k_main, maps, (const bf16*)d_in[0], (const bf16*)d_in[1], (const bf16*)d_in[9], (const bf16*)d_in[11], (bf16*)d_out, 0u);
  }
}
```

```cpp
#include <cuda_runtime.h>
#include <cuda_bf16.h>
#include <cuda.h>
#include <stdint.h>

typedef __nv_bfloat16 bf16;

#define S_TOK 2048
#define DM 512
#define NH 32
#define DH 128
#define HD 4096
#define NMEM 8
#define SEG 32
#define NSEG 64
#define FF 1792
#define NBLK 16
#define NREC 64
#define REPL 0
#define CLS 8

__device__ __align__(1024) bf16 g_xn[S_TOK * DM];
__device__ __align__(1024) bf16 g_y[S_TOK * DM];
__device__ __align__(1024) bf16 g_qkv[(size_t)S_TOK * 3 * HD];
__device__ __align__(1024) bf16 g_h1[S_TOK * FF];
__device__ __align__(1024) bf16 g_g[S_TOK * DM];
__device__ __align__(1024) bf16 g_o[(size_t)S_TOK * HD];
__device__ __align__(1024) bf16 g_km[NSEG * NH * NMEM * DH];
__device__ __align__(1024) bf16 g_vmt[NSEG * NH * DH * NMEM];
__device__ __align__(1024) float g_opart[(size_t)4 * S_TOK * DM];
__device__ __align__(1024) float g_opl[(size_t)16 * 128 * DM];
__device__ __align__(1024) unsigned g_part[2 * 8 * 8 * 512];
struct Flags {
  unsigned qkv[NBLK * 48];
  unsigned h1[NBLK];
  unsigned g[NBLK];
  unsigned o[NBLK * 4];
  unsigned p[NBLK];
  unsigned o16[16];
  unsigned ctr;
  unsigned rec[NREC];
  unsigned abort_;
};
__device__ __align__(1024) Flags g_flags;

#define RSTAMP(k)
#define DBGMODE 0
#define ISTAMP(i, k)
__device__ __forceinline__ unsigned smem_u32(const void* p) { return (unsigned)__cvta_generic_to_shared(p); }
__device__ __forceinline__ float bf16r(float x) { unsigned u; asm("cvt.rn.bf16x2.f32 %0, %1, %2;" : "=r"(u) : "f"(x), "f"(0.0f)); return __uint_as_float(u); }
__device__ __forceinline__ unsigned pack_bf16(float lo, float hi) {
  __nv_bfloat162 v = __floats2bfloat162_rn(lo, hi);
  return *reinterpret_cast<unsigned*>(&v);
}
__device__ __forceinline__ float bf_lo(unsigned u) { return __uint_as_float(u << 16); }
__device__ __forceinline__ float bf_hi(unsigned u) { return __uint_as_float(u & 0xffff0000u); }

#define SPIN_LIMIT (1u << 20)
#define TRAP_IF(x) if ((x) > SPIN_LIMIT) { asm volatile("st.global.u32 [%0], %1;" ::"l"(0ull), "r"(0u) : "memory"); break; }
__device__ __forceinline__ unsigned ld_acquire(const unsigned* p) {
  unsigned v; asm volatile("ld.acquire.gpu.global.u32 %0, [%1];" : "=r"(v) : "l"(p) : "memory"); return v;
}
__device__ __forceinline__ unsigned ld_relaxed(const unsigned* p) {
  unsigned v; asm volatile("ld.relaxed.gpu.global.u32 %0, [%1];" : "=r"(v) : "l"(p) : "memory"); return v;
}
__device__ __forceinline__ void red_release_add(unsigned* p, unsigned v) {
  asm volatile("red.release.gpu.global.add.u32 [%0], %1;" ::"l"(p), "r"(v) : "memory");
}
__device__ __forceinline__ void st_release(unsigned* p, unsigned v) {
  asm volatile("st.release.gpu.global.u32 [%0], %1;" ::"l"(p), "r"(v) : "memory");
}
__device__ __forceinline__ void wait_flag_ge(const unsigned* p, unsigned target) {
  unsigned it = 0;
  while (ld_acquire(p) < target) {
    __nanosleep(64);
    TRAP_IF(++it);
  }
}
__device__ __forceinline__ void wait_step_ge(const unsigned* p, unsigned target) {
  unsigned it = 0, v;
  while ((v = ld_acquire(p)) < target) {
    __nanosleep(target - v >= 2 ? 1500 : 64);
    TRAP_IF(++it);
  }
}
__device__ __forceinline__ uint4 ldv4_relaxed(const void* p) {
  uint4 a; asm volatile("ld.relaxed.gpu.global.v4.u32 {%0,%1,%2,%3}, [%4];" : "=r"(a.x), "=r"(a.y), "=r"(a.z), "=r"(a.w) : "l"(p) : "memory"); return a;
}
__device__ __forceinline__ uint2 ldv2_relaxed(const void* p) {
  uint2 a; asm volatile("ld.relaxed.gpu.global.v2.u32 {%0,%1}, [%2];" : "=r"(a.x), "=r"(a.y) : "l"(p) : "memory"); return a;
}
__device__ __forceinline__ void mbar_init(unsigned mb, unsigned cnt) { asm volatile("mbarrier.init.shared::cta.b64 [%0], %1;" ::"r"(mb), "r"(cnt) : "memory"); }
__device__ __forceinline__ void mbar_expect_tx(unsigned mb, unsigned bytes) { asm volatile("mbarrier.arrive.expect_tx.shared::cta.b64 _, [%0], %1;" ::"r"(mb), "r"(bytes) : "memory"); }
__device__ __forceinline__ void mbar_arrive(unsigned mb) { asm volatile("mbarrier.arrive.shared::cta.b64 _, [%0];" ::"r"(mb) : "memory"); }
__device__ __forceinline__ void mbar_wait(unsigned mb, unsigned parity) {
  unsigned ok, it = 0;
  while (true) {
    asm volatile("{.reg .pred p; mbarrier.try_wait.parity.shared::cta.b64 p, [%1], %2; selp.u32 %0,1,0,p;}" : "=r"(ok) : "r"(mb), "r"(parity) : "memory");
    if (ok) break;
    TRAP_IF(++it);
  }
}
__device__ __forceinline__ void mbar_wait_sleep(unsigned mb, unsigned parity) {
  unsigned ok, it = 0;
  while (true) {
    asm volatile("{.reg .pred p; mbarrier.test_wait.parity.shared::cta.b64 p, [%1], %2; selp.u32 %0,1,0,p;}" : "=r"(ok) : "r"(mb), "r"(parity) : "memory");
    if (ok) break;
    __nanosleep(200);
    TRAP_IF(++it);
  }
}
__device__ __forceinline__ float ex2f(float x) { float y; asm("ex2.approx.ftz.f32 %0, %1;" : "=f"(y) : "f"(x)); return y; }
__device__ __forceinline__ int opaque_tid() { int t = threadIdx.x; t = __shfl_sync(~0u, t, t & 31); return t; }
#define LOG2E 1.4426950408889634f
__device__ __forceinline__ void mbar_wait_cluster(unsigned mb, unsigned parity) {
  unsigned ok, it = 0;
  while (true) {
    asm volatile("{.reg .pred p; mbarrier.try_wait.parity.acquire.cluster.shared::cta.b64 p, [%1], %2; selp.u32 %0,1,0,p;}" : "=r"(ok) : "r"(mb), "r"(parity) : "memory");
    if (ok) break;
    TRAP_IF(++it);
  }
}
__device__ __forceinline__ void bar_sync(int id, int n) { asm volatile("bar.sync %0, %1;" ::"r"(id), "r"(n) : "memory"); }
__device__ __forceinline__ void bar_arrive(int id, int n) { asm volatile("bar.arrive %0, %1;" ::"r"(id), "r"(n) : "memory"); }
__device__ __forceinline__ void tma_load_2d(unsigned dst, const CUtensorMap* map, int c0, int c1, unsigned mb) {
  asm volatile("cp.async.bulk.tensor.2d.shared::cluster.global.mbarrier::complete_tx::bytes [%0], [%1, {%3, %4}], [%2];"
               ::"r"(dst), "l"((uint64_t)map), "r"(mb), "r"(c0), "r"(c1) : "memory");
}
__device__ __forceinline__ void tma_store_2d(const CUtensorMap* map, unsigned src, int c0, int c1) {
  asm volatile("cp.async.bulk.tensor.2d.global.shared::cta.bulk_group [%0, {%2, %3}], [%1];"
               ::"l"((uint64_t)map), "r"(src), "r"(c0), "r"(c1) : "memory");
}
__device__ __forceinline__ void fence_proxy_async() { asm volatile("fence.proxy.async;" ::: "memory"); }
__device__ __forceinline__ void fence_proxy_async_smem() { asm volatile("fence.proxy.async.shared::cta;" ::: "memory"); }
__device__ __forceinline__ void ldsm_x4(unsigned* r, unsigned addr) {
  asm volatile("ldmatrix.sync.aligned.m8n8.x4.shared.b16 {%0,%1,%2,%3}, [%4];" : "=r"(r[0]), "=r"(r[1]), "=r"(r[2]), "=r"(r[3]) : "r"(addr) : "memory");
}
__device__ __forceinline__ void ldsm_x4_t(unsigned* r, unsigned addr) {
  asm volatile("ldmatrix.sync.aligned.m8n8.x4.trans.shared.b16 {%0,%1,%2,%3}, [%4];" : "=r"(r[0]), "=r"(r[1]), "=r"(r[2]), "=r"(r[3]) : "r"(addr) : "memory");
}
__device__ __forceinline__ void stsm_x2_t(unsigned addr, unsigned r0, unsigned r1) {
  asm volatile("stmatrix.sync.aligned.m8n8.x2.trans.shared.b16 [%0], {%1,%2};" ::"r"(addr), "r"(r0), "r"(r1) : "memory");
}
__device__ __forceinline__ void stsm_x4(unsigned addr, unsigned r0, unsigned r1, unsigned r2, unsigned r3) {
  asm volatile("stmatrix.sync.aligned.m8n8.x4.shared.b16 [%0], {%1,%2,%3,%4};" ::"r"(addr), "r"(r0), "r"(r1), "r"(r2), "r"(r3) : "memory");
}
__device__ __forceinline__ void mma16816(float* d, const unsigned* a, unsigned b0, unsigned b1) {
  asm volatile("mma.sync.aligned.m16n8k16.row.col.f32.bf16.bf16.f32 {%0,%1,%2,%3}, {%4,%5,%6,%7}, {%8,%9}, {%0,%1,%2,%3};"
               : "+f"(d[0]), "+f"(d[1]), "+f"(d[2]), "+f"(d[3]) : "r"(a[0]), "r"(a[1]), "r"(a[2]), "r"(a[3]), "r"(b0), "r"(b1));
}
__device__ __forceinline__ void mma1688(float* d, unsigned a0, unsigned a1, unsigned b0) {
  asm volatile("mma.sync.aligned.m16n8k8.row.col.f32.bf16.bf16.f32 {%0,%1,%2,%3}, {%4,%5}, {%6}, {%0,%1,%2,%3};"
               : "+f"(d[0]), "+f"(d[1]), "+f"(d[2]), "+f"(d[3]) : "r"(a0), "r"(a1), "r"(b0));
}
__device__ __forceinline__ uint64_t mkdesc(unsigned addr, unsigned lbo, unsigned sbo) {
  return (uint64_t)((addr >> 4) & 0x3fff) | ((uint64_t)(lbo >> 4) << 16) | ((uint64_t)(sbo >> 4) << 32) | (1ull << 62);
}
#define R8(b) "+f"(d[b]), "+f"(d[b + 1]), "+f"(d[b + 2]), "+f"(d[b + 3]), "+f"(d[b + 4]), "+f"(d[b + 5]), "+f"(d[b + 6]), "+f"(d[b + 7])
#define R32(b) R8(b), R8(b + 8), R8(b + 16), R8(b + 24)
__device__ __forceinline__ void wgmma_n256(float* d, uint64_t ad, uint64_t bd, int acc) {
  asm volatile(
      "{.reg .pred p; setp.ne.b32 p, %130, 0;\n"
      "wgmma.mma_async.sync.aligned.m64n256k16.f32.bf16.bf16 "
      "{%0,%1,%2,%3,%4,%5,%6,%7,%8,%9,%10,%11,%12,%13,%14,%15,%16,%17,%18,%19,%20,%21,%22,%23,%24,%25,%26,%27,%28,%29,%30,%31,"
      "%32,%33,%34,%35,%36,%37,%38,%39,%40,%41,%42,%43,%44,%45,%46,%47,%48,%49,%50,%51,%52,%53,%54,%55,%56,%57,%58,%59,%60,%61,%62,%63,"
      "%64,%65,%66,%67,%68,%69,%70,%71,%72,%73,%74,%75,%76,%77,%78,%79,%80,%81,%82,%83,%84,%85,%86,%87,%88,%89,%90,%91,%92,%93,%94,%95,"
      "%96,%97,%98,%99,%100,%101,%102,%103,%104,%105,%106,%107,%108,%109,%110,%111,%112,%113,%114,%115,%116,%117,%118,%119,%120,%121,%122,%123,%124,%125,%126,%127},"
      "%128, %129, p, 1, 1, 0, 1;}\n"
      : R32(0), R32(32), R32(64), R32(96)
      : "l"(ad), "l"(bd), "r"(acc));
}

__device__ __forceinline__ void wgmma_n128(float* d, uint64_t ad, uint64_t bd, int acc) {
  asm volatile(
      "{.reg .pred p; setp.ne.b32 p, %66, 0;\n"
      "wgmma.mma_async.sync.aligned.m64n128k16.f32.bf16.bf16 {%0,%1,%2,%3,%4,%5,%6,%7,%8,%9,%10,%11,%12,%13,%14,%15,%16,%17,%18,%19,%20,%21,%22,%23,%24,%25,%26,%27,%28,%29,%30,%31,%32,%33,%34,%35,%36,%37,%38,%39,%40,%41,%42,%43,%44,%45,%46,%47,%48,%49,%50,%51,%52,%53,%54,%55,%56,%57,%58,%59,%60,%61,%62,%63}, %64, %65, p, 1, 1, 0, 1;}\n"
      : R32(0), R32(32)
      : "l"(ad), "l"(bd), "r"(acc));
}

__device__ __forceinline__ void ln16(const float* x, float* o) {
  float s = 0;
#pragma unroll
  for (int i = 0; i < 16; i++) s += x[i];
#pragma unroll
  for (int of = 16; of > 0; of >>= 1) s += __shfl_xor_sync(~0u, s, of);
  float mean = s * (1.0f / DM);
  float v = 0;
#pragma unroll
  for (int i = 0; i < 16; i++) { float dd = x[i] - mean; v += dd * dd; }
#pragma unroll
  for (int of = 16; of > 0; of >>= 1) v += __shfl_xor_sync(~0u, v, of);
  float mb = bf16r(mean);
  float vb = bf16r(v * (1.0f / DM));
  float den = bf16r(sqrtf(bf16r(vb + 1e-5f)));
#pragma unroll
  for (int i = 0; i < 16; i++) o[i] = bf16r(__fdiv_rn(bf16r(x[i] - mb), den));
}
__global__ void __launch_bounds__(256) k_pre(const bf16* __restrict__ x, const char* wq, const char* wk, const char* wv, const char* wo) {
  int t = threadIdx.x, lane = t & 31, w = t >> 5;
  {
    int g2 = blockIdx.x * 256 + t, o = (g2 & 32767) * 128;
    asm volatile("prefetch.global.L2 [%0];" ::"l"((g2 < 32768 ? wk : wv) + o));
    asm volatile("prefetch.global.L2 [%0];" ::"l"((g2 < 32768 ? wq : wo) + o));
  }
  int row = blockIdx.x * 8 + w;
  const uint4* src = reinterpret_cast<const uint4*>(x + (size_t)row * DM);
  uint4 a = src[lane], b = src[lane + 32];
  unsigned u[8] = {a.x, a.y, a.z, a.w, b.x, b.y, b.z, b.w};
  float f[16], o[16], o2[16];
#pragma unroll
  for (int i = 0; i < 8; i++) { f[2 * i] = bf_lo(u[i]); f[2 * i + 1] = bf_hi(u[i]); }
  ln16(f, o);
  ln16(o, o2);
  uint4* d1 = reinterpret_cast<uint4*>(g_xn + (size_t)row * DM);
  uint4* d2 = reinterpret_cast<uint4*>(g_y + (size_t)row * DM);
  d1[lane] = make_uint4(pack_bf16(o[0], o[1]), pack_bf16(o[2], o[3]), pack_bf16(o[4], o[5]), pack_bf16(o[6], o[7]));
  d1[lane + 32] = make_uint4(pack_bf16(o[8], o[9]), pack_bf16(o[10], o[11]), pack_bf16(o[12], o[13]), pack_bf16(o[14], o[15]));
  d2[lane] = make_uint4(pack_bf16(o2[0], o2[1]), pack_bf16(o2[2], o2[3]), pack_bf16(o2[4], o2[5]), pack_bf16(o2[6], o2[7]));
  d2[lane + 32] = make_uint4(pack_bf16(o2[8], o2[9]), pack_bf16(o2[10], o2[11]), pack_bf16(o2[12], o2[13]), pack_bf16(o2[14], o2[15]));
  int gt = blockIdx.x * 256 + t;
  uint4 z = make_uint4(0, 0, 0, 0);
  if (gt < 16384) reinterpret_cast<uint4*>(g_part)[gt] = z;
  if (gt < (int)(sizeof(Flags) / 4)) reinterpret_cast<unsigned*>(&g_flags)[gt] = 0;
}

struct Maps { CUtensorMap xn, y, h1, o, qkv_st, qkv_ld, g, wq, wk, wv, wo, w1, w2; };

#define NSTAGE 3
#define STAGE_BYTES 49152
#define B_STG (NSTAGE * STAGE_BYTES)
#define R_WO 0
#define R_T1 65536
#define R_T2 131072
#define R_RING 65536
#define RING_N 4
#define RING_BYTES 12288
#define R_MEM 196608
#define R_QS (R_MEM + 8448)
#define R_KS (R_QS + 1152)
#define R_OS (R_KS + 1152)
#define R_SOWN (R_OS + 2176)
#define R_SPEER (R_SOWN + 1280)
#define R_VM (R_SPEER + 1280)
#define R_VRED (R_VM + 2048)
#define R_RS (R_VRED + 6144)
#define SM_BAR (R_RS + 8192)
#define SMEM_TOTAL (SM_BAR + 256 + 1024)
#define MB_FULL 0
#define MB_EMPTY 8
#define MB_STGF 16
#define MB_STGE 17
#define MB_W0 18
#define MB_W1 19
#define MB_WO 20
#define MB_S 21
#define MB_V 22
#define MB_KVR 23
#define MB_KVF 24
#define MB_RS 25
#define MB_AG 26
#define SM_MISC (SM_BAR + 224)

#define N_KV 544
#define I_M1 544
#define I_Q 656
#define I_M2 912
#define I_POST 944
#define I_TAIL (I_POST + 16 * 32)
#define N_ITEMS (I_TAIL + 7 * 8 + 64 + 32 + 64)
enum { T_QKV = 0, T_M1 = 1, T_M2 = 2, T_ATT = 3, T_OUT = 4, T_OUTL = 5, T_RED = 6, T_REDL = 7 };
struct Item { int type, b, c, ks, hf; };
__device__ __forceinline__ Item decode_item(int i) {
  Item it; it.ks = 0; it.hf = 0;
  if (i < 64) { it.type = T_QKV; it.b = 0; it.c = 16 + (i >> 1); it.hf = 1 + (i & 1); }
  else if (i < N_KV) { it.type = T_QKV; it.b = (i - 32) >> 5; it.c = 16 + (i & 31); }
  else if (i < I_Q) { it.type = T_M1; it.b = (i - I_M1) / 7; it.c = (i - I_M1) % 7; }
  else if (i < I_M2) { it.type = T_QKV; it.b = (i - I_Q) >> 4; it.c = (i - I_Q) & 15; }
  else if (i < I_POST) { it.type = T_M2; it.b = (i - I_M2) >> 1; it.c = (i - I_M2) & 1; }
  else if (i < I_TAIL) {
    int x = i - I_POST, p = x >> 5, r = x & 31;
    if (r < 16) { it.type = T_ATT; it.b = p; it.c = r; }
    else if (r < 24) { it.type = T_OUT; it.b = p - 3; it.c = r & 1; it.ks = (r - 16) >> 1; }
    else { it.type = T_RED; it.b = p - 5; it.c = r - 24; }
  } else {
    int x = i - I_TAIL, r = x & 7;
    if (x < 16 || (x >= 24 && x < 40)) { int y = x < 16 ? x : x - 24; it.type = T_OUT; it.b = x < 16 ? 13 : 14; it.c = (y >> 1) & 1; it.ks = y >> 2; it.hf = 1 + (y & 1); }
    else if (x < 56) { it.type = T_RED; it.b = x < 24 ? 11 : 7 + (x >> 3); it.c = r; }
    else if (x < 120) { it.type = T_OUTL; it.b = 15; it.c = (x >> 1) & 1; it.ks = (x - 56) >> 2; it.hf = 1 + (x & 1); }
    else if (x < 152) { it.type = T_RED; it.b = 14; it.c = x - 120; it.ks = 1; }
    else { it.type = T_REDL; it.b = 15; it.c = x - 152; }
  }
  return it;
}
__device__ __forceinline__ int item_nkb(int type) { return type == T_M2 ? 28 : (type == T_OUT ? 16 : (type >= T_RED ? 1 : (type >= T_ATT ? 4 : 8))); }

__device__ __forceinline__ void st_async_b64(unsigned raddr, unsigned lo, unsigned hi, unsigned rmb) {
  asm volatile("st.async.weak.shared::cluster.mbarrier::complete_tx::bytes.v2.b32 [%0], {%1,%2}, [%3];" ::"r"(raddr), "r"(lo), "r"(hi), "r"(rmb) : "memory");
}
__device__ __forceinline__ void st_async_b32(unsigned raddr, unsigned v, unsigned rmb) {
  asm volatile("st.async.weak.shared::cluster.mbarrier::complete_tx::bytes.b32 [%0], %1, [%2];" ::"r"(raddr), "r"(v), "r"(rmb) : "memory");
}
__device__ __forceinline__ unsigned mapa(unsigned a, unsigned rank) {
  unsigned r; asm volatile("mapa.shared::cluster.u32 %0, %1, %2;" : "=r"(r) : "r"(a), "r"(rank)); return r;
}
__device__ __forceinline__ void sts64(unsigned a, unsigned x, unsigned y) { asm volatile("st.shared.v2.b32 [%0], {%1,%2};" ::"r"(a), "r"(x), "r"(y) : "memory"); }
__device__ __forceinline__ void sts128(unsigned a, uint4 v) { asm volatile("st.shared.v4.b32 [%0], {%1,%2,%3,%4};" ::"r"(a), "r"(v.x), "r"(v.y), "r"(v.z), "r"(v.w) : "memory"); }
__device__ __forceinline__ uint2 lds64(unsigned a) { uint2 v; asm volatile("ld.shared.v2.b32 {%0,%1}, [%2];" : "=r"(v.x), "=r"(v.y) : "r"(a) : "memory"); return v; }
__device__ __forceinline__ uint4 lds128(unsigned a) { uint4 v; asm volatile("ld.shared.v4.b32 {%0,%1,%2,%3}, [%4];" : "=r"(v.x), "=r"(v.y), "=r"(v.z), "=r"(v.w) : "r"(a) : "memory"); return v; }
__device__ __forceinline__ float lds32f(unsigned a) { float v; asm volatile("ld.shared.f32 %0, [%1];" : "=f"(v) : "r"(a) : "memory"); return v; }
#define spin_check(it) TRAP_IF(++it)
#define POLLV 0
#define BAR8 0
#define D_STAG 150
#define D_RED 540
#define D_PUB 0
#define DELAY(n) do { unsigned c0_, c1_; asm volatile("mov.u32 %0, %%clock;" : "=r"(c0_)); do { asm volatile("mov.u32 %0, %%clock;" : "=r"(c1_)); } while (c1_ - c0_ < (n)); } while (0)
#define VD 2
#define NPRE 3
#define SELP 1
#define SCALE_QK 0.08838834764831845f

__device__ __forceinline__ void rec_worker(const Maps& maps, unsigned sb, const bf16* __restrict__ mem0, const int c) {
  const int h = c >> 1, j = c & 1;
  const int t = opaque_tid(), lane = t & 31, w = t >> 5, g = lane >> 2, tq = lane & 3;
  const int m = lane >> 3, r8 = lane & 7, kh = w >> 2, et = w & 3;
  const unsigned bar = sb + SM_BAR;
  unsigned wq[16][4], wk[16][4], wo[8][4];
  const unsigned woff = (kh * 4) * 8192 + ((m >> 1) * 8 + r8) * 128 + (((et * 2 + (m & 1)) ^ r8) << 4);
  mbar_wait(bar + 8 * MB_W0, 0);
#pragma unroll
  for (int i = 0; i < 16; i++) {
    ldsm_x4_t(wq[i], sb + R_WO + woff + (i >> 2) * 8192 + (i & 3) * 2048);
    ldsm_x4_t(wk[i], sb + R_T1 + woff + (i >> 2) * 8192 + (i & 3) * 2048);
  }
  bar_sync(2, 288);
  if (t == 0) {
    fence_proxy_async_smem();
    mbar_expect_tx(bar + 8 * MB_WO, 65536);
    for (int kb = 0; kb < 2; kb++)
      for (int cb = 0; cb < 4; cb++) tma_load_2d(sb + R_WO + (kb * 4 + cb) * 8192, &maps.wo, j * 256 + cb * 64, h * 128 + kb * 64, bar + 8 * MB_WO);
  }
  mbar_wait(bar + 8 * MB_W1, 0);
  const unsigned pV = sb + R_T2 + woff;
  const unsigned rk = c & 7, peer = rk ^ 1, cl = c >> 3;
#define KEEP(x) x = __shfl_sync(~0u, x, lane)
  unsigned pA = sb + R_MEM + kh * 4096 + lane * 16;
  unsigned pW0 = sb + R_WO + (w >> 1) * 8192 + ((m >> 1) * 8 + r8) * 128 + ((((w & 1) * 4 + (m & 1)) ^ r8) << 4);
  unsigned pW1 = pW0 ^ 32;
  unsigned pVk = pV;
  unsigned aX = sb + R_VRED + et * 512 + lane * 16;
  unsigned aQKst = sb + (kh ? R_KS : R_QS) + r8 * 144 + (et * 16 + (m & 1) * 8) * 2;
  unsigned aL8 = sb + lane * 8;
  unsigned aSl = mapa(sb + R_SOWN + w * 256 + lane * 8, rk), aSr = mapa(sb + R_SPEER + w * 256 + lane * 8, peer);
  unsigned aVl = mapa(sb + R_VM + (j * 4 + et) * 256 + lane * 8, rk), aVr = mapa(sb + R_VM + (j * 4 + et) * 256 + lane * 8, peer);
  const unsigned mbSl = mapa(bar + 8 * MB_S, rk), mbSr = mapa(bar + 8 * MB_S, peer), mbVl = mbSl + 8, mbVr = mbSr + 8;
  unsigned aQ = sb + R_QS + r8 * 144 + m * 16;
  unsigned oKx = (et * 8 + r8) * 128 + ((m ^ r8) << 4);
  unsigned oVx = 4096 + (et >> 1) * 4096 + ((m >> 1) * 8 + r8) * 128 + ((((et & 1) * 4 + (m & 1)) ^ r8) << 4);
  unsigned aOst = sb + R_OS + r8 * 272 + (et * 32 + m * 8) * 2;
  unsigned aOld = sb + R_OS + r8 * 272 + m * 16;
  unsigned aVm = sb + R_VM + et * 512 + lane * 8;
  unsigned aRSr = mapa(sb + R_RS + (h & 3) * 2048 + (w & 1) * 1024 + lane * 8, j * 4 + (w >> 1));
  unsigned mbRSr = mapa(bar + 8 * MB_RS, j * 4 + (w >> 1));
  unsigned t8 = t * 8;
  KEEP(pA); KEEP(pW0); KEEP(pW1); KEEP(pVk); KEEP(aX); KEEP(aQKst); KEEP(aL8); KEEP(aSl); KEEP(aSr); KEEP(aVl); KEEP(aVr); KEEP(aQ); KEEP(oKx); KEEP(oVx);
  KEEP(aOst); KEEP(aOld); KEEP(aVm); KEEP(aRSr); KEEP(mbRSr); KEEP(t8);
  mbar_wait(bar + 8 * MB_WO, 0);
#pragma unroll
  for (int ks = 0; ks < 4; ks++) { ldsm_x4_t(wo[2 * ks], pW0 + ks * 2048); ldsm_x4_t(wo[2 * ks + 1], pW1 + ks * 2048); }
  {
    unsigned v[8];
#pragma unroll
    for (int q = 0; q < 8; q++) v[q] = __ldg(reinterpret_cast<const unsigned*>(mem0) + q * 256 + t);
    sts128(sb + R_MEM + t * 32, make_uint4(__byte_perm(v[0], v[1], 0x5410), __byte_perm(v[2], v[3], 0x5410), __byte_perm(v[4], v[5], 0x5410), __byte_perm(v[6], v[7], 0x5410)));
    sts128(sb + R_MEM + t * 32 + 16, make_uint4(__byte_perm(v[0], v[1], 0x7632), __byte_perm(v[2], v[3], 0x7632), __byte_perm(v[4], v[5], 0x7632), __byte_perm(v[6], v[7], 0x7632)));
  }
  bar_sync(1, 256);

#pragma unroll 1
  for (int s = 0;; s++) {
    const unsigned par = s & 1;
    const unsigned slot = s & (RING_N - 1), rpar = (s / RING_N) & 1;
    const unsigned ring = sb + R_RING + slot * RING_BYTES;
    asm volatile("" : "+r"(t8));
    RSTAMP(1);
    RSTAMP(2);
    float aq[4] = {0, 0, 0, 0}, ak[4] = {0, 0, 0, 0}, av[4] = {0, 0, 0, 0};
    {
      unsigned b[8][4], f1[8][4], f0[8][4];
#define VLD(i) do { ldsm_x4_t(b[i], pA + (i) * 512); ldsm_x4_t(f0[i], pVk + ((i) >> 1) * 8192 + ((i) & 1) * 4096); ldsm_x4_t(f1[i], pVk + ((i) >> 1) * 8192 + ((i) & 1) * 4096 + 2048); } while (0)
      VLD(0);
      if (VD > 1) VLD(1);
#pragma unroll
      for (int i = 0; i < 8; i++) {
        if (i + VD < 8) VLD(i + VD);
        mma16816(aq, wq[2 * i], b[i][0], b[i][1]); mma16816(ak, wk[2 * i], b[i][0], b[i][1]); mma16816(av, f0[i], b[i][0], b[i][1]);
        mma16816(aq, wq[2 * i + 1], b[i][2], b[i][3]); mma16816(ak, wk[2 * i + 1], b[i][2], b[i][3]); mma16816(av, f1[i], b[i][2], b[i][3]);
      }
    }
    RSTAMP(3);
#define STSF4(a, v) asm volatile("st.shared.v4.f32 [%0], {%1,%2,%3,%4};" ::"r"(a), "f"(v[0]), "f"(v[1]), "f"(v[2]), "f"(v[3]) : "memory")
    unsigned f[8][4];
#define WO_PREFETCH() do { _Pragma("unroll") for (int i = 0; i < NPRE; i++) { ldsm_x4_t(f[2 * i], pW0 + 32768 + i * 2048); ldsm_x4_t(f[2 * i + 1], pW1 + 32768 + i * 2048); } } while (0)
    if (kh) {
      STSF4(aX, aq);
      bar_sync(4 + et, 64);
      uint4 o = lds128(aX + 2048), o2 = lds128(aX + 4096);
      stsm_x2_t(aQKst, pack_bf16(ak[0] + __uint_as_float(o.x), ak[1] + __uint_as_float(o.y)), pack_bf16(ak[2] + __uint_as_float(o.z), ak[3] + __uint_as_float(o.w)));
      bar_arrive(1, 256);
      unsigned x = pack_bf16(av[0] + __uint_as_float(o2.x), av[1] + __uint_as_float(o2.y)), y = pack_bf16(av[2] + __uint_as_float(o2.z), av[3] + __uint_as_float(o2.w));
      st_async_b64(aVr, x, y, mbVr);
      st_async_b64(aVl, x, y, mbVl);
      if (s == NSEG - 1) {
        mbar_wait(bar + 8 * MB_V, par);
        bar_sync(8, 128);
        if (t == 128) mbar_arrive(bar + 8 * MB_KVR);
        break;
      }
      mbar_wait(bar + 8 * (MB_FULL + slot), rpar);
      unsigned vx[4][4];
      ldsm_x4_t(vx[0], ring + oVx); ldsm_x4_t(vx[1], ring + oVx + 2048); ldsm_x4_t(vx[2], ring + (oVx ^ 32)); ldsm_x4_t(vx[3], ring + (oVx ^ 32) + 2048);
      RSTAMP(4); RSTAMP(5); RSTAMP(6); RSTAMP(7);
      mbar_wait(bar + 8 * MB_S, par);
      RSTAMP(8);
      float sc[10];
#pragma unroll
      for (int i = 0; i < 5; i++) {
        uint2 o = lds64(aL8 + R_SOWN + i * 256), p = lds64(aL8 + R_SPEER + i * 256);
        sc[2 * i] = __uint_as_float(o.x) + __uint_as_float(p.x); sc[2 * i + 1] = __uint_as_float(o.y) + __uint_as_float(p.y);
      }
      mbar_wait(bar + 8 * MB_V, par);
      uint2 vm0 = lds64(aVm), vm1 = lds64(aVm + 256);
      float mx = fmaxf(fmaxf(fmaxf(sc[0], sc[1]), fmaxf(sc[2], sc[3])), fmaxf(fmaxf(fmaxf(sc[4], sc[5]), fmaxf(sc[6], sc[7])), fmaxf(sc[8], sc[9])));
      mx = fmaxf(mx, __shfl_xor_sync(~0u, mx, 1)); mx = fmaxf(mx, __shfl_xor_sync(~0u, mx, 2));
      const float nm = -mx * (SCALE_QK * LOG2E);
      unsigned p[5];
#pragma unroll
      for (int i = 0; i < 5; i++) p[i] = pack_bf16(ex2f(fmaf(sc[2 * i], SCALE_QK * LOG2E, nm)), ex2f(fmaf(sc[2 * i + 1], SCALE_QK * LOG2E, nm)));
      RSTAMP(9);
      float o0[4] = {0, 0, 0, 0}, o1[4] = {0, 0, 0, 0}, o3[4] = {0, 0, 0, 0}, o4[4] = {0, 0, 0, 0}, z0[4] = {0, 0, 0, 0}, z1[4] = {0, 0, 0, 0};
      const unsigned ones[4] = {0x3F803F80u, 0u, 0x3F803F80u, 0u};
      mma16816(z0, ones, p[0], p[1]); mma16816(z1, ones, p[2], p[3]);
      mma16816(o0, vx[0], p[0], p[1]); mma16816(o3, vx[2], p[0], p[1]);
      mma1688(z0, 0x3F803F80u, 0u, p[4]);
      mma16816(o1, vx[1], p[2], p[3]); mma16816(o4, vx[3], p[2], p[3]);
      mma1688(o0, vm0.x, vm0.y, p[4]); mma1688(o3, vm1.x, vm1.y, p[4]);
      float i0, i1;
      asm("rcp.approx.ftz.f32 %0, %1;" : "=f"(i0) : "f"(z0[0] + z1[0])); asm("rcp.approx.ftz.f32 %0, %1;" : "=f"(i1) : "f"(z0[1] + z1[1]));
      asm volatile("stmatrix.sync.aligned.m8n8.x4.trans.shared.b16 [%0], {%1,%2,%3,%4};" ::"r"(aOst), "r"(pack_bf16((o0[0] + o1[0]) * i0, (o0[1] + o1[1]) * i1)), "r"(pack_bf16((o0[2] + o1[2]) * i0, (o0[3] + o1[3]) * i1)),
                   "r"(pack_bf16((o3[0] + o4[0]) * i0, (o3[1] + o4[1]) * i1)), "r"(pack_bf16((o3[2] + o4[2]) * i0, (o3[3] + o4[3]) * i1)) : "memory");
      RSTAMP(10);
      bar_sync(1, 256);
      WO_PREFETCH();
    } else {
      STSF4(aX + 2048, ak); STSF4(aX + 4096, av);
      unsigned kb[8];
      mbar_wait(bar + 8 * (MB_FULL + slot), rpar);
      ldsm_x4(kb, ring + oKx); ldsm_x4(kb + 4, ring + (oKx ^ 64));
      bar_sync(4 + et, 64);
      uint4 o = lds128(aX);
      stsm_x2_t(aQKst, pack_bf16(aq[0] + __uint_as_float(o.x), aq[1] + __uint_as_float(o.y)), pack_bf16(aq[2] + __uint_as_float(o.z), aq[3] + __uint_as_float(o.w)));
      RSTAMP(4);
      bar_sync(1, 256);
      RSTAMP(5);
      if (s == NSEG - 1) break;
      unsigned qa[8], km[8];
      ldsm_x4(qa, aQ); ldsm_x4(qa + 4, aQ + 64);
      if (w == 3) { ldsm_x4(km, aQ + 1152); ldsm_x4(km + 4, aQ + 1152 + 64); }
      float s0[4] = {0, 0, 0, 0}, s1[4] = {0, 0, 0, 0};
      unsigned af[4][4];
#pragma unroll
      for (int i = 0; i < 4; i++) { af[i][0] = qa[2 * i]; af[i][1] = 0; af[i][2] = qa[2 * i + 1]; af[i][3] = 0; }
      mma16816(s0, af[0], kb[0], kb[1]); mma16816(s1, af[1], kb[2], kb[3]);
      mma16816(s0, af[2], kb[4], kb[5]); mma16816(s1, af[3], kb[6], kb[7]);
      if (w == 3) {
        float m0[4] = {0, 0, 0, 0}, m1[4] = {0, 0, 0, 0};
        mma16816(m0, af[0], km[0], km[1]); mma16816(m1, af[1], km[2], km[3]);
        mma16816(m0, af[2], km[4], km[5]); mma16816(m1, af[3], km[6], km[7]);
        unsigned x = __float_as_uint(m0[0] + m1[0]), y = __float_as_uint(m0[1] + m1[1]);
        st_async_b64(aSr + 256, x, y, mbSr); st_async_b64(aSl + 256, x, y, mbSl);
      }
      unsigned x = __float_as_uint(s0[0] + s1[0]), y = __float_as_uint(s0[1] + s1[1]);
      st_async_b64(aSr, x, y, mbSr); st_async_b64(aSl, x, y, mbSl);
      RSTAMP(6);
      WO_PREFETCH();
      RSTAMP(7); RSTAMP(8); RSTAMP(9); RSTAMP(10);
      bar_sync(1, 256);
    }
    RSTAMP(11);
    float d0[4] = {0, 0, 0, 0}, d1[4] = {0, 0, 0, 0}, e0[4] = {0, 0, 0, 0}, e1[4] = {0, 0, 0, 0};
    unsigned ob[4][4];
#pragma unroll
    for (int k2 = 0; k2 < 4; k2++) ldsm_x4(ob[k2], aOld + k2 * 64);
#pragma unroll
    for (int i = NPRE; i < 4; i++) { ldsm_x4_t(f[2 * i], pW0 + 32768 + i * 2048); ldsm_x4_t(f[2 * i + 1], pW1 + 32768 + i * 2048); }
    mma16816(d0, wo[0], ob[0][0], ob[0][1]); mma16816(d1, wo[1], ob[0][0], ob[0][1]);
    mma16816(e0, wo[2], ob[0][2], ob[0][3]); mma16816(e1, wo[3], ob[0][2], ob[0][3]);
    mma16816(d0, wo[4], ob[1][0], ob[1][1]); mma16816(d1, wo[5], ob[1][0], ob[1][1]);
    mma16816(e0, wo[6], ob[1][2], ob[1][3]); mma16816(e1, wo[7], ob[1][2], ob[1][3]);
    mma16816(d0, f[0], ob[2][0], ob[2][1]); mma16816(d1, f[1], ob[2][0], ob[2][1]);
    mma16816(e0, f[2], ob[2][2], ob[2][3]); mma16816(e1, f[3], ob[2][2], ob[2][3]);
    mma16816(d0, f[4], ob[3][0], ob[3][1]); mma16816(d1, f[5], ob[3][0], ob[3][1]);
    mma16816(e0, f[6], ob[3][2], ob[3][3]); mma16816(e1, f[7], ob[3][2], ob[3][3]);
    st_async_b64(aRSr, __float_as_uint(d0[0] + e0[0]), __float_as_uint(d0[1] + e0[1]), mbRSr);
    st_async_b64(aRSr + 256, __float_as_uint(d0[2] + e0[2]), __float_as_uint(d0[3] + e0[3]), mbRSr);
    st_async_b64(aRSr + 512, __float_as_uint(d1[0] + e1[0]), __float_as_uint(d1[1] + e1[1]), mbRSr);
    st_async_b64(aRSr + 768, __float_as_uint(d1[2] + e1[2]), __float_as_uint(d1[3] + e1[3]), mbRSr);
    RSTAMP(12);
    if (t == 128) {
      mbar_arrive(bar + 8 * (MB_EMPTY + slot)); mbar_arrive(bar + 8 * MB_KVR);
      mbar_expect_tx(bar + 8 * MB_S, 2560); mbar_expect_tx(bar + 8 * MB_V, 2048);
    }
    const unsigned tag = ((s >> 1) & 1) ^ 1;
    const char* gp = reinterpret_cast<const char*>(g_part);
    const unsigned goff = (par * 8 + rk) * 16384 + cl * 2048 + t8;
    unsigned mbA[8];
#pragma unroll
    for (int i = 0; i < 8; i++) mbA[i] = mapa(bar + 8 * MB_AG, i);
    const unsigned dlt = (R_MEM + rk * 1024) - (SM_BAR + 8 * MB_AG) + (t8 >> 1);
    mbar_wait(bar + 8 * MB_RS, par);
    RSTAMP(13);
    uint2 a[8];
    {
      uint2 x0 = lds64(sb + R_RS + t8), x1 = lds64(sb + R_RS + 2048 + t8), x2 = lds64(sb + R_RS + 4096 + t8), x3 = lds64(sb + R_RS + 6144 + t8);
      float r0 = (__uint_as_float(x0.x) + __uint_as_float(x1.x)) + (__uint_as_float(x2.x) + __uint_as_float(x3.x));
      float r1 = (__uint_as_float(x0.y) + __uint_as_float(x1.y)) + (__uint_as_float(x2.y) + __uint_as_float(x3.y));
      a[0].x = (__float_as_uint(r0) & ~1u) | tag; a[0].y = (__float_as_uint(r1) & ~1u) | tag;
      asm volatile("st.relaxed.gpu.global.v2.u32 [%0], {%1,%2};" ::"l"(gp + goff), "r"(a[0].x), "r"(a[0].y) : "memory");
    }
    RSTAMP(14);
    if (t == 128) mbar_expect_tx(bar + 8 * MB_RS, 8192);
    {
      unsigned it = 0;
#define PLOAD(a) _Pragma("unroll") for (int i = 1; i < 8; i++) a[i] = ldv2_relaxed(gp + (goff ^ (i * 2048)))
#define PAND(a) (((a[1].x & a[1].y) & (a[2].x & a[2].y) & (a[3].x & a[3].y)) & ((a[4].x & a[4].y) & (a[5].x & a[5].y)) & ((a[6].x & a[6].y) & (a[7].x & a[7].y)))
#define POR(a) (((a[1].x | a[1].y) | (a[2].x | a[2].y) | (a[3].x | a[3].y)) | ((a[4].x | a[4].y) | (a[5].x | a[5].y)) | ((a[6].x | a[6].y) | (a[7].x | a[7].y)))
#define POK(a) (((tag ? PAND(a) : ~POR(a)) & 1u) != 0)
      if (D_RED) DELAY(D_RED);
      PLOAD(a);
      while (!POK(a)) {
#pragma unroll
        for (int i = 1; i < 8; i++) if (((a[i].x ^ tag) | (a[i].y ^ tag)) & 1u) a[i] = ldv2_relaxed(gp + (goff ^ (i * 2048)));
        spin_check(it);
      }
    }
    RSTAMP(15);
    {
#define AF(i, c) __uint_as_float(a[i].c)
      unsigned u = pack_bf16(((AF(0, x) + AF(1, x)) + (AF(2, x) + AF(3, x))) + ((AF(4, x) + AF(5, x)) + (AF(6, x) + AF(7, x))),
                             ((AF(0, y) + AF(1, y)) + (AF(2, y) + AF(3, y))) + ((AF(4, y) + AF(5, y)) + (AF(6, y) + AF(7, y))));
      __syncwarp();
#pragma unroll
      for (int i = 0; i < 8; i++) st_async_b32(mbA[i] + dlt, u, mbA[i]);
    }
    mbar_wait(bar + 8 * MB_KVF, par);
    mbar_wait(bar + 8 * MB_AG, par);
    if (t == 128) mbar_expect_tx(bar + 8 * MB_AG, 8192);
  }
}

__device__ __forceinline__ void rec_ring(const Maps& maps, unsigned sb, const int c) {
  const int h = c >> 1, j = c & 1;
  const unsigned bar = sb + SM_BAR;
  const int lane = threadIdx.x & 31;
  __syncwarp();
  bar_sync(2, 288);
  if (lane == 0) {
    fence_proxy_async_smem();
    for (int s = 0; s < NSEG; s++) {
      unsigned slot = s & (RING_N - 1);
      if ((s & 3) == 0 && !DBGMODE) {
        wait_flag_ge(&g_flags.qkv[(s >> 2) * 48 + 16 + (h >> 1)], 2);
        wait_flag_ge(&g_flags.qkv[(s >> 2) * 48 + 32 + (h >> 1)], 2);
        fence_proxy_async();
      }
      if (s >= RING_N) mbar_wait_sleep(bar + 8 * (MB_EMPTY + slot), ((s / RING_N) - 1) & 1);
      unsigned dst = sb + R_RING + slot * RING_BYTES, mb = bar + 8 * (MB_FULL + slot);
      mbar_expect_tx(mb, RING_BYTES);
      tma_load_2d(dst, &maps.qkv_ld, HD + h * 128 + j * 64, s * SEG, mb);
      tma_load_2d(dst + 4096, &maps.qkv_ld, 2 * HD + h * 128, s * SEG, mb);
      tma_load_2d(dst + 8192, &maps.qkv_ld, 2 * HD + h * 128 + 64, s * SEG, mb);
    }
  }
}
__device__ __forceinline__ void rec_copy(unsigned sb, const int c) {
  const int h = c >> 1, j = c & 1;
  const unsigned bar = sb + SM_BAR;
  const int lane = threadIdx.x & 31;
  for (int s = 0; s < NSEG; s++) {
    if (s < NSEG - 1) mbar_wait_sleep(bar + 8 * MB_KVR, s & 1); else mbar_wait(bar + 8 * MB_KVR, s & 1);
    uint4 k0 = lds128(sb + R_KS + (lane >> 3) * 144 + (lane & 7) * 16), k1 = lds128(sb + R_KS + (4 + (lane >> 3)) * 144 + (lane & 7) * 16);
    uint2 v[4];
#pragma unroll
    for (int i = 0; i < 4; i++) v[i] = lds64(sb + R_VM + (j * 4 + i) * 256 + lane * 8);
    __syncwarp();
    if (lane == 0) mbar_arrive(bar + 8 * MB_KVF);
    bf16* kd = g_km + ((size_t)(s * NH + h) * NMEM) * DH + j * 64;
    *reinterpret_cast<uint4*>(kd + (lane >> 3) * DH + (lane & 7) * 8) = k0;
    *reinterpret_cast<uint4*>(kd + (4 + (lane >> 3)) * DH + (lane & 7) * 8) = k1;
    unsigned* vd = reinterpret_cast<unsigned*>(g_vmt) + ((size_t)(s * NH + h) * DH + j * 64) * 4;
#pragma unroll
    for (int i = 0; i < 4; i++) { vd[(i * 16) * 4 + lane] = v[i].x; vd[(i * 16 + 8) * 4 + lane] = v[i].y; }
    __syncwarp();
    if (lane == 0) st_release(&g_flags.rec[c], s + 1);
  }
}

__device__ __forceinline__ void bulk_producer(const Maps& maps, unsigned sb, int* misc) {
  const unsigned bar = sb + SM_BAR;
  const int lane = threadIdx.x & 31;
  unsigned st = 0, ph = 0, seq = 0;
  while (true) {
    int idx = 0;
    if (lane == 0) idx = (int)atomicAdd(&g_flags.ctr, 1u);
    idx = __shfl_sync(~0u, idx, 0);
    if (idx >= N_ITEMS) {
      if (lane == 0) {
        mbar_wait(bar + 8 * (MB_EMPTY + st), ph ^ 1);
        misc[seq & 3] = -1;
        mbar_arrive(bar + 8 * (MB_FULL + st));
      }
      break;
    }
    if (lane == 0) ISTAMP(idx, 0);
    Item it = decode_item(idx);
    if (it.b < 0) continue;
    const CUtensorMap* mp; int c0, c1, dc0, dc1; unsigned doff;
    const unsigned* fl = nullptr; unsigned tgt = 1; int nbox = 5, rdy = 0;
    if (it.type == T_ATT) {
      mp = &maps.qkv_ld; nbox = 12; doff = lane * 4096;
      c0 = (lane >> 2) * HD + it.c * 256 + (lane & 1) * 64; c1 = it.b * 128 + ((lane >> 1) & 1) * 32; dc0 = dc1 = 0;
      if (lane < 3) fl = &g_flags.qkv[it.b * 48 + lane * 16 + it.c];
      tgt = 2;
      bool ok = true;
      if (lane >= 4 && lane < 8) ok = ld_acquire(&g_flags.rec[it.c * 4 + lane - 4]) >= (unsigned)(it.b * 4 + 4);
      rdy = __all_sync(~0u, ok) ? 65536 : 0;
    } else {
      int k0 = 0, nb0 = it.c * 256;
      if (it.type == T_QKV) { mp = lane == 0 ? &maps.xn : (it.c < 16 ? &maps.wq : (it.c < 32 ? &maps.wk : &maps.wv)); nb0 = (it.c & 15) * 256; }
      else if (it.type == T_M1) mp = lane == 0 ? &maps.y : &maps.w1;
      else if (it.type == T_M2) { mp = lane == 0 ? &maps.h1 : &maps.w2; fl = &g_flags.h1[it.b]; tgt = 7; }
      else {
        mp = lane == 0 ? &maps.o : &maps.wo;
        if (it.type == T_OUT) { k0 = it.ks * 1024; fl = &g_flags.o[it.b * 4 + it.ks]; tgt = 4; }
        else if (it.type == T_OUTL) { k0 = it.ks * 256; fl = &g_flags.o16[it.ks]; }
        else if (lane == 1) { fl = &g_flags.g[it.b]; tgt = 2; }
        else { fl = &g_flags.p[it.b]; tgt = it.type == T_RED ? (it.b >= 13 ? 16 : 8) : 64; }
      }
      if (lane > (it.type >= T_RED ? 1 : 0)) fl = nullptr;
      if (it.hf) { nbox = 3; nb0 += (it.hf - 1) * 128; }
      if (lane == 0) { c0 = k0; c1 = it.b * 128; dc0 = 64; dc1 = 0; doff = 0; }
      else { c0 = nb0 + (lane - 1) * 64; c1 = k0; dc0 = 0; dc1 = 64; doff = 8192 + lane * 8192; }
    }
    if (fl) wait_flag_ge(fl, tgt);
    __syncwarp();
    fence_proxy_async();
    if (lane == 0) ISTAMP(idx, 1);
    const int nkb = item_nkb(it.type);
    for (int kb = 0; kb < nkb; kb++) {
      const unsigned mb = bar + 8 * (MB_FULL + st);
      mbar_wait(bar + 8 * (MB_EMPTY + st), ph ^ 1);
      if (lane == 0) {
        if (kb == 0) misc[seq & 3] = idx | rdy;
        if (it.type >= T_RED) mbar_arrive(mb); else mbar_expect_tx(mb, it.hf ? 32768 : STAGE_BYTES);
      }
      if (it.type == T_ATT) { if (lane < 12) tma_load_2d(sb + st * STAGE_BYTES + doff, mp, c0 + (kb & 1) * 128, c1 + (kb >> 1) * 64, mb); }
      else if (lane < nbox && it.type < T_RED) tma_load_2d(sb + st * STAGE_BYTES + doff, mp, c0 + kb * dc0, c1 + kb * dc1, mb);
      __syncwarp();
      if (++st == NSTAGE) { st = 0; ph ^= 1; }
    }
    seq++;
  }
}
__device__ __forceinline__ void bulk_store(const Maps& maps, unsigned sb, volatile int* misc) {
  const unsigned bar = sb + SM_BAR;
  unsigned ph = 0;
  while (true) {
    mbar_wait(bar + 8 * MB_STGF, ph); ph ^= 1;
    int idx = misc[4];
    if (idx < 0) break;
    Item it = decode_item(idx);
    const CUtensorMap* mp = it.type == T_QKV ? &maps.qkv_st : (it.type == T_M1 ? &maps.h1 : (it.type == T_M2 ? &maps.g : &maps.o));
    unsigned* flag = it.type == T_QKV ? &g_flags.qkv[it.b * 48 + it.c] : (it.type == T_M1 ? &g_flags.h1[it.b] : (it.type == T_M2 ? &g_flags.g[it.b] : (it.b == 15 ? &g_flags.o16[it.c] : &g_flags.o[it.b * 4 + (it.c >> 2)])));
    for (int i = 0; i < (it.hf ? 2 : 4); i++) tma_store_2d(mp, sb + B_STG + i * 16384, it.c * 256 + (it.hf >> 1) * 128 + i * 64, it.b * 128);
    asm volatile("cp.async.bulk.commit_group;" ::: "memory");
    asm volatile("cp.async.bulk.wait_group.read 0;" ::: "memory");
    mbar_arrive(bar + 8 * MB_STGE);
    asm volatile("cp.async.bulk.wait_group 0;" ::: "memory");
    fence_proxy_async();
    red_release_add(flag, it.type == T_QKV && !it.hf ? 2 : 1);
    ISTAMP(idx, 3);
  }
}
__device__ __forceinline__ float rcpf(float x) { float y; asm("rcp.approx.ftz.f32 %0, %1;" : "=f"(y) : "f"(x)); return y; }
__device__ __forceinline__ float gelu_t(float x) {
  float e = ex2f(x * fmaf(x * x, -2.0f * LOG2E * 0.7978845608028654f * 0.044715f, -2.0f * LOG2E * 0.7978845608028654f));
  return x * rcpf(1.0f + e);
}
__device__ __forceinline__ float silu_f(float x) { return x * rcpf(1.0f + ex2f(-LOG2E * x)); }
__device__ __forceinline__ unsigned badd2(unsigned a, unsigned b) { unsigned r; asm("add.rn.bf16x2 %0, %1, %2;" : "=r"(r) : "r"(a), "r"(b)); return r; }

__device__ __forceinline__ void final_out(bf16* __restrict__ out, const bf16* __restrict__ x, size_t o, float4 s) {
  uint2 gv = __ldcg(reinterpret_cast<const uint2*>(g_g + o)), xv = __ldg(reinterpret_cast<const uint2*>(x + o));
  uint2 r;
  r.x = pack_bf16(bf_lo(xv.x) + bf16r(bf16r(s.x) * bf_lo(gv.x)), bf_hi(xv.x) + bf16r(bf16r(s.y) * bf_hi(gv.x)));
  r.y = pack_bf16(bf_lo(xv.y) + bf16r(bf16r(s.z) * bf_lo(gv.y)), bf_hi(xv.y) + bf16r(bf16r(s.w) * bf_hi(gv.y)));
  *reinterpret_cast<uint2*>(out + o) = r;
}
__device__ __forceinline__ void bulk_att_load(unsigned* km, unsigned* vm, int b, int hp, int kb, int w, int lane) {
  const int g = lane >> 2, tq = lane & 3, seg = w >> 2, eh = w & 1;
  const int head = hp * 2 + (kb & 1), sg = b * 4 + (kb >> 1) * 2 + seg;
  const unsigned* kmp = reinterpret_cast<const unsigned*>(g_km + ((size_t)(sg * NH + head) * NMEM + g) * DH) + tq;
  const unsigned* vmp = reinterpret_cast<const unsigned*>(g_vmt) + ((size_t)(sg * NH + head) * DH + eh * 64) * 4 + lane;
#pragma unroll
  for (int i = 0; i < 16; i++) asm volatile("ld.global.cg.u32 %0, [%1];" : "=r"(km[i]) : "l"(kmp + i * 4) : "memory");
#pragma unroll
  for (int i = 0; i < 8; i++) asm volatile("ld.global.cg.u32 %0, [%1];" : "=r"(vm[i]) : "l"(vmp + i * 32) : "memory");
}
__device__ __forceinline__ void bulk_att_stage(unsigned sa, unsigned stg, const unsigned* km, const unsigned* vm, int kb, int w, int lane) {
  const int g = lane >> 2, tq = lane & 3, m = lane >> 3, r8 = lane & 7;
  const int seg = w >> 2, mt = (w >> 1) & 1, eh = w & 1;
  float s[5][4];
#pragma unroll
  for (int i = 0; i < 5; i++) { s[i][0] = s[i][1] = s[i][2] = s[i][3] = 0; }
  const unsigned qb = sa + (0 * 2 + seg) * 8192, kbs = sa + (1 * 2 + seg) * 8192, vb = sa + (2 * 2 + seg) * 8192 + eh * 4096;
  unsigned qa[8][4];
#pragma unroll
  for (int ks = 0; ks < 8; ks++) {
    int row = mt * 16 + (m & 1) * 8 + r8;
    ldsm_x4(qa[ks], qb + (ks >> 2) * 4096 + row * 128 + ((((ks & 3) * 2 + (m >> 1)) ^ r8) << 4));
    unsigned kf[4];
    int krow = (m >> 1) * 8 + r8;
    unsigned ka = kbs + (ks >> 2) * 4096 + krow * 128 + ((((ks & 3) * 2 + (m & 1)) ^ r8) << 4);
    ldsm_x4(kf, ka);
    mma16816(s[0], qa[ks], kf[0], kf[1]); mma16816(s[1], qa[ks], kf[2], kf[3]);
    if (mt) { ldsm_x4(kf, ka + 2048); mma16816(s[2], qa[ks], kf[0], kf[1]); mma16816(s[3], qa[ks], kf[2], kf[3]); }
  }
#pragma unroll
  for (int ks = 0; ks < 8; ks++) mma16816(s[4], qa[ks], km[2 * ks], km[2 * ks + 1]);
  float mx0 = -INFINITY, mx1 = -INFINITY;
  const int t0 = mt * 16 + g, t1 = t0 + 8;
#pragma unroll
  for (int i = 0; i < 5; i++) {
#pragma unroll
    for (int e = 0; e < 4; e++) {
      float v = s[i][e];
      if (i < 4) { int kj = i * 8 + 2 * tq + (e & 1); if (kj > (e < 2 ? t0 : t1)) v = -INFINITY; }
      s[i][e] = v;
      if (e < 2) mx0 = fmaxf(mx0, v); else mx1 = fmaxf(mx1, v);
    }
  }
  mx0 = fmaxf(mx0, __shfl_xor_sync(~0u, mx0, 1)); mx0 = fmaxf(mx0, __shfl_xor_sync(~0u, mx0, 2));
  mx1 = fmaxf(mx1, __shfl_xor_sync(~0u, mx1, 1)); mx1 = fmaxf(mx1, __shfl_xor_sync(~0u, mx1, 2));
  float sm0 = 0, sm1 = 0;
#pragma unroll
  for (int i = 0; i < 5; i++) {
    s[i][0] = ex2f((s[i][0] - mx0) * (SCALE_QK * LOG2E)); s[i][1] = ex2f((s[i][1] - mx0) * (SCALE_QK * LOG2E));
    s[i][2] = ex2f((s[i][2] - mx1) * (SCALE_QK * LOG2E)); s[i][3] = ex2f((s[i][3] - mx1) * (SCALE_QK * LOG2E));
    sm0 += s[i][0] + s[i][1]; sm1 += s[i][2] + s[i][3];
  }
  sm0 += __shfl_xor_sync(~0u, sm0, 1); sm0 += __shfl_xor_sync(~0u, sm0, 2);
  sm1 += __shfl_xor_sync(~0u, sm1, 1); sm1 += __shfl_xor_sync(~0u, sm1, 2);
  const float i0 = __fdividef(1.0f, sm0), i1 = __fdividef(1.0f, sm1);
  unsigned pa[2][4], pm0, pm1;
#pragma unroll
  for (int kk = 0; kk < 2; kk++) {
    pa[kk][0] = pack_bf16(s[2 * kk][0] * i0, s[2 * kk][1] * i0); pa[kk][1] = pack_bf16(s[2 * kk][2] * i1, s[2 * kk][3] * i1);
    pa[kk][2] = pack_bf16(s[2 * kk + 1][0] * i0, s[2 * kk + 1][1] * i0); pa[kk][3] = pack_bf16(s[2 * kk + 1][2] * i1, s[2 * kk + 1][3] * i1);
  }
  pm0 = pack_bf16(s[4][0] * i0, s[4][1] * i0); pm1 = pack_bf16(s[4][2] * i1, s[4][3] * i1);
  const int orow = (kb >> 1) * 64 + seg * 32 + mt * 16 + (m & 1) * 8 + r8;
  const unsigned ob = stg + ((kb & 1) * 2 + eh) * 16384 + orow * 128;
#pragma unroll
  for (int cp = 0; cp < 4; cp++) {
    float o0[4] = {0, 0, 0, 0}, o1[4] = {0, 0, 0, 0};
    mma1688(o0, pm0, pm1, vm[2 * cp]); mma1688(o1, pm0, pm1, vm[2 * cp + 1]);
    unsigned vf[4];
    int row = (m & 1) * 8 + r8;
    unsigned va = vb + row * 128 + (((cp * 2 + (m >> 1)) ^ r8) << 4);
    ldsm_x4_t(vf, va);
    mma16816(o0, pa[0], vf[0], vf[1]); mma16816(o1, pa[0], vf[2], vf[3]);
    if (mt) { ldsm_x4_t(vf, va + 2048); mma16816(o0, pa[1], vf[0], vf[1]); mma16816(o1, pa[1], vf[2], vf[3]); }
    stsm_x4(ob + (((cp * 2 + (m >> 1)) ^ r8) << 4), pack_bf16(o0[0], o0[1]), pack_bf16(o0[2], o0[3]), pack_bf16(o1[0], o1[1]), pack_bf16(o1[2], o1[3]));
  }
}

__device__ __forceinline__ void bulk_worker(unsigned sb, volatile int* misc, const bf16* __restrict__ x, const bf16* __restrict__ b1, const bf16* __restrict__ b2, bf16* __restrict__ out) {
  const int t = threadIdx.x, lane = t & 31, w = t >> 5, wg = w >> 2, g = lane >> 2, tq = lane & 3, m = lane >> 3, r8 = lane & 7;
  const unsigned bar = sb + SM_BAR;
  unsigned st = 0, ph = 0, seq = 0, sph = 0;
  float d[128];
  while (true) {
    mbar_wait(bar + 8 * (MB_FULL + st), ph);
    const int idr = misc[seq & 3]; seq++;
    const int idx = idr & 65535;
    if (idr < 0 || idx >= N_ITEMS) break;
    if (t == 0) ISTAMP(idx, 2);
    const Item it = decode_item(idx);
    const int nkb = item_nkb(it.type);
    if (it.type == T_ATT) {
      unsigned km[16], vm[8], kn[16], vn[8];
      const bool pref = idr >= 65536;
      if (pref) bulk_att_load(kn, vn, it.b, it.c, 0, w, lane);
      mbar_wait(bar + 8 * MB_STGE, sph ^ 1);
#pragma unroll 1
      for (int kb = 0; kb < 4; kb++) {
        if (!pref && !(kb & 1)) {
          if (lane < 4) wait_step_ge(&g_flags.rec[it.c * 4 + lane], it.b * 4 + (kb >> 1) * 2 + wg + 1);
          __syncwarp();
          bulk_att_load(kn, vn, it.b, it.c, kb, w, lane);
        }
        if (kb) mbar_wait(bar + 8 * (MB_FULL + st), ph);
#pragma unroll
        for (int i = 0; i < 16; i++) km[i] = kn[i];
#pragma unroll
        for (int i = 0; i < 8; i++) vm[i] = vn[i];
        if (pref ? kb != 3 : !(kb & 1)) bulk_att_load(kn, vn, it.b, it.c, kb + 1, w, lane);
        bulk_att_stage(sb + st * STAGE_BYTES, sb + B_STG, km, vm, kb, w, lane);
        __syncwarp();
        if (lane == 0) mbar_arrive(bar + 8 * (MB_EMPTY + st));
        if (++st == NSTAGE) { st = 0; ph ^= 1; }
      }
      if (t == 0) misc[4] = idx;
      fence_proxy_async_smem();
      mbar_arrive(bar + 8 * MB_STGF); sph ^= 1;
      continue;
    }
    if (it.type >= T_RED) {
      __syncwarp();
      if (lane == 0) mbar_arrive(bar + 8 * (MB_EMPTY + st));
      if (++st == NSTAGE) { st = 0; ph ^= 1; }
      if (it.type == T_RED) {
#pragma unroll 2
        for (int i = 0; i < (it.ks ? 2 : 8); i++) {
          size_t o = ((size_t)it.b * 128 + it.c * (it.ks ? 4 : 16) + i * 2 + (t >> 7)) * DM + (t & 127) * 4;
          float4 a = __ldcg(reinterpret_cast<const float4*>(g_opart + o)), b = __ldcg(reinterpret_cast<const float4*>(g_opart + o + (size_t)S_TOK * DM));
          float4 c = __ldcg(reinterpret_cast<const float4*>(g_opart + o + (size_t)2 * S_TOK * DM)), e = __ldcg(reinterpret_cast<const float4*>(g_opart + o + (size_t)3 * S_TOK * DM));
          final_out(out, x, o, make_float4((a.x + b.x) + (c.x + e.x), (a.y + b.y) + (c.y + e.y), (a.z + b.z) + (c.z + e.z), (a.w + b.w) + (c.w + e.w)));
        }
      } else {
        size_t ol = ((size_t)it.c * 2 + (t >> 7)) * DM + (t & 127) * 4;
        float4 v[16];
#pragma unroll
        for (int i = 0; i < 16; i++) v[i] = __ldcg(reinterpret_cast<const float4*>(g_opl + ol + (size_t)i * 128 * DM));
#pragma unroll
        for (int st2 = 1; st2 < 16; st2 <<= 1)
#pragma unroll
          for (int i = 0; i < 16; i += 2 * st2) { v[i].x += v[i + st2].x; v[i].y += v[i + st2].y; v[i].z += v[i + st2].z; v[i].w += v[i + st2].w; }
        final_out(out, x, ol + (size_t)15 * 128 * DM, v[0]);
      }
      if (t == 0) ISTAMP(idx, 3);
      continue;
    }
    unsigned pst = 0, bv[32];
#pragma unroll
    for (int i = 0; i < 128; i++) d[i] = 0.0f;
    if (it.type == T_M1 || it.type == T_M2) {
      const unsigned* bp = reinterpret_cast<const unsigned*>((it.type == T_M1 ? b1 : b2) + it.c * 256) + tq;
#pragma unroll
      for (int i = 0; i < 32; i++) asm volatile("ld.global.nc.u32 %0, [%1];" : "=r"(bv[i]) : "l"(bp + i * 4));
    } else {
#pragma unroll
      for (int i = 0; i < 32; i++) bv[i] = 0;
    }
#define KLOOP(WG) \
    for (int kb = 0; kb < nkb; kb++) { \
      if (kb) mbar_wait(bar + 8 * (MB_FULL + st), ph); \
      unsigned sa = sb + st * STAGE_BYTES; \
      uint64_t ad = mkdesc(sa + wg * 8192, 16, 1024), bd = mkdesc(sa + 16384, 8192, 1024); \
      asm volatile("wgmma.fence.sync.aligned;" ::: "memory"); \
      _Pragma("unroll") for (int k = 0; k < 4; k++) WG(d, ad + k * 2, bd + k * 128, (kb | k) != 0); \
      asm volatile("wgmma.commit_group.sync.aligned;" ::: "memory"); \
      if (kb) { \
        asm volatile("wgmma.wait_group.sync.aligned 1;" ::: "memory"); \
        if (lane == 0) mbar_arrive(bar + 8 * (MB_EMPTY + pst)); \
      } \
      pst = st; \
      if (++st == NSTAGE) { st = 0; ph ^= 1; } \
    } \
    asm volatile("wgmma.wait_group.sync.aligned 0;" ::: "memory");
    if (it.hf) { KLOOP(wgmma_n128) } else { KLOOP(wgmma_n256) }
    if (lane == 0) mbar_arrive(bar + 8 * (MB_EMPTY + pst));
    if (it.type >= T_OUT) {
      const int col = it.c * 256 + (it.hf >> 1) * 128 + 2 * tq;
      float* pp = it.type == T_OUT ? g_opart + ((size_t)it.ks * S_TOK + it.b * 128 + w * 16 + g) * DM + col : g_opl + ((size_t)it.ks * 128 + w * 16 + g) * DM + col;
#pragma unroll
      for (int i = 0; i < 32; i++) {
        if (i == 16 && it.hf) break;
        __stcg(reinterpret_cast<float2*>(pp + i * 8), make_float2(d[4 * i], d[4 * i + 1]));
        __stcg(reinterpret_cast<float2*>(pp + 8 * DM + i * 8), make_float2(d[4 * i + 2], d[4 * i + 3]));
      }
      bar_sync(1, 256);
      if (t == 0) { red_release_add(&g_flags.p[it.b], 1); ISTAMP(idx, 3); }
      continue;
    }
#define ACT(F) _Pragma("unroll") for (int i = 0; i < 32; i++) { \
        unsigned u0 = badd2(pack_bf16(d[4 * i], d[4 * i + 1]), bv[i]), u1 = badd2(pack_bf16(d[4 * i + 2], d[4 * i + 3]), bv[i]); \
        d[4 * i] = F(bf_lo(u0)); d[4 * i + 1] = F(bf_hi(u0)); d[4 * i + 2] = F(bf_lo(u1)); d[4 * i + 3] = F(bf_hi(u1)); }
    if (it.type == T_M1) { ACT(gelu_t) } else if (it.type == T_M2) { ACT(silu_f) }
    mbar_wait(bar + 8 * MB_STGE, sph ^ 1);
    {
      const unsigned ob = sb + B_STG + (w * 16 + (m & 1) * 8 + r8) * 128;
#pragma unroll
      for (int i = 0; i < 16; i++)
        if (i < 8 || !it.hf) stsm_x4(ob + (i >> 2) * 16384 + ((((i & 3) * 2 + (m >> 1)) ^ r8) << 4), pack_bf16(d[8 * i], d[8 * i + 1]), pack_bf16(d[8 * i + 2], d[8 * i + 3]),
                pack_bf16(d[8 * i + 4], d[8 * i + 5]), pack_bf16(d[8 * i + 6], d[8 * i + 7]));
    }
    if (t == 0) misc[4] = idx;
    fence_proxy_async_smem();
    mbar_arrive(bar + 8 * MB_STGF); sph ^= 1;
  }
  mbar_wait(bar + 8 * MB_STGE, sph ^ 1);
  if (t == 0) misc[4] = -1;
  mbar_arrive(bar + 8 * MB_STGF);
}

__global__ void __launch_bounds__(384, 1)
k_main(const __grid_constant__ Maps maps, const bf16* __restrict__ x, const bf16* __restrict__ mem0, const bf16* __restrict__ b1, const bf16* __restrict__ b2, bf16* __restrict__ out, unsigned recmask) {
  extern __shared__ unsigned char smem_raw[];
  const unsigned sraw = smem_u32(smem_raw);
  const unsigned sb = (sraw + 1023u) & ~1023u;
  int* misc = reinterpret_cast<int*>(smem_raw + (sb - sraw) + SM_MISC);
  const int w = threadIdx.x >> 5;
  const bool helper = recmask == 0;
  const unsigned kc = blockIdx.x / CLS;
  const bool rec = kc < 32 && ((recmask >> kc) & 1);
  const int c = __popc(recmask & ((1u << (kc & 31)) - 1)) * CLS + (blockIdx.x & (CLS - 1));
  if (threadIdx.x == 0) {
    const unsigned bar = sb + SM_BAR;
    for (int i = 0; i < 8; i++) { mbar_init(bar + 8 * (MB_FULL + i), 1); mbar_init(bar + 8 * (MB_EMPTY + i), rec ? 1 : 8); }
    mbar_init(bar + 8 * MB_STGF, 256); mbar_init(bar + 8 * MB_STGE, 1);
    for (int i = MB_W0; i <= MB_AG; i++) mbar_init(bar + 8 * i, 1);
    if (rec) { mbar_expect_tx(bar + 8 * MB_S, 2560); mbar_expect_tx(bar + 8 * MB_V, 2048); mbar_expect_tx(bar + 8 * MB_RS, 8192); mbar_expect_tx(bar + 8 * MB_AG, 8192); }
    asm volatile("fence.mbarrier_init.release.cluster;" ::: "memory");
  }
  __syncthreads();
  asm volatile("barrier.cluster.arrive.release.aligned;\nbarrier.cluster.wait.acquire.aligned;" ::: "memory");
  if (rec && threadIdx.x == 256) {
    const unsigned bar = sb + SM_BAR; const int col = c * 64;
    mbar_expect_tx(bar + 8 * MB_W0, 131072);
    for (int kb = 0; kb < 8; kb++) tma_load_2d(sb + R_WO + kb * 8192, &maps.wq, col, kb * 64, bar + 8 * MB_W0);
    for (int kb = 0; kb < 8; kb++) tma_load_2d(sb + R_T1 + kb * 8192, &maps.wk, col, kb * 64, bar + 8 * MB_W0);
    mbar_expect_tx(bar + 8 * MB_W1, 65536);
    for (int kb = 0; kb < 8; kb++) tma_load_2d(sb + R_T2 + kb * 8192, &maps.wv, col, kb * 64, bar + 8 * MB_W1);
  }
  if (!helper) {
    asm volatile("griddepcontrol.wait;" ::: "memory");
    asm volatile("griddepcontrol.launch_dependents;");
  }
  if (DBGMODE && !rec) { if (helper) asm volatile("griddepcontrol.wait;" ::: "memory"); return; }
  if (w >= 8) {
    asm volatile("setmaxnreg.dec.sync.aligned.u32 24;");
    if (rec) { if (w == 8) rec_ring(maps, sb, c); else if (w == 9) rec_copy(sb, c); }
    else if (w == 8) bulk_producer(maps, sb, misc);
    else if ((threadIdx.x & 31) == 0) { if (w == 9) bulk_store(maps, sb, misc);
      else if (w == 10 && helper) asm volatile("griddepcontrol.wait;" ::: "memory"); }
  } else {
    if (rec) { asm volatile("setmaxnreg.inc.sync.aligned.u32 240;"); rec_worker(maps, sb, mem0, c); }
    else { asm volatile("setmaxnreg.inc.sync.aligned.u32 240;"); bulk_worker(sb, misc, x, b1, b2, out); }
  }
}

typedef CUresult (*EncFn)(CUtensorMap*, CUtensorMapDataType, cuuint32_t, void*, const cuuint64_t*, const cuuint64_t*, const cuuint32_t*, const cuuint32_t*,
                          CUtensorMapInterleave, CUtensorMapSwizzle, CUtensorMapL2promotion, CUtensorMapFloatOOBfill);
static void mk_map(EncFn enc, CUtensorMap* m, const void* ptr, uint64_t rows, uint64_t cols, uint32_t box_rows) {
  cuuint64_t dims[2] = {cols, rows}; cuuint64_t strides[1] = {cols * 2};
  cuuint32_t box[2] = {64, box_rows}, es[2] = {1, 1};
  enc(m, CU_TENSOR_MAP_DATA_TYPE_BFLOAT16, 2, const_cast<void*>(ptr), dims, strides, box, es, CU_TENSOR_MAP_INTERLEAVE_NONE, CU_TENSOR_MAP_SWIZZLE_128B,
      CU_TENSOR_MAP_L2_PROMOTION_L2_256B, CU_TENSOR_MAP_FLOAT_OOB_FILL_NONE);
}
extern "C" void kernel_launch(void* const* d_in, const int* in_sizes, int n_in, void* d_out, int out_size) {
  static EncFn enc = nullptr;
  static int ncl = 0, nhelp = 0;
  static unsigned recmask = 0xFFu;
  static void *p_xn, *p_y, *p_h1, *p_o, *p_qkv, *p_g;
  if (!enc) {
    void* fn = nullptr; cudaDriverEntryPointQueryResult qr;
    cudaGetDriverEntryPoint("cuTensorMapEncodeTiled", &fn, cudaEnableDefault, &qr);
    enc = (EncFn)fn;
    cudaGetSymbolAddress(&p_xn, g_xn); cudaGetSymbolAddress(&p_y, g_y); cudaGetSymbolAddress(&p_h1, g_h1);
    cudaGetSymbolAddress(&p_o, g_o); cudaGetSymbolAddress(&p_qkv, g_qkv); cudaGetSymbolAddress(&p_g, g_g);
    cudaFuncSetAttribute(k_main, cudaFuncAttributeMaxDynamicSharedMemorySize, SMEM_TOTAL);
    cudaLaunchConfig_t cfg = {}; cfg.gridDim = dim3(128); cfg.blockDim = dim3(384); cfg.dynamicSmemBytes = SMEM_TOTAL;
    cudaLaunchAttribute at[1]; at[0].id = cudaLaunchAttributeClusterDimension; at[0].val.clusterDim.x = CLS; at[0].val.clusterDim.y = 1; at[0].val.clusterDim.z = 1;
    cfg.attrs = at; cfg.numAttrs = 1;
    if (cudaOccupancyMaxActiveClusters(&ncl, k_main, &cfg) != cudaSuccess) { cudaGetLastError(); ncl = 14; }
    ncl = ncl > 16 ? 16 : (ncl < 9 ? 9 : ncl);
    int nsm = 0, dev = 0; cudaGetDevice(&dev); cudaDeviceGetAttribute(&nsm, cudaDevAttrMultiProcessorCount, dev);
    nhelp = nsm - ncl * CLS;
  }
  Maps maps;
  mk_map(enc, &maps.xn, p_xn, S_TOK, DM, 128); mk_map(enc, &maps.y, p_y, S_TOK, DM, 128); mk_map(enc, &maps.h1, p_h1, S_TOK, FF, 128);
  mk_map(enc, &maps.o, p_o, S_TOK, HD, 128); mk_map(enc, &maps.qkv_st, p_qkv, S_TOK, 3 * HD, 128); mk_map(enc, &maps.qkv_ld, p_qkv, S_TOK, 3 * HD, 32);
  mk_map(enc, &maps.g, p_g, S_TOK, DM, 128);
  mk_map(enc, &maps.wq, d_in[2], DM, HD, 64); mk_map(enc, &maps.wk, d_in[3], DM, HD, 64); mk_map(enc, &maps.wv, d_in[4], DM, HD, 64);
  mk_map(enc, &maps.wo, d_in[5], HD, DM, 64); mk_map(enc, &maps.w1, d_in[8], DM, FF, 64); mk_map(enc, &maps.w2, d_in[10], FF, DM, 64);
  cudaStream_t st = cudaStreamPerThread;
  k_pre<<<256, 256, 0, st>>>((const bf16*)d_in[0], (const char*)d_in[2], (const char*)d_in[3], (const char*)d_in[4], (const char*)d_in[5]);
  cudaLaunchConfig_t cfg = {}; cfg.gridDim = dim3(ncl * CLS); cfg.blockDim = dim3(384); cfg.dynamicSmemBytes = SMEM_TOTAL; cfg.stream = st;
  cudaLaunchAttribute at[2]; at[1].id = cudaLaunchAttributeClusterDimension; at[1].val.clusterDim.x = CLS; at[1].val.clusterDim.y = 1; at[1].val.clusterDim.z = 1;
  at[0].id = cudaLaunchAttributeProgrammaticStreamSerialization; at[0].val.programmaticStreamSerializationAllowed = 1;
#define PDL1 0
  cfg.attrs = at + (PDL1 ? 0 : 1); cfg.numAttrs = PDL1 ? 2 : 1;
  cudaLaunchKernelEx(&cfg, k_main, maps, (const bf16*)d_in[0], (const bf16*)d_in[1], (const bf16*)d_in[9], (const bf16*)d_in[11], (bf16*)d_out, recmask);
  if (nhelp > 0) {
    cfg.gridDim = dim3(nhelp);
    cfg.attrs = at; cfg.numAttrs = 1;
    cudaLaunchKernelEx(&cfg, k_main, maps, (const bf16*)d_in[0], (const bf16*)d_in[1], (const bf16*)d_in[9], (const bf16*)d_in[11], (bf16*)d_out, 0u);
  }
}
```
